```python
import torch

def _softmax(x, axis=-1):
    return torch.softmax(x, dim=axis)
def _gelu(x):
    return torch.nn.functional.gelu(x, approximate="tanh")
def _silu(x):
    return torch.nn.functional.silu(x)
def _sigmoid(x):
    return torch.sigmoid(x)
def _layernorm(x, axis=-1, eps=1e-5):
    m = x.mean(dim=axis, keepdim=True)
    v = x.var(dim=axis, keepdim=True, unbiased=False)
    return (x - m) / torch.sqrt(v + eps)
def _scatter_add(tgt, idx, src, axis=0):
    return tgt.clone().index_add_(axis, idx, src)
def _segment_sum(src, seg, n):
    out = torch.zeros((n,) + src.shape[1:], dtype=src.dtype)
    return out.index_add_(0, seg, src)
def _pad(x, pw):
    flat = tuple(v for pair in reversed(pw) for v in pair)
    return torch.nn.functional.pad(x, flat)

kernel_name = 'interleave_layers__ssm_conv_h3__mixer_s_mlp__prompt'

def setup_inputs():

    _w = (lambda a: (lambda t: t.to(torch.bfloat16) if t.is_floating_point() else t)(torch.as_tensor(a)))
    def _A_setup():
        B, S, D = 1, 2048, 1024
        ks = 4
        return {
            "q": _w((lambda *s: torch.randn(*s, dtype=torch.bfloat16) * 0.05)(B, S, D)),
            "k": _w((lambda *s: torch.randn(*s, dtype=torch.bfloat16) * 0.4)(B, S, D)),
            "v": _w((lambda *s: torch.randn(*s, dtype=torch.bfloat16) * 0.4)(B, S, D)),
            "shift_k": _w((lambda *s: torch.randn(*s, dtype=torch.bfloat16) * 0.4)(D, ks) * 0.5),
            "ssm_k": _w((lambda *s: torch.randn(*s, dtype=torch.bfloat16) * 0.4)(D, S) * (1.0 / S ** 0.5)),
            "ssm_D": _w((lambda *s: torch.randn(*s, dtype=torch.bfloat16) * 0.4)(D)),
        }
    _A_in = _A_setup()

    def _B_setup():
        B, S, D, F = 1, 2048, 1024, 3584
        return {
            "x":  _w((lambda *s: torch.randn(*s, dtype=torch.bfloat16) * 0.05)(B, S, D)),
            "w1": _w((lambda *s: torch.randn(*s, dtype=torch.bfloat16) * 1.6)(D, D) * (D ** -0.5)),
            "w2": _w((lambda *s: torch.randn(*s, dtype=torch.bfloat16) * 1.6)(D, D) * (D ** -0.5)),
            "w3": _w((lambda *s: torch.randn(*s, dtype=torch.bfloat16) * 1.6)(D, F) * (D ** -0.5)),
            "w4": _w((lambda *s: torch.randn(*s, dtype=torch.bfloat16) * 1.6)(F, D) * (F ** -0.5)),
        }
    _B_in = _B_setup()

    return {
        "A_q": _A_in["q"],
        "A_k": _A_in["k"],
        "A_v": _A_in["v"],
        "A_shift_k": _A_in["shift_k"],
        "A_ssm_k": _A_in["ssm_k"],
        "A_ssm_D": _A_in["ssm_D"],
        "B_x": _B_in["x"],
        "B_w1": _B_in["w1"],
        "B_w2": _B_in["w2"],
        "B_w3": _B_in["w3"],
        "B_w4": _B_in["w4"],
    }

def reference(A_q, A_k, A_v, A_shift_k, A_ssm_k, A_ssm_D, B_x, B_w1, B_w2, B_w3, B_w4):
    def _A_ref(q, k, v, shift_k, ssm_k, ssm_D):
        B, S, D = q.shape
        ks = shift_k.shape[-1]
        k_pad = _pad(k, ((0, 0), (ks - 1, 0), (0, 0)))
        k_shift = torch.zeros_like(k)
        for t in range(ks):
            k_shift = k_shift + k_pad[:, t:t + S, :] * shift_k[:, ks - 1 - t][None, None, :]
        kv = k_shift * v
        L = 2 * S
        kv_pad = _pad(kv, ((0, 0), (0, S), (0, 0)))
        kf_pad = _pad(ssm_k, ((0, 0), (0, S)))
        kv_f = (lambda x, axes=(-2,-1): torch.fft.rfft2(x.float(), dim=axes))(kv_pad[:, None, :, :], axes=(1, 2))
        kf_f = (lambda x, axes=(-2,-1): torch.fft.rfft2(x.float(), dim=axes))(kf_pad[:, None, :], axes=(1, 2))
        kf_f = (lambda x, *d: x.permute(*d))(kf_f, 1, 2, 0)
        y_f = kv_f * kf_f[None, :, :, :]
        y = (lambda x, s, axes=(-2,-1): torch.fft.irfft2(x, s=s, dim=axes).to(torch.bfloat16))(y_f, (1, L), axes=(1, 2))[:, 0, :S, :]
        y = y + kv * ssm_D[None, None, :]
        return q * y

    def _B_ref(x, w1, w2, w3, w4):
        B, S, D = x.shape
        h = _gelu(_layernorm(x, axis=-1) @ w1)
        c = D // 4
        g0 = _pad(h[:, :, 0*c:1*c], ((0, 0), (1, 0), (0, 0)))[:, :S, :]
        g1 = _pad(h[:, :, 1*c:2*c], ((0, 0), (0, 1), (0, 0)))[:, 1:, :]
        g2 = _pad(h[:, :, 2*c:3*c], ((0, 0), (2, 0), (0, 0)))[:, :S, :]
        g3 = _pad(h[:, :, 3*c:   ], ((0, 0), (0, 2), (0, 0)))[:, 2:, :]
        hs = torch.concatenate([g0, g1, g2, g3], axis=-1) @ w2
        x1 = x + hs
        h2 = _gelu(_layernorm(x1, axis=-1) @ w3) @ w4
        return x1 + h2

    x = A_q
    x = x + _A_ref(_layernorm(x, axis=-1), A_k, A_v, A_shift_k, A_ssm_k, A_ssm_D)
    x = x + _B_ref(_layernorm(x, axis=-1), B_w1, B_w2, B_w3, B_w4)
    x = x + _A_ref(_layernorm(x, axis=-1), A_k, A_v, A_shift_k, A_ssm_k, A_ssm_D)
    x = x + _B_ref(_layernorm(x, axis=-1), B_w1, B_w2, B_w3, B_w4)
    return x
```

```cpp
#include <cuda_runtime.h>
#include <cuda_bf16.h>
#include <cuda.h>
#include <stdint.h>

typedef __nv_bfloat16 bf16;

constexpr int S_ = 2048;
constexpr int D_ = 1024;
constexpr int F_ = 3584;

constexpr int R_XA = 0, R_X1 = 256, R_H2 = 512, R_Y = 1536, R_H = 16384 + 8, R_HP = S_ + 8, R_END = R_H + 2 * R_HP;
__device__ __align__(1024) bf16 g_act[(size_t)(R_END + 1024) * D_];
__device__ __align__(16) float g_cpart[16 * (F_ + D_)];
__device__ float2 g_stats[3 * S_ * 8];

__device__ __forceinline__ float bfr(float x) { return __bfloat162float(__float2bfloat16_rn(x)); }
__device__ __forceinline__ uint32_t pack2(float lo, float hi) {
    __nv_bfloat162 v = __floats2bfloat162_rn(lo, hi);
    return *reinterpret_cast<uint32_t*>(&v);
}
__device__ __forceinline__ float lo2f(uint32_t v) { return __uint_as_float(v << 16); }
__device__ __forceinline__ float hi2f(uint32_t v) { return __uint_as_float(v & 0xffff0000u); }
__device__ __forceinline__ float frcp(float x) { float r; asm("rcp.approx.f32 %0, %1;" : "=f"(r) : "f"(x)); return r; }
__device__ __forceinline__ float fsqrt(float x) { float r; asm("sqrt.approx.f32 %0, %1;" : "=f"(r) : "f"(x)); return r; }
__device__ __forceinline__ uint32_t smem_u32(const void* p) { return (uint32_t)__cvta_generic_to_shared(p); }

__device__ __forceinline__ void mbar_init(uint32_t bar, uint32_t cnt) {
    asm volatile("mbarrier.init.shared::cta.b64 [%0], %1;" ::"r"(bar), "r"(cnt));
}
__device__ __forceinline__ void mbar_expect_tx(uint32_t bar, uint32_t bytes) {
    asm volatile("mbarrier.arrive.expect_tx.shared::cta.b64 _, [%0], %1;" ::"r"(bar), "r"(bytes) : "memory");
}
__device__ __forceinline__ void mbar_arrive(uint32_t bar) {
    asm volatile("mbarrier.arrive.shared::cta.b64 _, [%0];" ::"r"(bar) : "memory");
}
__device__ __forceinline__ void mbar_wait(uint32_t bar, uint32_t parity) {
    asm volatile(
        "{\n.reg .pred p;\n.reg .u32 n;\n"
        "mov.u32 n, 0;\n"
        "LW:\n"
        "mbarrier.try_wait.parity.shared::cta.b64 p, [%0], %1;\n"
        "@p bra LD;\n"
        "add.u32 n, n, 1;\n"
        "setp.lt.u32 p, n, 0x400000;\n"
        "@p bra LW;\n"
        "LD:\n}\n"
        ::"r"(bar), "r"(parity) : "memory");
}
__device__ __forceinline__ void tma_load_2d(uint32_t dst, const CUtensorMap* tm, uint32_t bar, int c0, int c1) {
    asm volatile(
        "cp.async.bulk.tensor.2d.shared::cluster.global.mbarrier::complete_tx::bytes [%0], [%1, {%3, %4}], [%2];"
        ::"r"(dst), "l"((uint64_t)tm), "r"(bar), "r"(c0), "r"(c1) : "memory");
}
__device__ __forceinline__ void tma_load_2d_mc(uint32_t dst, const CUtensorMap* tm, uint32_t bar, int c0, int c1) {
    asm volatile(
        "cp.async.bulk.tensor.2d.shared::cluster.global.mbarrier::complete_tx::bytes.multicast::cluster [%0], [%1, {%3, %4}], [%2], %5;"
        ::"r"(dst), "l"((uint64_t)tm), "r"(bar), "r"(c0), "r"(c1), "h"((uint16_t)3) : "memory");
}
__device__ __forceinline__ void tma_prefetch_2d(const CUtensorMap* tm, int c0, int c1) {
    asm volatile("cp.async.bulk.prefetch.tensor.2d.L2.global.tile [%0, {%1, %2}];" ::"l"((uint64_t)tm), "r"(c0), "r"(c1) : "memory");
}
__device__ __forceinline__ void tma_store_2d(const CUtensorMap* tm, uint32_t src, int c0, int c1) {
    asm volatile("cp.async.bulk.tensor.2d.global.shared::cta.bulk_group [%0, {%2, %3}], [%1];"
                 ::"l"((uint64_t)tm), "r"(src), "r"(c0), "r"(c1) : "memory");
}
__device__ __forceinline__ void wgmma_fence() { asm volatile("wgmma.fence.sync.aligned;" ::: "memory"); }
__device__ __forceinline__ void wgmma_commit() { asm volatile("wgmma.commit_group.sync.aligned;" ::: "memory"); }
template <int N> __device__ __forceinline__ void wgmma_wait() { asm volatile("wgmma.wait_group.sync.aligned %0;" ::"n"(N) : "memory"); }
__device__ __forceinline__ void named_bar_arrive(int id, int n) { asm volatile("bar.arrive %0, %1;" ::"r"(id), "r"(n) : "memory"); }
__device__ __forceinline__ void named_bar_sync(int id, int n) { asm volatile("bar.sync %0, %1;" ::"r"(id), "r"(n) : "memory"); }

__device__ __forceinline__ void pdl_wait() { asm volatile("griddepcontrol.wait;" ::: "memory"); }
__device__ __forceinline__ void pdl_launch() { asm volatile("griddepcontrol.launch_dependents;" ::: "memory"); }

__device__ __forceinline__ uint64_t make_desc(uint32_t addr, uint32_t lbo_bytes, uint32_t sbo_bytes, uint32_t layout = 1) {
    uint64_t d = 0;
    d |= (uint64_t)((addr & 0x3FFFF) >> 4);
    d |= (uint64_t)((lbo_bytes >> 4) & 0x3FFF) << 16;
    d |= (uint64_t)((sbo_bytes >> 4) & 0x3FFF) << 32;
    d |= (uint64_t)layout << 62;
    return d;
}

__device__ __forceinline__ void wgmma_m64n192k16(float (&d)[96], uint64_t descA, uint64_t descB, int scaleD) {
  asm volatile("{\n.reg .pred p;\nsetp.ne.b32 p, %98, 0;\n"
    "wgmma.mma_async.sync.aligned.m64n192k16.f32.bf16.bf16 "
    "{%0, %1, %2, %3, %4, %5, %6, %7, %8, %9, %10, %11, %12, %13, %14, %15, %16, %17, %18, %19, %20, %21, %22, %23, %24, %25, %26, %27, %28, %29, %30, %31, %32, %33, %34, %35, %36, %37, %38, %39, %40, %41, %42, %43, %44, %45, %46, %47, %48, %49, %50, %51, %52, %53, %54, %55, %56, %57, %58, %59, %60, %61, %62, %63, %64, %65, %66, %67, %68, %69, %70, %71, %72, %73, %74, %75, %76, %77, %78, %79, %80, %81, %82, %83, %84, %85, %86, %87, %88, %89, %90, %91, %92, %93, %94, %95}, "
    "%96, %97, p, 1, 1, 0, 1;\n}\n"
    : "+f"(d[0]), "+f"(d[1]), "+f"(d[2]), "+f"(d[3]), "+f"(d[4]), "+f"(d[5]), "+f"(d[6]), "+f"(d[7]), "+f"(d[8]), "+f"(d[9]), "+f"(d[10]), "+f"(d[11]), "+f"(d[12]), "+f"(d[13]), "+f"(d[14]), "+f"(d[15]), "+f"(d[16]), "+f"(d[17]), "+f"(d[18]), "+f"(d[19]), "+f"(d[20]), "+f"(d[21]), "+f"(d[22]), "+f"(d[23]), "+f"(d[24]), "+f"(d[25]), "+f"(d[26]), "+f"(d[27]), "+f"(d[28]), "+f"(d[29]), "+f"(d[30]), "+f"(d[31]), "+f"(d[32]), "+f"(d[33]), "+f"(d[34]), "+f"(d[35]), "+f"(d[36]), "+f"(d[37]), "+f"(d[38]), "+f"(d[39]), "+f"(d[40]), "+f"(d[41]), "+f"(d[42]), "+f"(d[43]), "+f"(d[44]), "+f"(d[45]), "+f"(d[46]), "+f"(d[47]), "+f"(d[48]), "+f"(d[49]), "+f"(d[50]), "+f"(d[51]), "+f"(d[52]), "+f"(d[53]), "+f"(d[54]), "+f"(d[55]), "+f"(d[56]), "+f"(d[57]), "+f"(d[58]), "+f"(d[59]), "+f"(d[60]), "+f"(d[61]), "+f"(d[62]), "+f"(d[63]), "+f"(d[64]), "+f"(d[65]), "+f"(d[66]), "+f"(d[67]), "+f"(d[68]), "+f"(d[69]), "+f"(d[70]), "+f"(d[71]), "+f"(d[72]), "+f"(d[73]), "+f"(d[74]), "+f"(d[75]), "+f"(d[76]), "+f"(d[77]), "+f"(d[78]), "+f"(d[79]), "+f"(d[80]), "+f"(d[81]), "+f"(d[82]), "+f"(d[83]), "+f"(d[84]), "+f"(d[85]), "+f"(d[86]), "+f"(d[87]), "+f"(d[88]), "+f"(d[89]), "+f"(d[90]), "+f"(d[91]), "+f"(d[92]), "+f"(d[93]), "+f"(d[94]), "+f"(d[95])
    : "l"(descA), "l"(descB), "r"(scaleD));
}

__device__ __forceinline__ void wgmma_m64n256k16(float (&d)[128], uint64_t descA, uint64_t descB, int scaleD) {
  asm volatile("{\n.reg .pred p;\nsetp.ne.b32 p, %130, 0;\n"
    "wgmma.mma_async.sync.aligned.m64n256k16.f32.bf16.bf16 "
    "{%0, %1, %2, %3, %4, %5, %6, %7, %8, %9, %10, %11, %12, %13, %14, %15, %16, %17, %18, %19, %20, %21, %22, %23, %24, %25, %26, %27, %28, %29, %30, %31, %32, %33, %34, %35, %36, %37, %38, %39, %40, %41, %42, %43, %44, %45, %46, %47, %48, %49, %50, %51, %52, %53, %54, %55, %56, %57, %58, %59, %60, %61, %62, %63, %64, %65, %66, %67, %68, %69, %70, %71, %72, %73, %74, %75, %76, %77, %78, %79, %80, %81, %82, %83, %84, %85, %86, %87, %88, %89, %90, %91, %92, %93, %94, %95, %96, %97, %98, %99, %100, %101, %102, %103, %104, %105, %106, %107, %108, %109, %110, %111, %112, %113, %114, %115, %116, %117, %118, %119, %120, %121, %122, %123, %124, %125, %126, %127}, "
    "%128, %129, p, 1, 1, 0, 1;\n}\n"
    : "+f"(d[0]), "+f"(d[1]), "+f"(d[2]), "+f"(d[3]), "+f"(d[4]), "+f"(d[5]), "+f"(d[6]), "+f"(d[7]), "+f"(d[8]), "+f"(d[9]), "+f"(d[10]), "+f"(d[11]), "+f"(d[12]), "+f"(d[13]), "+f"(d[14]), "+f"(d[15]), "+f"(d[16]), "+f"(d[17]), "+f"(d[18]), "+f"(d[19]), "+f"(d[20]), "+f"(d[21]), "+f"(d[22]), "+f"(d[23]), "+f"(d[24]), "+f"(d[25]), "+f"(d[26]), "+f"(d[27]), "+f"(d[28]), "+f"(d[29]), "+f"(d[30]), "+f"(d[31]), "+f"(d[32]), "+f"(d[33]), "+f"(d[34]), "+f"(d[35]), "+f"(d[36]), "+f"(d[37]), "+f"(d[38]), "+f"(d[39]), "+f"(d[40]), "+f"(d[41]), "+f"(d[42]), "+f"(d[43]), "+f"(d[44]), "+f"(d[45]), "+f"(d[46]), "+f"(d[47]), "+f"(d[48]), "+f"(d[49]), "+f"(d[50]), "+f"(d[51]), "+f"(d[52]), "+f"(d[53]), "+f"(d[54]), "+f"(d[55]), "+f"(d[56]), "+f"(d[57]), "+f"(d[58]), "+f"(d[59]), "+f"(d[60]), "+f"(d[61]), "+f"(d[62]), "+f"(d[63]), "+f"(d[64]), "+f"(d[65]), "+f"(d[66]), "+f"(d[67]), "+f"(d[68]), "+f"(d[69]), "+f"(d[70]), "+f"(d[71]), "+f"(d[72]), "+f"(d[73]), "+f"(d[74]), "+f"(d[75]), "+f"(d[76]), "+f"(d[77]), "+f"(d[78]), "+f"(d[79]), "+f"(d[80]), "+f"(d[81]), "+f"(d[82]), "+f"(d[83]), "+f"(d[84]), "+f"(d[85]), "+f"(d[86]), "+f"(d[87]), "+f"(d[88]), "+f"(d[89]), "+f"(d[90]), "+f"(d[91]), "+f"(d[92]), "+f"(d[93]), "+f"(d[94]), "+f"(d[95]), "+f"(d[96]), "+f"(d[97]), "+f"(d[98]), "+f"(d[99]), "+f"(d[100]), "+f"(d[101]), "+f"(d[102]), "+f"(d[103]), "+f"(d[104]), "+f"(d[105]), "+f"(d[106]), "+f"(d[107]), "+f"(d[108]), "+f"(d[109]), "+f"(d[110]), "+f"(d[111]), "+f"(d[112]), "+f"(d[113]), "+f"(d[114]), "+f"(d[115]), "+f"(d[116]), "+f"(d[117]), "+f"(d[118]), "+f"(d[119]), "+f"(d[120]), "+f"(d[121]), "+f"(d[122]), "+f"(d[123]), "+f"(d[124]), "+f"(d[125]), "+f"(d[126]), "+f"(d[127])
    : "l"(descA), "l"(descB), "r"(scaleD));
}

__device__ __forceinline__ void wgmma_m64n128k16(float (&d)[64], uint64_t descA, uint64_t descB, int scaleD) {
  asm volatile("{\n.reg .pred p;\nsetp.ne.b32 p, %66, 0;\n"
    "wgmma.mma_async.sync.aligned.m64n128k16.f32.bf16.bf16 "
    "{%0, %1, %2, %3, %4, %5, %6, %7, %8, %9, %10, %11, %12, %13, %14, %15, %16, %17, %18, %19, %20, %21, %22, %23, %24, %25, %26, %27, %28, %29, %30, %31, %32, %33, %34, %35, %36, %37, %38, %39, %40, %41, %42, %43, %44, %45, %46, %47, %48, %49, %50, %51, %52, %53, %54, %55, %56, %57, %58, %59, %60, %61, %62, %63}, "
    "%64, %65, p, 1, 1, 0, 1;\n}\n"
    : "+f"(d[0]), "+f"(d[1]), "+f"(d[2]), "+f"(d[3]), "+f"(d[4]), "+f"(d[5]), "+f"(d[6]), "+f"(d[7]), "+f"(d[8]), "+f"(d[9]), "+f"(d[10]), "+f"(d[11]), "+f"(d[12]), "+f"(d[13]), "+f"(d[14]), "+f"(d[15]), "+f"(d[16]), "+f"(d[17]), "+f"(d[18]), "+f"(d[19]), "+f"(d[20]), "+f"(d[21]), "+f"(d[22]), "+f"(d[23]), "+f"(d[24]), "+f"(d[25]), "+f"(d[26]), "+f"(d[27]), "+f"(d[28]), "+f"(d[29]), "+f"(d[30]), "+f"(d[31]), "+f"(d[32]), "+f"(d[33]), "+f"(d[34]), "+f"(d[35]), "+f"(d[36]), "+f"(d[37]), "+f"(d[38]), "+f"(d[39]), "+f"(d[40]), "+f"(d[41]), "+f"(d[42]), "+f"(d[43]), "+f"(d[44]), "+f"(d[45]), "+f"(d[46]), "+f"(d[47]), "+f"(d[48]), "+f"(d[49]), "+f"(d[50]), "+f"(d[51]), "+f"(d[52]), "+f"(d[53]), "+f"(d[54]), "+f"(d[55]), "+f"(d[56]), "+f"(d[57]), "+f"(d[58]), "+f"(d[59]), "+f"(d[60]), "+f"(d[61]), "+f"(d[62]), "+f"(d[63])
    : "l"(descA), "l"(descB), "r"(scaleD));
}

template <int BN> struct WG;
template <> struct WG<128> { static __device__ __forceinline__ void mma(float (&d)[64], uint64_t a, uint64_t b, int s) { wgmma_m64n128k16(d, a, b, s); } };
template <> struct WG<256> { static __device__ __forceinline__ void mma(float (&d)[128], uint64_t a, uint64_t b, int s) { wgmma_m64n256k16(d, a, b, s); } };
template <> struct WG<192> { static __device__ __forceinline__ void mma(float (&d)[96], uint64_t a, uint64_t b, int s) { wgmma_m64n192k16(d, a, b, s); } };

#define DBG_T(i)
__device__ __forceinline__ void fence_async_smem() { asm volatile("fence.proxy.async.shared::cta;" ::: "memory"); }
__device__ __forceinline__ void prefetch_tmap(const CUtensorMap* tm) { asm volatile("prefetch.tensormap [%0];" ::"l"((uint64_t)tm) : "memory"); }
__device__ __forceinline__ uint32_t mapa_u32(uint32_t addr, uint32_t cta) {
    uint32_t r;
    asm volatile("mapa.shared::cluster.u32 %0, %1, %2;" : "=r"(r) : "r"(addr), "r"(cta));
    return r;
}
__device__ __forceinline__ void mbar_arrive_cluster(uint32_t cluster_addr) {
    asm volatile("mbarrier.arrive.shared::cluster.b64 _, [%0];" ::"r"(cluster_addr) : "memory");
}
__device__ __forceinline__ bool elect_one() {
    uint32_t p;
    asm volatile("{\n.reg .pred P;\nelect.sync _|P, 0xffffffff;\nselp.u32 %0, 1, 0, P;\n}\n" : "=r"(p));
    return p != 0;
}
__device__ __forceinline__ void cluster_arrive_relaxed() { asm volatile("barrier.cluster.arrive.relaxed.aligned;" ::: "memory"); }
__device__ __forceinline__ void cluster_wait() { asm volatile("barrier.cluster.wait.acquire.aligned;" ::: "memory"); }

__device__ __forceinline__ uint32_t bsub2(uint32_t a, uint32_t b) {
    __nv_bfloat162 r = __hsub2(*reinterpret_cast<__nv_bfloat162*>(&a), *reinterpret_cast<__nv_bfloat162*>(&b));
    return *reinterpret_cast<uint32_t*>(&r);
}
__device__ __forceinline__ uint32_t bmul2(uint32_t a, uint32_t b) {
    __nv_bfloat162 r = __hmul2(*reinterpret_cast<__nv_bfloat162*>(&a), *reinterpret_cast<__nv_bfloat162*>(&b));
    return *reinterpret_cast<uint32_t*>(&r);
}
__device__ __forceinline__ uint32_t badd2(uint32_t a, uint32_t b) {
    __nv_bfloat162 r = __hadd2(*reinterpret_cast<__nv_bfloat162*>(&a), *reinterpret_cast<__nv_bfloat162*>(&b));
    return *reinterpret_cast<uint32_t*>(&r);
}
constexpr int BM = 128, BK = 64;
constexpr int R5_STAGE = 32768, R5_N = 5;
constexpr int R4_STAGE = 49152, R4_N = 4;
constexpr int R4B_STAGE = 40960;
constexpr int OFF_STG5 = 163840;
constexpr int OFF_EPI = 196608;
constexpr int OFF_BAR = OFF_EPI + 32768;
constexpr int OFF_RS = OFF_BAR + 256;
constexpr int OFF_CS = OFF_RS + 1024;
constexpr int MEGA_SMEM = OFF_CS + 1792;
enum { FL_PS = 0, FL_XA = 1, FL_H = 2, FL_X1 = 3, FL_HA = 4, FL_H2 = 5, FL_KINDS = 9 };
constexpr int FL_PITCH = 64;
constexpr int FL_WORDS = 2 * FL_KINDS * 16 * FL_PITCH;
__device__ unsigned int g_flag[FL_WORDS];
__device__ unsigned int g_ticket[9 * FL_PITCH];
__device__ __forceinline__ unsigned int* flag_ptr(int layer, int kind, int i) { return g_flag + ((layer * FL_KINDS + kind) * 16 + i) * FL_PITCH; }

__device__ __forceinline__ void wait_flag(const unsigned int* p, unsigned int target) {
    long long t0 = clock64();
    while (true) {
        unsigned int v;
        asm volatile("ld.relaxed.gpu.global.u32 %0, [%1];" : "=r"(v) : "l"(p) : "memory");
        if (v >= target) break;
        if (clock64() - t0 > 2000000000LL) break;
    }
    asm volatile("fence.acquire.gpu;" ::: "memory");
}
__device__ __forceinline__ void fence_proxy_async() {
    asm volatile("fence.proxy.async.global;" ::: "memory");
    asm volatile("fence.proxy.async.shared::cta;" ::: "memory");
}
__device__ __forceinline__ void stsm4(uint32_t addr, uint32_t r0, uint32_t r1, uint32_t r2, uint32_t r3) {
    asm volatile("stmatrix.sync.aligned.m8n8.x4.shared.b16 [%0], {%1,%2,%3,%4};" ::"r"(addr), "r"(r0), "r"(r1), "r"(r2), "r"(r3));
}
__device__ __forceinline__ uint4 lds128(uint32_t a) {
    uint4 v;
    asm volatile("ld.shared.v4.b32 {%0,%1,%2,%3}, [%4];" : "=r"(v.x), "=r"(v.y), "=r"(v.z), "=r"(v.w) : "r"(a) : "memory");
    return v;
}
__device__ __forceinline__ void stg128(void* p, uint4 v) {
    asm volatile("st.global.v4.b32 [%0], {%1,%2,%3,%4};" ::"l"(p), "r"(v.x), "r"(v.y), "r"(v.z), "r"(v.w) : "memory");
}
__device__ __forceinline__ float gelu_tanh_h(float hx) {
    float z = hx * fmaf(hx * hx, 8.0f * 0.035677408136300125f, 2.0f * 0.7978845608028654f);
    float t;
    asm("tanh.approx.f32 %0, %1;" : "=f"(t) : "f"(z));
    return fmaf(hx, t, hx);
}
__device__ __forceinline__ uint32_t gelu2h(uint32_t p) { return pack2(gelu_tanh_h(lo2f(p)), gelu_tanh_h(hi2f(p))); }
__device__ __forceinline__ uint4 gelu8h(uint4 v) { return make_uint4(gelu2h(v.x), gelu2h(v.y), gelu2h(v.z), gelu2h(v.w)); }

__device__ __forceinline__ void row_stats(const float2* p, float& mean, float& var) {
    float2 v[8];
#pragma unroll
    for (int i = 0; i < 8; i++) v[i] = __ldcg(p + 128 * i);
    mean = (((v[0].x + v[1].x) + (v[2].x + v[3].x)) + ((v[4].x + v[5].x) + (v[6].x + v[7].x))) * 0.125f;
    float m2 = 0.f, d2 = 0.f;
#pragma unroll
    for (int i = 0; i < 8; i++) { m2 += v[i].y; d2 = fmaf(v[i].x - mean, v[i].x - mean, d2); }
    var = fmaf(128.0f, d2, m2) * (1.0f / D_);
}
struct RingState { int st; uint32_t ph; };
struct Rel { bool on; uint32_t delta; };

#define DT(i)
#define GT(i)

template <int BN, int NST, int STAGE>
__device__ __forceinline__ void kblock(float (&acc)[BN / 2], uint32_t sa, uint32_t sbase, uint32_t bfull, RingState& rs) {
    mbar_wait(bfull + 8 * rs.st, (rs.ph >> rs.st) & 1);
    uint64_t da = make_desc(sa, 16, 1024);
    uint64_t db = make_desc(sbase + rs.st * STAGE + BM * BK * 2, 8192, 1024);
    wgmma_fence();
#pragma unroll
    for (int k = 0; k < 4; k++) WG<BN>::mma(acc, da + (uint64_t)(k * 2), db + (uint64_t)(k * 128), 1);
    wgmma_commit();
    rs.ph ^= 1u << rs.st;
    if (++rs.st == NST) rs.st = 0;
}
template <int BN, int NST, int STAGE, bool PRE = false>
__device__ __forceinline__ void mainloop(float (&acc)[BN / 2], int KB, uint32_t sbase, uint32_t bfull, uint32_t bempty, RingState& rs,
                                         int wg, Rel rel, int dbg) {
    int prev = PRE ? rs.st - 1 : 0;
#pragma unroll 1
    for (int kk = 0; kk < KB; kk++) {
        const int cur = rs.st;
        kblock<BN, NST, STAGE>(acc, sbase + cur * STAGE + wg * 8192, sbase, bfull, rs);
        if (PRE || kk > 0) {
            wgmma_wait<1>();
            if (rel.on) {
                if (PRE && kk == 0) mbar_arrive_cluster(bempty + 8 * (prev - 1) + rel.delta);
                mbar_arrive_cluster(bempty + 8 * prev + rel.delta);
            }
        }
        prev = cur;
    }
    wgmma_wait<0>();
#pragma unroll
    for (int i = 0; i < BN / 2; i++) asm volatile("" : "+f"(acc[i])::"memory");
    if (rel.on) mbar_arrive_cluster(bempty + 8 * prev + rel.delta);
}
template <int N> __device__ __forceinline__ void zero_acc(float (&acc)[N]) {
#pragma unroll
    for (int i = 0; i < N; i++) acc[i] = 0.f;
}
__device__ __forceinline__ void ldsm4(uint32_t& r0, uint32_t& r1, uint32_t& r2, uint32_t& r3, uint32_t addr) {
    asm volatile("ldmatrix.sync.aligned.m8n8.x4.shared.b16 {%0,%1,%2,%3}, [%4];" : "=r"(r0), "=r"(r1), "=r"(r2), "=r"(r3) : "r"(addr));
}

__device__ __forceinline__ void ldsm4t(uint32_t& r0, uint32_t& r1, uint32_t& r2, uint32_t& r3, uint32_t addr) {
    asm volatile("ldmatrix.sync.aligned.m8n8.x4.trans.shared.b16 {%0,%1,%2,%3}, [%4];" : "=r"(r0), "=r"(r1), "=r"(r2), "=r"(r3) : "r"(addr));
}

struct MegaMaps {
    CUtensorMap q, act;
    CUtensorMap w1, w2, w3, w4;
};

__global__ void __cluster_dims__(2, 1, 1) __launch_bounds__(384, 1)
mega_kernel(const __grid_constant__ MegaMaps tm, bf16* __restrict__ outp, bf16* act) {
    extern __shared__ __align__(1024) uint8_t sgen[];
    const uint32_t sbase = smem_u32(sgen);
    DT(0);
    GT(2);
    const int warp = threadIdx.x >> 5, lane = threadIdx.x & 31;
    const int rank = blockIdx.x & 1;
    const uint32_t s_bar = sbase + OFF_BAR;
    const uint32_t f5 = s_bar, e5 = s_bar + 48, f4 = s_bar + 96, e4 = s_bar + 128;
    const uint32_t b_rfull = s_bar + 176, b_stg = s_bar + 184, b_h2 = s_bar + 192;
    const uint32_t s_epi = sbase + OFF_EPI, s_stg = sbase + OFF_STG5;

    if (threadIdx.x == 256) {
        for (int i = 0; i < R5_N; i++) { mbar_init(f5 + 8 * i, 1); mbar_init(e5 + 8 * i, 4); }
        for (int i = 0; i < R4_N; i++) { mbar_init(f4 + 8 * i, 1); mbar_init(e4 + 8 * i, 4); }
        mbar_init(b_rfull, 1); mbar_init(b_stg, 8);
        for (int i = 1; i < 4; i++) mbar_init(b_h2 + 8 * i, 1);
        for (int i = 0; i < 6; i++) reinterpret_cast<uint32_t*>(sgen + OFF_BAR + 224)[i] = 0;
        asm volatile("fence.mbarrier_init.release.cluster;" ::: "memory");
        fence_async_smem();
        prefetch_tmap(&tm.act);
    }
    if (threadIdx.x == 288 && rank == 0) {
        uint32_t smid;
        asm volatile("mov.u32 %0, %%smid;" : "=r"(smid));
        const int t = smid >> 1;
        int team = t < 32 ? t & 7 : t < 60 ? 1 + (t - 32) % 7 : t < 62 ? t - 54 : 0;
        int slot = atomicAdd(g_ticket + team * FL_PITCH, 1u);
        atomicAdd(g_ticket + 8 * FL_PITCH, 1u);
        if (slot >= 8) {
            const long long t0 = clock64();
            while (*(volatile unsigned int*)(g_ticket + 8 * FL_PITCH) < gridDim.x / 2 && clock64() - t0 < 100000) {}
            for (team = 0; team < 8; team++)
                if ((slot = atomicAdd(g_ticket + team * FL_PITCH, 1u)) < 8) break;
        }
        const uint32_t role = team * 8 + slot, ra = s_bar + 192;
        asm volatile("st.shared::cluster.u32 [%0], %1;" ::"r"(mapa_u32(ra, 0)), "r"(role) : "memory");
        asm volatile("st.shared::cluster.u32 [%0], %1;" ::"r"(mapa_u32(ra, 1)), "r"(role) : "memory");
        asm volatile("fence.acq_rel.cluster;" ::: "memory");
    }
    __syncwarp();
    cluster_arrive_relaxed();
    cluster_wait();
    const int role = *reinterpret_cast<const volatile int*>(sgen + OFF_BAR + 192);
    if (role >= 64) return;
    const int bi = (role >> 3) * 2 + rank, bj = role & 7, m0 = bi * BM, tb = (role >> 3) * 2048 + rank * 128;
    if (threadIdx.x == 256) {
        mbar_expect_tx(b_rfull, 32768);
        tma_load_2d(s_epi, &tm.q, b_rfull, bj * 128, m0);
        tma_load_2d(s_epi + 16384, &tm.q, b_rfull, bj * 128 + 64, m0);
    }

    if (warp >= 8) {
        asm volatile("setmaxnreg.dec.sync.aligned.u32 72;");
        if (warp == 8) { if (elect_one()) {
            int s5 = 0, s4 = 0;
            uint32_t p5 = 31, p4 = 1;
            auto putB = [&](const CUtensorMap* tB, int kc, uint32_t bytes) {
                const uint32_t full = f5 + 8 * s5;
                mbar_wait(full + 48, (p5 >> s5) & 1);
                mbar_expect_tx(full, bytes);
                tma_load_2d_mc(sbase + 16384 + rank * 8192 + s5 * R5_STAGE, tB, full, bj * 128 + rank * 64, kc);
                p5 ^= 1u << s5;
            };
            auto putA = [&](int c, int r) {
                tma_load_2d(sbase + s5 * R5_STAGE, &tm.act, f5 + 8 * s5, c, r);
                if (++s5 == R5_N) s5 = 0;
            };
            pdl_wait();
            prefetch_tmap(&tm.w1); prefetch_tmap(&tm.w2); prefetch_tmap(&tm.w3); prefetch_tmap(&tm.w4);
            auto own_first = [&](int it) { return (it < 2 ? 2 * bj + it : it - 2 < 2 * bj ? it - 2 : it) * BK; };
            const unsigned int nh = (bi == 0 || bi == 15) ? 16 : 24;
#pragma unroll 1
            for (int layer = 0; layer < 2; layer++) {
                mbar_wait(e5 + 8, (p5 >> 1) & 1);
                mbar_expect_tx(f5 + 8, 32768);
                tma_load_2d(sbase + R5_STAGE, &tm.act, f5 + 8, (bj >> 1) * 256 + rank * 128, R_Y + (tb & ~255) + (bj & 1) * 128);
                tma_load_2d(sbase + R5_STAGE + 16384, &tm.act, f5 + 8, (bj >> 1) * 256 + rank * 128 + 64, R_Y + (tb & ~255) + (bj & 1) * 128);
                p5 ^= 2;
                s5 = 2;
#pragma unroll 1
                for (int kk = 0; kk < 4; kk++) { putB(&tm.w1, own_first(kk), kk < 2 ? 16384 : R5_STAGE); if (++s5 == R5_N) s5 = 0; }
                wait_flag(flag_ptr(layer, FL_XA, bi), 8);
                fence_proxy_async();
                s5 = 4;
#pragma unroll 1
                for (int kk = 2; kk < 16; kk++) {
                    const int kc = own_first(kk);
                    if (kk >= 4) putB(&tm.w1, kc, R5_STAGE);
                    putA(kc, R_XA + tb);
                }
                s5 = 4;
#pragma unroll 1
                for (int kk = 0; kk < 5; kk++) { putB(&tm.w2, kk * 2 * BK, R5_STAGE); if (++s5 == R5_N) s5 = 0; }
#pragma unroll 1
                for (int kk = 0; kk < 16; kk++) {
                    const int kc = ((kk & 7) * 2 + (kk >> 3)) * BK;
                    if (kk >= 5) putB(&tm.w2, kc, R5_STAGE);
                    if ((kk & 7) == 0) {
                        wait_flag(flag_ptr(layer, kk ? FL_H : FL_HA, bi), nh);
                        fence_proxy_async();
                    }
                    putA(kc, R_H + layer * R_HP + m0 + (int)((0x4031u >> ((kk & 6) << 1)) & 7) - 2);
                }
#pragma unroll 1
                for (int it = 0; it < 32; it++) {
                    const int kc = it >= 16 ? (it - 16) * BK : own_first(it);
                    const int nb = it < 16 ? 4 : 3, n0 = bj * 448 + (it < 16 ? 0 : 256);
                    if (it < 3) {
                        const int i = it * 3 >> 1;
                        mbar_wait(e5 + 8 * i, (p5 >> i) & 1);
                        mbar_wait(e5 + 8 * i + 8, (p5 >> (i + 1)) & 1);
                    }
                    mbar_wait(e4 + 8 * s4, p4);
                    uint32_t sa = sbase + s4 * (it < 16 ? R4_STAGE : R4B_STAGE), full = f4 + 8 * s4;
                    mbar_expect_tx(full, (it < 2 ? 0 : 16384) + nb * 8192);
#pragma unroll 1
                    for (int j = (it ^ rank) & 1; j < nb; j += 2) tma_load_2d_mc(sa + 16384 + j * 8192, &tm.w3, full, n0 + j * 64, kc);
                    if (it == 3) {
                        wait_flag(flag_ptr(layer, FL_X1, bi), 8);
                        fence_proxy_async();
                        tma_load_2d(sbase + 2 * R4_STAGE, &tm.act, f4 + 16, own_first(2), R_X1 + tb);
                    }
                    if (it >= 3) tma_load_2d(sa, &tm.act, full, kc, R_X1 + tb);
                    if (++s4 == R4_N) { s4 = 0; p4 ^= 1; }
                }
                wait_flag(flag_ptr(layer, FL_H2, bi), 8);
                fence_proxy_async();
                s5 = 0;
#pragma unroll 1
                for (int j = 0; j < 7; j++) {
                    if (j > 0 && (j & 1) == 0) {
                        mbar_wait(b_h2 + 4 * j, layer);
                        fence_proxy_async();
                    }
                    const int ra = R_H2 + (j >> 1) * 256 + tb;
#pragma unroll 1
                    for (int b = 0; b < 8; b++) {
                        if (j == 0 && b < R4_N) mbar_wait(e4 + 8 * b, p4);
                        putB(&tm.w4, (7 * b + j) * BK, R5_STAGE);
                        putA(((j & 1) * 8 + b) * BK, ra);
                    }
                }
            }
        } } else {
            pdl_wait();
            auto publish = [&](int layer, int kind) {
                if (lane == 0) {
                    if (kind == FL_XA || kind == FL_X1) {
                        tma_store_2d(&tm.act, s_epi + 16384, bj * 128 + 64, (kind == FL_XA ? R_XA : R_X1) + tb);
                        asm volatile("cp.async.bulk.commit_group;\ncp.async.bulk.wait_group 0;" ::: "memory");
                    }
                    asm volatile("fence.proxy.async.global;" ::: "memory");
                    asm volatile("fence.release.gpu;" ::: "memory");
                    unsigned int* fp = flag_ptr(layer, kind, bi);
                    asm volatile("red.relaxed.gpu.global.add.u32 [%0], 1;" ::"l"(fp) : "memory");
                    if (kind == FL_H || kind == FL_HA) {
                        if (bi > 0) asm volatile("red.relaxed.gpu.global.add.u32 [%0], 1;" ::"l"(fp - FL_PITCH) : "memory");
                        if (bi < 15) asm volatile("red.relaxed.gpu.global.add.u32 [%0], 1;" ::"l"(fp + FL_PITCH) : "memory");
                    }
                }
                __syncwarp();
            };
#pragma unroll 1
            for (int layer = 0; layer < 2; layer++) {
                if (warp == 10) {
#pragma unroll 1
                    for (int kind = 1 - layer; kind < 4; kind++) {
                        if (kind & 1) {
                            named_bar_sync(12, 288);
                            if (lane == 0) tma_store_2d(&tm.act, s_epi, bj * 128, (kind == FL_XA ? R_XA : R_X1) + tb);
                            __syncwarp();
                        }
                        if (kind == FL_H) { named_bar_sync(12, 288); publish(layer, FL_HA); }
                        named_bar_sync(5 + (kind & 1), 288);
                        publish(layer, kind);
                    }
                } else if (warp == 9) {
                    uint32_t* rs = reinterpret_cast<uint32_t*>(sgen + OFF_RS);
                    float* cs = reinterpret_cast<float*>(sgen + OFF_CS);
#pragma unroll 1
                    for (int which = 0; which < 2; which++) {
                        if (lane == 0 && (layer | which)) wait_flag(flag_ptr(layer, which == 0 ? FL_XA : FL_X1, bi), 8);
                        __syncwarp();
#pragma unroll 1
                        for (int c = (which == 0 && layer == 0 ? 0 : 256) + lane * 4; c < (which == 0 ? 384 : 448); c += 128) {
                            const float* cp = g_cpart + (which == 0 && c >= 256 ? F_ + bj * 128 - 256 : bj * 448) + c;
                            float4 a = make_float4(0.f, 0.f, 0.f, 0.f);
#pragma unroll
                            for (int r0 = 0; r0 < 16; r0 += 8) {
                                float4 v[8];
#pragma unroll
                                for (int r = 0; r < 8; r++) v[r] = __ldcg(reinterpret_cast<const float4*>(cp + (r0 + r) * (F_ + D_)));
#pragma unroll
                                for (int r = 0; r < 8; r++) { a.x += v[r].x; a.y += v[r].y; a.z += v[r].z; a.w += v[r].w; }
                            }
                            *reinterpret_cast<float4*>(cs + c) = a;
                        }
                        if (lane == 0 && !(layer | which)) wait_flag(flag_ptr(0, FL_XA, bi), 8);
                        __syncwarp();
#pragma unroll 1
                        for (int i = 0; i < 4; i++) {
                            const int r = i * 32 + lane;
                            float mean, var;
                            row_stats(g_stats + (size_t)(1 + which) * S_ * 8 + bi * 1024 + r, mean, var);
                            const uint32_t c0 = pack2(mean, fsqrt(bfr(bfr(var) + 1e-5f)));
                            rs[r] = c0;
                            const float rd = frcp(hi2f(c0));
                            rs[128 + r] = pack2((mean - lo2f(c0)) * rd, fsqrt(bfr(bfr(var * rd * rd) + 1e-5f)));
                        }
                        named_bar_arrive(3, 288);
                    }
                }
                const uint32_t s_cnt = s_bar + 224;
                auto ticket = [&](uint32_t a) {
                    uint32_t v = 0;
                    if (lane == 0) asm volatile("atom.acq_rel.cta.shared.add.u32 %0, [%1], 1;" : "=r"(v) : "r"(a) : "memory");
                    return v;
                };
                mbar_wait(b_stg, 0);
                int u = __shfl_sync(0xffffffffu, ticket(s_cnt + 16 + 4 * layer), 0), step = 0;
#pragma unroll 1
                while (true) {
#pragma unroll 1
                    for (; step < 5 && u >= (int)((0x3830201810ull >> (8 * step)) & 255); step++) {
                        if (step == 1) { named_bar_arrive(4, 352); continue; }
                        const int part = step ? step - 1 : 0;
                        __syncwarp();
                        if (ticket(s_cnt + 4 * part) == 3 * layer + 2) {
                            asm volatile("fence.release.gpu;" ::: "memory");
                            unsigned int* fp = flag_ptr(layer, FL_H2 + part, bi);
                            asm volatile("red.relaxed.gpu.global.add.u32 [%0], 1;" ::"l"(fp) : "memory");
                            if (part > 0) { wait_flag(fp, 8); mbar_arrive(b_h2 + 8 * part); }
                        }
                        __syncwarp();
                        if (step == 2) mbar_wait(b_stg, 1);
                    }
                    if (u >= 56) break;
                    const uint32_t un = ticket(s_cnt + 16 + 4 * layer);
                    const int job = u >> 3, r = (u & 7) * 16 + (lane >> 3);
                    const uint32_t sp = sbase + ((job & 2) ? OFF_STG5 : OFF_EPI) + r * 256 + (job & 1) * 128;
                    bf16* gp = act + (size_t)(R_H2 + (job >> 1) * 256 + tb + r) * D_ + ((job & 1) * 8 + bj) * 64 + (lane & 7) * 8;
                    uint4 v[4];
#pragma unroll
                    for (int e = 0; e < 4; e++) v[e] = lds128(sp + e * 1024 + (((lane & 7) ^ ((r + 4 * e) & 7)) << 4));
#pragma unroll
                    for (int e = 0; e < 4; e++) stg128(gp + 4 * e * D_, gelu8h(v[e]));
                    u = __shfl_sync(0xffffffffu, un, 0);
                }
            }
        }
        __syncwarp();
        asm volatile("barrier.cluster.arrive.relaxed.aligned;\nbarrier.cluster.wait.acquire.aligned; // helpers" ::: "memory");
    } else {
        asm volatile("setmaxnreg.inc.sync.aligned.u32 216;");
        const int tid = threadIdx.x;
        const int wg = warp >> 2;
        const Rel rel{(tid & 95) == 0, mapa_u32(sbase, (tid & 32) ? rank ^ 1 : rank) - sbase};
        const int t = lane & 3;
        const int row = warp * 16 + (lane >> 2);
        const uint32_t st_w = (uint32_t)((warp * 16 + ((lane >> 3) & 1) * 8 + (lane & 7)) * 256 + (((lane >> 4) ^ (lane & 7)) << 4));
        const uint32_t st_r = (uint32_t)((tid >> 3) * 256 + (((tid & 7) ^ ((tid >> 3) & 7)) << 4));
        const uint32_t fr = (uint32_t)((warp * 16 + ((lane >> 3) & 1) * 8 + (lane & 7)) * 128 + (((lane >> 4) ^ (lane & 7)) << 4));
        auto copy_out = [&](bf16* dst, uint32_t src) {
            const int r = warp * 16 + (lane >> 4);
            bf16* ox = dst + (size_t)(m0 + r) * D_ + bj * 128 + (lane & 15) * 8;
            const uint32_t ra = src + ((lane & 15) >> 3) * 16384 + r * 128;
            uint4 v[8];
#pragma unroll
            for (int it = 0; it < 8; it++) v[it] = lds128(ra + it * 256 + (((lane & 7) ^ ((2 * it + (lane >> 4)) & 7)) << 4));
#pragma unroll
            for (int it = 0; it < 8; it++) *reinterpret_cast<uint4*>(ox + (size_t)it * 2 * D_) = v[it];
        };
        auto put_stats = [&](float (&sm)[2], float (&sq)[2], int which) {
#pragma unroll
            for (int of = 1; of < 4; of <<= 1)
#pragma unroll
                for (int e = 0; e < 2; e++) { sm[e] += __shfl_xor_sync(0xffffffffu, sm[e], of); sq[e] += __shfl_xor_sync(0xffffffffu, sq[e], of); }
            if (t < 2) {
                const float s1 = t ? sm[1] : sm[0], q1 = t ? sq[1] : sq[0], mu = s1 * (1.0f / 128);
                g_stats[(size_t)which * S_ * 8 + (bi * 8 + bj) * 128 + row + 8 * t] = make_float2(mu, fmaxf(q1 - s1 * mu, 0.f));
            }
        };
        const float* csp = reinterpret_cast<const float*>(sgen + OFF_CS) + 2 * t;
        float mrow[2], rrow[2];
        const uint32_t* rsp = reinterpret_cast<const uint32_t*>(sgen + OFF_RS) + row;
        auto row_consts = [&](bool twice) {
#pragma unroll
            for (int e = 0; e < 2; e++) {
                const uint32_t q0 = rsp[8 * e], q1 = rsp[128 + 8 * e];
                mrow[e] = twice ? fmaf(lo2f(q1), hi2f(q0), lo2f(q0)) : lo2f(q0);
                rrow[e] = 0.5f * frcp(twice ? hi2f(q0) * hi2f(q1) : hi2f(q0));
            }
        };
        auto stage = [&](const float* acc, uint32_t dst, int j0, float2 (&cs)[8], const float* cnext) {
            float2 cn[8];
#pragma unroll
            for (int e = 0; e < 8; e++) cn[e] = *reinterpret_cast<const float2*>(cnext + 8 * e);
#pragma unroll
            for (int j = 0; j < 8; j += 2) {
                uint32_t w[4];
#pragma unroll
                for (int e = 0; e < 2; e++) {
                    const float* a = acc + 4 * (j + e);
                    w[2 * e] = pack2(fmaf(-mrow[0], cs[j + e].x, a[0]) * rrow[0], fmaf(-mrow[0], cs[j + e].y, a[1]) * rrow[0]);
                    w[2 * e + 1] = pack2(fmaf(-mrow[1], cs[j + e].x, a[2]) * rrow[1], fmaf(-mrow[1], cs[j + e].y, a[3]) * rrow[1]);
                }
                stsm4((dst + st_w) ^ (((j0 + j) & 15) << 4), w[0], w[1], w[2], w[3]);
            }
#pragma unroll
            for (int e = 0; e < 8; e++) cs[e] = cn[e];
        };
        RingState r5{0, 0}, r4{0, 0};
        DT(1);
        uint32_t x[32];
        mbar_wait(b_rfull, 0);
#pragma unroll
        for (int jp = 0; jp < 8; jp++) ldsm4(x[4 * jp], x[4 * jp + 1], x[4 * jp + 2], x[4 * jp + 3], s_epi + (fr ^ ((jp & 3) << 5)) + (jp >> 2) * 16384);
#pragma unroll 1
        for (int layer = 0; layer < 2; layer++) {
            {
                DT(2 + 24 * layer);
                if (layer == 1) {
                    float sm[2] = {0.f, 0.f}, sq[2] = {0.f, 0.f};
#pragma unroll
                    for (int e = 0; e < 32; e++) {
                        const float e0 = lo2f(x[e]), e1 = hi2f(x[e]);
                        sm[e & 1] += e0 + e1; sq[e & 1] = fmaf(e0, e0, fmaf(e1, e1, sq[e & 1]));
                    }
                    put_stats(sm, sq, 0);
                    named_bar_arrive(5, 288);
                    DT(20 + 24 * layer);
                    if (lane == 0) wait_flag(flag_ptr(layer, FL_PS, bi), 8);
                    __syncwarp();
                } else pdl_wait();
                DT(22 + 24 * layer);
                uint32_t mb[2];
                float rd[2];
                {
                    float mean, var;
                    row_stats(g_stats + bi * 1024 + warp * 16 + (lane & 15), mean, var);
                    const float r1 = frcp(bfr(fsqrt(bfr(bfr(var) + 1e-5f))));
                    const uint32_t m1 = pack2(mean, mean);
#pragma unroll
                    for (int e = 0; e < 2; e++) { mb[e] = __shfl_sync(0xffffffffu, m1, (lane >> 2) + 8 * e); rd[e] = __shfl_sync(0xffffffffu, r1, (lane >> 2) + 8 * e); }
                }
                DT(21 + 24 * layer);
                mbar_wait(f5 + 8, (r5.ph >> 1) & 1);
                if (layer == 0) GT(3);
                const uint32_t ya = sbase + R5_STAGE + wg * 16384 + ((lane >> 4) * 8 + (lane & 7)) * 128 + ((((warp & 3) * 2 + ((lane >> 3) & 1)) ^ (lane & 7)) << 4);
                uint32_t y[32];
#pragma unroll
                for (int jp = 0; jp < 8; jp++) ldsm4t(y[4 * jp], y[4 * jp + 1], y[4 * jp + 2], y[4 * jp + 3], ya + jp * 2048);
                float sm[2] = {0.f, 0.f}, sq[2] = {0.f, 0.f};
#pragma unroll
                for (int e = 0; e < 32; e++) {
                    const uint32_t d = bsub2(x[e], mb[e & 1]);
                    x[e] = badd2(x[e], bmul2(pack2(lo2f(d) * rd[e & 1], hi2f(d) * rd[e & 1]), y[e]));
                    const float e0 = lo2f(x[e]), e1 = hi2f(x[e]);
                    sm[e & 1] += e0 + e1; sq[e & 1] = fmaf(e0, e0, fmaf(e1, e1, sq[e & 1]));
                    if ((e & 3) == 3) stsm4(s_epi + (fr ^ (((e >> 2) & 3) << 5)) + (e >> 4) * 16384, x[e - 3], x[e - 2], x[e - 1], x[e]);
                    if (e == 15) { fence_async_smem(); named_bar_arrive(12, 288); }
                }
                put_stats(sm, sq, 1);
                DT(19 + 24 * layer);
                fence_async_smem();
                named_bar_arrive(6, 288);
                named_bar_sync(9 + wg, 128);
                if (rel.on) mbar_arrive_cluster(e5 + 8 + rel.delta);
                r5.ph ^= 2;
                DT(3 + 24 * layer);
            }
            {
                float acc[64];
                zero_acc(acc);
                r5.st = 2;
                kblock<128, R5_N, R5_STAGE>(acc, s_epi + wg * 8192, sbase, f5, r5);
                kblock<128, R5_N, R5_STAGE>(acc, s_epi + 16384 + wg * 8192, sbase, f5, r5);
                mainloop<128, R5_N, R5_STAGE, true>(acc, 14, sbase, f5, e5, r5, wg, rel, 15 + 24 * layer);
                DT(4 + 24 * layer);
                named_bar_sync(3, 288);
                row_consts(true);
                float2 cs[8];
#pragma unroll
                for (int e = 0; e < 8; e++) cs[e] = *reinterpret_cast<const float2*>(csp + 256 + 8 * e);
#pragma unroll
                for (int j = 0; j < 16; j += 8) stage(acc + 4 * j, s_stg, j, cs, csp + 256 + 64);
                named_bar_sync(1, 256);
                bf16* op = act + (size_t)(R_H + layer * R_HP + m0 + (tid >> 3)) * D_ + bj * 128 + (tid & 7) * 8;
#pragma unroll
                for (int hf = 0; hf < 2; hf++) {
#pragma unroll
                    for (int it = 0; it < 4; it++)
                        *reinterpret_cast<uint4*>(op + (size_t)it * 32 * D_ + hf * 64) = gelu8h(*reinterpret_cast<const uint4*>(sgen + OFF_STG5 + st_r + it * 8192 + hf * 128));
                    if (hf == 0) named_bar_arrive(12, 288);
                }
                named_bar_arrive(5, 288);
                DT(5 + 24 * layer);
            }
            {
                float acc[64];
                zero_acc(acc);
                r5.st = 4;
                mainloop<128, R5_N, R5_STAGE>(acc, 16, sbase, f5, e5, r5, wg, rel, 16 + 24 * layer);
                DT(6 + 24 * layer);
                uint32_t mb[2];
                float rd[2];
#pragma unroll
                for (int e = 0; e < 2; e++) { const uint32_t q0 = rsp[8 * e]; mb[e] = (q0 & 0xffffu) * 0x10001u; rd[e] = frcp(hi2f(q0)); }
                float sm[2] = {0.f, 0.f}, sq[2] = {0.f, 0.f};
#pragma unroll
                for (int j = 0; j < 16; j += 2) {
                    const uint32_t o = s_epi + (fr ^ ((j & 7) << 4)) + (j >> 3) * 16384;
                    uint32_t w[4];
                    ldsm4(w[0], w[1], w[2], w[3], o);
#pragma unroll
                    for (int e = 0; e < 4; e++) {
                        const uint32_t d = bsub2(w[e], mb[e & 1]), xa = w[e];
                        w[e] = badd2(pack2(lo2f(d) * rd[e & 1], hi2f(d) * rd[e & 1]), pack2(acc[4 * j + 2 * e], acc[4 * j + 2 * e + 1]));
                        x[2 * j + e] = badd2(xa, w[e]);
                        float e0 = lo2f(w[e]), e1 = hi2f(w[e]);
                        sm[e & 1] += e0 + e1; sq[e & 1] = fmaf(e0, e0, fmaf(e1, e1, sq[e & 1]));
                    }
                    stsm4(o, w[0], w[1], w[2], w[3]);
                    if (j == 6) { fence_async_smem(); named_bar_arrive(12, 288); }
                }
                put_stats(sm, sq, 2);
                fence_async_smem();
                named_bar_arrive(6, 288);
                named_bar_sync(9 + wg, 128);
                DT(7 + 24 * layer);
            }
            {
                float2 cs[8];
                {
                    float acc[128];
                    zero_acc(acc);
                    kblock<256, R4_N, R4_STAGE>(acc, s_epi + wg * 8192, sbase, f4, r4);
                    kblock<256, R4_N, R4_STAGE>(acc, s_epi + 16384 + wg * 8192, sbase, f4, r4);
                    mainloop<256, R4_N, R4_STAGE, true>(acc, 14, sbase, f4, e4, r4, wg, rel, 17 + 24 * layer);
                    DT(8 + 24 * layer);
                    named_bar_sync(3, 288);
                    row_consts(false);
#pragma unroll
                    for (int e = 0; e < 8; e++) cs[e] = *reinterpret_cast<const float2*>(csp + 8 * e);
#pragma unroll
                    for (int j = 0; j < 32; j += 8) stage(acc + 4 * j, j < 16 ? s_epi : s_stg, j, cs, csp + 8 * (j + 8));
                    __syncwarp();
                if (lane == 0) mbar_arrive(b_stg);
                }
                DT(9 + 24 * layer);
                float acc[96];
                zero_acc(acc);
                mainloop<192, R4_N, R4B_STAGE>(acc, 16, sbase, f4, e4, r4, wg, rel, -1);
                DT(10 + 24 * layer);
                named_bar_sync(4, 352);
#pragma unroll
                for (int j = 0; j < 24; j += 8) stage(acc + 4 * j, j < 16 ? s_epi : s_stg, j, cs, csp + 256 + 8 * (j < 16 ? j + 8 : 0));
                __syncwarp();
                if (lane == 0) mbar_arrive(b_stg);
                DT(11 + 24 * layer);
            }
            {
                float acc[64];
#pragma unroll
                for (int i = 0; i < 32; i++) asm volatile("shl.b32 %0, %2, 16;\nand.b32 %1, %2, 0xffff0000;" : "=f"(acc[2 * i]), "=f"(acc[2 * i + 1]) : "r"(x[i]));
                r5.st = 0;
                mainloop<128, R5_N, R5_STAGE>(acc, 56, sbase, f5, e5, r5, wg, rel, 18 + 24 * layer);
                DT(12 + 24 * layer);
#pragma unroll
                for (int i = 0; i < 32; i++) x[i] = pack2(acc[2 * i], acc[2 * i + 1]);
                DT(13 + 24 * layer);
                DT(14 + 24 * layer);
            }
        }
#pragma unroll
        for (int jp = 0; jp < 8; jp++) stsm4(s_epi + (fr ^ ((jp & 3) << 5)) + (jp >> 2) * 16384, x[4 * jp], x[4 * jp + 1], x[4 * jp + 2], x[4 * jp + 3]);
        __syncwarp();
        copy_out(outp, s_epi);
        DT(38);
        GT(4);
        cluster_arrive_relaxed();
        cluster_wait();
    }
}

constexpr int CV_CH = 8;
constexpr int CV_UPITCH = 72;
constexpr int CV_UROWS = 40;
constexpr int CV_U_BYTES = CV_UROWS * CV_UPITCH * 2;
constexpr int CV_P_WORDS = 2048 + 16;
constexpr int CV_P_BYTES = CV_P_WORDS * 4;
constexpr int CV_Y_BYTES = 8 * CV_UPITCH * 2;
constexpr int CV_SMEM = CV_CH * (CV_U_BYTES + CV_P_BYTES + CV_Y_BYTES) + 2 * 8 * 16 * 32 * 4 + 128 + (128 + 2048 * 16) + 2048 * 16;

__device__ __forceinline__ void mma16816(float (&d)[4], uint32_t a0, uint32_t a1, uint32_t a2, uint32_t a3, uint32_t b0, uint32_t b1) {
    asm volatile("mma.sync.aligned.m16n8k16.row.col.f32.bf16.bf16.f32 {%0,%1,%2,%3}, {%4,%5,%6,%7}, {%8,%9}, {%0,%1,%2,%3};"
                 : "+f"(d[0]), "+f"(d[1]), "+f"(d[2]), "+f"(d[3]) : "r"(a0), "r"(a1), "r"(a2), "r"(a3), "r"(b0), "r"(b1));
}
__device__ __forceinline__ void stsm4t(uint32_t addr, uint32_t r0, uint32_t r1, uint32_t r2, uint32_t r3) {
    asm volatile("stmatrix.sync.aligned.m8n8.x4.trans.shared.b16 [%0], {%1,%2,%3,%4};" ::"r"(addr), "r"(r0), "r"(r1), "r"(r2), "r"(r3) : "memory");
}
__device__ __forceinline__ void ldsm4c(uint32_t& r0, uint32_t& r1, uint32_t& r2, uint32_t& r3, uint32_t addr) {
    asm volatile("ldmatrix.sync.aligned.m8n8.x4.shared.b16 {%0,%1,%2,%3}, [%4];" : "=r"(r0), "=r"(r1), "=r"(r2), "=r"(r3) : "r"(addr));
}
__global__ void __launch_bounds__(640, 1)
conv_kernel(const __grid_constant__ CUtensorMap tmK, const __grid_constant__ CUtensorMap tmV, const bf16* __restrict__ kp,
            const bf16* __restrict__ vp, const bf16* __restrict__ shk,
            const bf16* __restrict__ ssk, const bf16* __restrict__ ssD, const bf16* __restrict__ w1p, const bf16* __restrict__ w3p,
            const bf16* __restrict__ xq, bf16* act) {
    extern __shared__ __align__(128) uint8_t sm[];
    uint8_t* sU = sm;
    uint8_t* sP = sm + CV_CH * CV_U_BYTES;
    uint8_t* sY = sP + CV_CH * CV_P_BYTES;
    float* sR = reinterpret_cast<float*>(sY + CV_CH * CV_Y_BYTES);
    const int tid = threadIdx.x, warp = tid >> 5, lane = tid & 31;
    const int d0 = blockIdx.x * CV_CH;
    const uint32_t bar0 = smem_u32(sR + 2 * 8 * 16 * 32);
    const uint8_t* sK = reinterpret_cast<const uint8_t*>(sR + 2 * 8 * 16 * 32) + 128 + 128;
    const uint8_t* sV = sK + 2048 * 16;
    DBG_T(0);
    GT(0);
    auto load_kv = [&](int q) {
        mbar_expect_tx(bar0 + 64 + 8 * q, 4 * 4096);
        for (int i = 0; i < 2; i++) {
            int r0 = 512 * q + 256 * i;
            tma_load_2d(smem_u32(sK) + r0 * 16, &tmK, bar0 + 64 + 8 * q, d0, r0);
            tma_load_2d(smem_u32(sV) + r0 * 16, &tmV, bar0 + 64 + 8 * q, d0, r0);
        }
    };
    uint4 k0, v0;
    if (tid < 512) {
        k0 = __ldg(reinterpret_cast<const uint4*>(kp + (size_t)tid * D_ + d0));
        v0 = __ldg(reinterpret_cast<const uint4*>(vp + (size_t)tid * D_ + d0));
    }
    if (tid == 512) {
        for (int i = 0; i < 4; i++) { mbar_init(bar0 + 8 * i, 4); mbar_init(bar0 + 32 + 8 * i, 4); mbar_init(bar0 + 64 + 8 * i, i == 0 ? 16 : 1); }
        asm volatile("fence.mbarrier_init.release.cluster;" ::: "memory");
        fence_async_smem();
    }
    if (tid >= 32 && tid < 35) *reinterpret_cast<uint4*>(const_cast<uint8_t*>(sK) - 16 * (tid - 31)) = make_uint4(0, 0, 0, 0);
    for (int i = tid; tid < 512 && i < CV_CH * 8 * CV_UPITCH / 8; i += 512) {
        int c2 = i / (8 * CV_UPITCH / 8), r = i % (8 * CV_UPITCH / 8);
        *reinterpret_cast<uint4*>(sU + c2 * CV_U_BYTES + r * 16) = make_uint4(0, 0, 0, 0);
    }
    if (warp < 8 && lane < 16) reinterpret_cast<uint32_t*>(sP + warp * CV_P_BYTES)[lane] = 0;

    if (warp >= 16) {
        const int bt = tid - 512;
        uint32_t wv[4][4];
#pragma unroll
        for (int pr = 0; pr < 4; pr++) {
            uint2 wa = *reinterpret_cast<const uint2*>(shk + (d0 + 2 * pr) * 4);
            uint2 wb = *reinterpret_cast<const uint2*>(shk + (d0 + 2 * pr + 1) * 4);
            wv[0][pr] = (wa.x & 0xffffu) | (wb.x << 16);
            wv[1][pr] = (wa.x >> 16) | (wb.x & 0xffff0000u);
            wv[2][pr] = (wa.y & 0xffffu) | (wb.y << 16);
            wv[3][pr] = (wa.y >> 16) | (wb.y & 0xffff0000u);
        }
        const int pch = bt >> 4, pl = bt & 15;
        const bf16* hrow = ssk + (size_t)(d0 + pch) * S_ + pl * 8;
        uint32_t* Pw = reinterpret_cast<uint32_t*>(sP + pch * CV_P_BYTES) + 16 + pl * 8;
        uint4 pf[4];
        uint32_t hprev[4];
        auto prefetch = [&](int q) {
#pragma unroll
            for (int i = 0; i < 4; i++) {
                int j0 = 512 * q + i * 128;
                pf[i] = __ldg(reinterpret_cast<const uint4*>(hrow + j0));
                hprev[i] = (j0 + pl > 0) ? (uint32_t)__bfloat16_as_ushort(hrow[j0 - 1]) : 0u;
            }
        };
        prefetch(0);
        asm volatile("barrier.sync 0, 640;" ::: "memory");
        pdl_wait();
        if (blockIdx.x == 0) {
            for (int i = bt; i < FL_WORDS / FL_PITCH; i += 128) g_flag[i * FL_PITCH] = 0;
            if (bt < 9) { g_ticket[bt * FL_PITCH] = 0; __threadfence(); }
        }
        __syncwarp();
        if (warp == 16) pdl_launch();
#pragma unroll 1
        for (int q = 0; q < 4; q++) {
#pragma unroll
            for (int i = 0; i < 4; i++) {
                int j0 = 512 * q + i * 128;
                uint32_t x0 = pf[i].x, x1 = pf[i].y, x2 = pf[i].z, x3 = pf[i].w;
                uint4 o0, o1;
                o0.x = (x0 & 0xffffu) | (hprev[i] << 16);
                o0.y = (x0 >> 16) | (x0 << 16);
                o0.z = (x1 & 0xffffu) | (x0 & 0xffff0000u);
                o0.w = (x1 >> 16) | (x1 << 16);
                o1.x = (x2 & 0xffffu) | (x1 & 0xffff0000u);
                o1.y = (x2 >> 16) | (x2 << 16);
                o1.z = (x3 & 0xffffu) | (x2 & 0xffff0000u);
                o1.w = (x3 >> 16) | (x3 << 16);
                *reinterpret_cast<uint4*>(Pw + j0) = o0;
                *reinterpret_cast<uint4*>(Pw + j0 + 4) = o1;
            }
            DBG_T(1 + 3 * q);
            mbar_wait(bar0 + 64 + 8 * q, 0);
            if (q < 3) {
                if (bt == 0) load_kv(q + 1);
                prefetch(q + 1);
            }
            DBG_T(2 + 3 * q);
#pragma unroll 1
            for (int hf = 0; hf < 2; hf++) {
                const int s0 = 512 * q + 256 * hf + 2 * bt;
                const int a = s0 >> 6, b = s0 & 63;
                uint4 kf[7];
#pragma unroll
                for (int i = 0; i < 5; i++) kf[i] = *reinterpret_cast<const uint4*>(sK + (s0 - 3 + i) * 16);
#pragma unroll
                for (int i = 0; i < 2; i++) kf[5 + i] = *reinterpret_cast<const uint4*>(sV + (s0 + i) * 16);
#pragma unroll
                for (int pr = 0; pr < 4; pr++) {
                    uint32_t k0 = reinterpret_cast<const uint32_t*>(&kf[0])[pr], k1 = reinterpret_cast<const uint32_t*>(&kf[1])[pr],
                             k2 = reinterpret_cast<const uint32_t*>(&kf[2])[pr], k3 = reinterpret_cast<const uint32_t*>(&kf[3])[pr],
                             k4 = reinterpret_cast<const uint32_t*>(&kf[4])[pr];
                    uint32_t r0 = bmul2(k0, wv[3][pr]);
                    r0 = badd2(r0, bmul2(k1, wv[2][pr]));
                    r0 = badd2(r0, bmul2(k2, wv[1][pr]));
                    r0 = badd2(r0, bmul2(k3, wv[0][pr]));
                    r0 = bmul2(r0, reinterpret_cast<const uint32_t*>(&kf[5])[pr]);
                    uint32_t r1 = bmul2(k1, wv[3][pr]);
                    r1 = badd2(r1, bmul2(k2, wv[2][pr]));
                    r1 = badd2(r1, bmul2(k3, wv[1][pr]));
                    r1 = badd2(r1, bmul2(k4, wv[0][pr]));
                    r1 = bmul2(r1, reinterpret_cast<const uint32_t*>(&kf[6])[pr]);
                    uint32_t c0 = (r0 & 0xffffu) | (r1 << 16), c1 = (r0 >> 16) | (r1 & 0xffff0000u);
                    *reinterpret_cast<uint32_t*>(sU + (2 * pr) * CV_U_BYTES + ((8 + a) * CV_UPITCH + b) * 2) = c0;
                    *reinterpret_cast<uint32_t*>(sU + (2 * pr + 1) * CV_U_BYTES + ((8 + a) * CV_UPITCH + b) * 2) = c1;
                }
            }
            __syncwarp();
            if (lane == 0) mbar_arrive(bar0 + 8 * q);
            DBG_T(3 + 3 * q);
        }
        {
            const int bi = blockIdx.x >> 3, bj = blockIdx.x & 7;
            const bool is3 = bt < 112;
            const int cg = is3 ? bt % 56 : bt - 112, pitch = is3 ? F_ : D_, col = is3 ? bj * 448 + cg * 8 : bj * 128 + cg * 8;
            const int r1 = is3 ? 32 : 64;
            const bf16* p = (is3 ? w3p + (size_t)(bt >= 56 ? 32 : 0) * F_ : w1p) + (size_t)(bi * 64) * pitch + col;
            float a8[8];
#pragma unroll
            for (int i = 0; i < 8; i++) a8[i] = 0.f;
#pragma unroll 1
            for (int r0 = 0; r0 < r1; r0 += 16) {
                uint4 v[16];
#pragma unroll
                for (int r = 0; r < 16; r++) v[r] = __ldg(reinterpret_cast<const uint4*>(p + (size_t)(r0 + r) * pitch));
#pragma unroll
                for (int r = 0; r < 16; r++) {
                    a8[0] += lo2f(v[r].x); a8[1] += hi2f(v[r].x); a8[2] += lo2f(v[r].y); a8[3] += hi2f(v[r].y);
                    a8[4] += lo2f(v[r].z); a8[5] += hi2f(v[r].z); a8[6] += lo2f(v[r].w); a8[7] += hi2f(v[r].w);
                }
            }
            float* sc = reinterpret_cast<float*>(const_cast<uint8_t*>(sK));
            mbar_wait(bar0, 0);
            if (bt >= 56 && is3) {
#pragma unroll
                for (int i = 0; i < 8; i++) sc[cg * 8 + i] = a8[i];
            }
            __syncwarp();
            if (lane == 0) mbar_arrive(bar0 + 32);
            mbar_wait(bar0 + 32, 0);
            if (bt < 56 || !is3) {
                if (is3) {
#pragma unroll
                    for (int i = 0; i < 8; i++) a8[i] += sc[cg * 8 + i];
                }
                float4* dst = reinterpret_cast<float4*>(g_cpart + bi * (F_ + D_) + (is3 ? 0 : F_) + col);
                dst[0] = make_float4(a8[0], a8[1], a8[2], a8[3]);
                dst[1] = make_float4(a8[4], a8[5], a8[6], a8[7]);
            }
        }
        {
            const int r = blockIdx.x * 16 + (warp - 16) * 4;
            uint4 v[16];
#pragma unroll
            for (int e = 0; e < 16; e++) v[e] = __ldg(reinterpret_cast<const uint4*>(xq + (size_t)r * D_ + e * 256 + lane * 8));
            float sm[4] = {0.f, 0.f, 0.f, 0.f}, sq[4] = {0.f, 0.f, 0.f, 0.f};
#pragma unroll
            for (int e = 0; e < 64; e++) {
                const uint32_t w = reinterpret_cast<const uint32_t*>(v)[e];
                sm[e >> 4] += lo2f(w) + hi2f(w); sq[e >> 4] = fmaf(lo2f(w), lo2f(w), fmaf(hi2f(w), hi2f(w), sq[e >> 4]));
            }
#pragma unroll
            for (int o = 16; o > 0; o >>= 1)
#pragma unroll
                for (int e = 0; e < 4; e++) { sm[e] += __shfl_xor_sync(0xffffffffu, sm[e], o); sq[e] += __shfl_xor_sync(0xffffffffu, sq[e], o); }
            const int e = lane >> 3;
            const float s1 = e == 0 ? sm[0] : e == 1 ? sm[1] : e == 2 ? sm[2] : sm[3], q1 = e == 0 ? sq[0] : e == 1 ? sq[1] : e == 2 ? sq[2] : sq[3];
            const float mu = s1 * (1.0f / D_);
            g_stats[((r >> 7) * 8 + (lane & 7)) * 128 + (r & 127) + e] = make_float2(mu, fmaxf(q1 - s1 * mu, 0.f) * 0.125f);
        }
        DBG_T(13);
        return;
    }

    asm volatile("barrier.sync 0, 640;" ::: "memory");
    *reinterpret_cast<uint4*>(const_cast<uint8_t*>(sK) + tid * 16) = k0;
    *reinterpret_cast<uint4*>(const_cast<uint8_t*>(sV) + tid * 16) = v0;
    __syncwarp();
    if (lane == 0) mbar_arrive(bar0 + 64);
    const int ch = warp & 7, par = warp >> 3;
    const int g = lane >> 2, t = lane & 3;
    const uint32_t* P = reinterpret_cast<const uint32_t*>(sP + ch * CV_P_BYTES) + 16 + (g - 2 * t);
    const uint32_t uB = smem_u32(sU + ch * CV_U_BYTES);
    const int lrow = lane & 7, lmat = lane >> 3;
    const uint32_t Dk2 = (uint32_t)__bfloat16_as_ushort(ssD[d0 + ch]) * 0x10001u;
    pdl_wait();
    GT(5);

#pragma unroll 1
    for (int q = 0; q < 4; q++) {
        mbar_wait(bar0 + 8 * q, 0);
        DBG_T(1 + 3 * q);
        float acc[4][4];
#pragma unroll
        for (int i = 0; i < 4; i++)
#pragma unroll
            for (int k = 0; k < 4; k++) acc[i][k] = 0.f;
        const int c0 = par * (4 * q + 4), c1 = c0 + 4 * q + 4;
        const uint32_t base0 = uB + ((8 + 8 * q + lrow) * CV_UPITCH) * 2 + lmat * 16;
        int c = c0;
        uint32_t pa[15];
        if (par == 0) {
#pragma unroll
            for (int j = 6; j < 15; j++) pa[j] = P[8 * (j - 7)];
            uint32_t b[8];
            ldsm4c(b[0], b[1], b[2], b[3], base0);
            ldsm4c(b[4], b[5], b[6], b[7], base0 + 64);
#pragma unroll
            for (int kk = 0; kk < 4; kk++)
#pragma unroll
                for (int mi = kk; mi < 4; mi++) {
                    int jj = 2 * (mi - kk) + 7;
                    mma16816(acc[mi], pa[jj], pa[jj + 1], pa[jj - 1], pa[jj], b[2 * kk], b[2 * kk + 1]);
                }
            c = 1;
        } else {
#pragma unroll
            for (int j = 8; j < 15; j++) pa[j] = P[8 * (8 * c - 15 + j)];
        }
#pragma unroll 2
        for (; c < c1; c++) {
#pragma unroll
            for (int j = 0; j < 7; j++) pa[j] = pa[j + 8];
#pragma unroll
            for (int j = 7; j < 15; j++) pa[j] = P[8 * (8 * c - 7 + j)];
            uint32_t b[8];
            uint32_t base = base0 - c * (CV_UPITCH * 2);
            ldsm4c(b[0], b[1], b[2], b[3], base);
            ldsm4c(b[4], b[5], b[6], b[7], base + 64);
#pragma unroll
            for (int kk = 3; kk >= 0; kk--)
#pragma unroll
                for (int mi = 0; mi < 4; mi++) {
                    int jj = 2 * (mi - kk) + 7;
                    mma16816(acc[mi], pa[jj], pa[jj + 1], pa[jj - 1], pa[jj], b[2 * kk], b[2 * kk + 1]);
                }
        }
        DBG_T(2 + 3 * q);
        float4* sRq = reinterpret_cast<float4*>(sR) + ((q & 1) * 8 + ch) * 128 + lane;
        if (par == 1) {
#pragma unroll
            for (int mi = 0; mi < 4; mi++) sRq[mi * 32] = make_float4(acc[mi][0], acc[mi][1], acc[mi][2], acc[mi][3]);
            named_bar_arrive(ch + 8 * (q & 1), 64);
        } else {
            uint32_t kv[8];
            ldsm4t(kv[0], kv[1], kv[2], kv[3], base0);
            ldsm4t(kv[4], kv[5], kv[6], kv[7], base0 + 64);
            named_bar_sync(ch + 8 * (q & 1), 64);
#pragma unroll
            for (int mi = 0; mi < 4; mi++) {
                const float4 o = sRq[mi * 32];
                kv[2 * mi] = badd2(pack2(acc[mi][0] + o.x, acc[mi][1] + o.y), bmul2(kv[2 * mi], Dk2));
                kv[2 * mi + 1] = badd2(pack2(acc[mi][2] + o.z, acc[mi][3] + o.w), bmul2(kv[2 * mi + 1], Dk2));
            }
            const uint32_t yb = smem_u32(sY + ch * CV_Y_BYTES);
            __syncwarp();
            stsm4t(yb + lrow * (CV_UPITCH * 2) + lmat * 16, kv[0], kv[1], kv[2], kv[3]);
            stsm4t(yb + lrow * (CV_UPITCH * 2) + lmat * 16 + 64, kv[4], kv[5], kv[6], kv[7]);
            __syncwarp();
            uint4* dst = reinterpret_cast<uint4*>(act + (size_t)(R_Y + q * 4096 + ((d0 + ch) & 255)) * D_ + (d0 & ~255)) + lane;
            const uint4 v0 = lds128(yb + (lane >> 3) * (CV_UPITCH * 2) + (lane & 7) * 16);
            const uint4 v1 = lds128(yb + (4 + (lane >> 3)) * (CV_UPITCH * 2) + (lane & 7) * 16);
            dst[0] = v0;
            dst[2048 * D_ / 8] = v1;
        }
        DBG_T(3 + 3 * q);
    }
    GT(1);
}

typedef CUresult (*PFN_encodeTiled)(CUtensorMap*, CUtensorMapDataType, cuuint32_t, void*, const cuuint64_t*, const cuuint64_t*,
                                    const cuuint32_t*, const cuuint32_t*, CUtensorMapInterleave, CUtensorMapSwizzle,
                                    CUtensorMapL2promotion, CUtensorMapFloatOOBfill);

static CUtensorMap make_map(PFN_encodeTiled enc, const void* ptr, int inner, int outer, int box_inner, int box_outer,
                            CUtensorMapSwizzle swz = CU_TENSOR_MAP_SWIZZLE_128B) {
    CUtensorMap m;
    cuuint64_t dims[2] = {(cuuint64_t)inner, (cuuint64_t)outer};
    cuuint64_t strides[1] = {(cuuint64_t)inner * 2};
    cuuint32_t box[2] = {(cuuint32_t)box_inner, (cuuint32_t)box_outer};
    cuuint32_t es[2] = {1, 1};
    enc(&m, CU_TENSOR_MAP_DATA_TYPE_BFLOAT16, 2, const_cast<void*>(ptr), dims, strides, box, es, CU_TENSOR_MAP_INTERLEAVE_NONE,
        swz, CU_TENSOR_MAP_L2_PROMOTION_L2_256B, CU_TENSOR_MAP_FLOAT_OOB_FILL_NONE);
    return m;
}

extern "C" void kernel_launch(void* const* d_in, const int* in_sizes, int n_in, void* d_out, int out_size) {
    const bf16* A_q = (const bf16*)d_in[0];
    const bf16* A_k = (const bf16*)d_in[1];
    const bf16* A_v = (const bf16*)d_in[2];
    const bf16* A_shk = (const bf16*)d_in[3];
    const bf16* A_ssk = (const bf16*)d_in[4];
    const bf16* A_ssD = (const bf16*)d_in[5];
    const bf16* w1 = (const bf16*)d_in[7];
    const bf16* w2 = (const bf16*)d_in[8];
    const bf16* w3 = (const bf16*)d_in[9];
    const bf16* w4 = (const bf16*)d_in[10];
    bf16* out = (bf16*)d_out;

    static PFN_encodeTiled enc = nullptr;
    static bool attr_done = false;
    if (!enc) {
        void* fn = nullptr;
        cudaDriverEntryPointQueryResult qr;
        cudaGetDriverEntryPoint("cuTensorMapEncodeTiled", &fn, cudaEnableDefault, &qr);
        enc = (PFN_encodeTiled)fn;
    }
    if (!attr_done) {
        cudaFuncSetAttribute(mega_kernel, cudaFuncAttributeMaxDynamicSharedMemorySize, MEGA_SMEM);
        cudaFuncSetAttribute(conv_kernel, cudaFuncAttributeMaxDynamicSharedMemorySize, CV_SMEM);
        attr_done = true;
    }
    void* p_act;
    cudaGetSymbolAddress(&p_act, g_act);
    bf16* act = (bf16*)(((uintptr_t)p_act + 0x1fffff) & ~(uintptr_t)0x1fffff);

    MegaMaps tm;
    tm.q = make_map(enc, A_q, D_, S_, 64, 128);
    tm.act = make_map(enc, act, D_, R_END, 64, 128);
    tm.w1 = make_map(enc, w1, D_, D_, 64, 64);
    tm.w2 = make_map(enc, w2, D_, D_, 64, 64);
    tm.w3 = make_map(enc, w3, F_, D_, 64, 64);
    tm.w4 = make_map(enc, w4, D_, F_, 64, 64);
    CUtensorMap tm_k = make_map(enc, A_k, D_, S_, 8, 256, CU_TENSOR_MAP_SWIZZLE_NONE);
    CUtensorMap tm_v = make_map(enc, A_v, D_, S_, 8, 256, CU_TENSOR_MAP_SWIZZLE_NONE);

    cudaStream_t st = cudaStreamPerThread;
    cudaLaunchAttribute at[2];
    at[0].id = cudaLaunchAttributeProgrammaticStreamSerialization;
    at[0].val.programmaticStreamSerializationAllowed = 1;
    at[1].id = cudaLaunchAttributeClusterDimension;
    at[1].val.clusterDim.x = 2;
    at[1].val.clusterDim.y = 1;
    at[1].val.clusterDim.z = 1;
    {
        cudaLaunchConfig_t cfg = {};
        cfg.gridDim = dim3(D_ / CV_CH);
        cfg.blockDim = dim3(640);
        cfg.dynamicSmemBytes = CV_SMEM;
        cfg.stream = st;
        cfg.attrs = at;
        cfg.numAttrs = 1;
        cudaLaunchKernelEx(&cfg, conv_kernel, tm_k, tm_v, A_k, A_v, A_shk, A_ssk, A_ssD, w1, w3, A_q, act);
    }
    {
        cudaLaunchConfig_t cfg = {};
        cfg.gridDim = dim3(132);
        cfg.blockDim = dim3(384);
        cfg.dynamicSmemBytes = MEGA_SMEM;
        cfg.stream = st;
        cfg.attrs = at;
        cfg.numAttrs = 2;
        cudaLaunchKernelEx(&cfg, mega_kernel, tm, out, act);
    }
}
```

```cpp
#include <cuda_runtime.h>
#include <cuda_bf16.h>
#include <cuda.h>
#include <stdint.h>

typedef __nv_bfloat16 bf16;

constexpr int S_ = 2048;
constexpr int D_ = 1024;
constexpr int F_ = 3584;

constexpr int R_XA = 0, R_X1 = 256, R_H2 = 512, R_Y = 1536, R_H = 16384 + 8, R_HP = S_ + 8, R_END = R_H + 2 * R_HP;
__device__ __align__(1024) bf16 g_act[(size_t)(R_END + 1024) * D_];
__device__ __align__(16) float g_cpart[16 * (F_ + D_)];
__device__ __align__(16) float2 g_stats[6 * S_ * 8];

__device__ __forceinline__ float bfr(float x) { return __bfloat162float(__float2bfloat16_rn(x)); }
__device__ __forceinline__ uint32_t pack2(float lo, float hi) {
    __nv_bfloat162 v = __floats2bfloat162_rn(lo, hi);
    return *reinterpret_cast<uint32_t*>(&v);
}
__device__ __forceinline__ float lo2f(uint32_t v) { return __uint_as_float(v << 16); }
__device__ __forceinline__ float hi2f(uint32_t v) { return __uint_as_float(v & 0xffff0000u); }
__device__ __forceinline__ float frcp(float x) { float r; asm("rcp.approx.f32 %0, %1;" : "=f"(r) : "f"(x)); return r; }
__device__ __forceinline__ float fsqrt(float x) { float r; asm("sqrt.approx.f32 %0, %1;" : "=f"(r) : "f"(x)); return r; }
__device__ __forceinline__ uint32_t smem_u32(const void* p) { return (uint32_t)__cvta_generic_to_shared(p); }

__device__ __forceinline__ void mbar_init(uint32_t bar, uint32_t cnt) {
    asm volatile("mbarrier.init.shared::cta.b64 [%0], %1;" ::"r"(bar), "r"(cnt));
}
__device__ __forceinline__ void mbar_expect_tx(uint32_t bar, uint32_t bytes) {
    asm volatile("mbarrier.arrive.expect_tx.shared::cta.b64 _, [%0], %1;" ::"r"(bar), "r"(bytes) : "memory");
}
__device__ __forceinline__ void mbar_arrive(uint32_t bar) {
    asm volatile("mbarrier.arrive.shared::cta.b64 _, [%0];" ::"r"(bar) : "memory");
}
__device__ __forceinline__ void mbar_wait(uint32_t bar, uint32_t parity) {
    asm volatile(
        "{\n.reg .pred p;\n.reg .u32 n;\n"
        "mbarrier.try_wait.parity.shared::cta.b64 p, [%0], %1;\n"
        "@p bra LD;\n"
        "mov.u32 n, 0;\n"
        "LW:\n"
        "mbarrier.try_wait.parity.shared::cta.b64 p, [%0], %1;\n"
        "@p bra LD;\n"
        "add.u32 n, n, 1;\n"
        "setp.lt.u32 p, n, 0x400000;\n"
        "@p bra LW;\n"
        "LD:\n}\n"
        ::"r"(bar), "r"(parity) : "memory");
}
__device__ __forceinline__ void tma_load_2d(uint32_t dst, const CUtensorMap* tm, uint32_t bar, int c0, int c1) {
    asm volatile(
        "cp.async.bulk.tensor.2d.shared::cluster.global.mbarrier::complete_tx::bytes [%0], [%1, {%3, %4}], [%2];"
        ::"r"(dst), "l"((uint64_t)tm), "r"(bar), "r"(c0), "r"(c1) : "memory");
}
__device__ __forceinline__ void tma_load_2d_mc(uint32_t dst, const CUtensorMap* tm, uint32_t bar, int c0, int c1) {
    asm volatile(
        "cp.async.bulk.tensor.2d.shared::cluster.global.mbarrier::complete_tx::bytes.multicast::cluster [%0], [%1, {%3, %4}], [%2], %5;"
        ::"r"(dst), "l"((uint64_t)tm), "r"(bar), "r"(c0), "r"(c1), "h"((uint16_t)3) : "memory");
}
__device__ __forceinline__ void tma_prefetch_2d(const CUtensorMap* tm, int c0, int c1) {
    asm volatile("cp.async.bulk.prefetch.tensor.2d.L2.global.tile [%0, {%1, %2}];" ::"l"((uint64_t)tm), "r"(c0), "r"(c1) : "memory");
}
__device__ __forceinline__ void tma_store_2d(const CUtensorMap* tm, uint32_t src, int c0, int c1) {
    asm volatile("cp.async.bulk.tensor.2d.global.shared::cta.bulk_group [%0, {%2, %3}], [%1];"
                 ::"l"((uint64_t)tm), "r"(src), "r"(c0), "r"(c1) : "memory");
}
__device__ __forceinline__ void wgmma_fence() { asm volatile("wgmma.fence.sync.aligned;" ::: "memory"); }
__device__ __forceinline__ void wgmma_commit() { asm volatile("wgmma.commit_group.sync.aligned;" ::: "memory"); }
template <int N> __device__ __forceinline__ void wgmma_wait() { asm volatile("wgmma.wait_group.sync.aligned %0;" ::"n"(N) : "memory"); }
__device__ __forceinline__ void named_bar_arrive(int id, int n) { asm volatile("bar.arrive %0, %1;" ::"r"(id), "r"(n) : "memory"); }
__device__ __forceinline__ void named_bar_sync(int id, int n) { asm volatile("bar.sync %0, %1;" ::"r"(id), "r"(n) : "memory"); }

__device__ __forceinline__ void pdl_wait() { asm volatile("griddepcontrol.wait;" ::: "memory"); }
__device__ __forceinline__ void pdl_launch() { asm volatile("griddepcontrol.launch_dependents;" ::: "memory"); }

__device__ __forceinline__ uint32_t desc_a(uint32_t addr) { return ((addr & 0x3FFFF) >> 4) | (1u << 16); }
__device__ __forceinline__ uint32_t desc_b(uint32_t addr) { return ((addr & 0x3FFFF) >> 4) | (512u << 16); }

__device__ __forceinline__ void wgmma_m64n192k16(float (&d)[96], uint32_t descA, uint32_t descB) {
  asm volatile("{\n.reg .pred p;\n.reg .b64 da, db;\nsetp.eq.b32 p, 0, 0;\nmov.b64 da, {%96, %98};\nmov.b64 db, {%97, %98};\n"
    "wgmma.mma_async.sync.aligned.m64n192k16.f32.bf16.bf16 "
    "{%0, %1, %2, %3, %4, %5, %6, %7, %8, %9, %10, %11, %12, %13, %14, %15, %16, %17, %18, %19, %20, %21, %22, %23, %24, %25, %26, %27, %28, %29, %30, %31, %32, %33, %34, %35, %36, %37, %38, %39, %40, %41, %42, %43, %44, %45, %46, %47, %48, %49, %50, %51, %52, %53, %54, %55, %56, %57, %58, %59, %60, %61, %62, %63, %64, %65, %66, %67, %68, %69, %70, %71, %72, %73, %74, %75, %76, %77, %78, %79, %80, %81, %82, %83, %84, %85, %86, %87, %88, %89, %90, %91, %92, %93, %94, %95}, "
    "da, db, p, 1, 1, 0, 1;\n}\n"
    : "+f"(d[0]), "+f"(d[1]), "+f"(d[2]), "+f"(d[3]), "+f"(d[4]), "+f"(d[5]), "+f"(d[6]), "+f"(d[7]), "+f"(d[8]), "+f"(d[9]), "+f"(d[10]), "+f"(d[11]), "+f"(d[12]), "+f"(d[13]), "+f"(d[14]), "+f"(d[15]), "+f"(d[16]), "+f"(d[17]), "+f"(d[18]), "+f"(d[19]), "+f"(d[20]), "+f"(d[21]), "+f"(d[22]), "+f"(d[23]), "+f"(d[24]), "+f"(d[25]), "+f"(d[26]), "+f"(d[27]), "+f"(d[28]), "+f"(d[29]), "+f"(d[30]), "+f"(d[31]), "+f"(d[32]), "+f"(d[33]), "+f"(d[34]), "+f"(d[35]), "+f"(d[36]), "+f"(d[37]), "+f"(d[38]), "+f"(d[39]), "+f"(d[40]), "+f"(d[41]), "+f"(d[42]), "+f"(d[43]), "+f"(d[44]), "+f"(d[45]), "+f"(d[46]), "+f"(d[47]), "+f"(d[48]), "+f"(d[49]), "+f"(d[50]), "+f"(d[51]), "+f"(d[52]), "+f"(d[53]), "+f"(d[54]), "+f"(d[55]), "+f"(d[56]), "+f"(d[57]), "+f"(d[58]), "+f"(d[59]), "+f"(d[60]), "+f"(d[61]), "+f"(d[62]), "+f"(d[63]), "+f"(d[64]), "+f"(d[65]), "+f"(d[66]), "+f"(d[67]), "+f"(d[68]), "+f"(d[69]), "+f"(d[70]), "+f"(d[71]), "+f"(d[72]), "+f"(d[73]), "+f"(d[74]), "+f"(d[75]), "+f"(d[76]), "+f"(d[77]), "+f"(d[78]), "+f"(d[79]), "+f"(d[80]), "+f"(d[81]), "+f"(d[82]), "+f"(d[83]), "+f"(d[84]), "+f"(d[85]), "+f"(d[86]), "+f"(d[87]), "+f"(d[88]), "+f"(d[89]), "+f"(d[90]), "+f"(d[91]), "+f"(d[92]), "+f"(d[93]), "+f"(d[94]), "+f"(d[95])
    : "r"(descA), "r"(descB), "r"(0x40000040u));
}

__device__ __forceinline__ void wgmma_m64n256k16(float (&d)[128], uint32_t descA, uint32_t descB) {
  asm volatile("{\n.reg .pred p;\n.reg .b64 da, db;\nsetp.eq.b32 p, 0, 0;\nmov.b64 da, {%128, %130};\nmov.b64 db, {%129, %130};\n"
    "wgmma.mma_async.sync.aligned.m64n256k16.f32.bf16.bf16 "
    "{%0, %1, %2, %3, %4, %5, %6, %7, %8, %9, %10, %11, %12, %13, %14, %15, %16, %17, %18, %19, %20, %21, %22, %23, %24, %25, %26, %27, %28, %29, %30, %31, %32, %33, %34, %35, %36, %37, %38, %39, %40, %41, %42, %43, %44, %45, %46, %47, %48, %49, %50, %51, %52, %53, %54, %55, %56, %57, %58, %59, %60, %61, %62, %63, %64, %65, %66, %67, %68, %69, %70, %71, %72, %73, %74, %75, %76, %77, %78, %79, %80, %81, %82, %83, %84, %85, %86, %87, %88, %89, %90, %91, %92, %93, %94, %95, %96, %97, %98, %99, %100, %101, %102, %103, %104, %105, %106, %107, %108, %109, %110, %111, %112, %113, %114, %115, %116, %117, %118, %119, %120, %121, %122, %123, %124, %125, %126, %127}, "
    "da, db, p, 1, 1, 0, 1;\n}\n"
    : "+f"(d[0]), "+f"(d[1]), "+f"(d[2]), "+f"(d[3]), "+f"(d[4]), "+f"(d[5]), "+f"(d[6]), "+f"(d[7]), "+f"(d[8]), "+f"(d[9]), "+f"(d[10]), "+f"(d[11]), "+f"(d[12]), "+f"(d[13]), "+f"(d[14]), "+f"(d[15]), "+f"(d[16]), "+f"(d[17]), "+f"(d[18]), "+f"(d[19]), "+f"(d[20]), "+f"(d[21]), "+f"(d[22]), "+f"(d[23]), "+f"(d[24]), "+f"(d[25]), "+f"(d[26]), "+f"(d[27]), "+f"(d[28]), "+f"(d[29]), "+f"(d[30]), "+f"(d[31]), "+f"(d[32]), "+f"(d[33]), "+f"(d[34]), "+f"(d[35]), "+f"(d[36]), "+f"(d[37]), "+f"(d[38]), "+f"(d[39]), "+f"(d[40]), "+f"(d[41]), "+f"(d[42]), "+f"(d[43]), "+f"(d[44]), "+f"(d[45]), "+f"(d[46]), "+f"(d[47]), "+f"(d[48]), "+f"(d[49]), "+f"(d[50]), "+f"(d[51]), "+f"(d[52]), "+f"(d[53]), "+f"(d[54]), "+f"(d[55]), "+f"(d[56]), "+f"(d[57]), "+f"(d[58]), "+f"(d[59]), "+f"(d[60]), "+f"(d[61]), "+f"(d[62]), "+f"(d[63]), "+f"(d[64]), "+f"(d[65]), "+f"(d[66]), "+f"(d[67]), "+f"(d[68]), "+f"(d[69]), "+f"(d[70]), "+f"(d[71]), "+f"(d[72]), "+f"(d[73]), "+f"(d[74]), "+f"(d[75]), "+f"(d[76]), "+f"(d[77]), "+f"(d[78]), "+f"(d[79]), "+f"(d[80]), "+f"(d[81]), "+f"(d[82]), "+f"(d[83]), "+f"(d[84]), "+f"(d[85]), "+f"(d[86]), "+f"(d[87]), "+f"(d[88]), "+f"(d[89]), "+f"(d[90]), "+f"(d[91]), "+f"(d[92]), "+f"(d[93]), "+f"(d[94]), "+f"(d[95]), "+f"(d[96]), "+f"(d[97]), "+f"(d[98]), "+f"(d[99]), "+f"(d[100]), "+f"(d[101]), "+f"(d[102]), "+f"(d[103]), "+f"(d[104]), "+f"(d[105]), "+f"(d[106]), "+f"(d[107]), "+f"(d[108]), "+f"(d[109]), "+f"(d[110]), "+f"(d[111]), "+f"(d[112]), "+f"(d[113]), "+f"(d[114]), "+f"(d[115]), "+f"(d[116]), "+f"(d[117]), "+f"(d[118]), "+f"(d[119]), "+f"(d[120]), "+f"(d[121]), "+f"(d[122]), "+f"(d[123]), "+f"(d[124]), "+f"(d[125]), "+f"(d[126]), "+f"(d[127])
    : "r"(descA), "r"(descB), "r"(0x40000040u));
}

__device__ __forceinline__ void wgmma_m64n128k16(float (&d)[64], uint32_t descA, uint32_t descB) {
  asm volatile("{\n.reg .pred p;\n.reg .b64 da, db;\nsetp.eq.b32 p, 0, 0;\nmov.b64 da, {%64, %66};\nmov.b64 db, {%65, %66};\n"
    "wgmma.mma_async.sync.aligned.m64n128k16.f32.bf16.bf16 "
    "{%0, %1, %2, %3, %4, %5, %6, %7, %8, %9, %10, %11, %12, %13, %14, %15, %16, %17, %18, %19, %20, %21, %22, %23, %24, %25, %26, %27, %28, %29, %30, %31, %32, %33, %34, %35, %36, %37, %38, %39, %40, %41, %42, %43, %44, %45, %46, %47, %48, %49, %50, %51, %52, %53, %54, %55, %56, %57, %58, %59, %60, %61, %62, %63}, "
    "da, db, p, 1, 1, 0, 1;\n}\n"
    : "+f"(d[0]), "+f"(d[1]), "+f"(d[2]), "+f"(d[3]), "+f"(d[4]), "+f"(d[5]), "+f"(d[6]), "+f"(d[7]), "+f"(d[8]), "+f"(d[9]), "+f"(d[10]), "+f"(d[11]), "+f"(d[12]), "+f"(d[13]), "+f"(d[14]), "+f"(d[15]), "+f"(d[16]), "+f"(d[17]), "+f"(d[18]), "+f"(d[19]), "+f"(d[20]), "+f"(d[21]), "+f"(d[22]), "+f"(d[23]), "+f"(d[24]), "+f"(d[25]), "+f"(d[26]), "+f"(d[27]), "+f"(d[28]), "+f"(d[29]), "+f"(d[30]), "+f"(d[31]), "+f"(d[32]), "+f"(d[33]), "+f"(d[34]), "+f"(d[35]), "+f"(d[36]), "+f"(d[37]), "+f"(d[38]), "+f"(d[39]), "+f"(d[40]), "+f"(d[41]), "+f"(d[42]), "+f"(d[43]), "+f"(d[44]), "+f"(d[45]), "+f"(d[46]), "+f"(d[47]), "+f"(d[48]), "+f"(d[49]), "+f"(d[50]), "+f"(d[51]), "+f"(d[52]), "+f"(d[53]), "+f"(d[54]), "+f"(d[55]), "+f"(d[56]), "+f"(d[57]), "+f"(d[58]), "+f"(d[59]), "+f"(d[60]), "+f"(d[61]), "+f"(d[62]), "+f"(d[63])
    : "r"(descA), "r"(descB), "r"(0x40000040u));
}

template <int BN> struct WG;
template <> struct WG<128> { static __device__ __forceinline__ void mma(float (&d)[64], uint32_t a, uint32_t b) { wgmma_m64n128k16(d, a, b); } };
template <> struct WG<256> { static __device__ __forceinline__ void mma(float (&d)[128], uint32_t a, uint32_t b) { wgmma_m64n256k16(d, a, b); } };
template <> struct WG<192> { static __device__ __forceinline__ void mma(float (&d)[96], uint32_t a, uint32_t b) { wgmma_m64n192k16(d, a, b); } };

#define DBG_T(i)
__device__ __forceinline__ void fence_async_smem() { asm volatile("fence.proxy.async.shared::cta;" ::: "memory"); }
__device__ __forceinline__ void prefetch_tmap(const CUtensorMap* tm) { asm volatile("prefetch.tensormap [%0];" ::"l"((uint64_t)tm) : "memory"); }
__device__ __forceinline__ uint32_t mapa_u32(uint32_t addr, uint32_t cta) {
    uint32_t r;
    asm volatile("mapa.shared::cluster.u32 %0, %1, %2;" : "=r"(r) : "r"(addr), "r"(cta));
    return r;
}
__device__ __forceinline__ void mbar_arrive_cluster(uint32_t cluster_addr) {
    asm volatile("mbarrier.arrive.shared::cluster.b64 _, [%0];" ::"r"(cluster_addr) : "memory");
}
__device__ __forceinline__ bool elect_one() {
    uint32_t p;
    asm volatile("{\n.reg .pred P;\nelect.sync _|P, 0xffffffff;\nselp.u32 %0, 1, 0, P;\n}\n" : "=r"(p));
    return p != 0;
}
__device__ __forceinline__ void cluster_arrive_relaxed() { asm volatile("barrier.cluster.arrive.relaxed.aligned;" ::: "memory"); }
__device__ __forceinline__ void cluster_wait() { asm volatile("barrier.cluster.wait.acquire.aligned;" ::: "memory"); }

__device__ __forceinline__ uint32_t bsub2(uint32_t a, uint32_t b) {
    __nv_bfloat162 r = __hsub2(*reinterpret_cast<__nv_bfloat162*>(&a), *reinterpret_cast<__nv_bfloat162*>(&b));
    return *reinterpret_cast<uint32_t*>(&r);
}
__device__ __forceinline__ uint32_t bmul2(uint32_t a, uint32_t b) {
    __nv_bfloat162 r = __hmul2(*reinterpret_cast<__nv_bfloat162*>(&a), *reinterpret_cast<__nv_bfloat162*>(&b));
    return *reinterpret_cast<uint32_t*>(&r);
}
__device__ __forceinline__ uint32_t badd2(uint32_t a, uint32_t b) {
    __nv_bfloat162 r = __hadd2(*reinterpret_cast<__nv_bfloat162*>(&a), *reinterpret_cast<__nv_bfloat162*>(&b));
    return *reinterpret_cast<uint32_t*>(&r);
}
constexpr int BM = 128, BK = 64;
constexpr int R5_STAGE = 32768, R5_N = 5;
constexpr int R4_STAGE = 49152, R4_N = 4;
constexpr int R4B_STAGE = 40960;
constexpr int OFF_STG5 = 163840;
constexpr int OFF_EPI = 196608;
constexpr int OFF_BAR = OFF_EPI + 32768;
constexpr int OFF_RS = OFF_BAR + 256;
constexpr int OFF_CS = OFF_RS + 1024;
constexpr int MEGA_SMEM = OFF_CS + 1792;
enum { FL_XA = 0, FL_H = 2, FL_X1 = 4, FL_H2 = 6, FL_KINDS = 10 };
constexpr int FL_PITCH = 64;
constexpr int FL_WORDS = 2 * FL_KINDS * 16 * FL_PITCH;
__device__ unsigned int g_flag[FL_WORDS];
__device__ unsigned int g_ticket[9 * FL_PITCH];
__device__ __forceinline__ unsigned int* flag_ptr(int layer, int kind, int i) { return g_flag + ((layer * FL_KINDS + kind) * 16 + i) * FL_PITCH; }

__device__ __forceinline__ void wait_flag(const unsigned int* p, unsigned int target) {
    long long t0 = clock64();
    while (true) {
        unsigned int v;
        asm volatile("ld.relaxed.gpu.global.u32 %0, [%1];" : "=r"(v) : "l"(p) : "memory");
        if (v >= target) break;
        if (clock64() - t0 > 2000000000LL) break;
    }
    asm volatile("fence.acquire.gpu;" ::: "memory");
}
__device__ __forceinline__ void fence_proxy_async() {
    asm volatile("fence.proxy.async.global;" ::: "memory");
    asm volatile("fence.proxy.async.shared::cta;" ::: "memory");
}
__device__ __forceinline__ void stsm4(uint32_t addr, uint32_t r0, uint32_t r1, uint32_t r2, uint32_t r3) {
    asm volatile("stmatrix.sync.aligned.m8n8.x4.shared.b16 [%0], {%1,%2,%3,%4};" ::"r"(addr), "r"(r0), "r"(r1), "r"(r2), "r"(r3));
}
__device__ __forceinline__ uint4 lds128(uint32_t a) {
    uint4 v;
    asm volatile("ld.shared.v4.b32 {%0,%1,%2,%3}, [%4];" : "=r"(v.x), "=r"(v.y), "=r"(v.z), "=r"(v.w) : "r"(a) : "memory");
    return v;
}
__device__ __forceinline__ void stg128(void* p, uint4 v) {
    asm volatile("st.global.v4.b32 [%0], {%1,%2,%3,%4};" ::"l"(p), "r"(v.x), "r"(v.y), "r"(v.z), "r"(v.w) : "memory");
}
__device__ __forceinline__ float gelu_tanh_h(float hx) {
    float z = hx * fmaf(hx * hx, 8.0f * 0.035677408136300125f, 2.0f * 0.7978845608028654f);
    float t;
    asm("tanh.approx.f32 %0, %1;" : "=f"(t) : "f"(z));
    return fmaf(hx, t, hx);
}
__device__ __forceinline__ uint32_t gelu2h(uint32_t p) { return pack2(gelu_tanh_h(lo2f(p)), gelu_tanh_h(hi2f(p))); }
__device__ __forceinline__ uint4 gelu8h(uint4 v) { return make_uint4(gelu2h(v.x), gelu2h(v.y), gelu2h(v.z), gelu2h(v.w)); }

__device__ __forceinline__ void row_stats(const float2* p, float& mean, float& var) {
    float2 v[8];
#pragma unroll 1
    for (int n = 0; n < (1 << 20); n++) {
#pragma unroll
        for (int i = 0; i < 8; i++)
            asm volatile("{\n.reg .b64 t;\nld.relaxed.gpu.global.b64 t, [%2];\nmov.b64 {%0, %1}, t;\n}" : "=f"(v[i].x), "=f"(v[i].y) : "l"(p + 128 * i) : "memory");
        if (fminf(fminf(fminf(v[0].y, v[1].y), fminf(v[2].y, v[3].y)), fminf(fminf(v[4].y, v[5].y), fminf(v[6].y, v[7].y))) >= 0.f) break;
    }
    mean = (((v[0].x + v[1].x) + (v[2].x + v[3].x)) + ((v[4].x + v[5].x) + (v[6].x + v[7].x))) * 0.125f;
    float m2 = 0.f, d2 = 0.f;
#pragma unroll
    for (int i = 0; i < 8; i++) { m2 += v[i].y; d2 = fmaf(v[i].x - mean, v[i].x - mean, d2); }
    var = fmaf(128.0f, d2, m2) * (1.0f / D_);
}
struct RingState { uint32_t st, ph; };

#define DT(i)
#define DP(i)
#define GT(i)

template <int BN, int NST>
__device__ __forceinline__ void kblock(float (&acc)[BN / 2], uint32_t da, uint32_t db, uint32_t bfull, RingState& rs) {
    mbar_wait(bfull + 8 * rs.st, rs.ph);
    wgmma_fence();
#pragma unroll
    for (int k = 0; k < 4; k++) WG<BN>::mma(acc, da + k * 2, db + k * 128);
    wgmma_commit();
    if (++rs.st == NST) { rs.st = 0; rs.ph ^= 1; }
}
template <int BN, int NST, int STAGE>
__device__ __forceinline__ void mainloop(float (&acc)[BN / 2], int KB, uint32_t da0, uint32_t db0, uint32_t bfull, uint32_t rel, bool rel_on,
                                         RingState& rs, int dbg) {
    uint32_t prev = rs.st ? rs.st - 1 : NST - 1;
#pragma unroll 1
    for (int kk = 0; kk < KB; kk++) {
        const uint32_t cur = rs.st;
        kblock<BN, NST>(acc, da0 + cur * (STAGE / 16), db0 + cur * (STAGE / 16), bfull, rs);
        wgmma_wait<1>();
        if (rel_on) mbar_arrive_cluster(rel + 8 * prev);
        prev = cur;
    }
    wgmma_wait<0>();
#pragma unroll
    for (int i = 0; i < BN / 2; i++) asm volatile("" : "+f"(acc[i])::"memory");
    if (rel_on) mbar_arrive_cluster(rel + 8 * prev);
}
template <int N> __device__ __forceinline__ void zero_acc(float (&acc)[N]) {
#pragma unroll
    for (int i = 0; i < N; i++) acc[i] = 0.f;
}
__device__ __forceinline__ void ldsm4(uint32_t& r0, uint32_t& r1, uint32_t& r2, uint32_t& r3, uint32_t addr) {
    asm volatile("ldmatrix.sync.aligned.m8n8.x4.shared.b16 {%0,%1,%2,%3}, [%4];" : "=r"(r0), "=r"(r1), "=r"(r2), "=r"(r3) : "r"(addr));
}

__device__ __forceinline__ void ldsm4t(uint32_t& r0, uint32_t& r1, uint32_t& r2, uint32_t& r3, uint32_t addr) {
    asm volatile("ldmatrix.sync.aligned.m8n8.x4.trans.shared.b16 {%0,%1,%2,%3}, [%4];" : "=r"(r0), "=r"(r1), "=r"(r2), "=r"(r3) : "r"(addr));
}

struct MegaMaps {
    CUtensorMap q, act;
    CUtensorMap w1, w2, w3, w4;
};

__global__ void __cluster_dims__(2, 1, 1) __launch_bounds__(384, 1)
mega_kernel(const __grid_constant__ MegaMaps tm, bf16* __restrict__ outp, bf16* act) {
    extern __shared__ __align__(1024) uint8_t sgen[];
    const uint32_t sbase = smem_u32(sgen);
    DT(0);
    GT(2);
    const int warp = __shfl_sync(0xffffffffu, threadIdx.x >> 5, 0), lane = threadIdx.x & 31;
    const int rank = blockIdx.x & 1;
    const uint32_t s_bar = sbase + OFF_BAR;
    const uint32_t f5 = s_bar, e5 = s_bar + 48, f4 = s_bar + 96, e4 = s_bar + 128;
    const uint32_t b_rfull = s_bar + 176, b_stg = s_bar + 184, b_h2 = s_bar + 192;
    const uint32_t s_epi = sbase + OFF_EPI, s_stg = sbase + OFF_STG5;

    if (threadIdx.x == 256) {
        for (int i = 0; i < R5_N; i++) { mbar_init(f5 + 8 * i, 1); mbar_init(e5 + 8 * i, 4); }
        for (int i = 0; i < R4_N; i++) { mbar_init(f4 + 8 * i, 1); mbar_init(e4 + 8 * i, 4); }
        mbar_init(b_rfull, 1); mbar_init(b_stg, 8);
        for (int i = 1; i < 4; i++) mbar_init(b_h2 + 8 * i, 1);
        for (int i = 0; i < 6; i++) reinterpret_cast<uint32_t*>(sgen + OFF_BAR + 224)[i] = 0;
        asm volatile("fence.mbarrier_init.release.cluster;" ::: "memory");
        fence_async_smem();
        prefetch_tmap(&tm.act);
    }
    if (threadIdx.x == 288 && rank == 0) {
        uint32_t smid;
        asm volatile("mov.u32 %0, %%smid;" : "=r"(smid));
        const int t = smid >> 1;
        int team = t < 32 ? t & 7 : t < 60 ? 1 + (t - 32) % 7 : t < 62 ? t - 54 : 0;
        int slot = atomicAdd(g_ticket + team * FL_PITCH, 1u);
        atomicAdd(g_ticket + 8 * FL_PITCH, 1u);
        if (slot >= 8) {
            const long long t0 = clock64();
            while (*(volatile unsigned int*)(g_ticket + 8 * FL_PITCH) < gridDim.x / 2 && clock64() - t0 < 100000) {}
            for (team = 0; team < 8; team++)
                if ((slot = atomicAdd(g_ticket + team * FL_PITCH, 1u)) < 8) break;
        }
        const uint32_t role = team * 8 + slot, ra = s_bar + 192;
        asm volatile("st.shared::cluster.u32 [%0], %1;" ::"r"(mapa_u32(ra, 0)), "r"(role) : "memory");
        asm volatile("st.shared::cluster.u32 [%0], %1;" ::"r"(mapa_u32(ra, 1)), "r"(role) : "memory");
        asm volatile("fence.acq_rel.cluster;" ::: "memory");
    }
    __syncwarp();
    cluster_arrive_relaxed();
    cluster_wait();
    const int role = *reinterpret_cast<const volatile int*>(sgen + OFF_BAR + 192);
    if (role >= 64) return;
    const int bi = (role >> 3) * 2 + rank, bj = role & 7, m0 = bi * BM, tb = (role >> 3) * 2048 + rank * 128;
    if (threadIdx.x == 256) {
        mbar_expect_tx(b_rfull, 32768);
        tma_load_2d(s_epi, &tm.q, b_rfull, bj * 128, m0);
        tma_load_2d(s_epi + 16384, &tm.q, b_rfull, bj * 128 + 64, m0);
    }

    if (warp >= 8) {
        asm volatile("setmaxnreg.dec.sync.aligned.u32 72;");
        if (warp == 8) { if (elect_one()) {
            int s5 = 0, s4 = 0;
            uint32_t p5 = 31, p4 = 1;
            auto putB = [&](const CUtensorMap* tB, int kc, uint32_t bytes) {
                const uint32_t full = f5 + 8 * s5;
                mbar_wait(full + 48, (p5 >> s5) & 1);
                mbar_expect_tx(full, bytes);
                tma_load_2d_mc(sbase + 16384 + rank * 8192 + s5 * R5_STAGE, tB, full, bj * 128 + rank * 64, kc);
                p5 ^= 1u << s5;
            };
            auto putA = [&](int c, int r) {
                tma_load_2d(sbase + s5 * R5_STAGE, &tm.act, f5 + 8 * s5, c, r);
                if (++s5 == R5_N) s5 = 0;
            };
            pdl_wait();
            prefetch_tmap(&tm.w1); prefetch_tmap(&tm.w2); prefetch_tmap(&tm.w3); prefetch_tmap(&tm.w4);
            auto own_first = [&](int it) {
                const int hf = it >= 9, c = it - 2 - 7 * hf;
                return (it < 2 ? 2 * bj + it : 2 * (c + (c >= bj)) + hf) * BK;
            };
            const unsigned int nh = (bi == 0 || bi == 15) ? 16 : 24;
#pragma unroll 1
            for (int layer = 0; layer < 2; layer++) {
                if (layer == 0) { mbar_arrive(f5); p5 ^= 1; }
                mbar_wait(e5 + 8, (p5 >> 1) & 1);
                mbar_expect_tx(f5 + 8, 32768);
                tma_load_2d(sbase + R5_STAGE, &tm.act, f5 + 8, (bj >> 1) * 256 + rank * 128, R_Y + (tb & ~255) + (bj & 1) * 128);
                tma_load_2d(sbase + R5_STAGE + 16384, &tm.act, f5 + 8, (bj >> 1) * 256 + rank * 128 + 64, R_Y + (tb & ~255) + (bj & 1) * 128);
                p5 ^= 2;
                s5 = 2;
#pragma unroll 1
                for (int kk = 0; kk < 4; kk++) { putB(&tm.w1, own_first(kk), kk < 2 ? 16384 : R5_STAGE); if (++s5 == R5_N) s5 = 0; }
                s5 = 4;
#pragma unroll 1
                for (int kk = 2; kk < 16; kk++) {
                    const int kc = own_first(kk);
                    if (kk >= 4) putB(&tm.w1, kc, R5_STAGE);
                    if (kk == 2 || kk == 9) {
                        wait_flag(flag_ptr(layer, FL_XA + (kk & 1), bi), 8);
                        DP(8 * (FL_XA + (kk & 1)) + 3);
                        fence_proxy_async();
                        DP(8 * (FL_XA + (kk & 1)) + 4);
                    }
                    putA(kc, R_XA + tb);
                }
                mbar_wait(e5 + 24, (p5 >> 3) & 1);
                mbar_arrive(f5 + 24);
                p5 ^= 8;
                s5 = 4;
#pragma unroll 1
                for (int kk = 0; kk < 5; kk++) { putB(&tm.w2, kk * 2 * BK, R5_STAGE); if (++s5 == R5_N) s5 = 0; }
#pragma unroll 1
                for (int kk = 0; kk < 16; kk++) {
                    const int kc = ((kk & 7) * 2 + (kk >> 3)) * BK;
                    if (kk >= 5) putB(&tm.w2, kc, R5_STAGE);
                    if ((kk & 7) == 0) {
                        wait_flag(flag_ptr(layer, FL_H + (kk >> 3), bi), nh);
                        DP(8 * (FL_H + (kk >> 3)) + 3);
                        fence_proxy_async();
                        DP(8 * (FL_H + (kk >> 3)) + 4);
                    }
                    putA(kc, R_H + layer * R_HP + m0 + (int)((0x4031u >> ((kk & 6) << 1)) & 7) - 2);
                }
#pragma unroll 1
                for (int it = 0; it < 32; it++) {
                    const int kc = it >= 16 ? (it - 16) * BK : own_first(it);
                    const int nb = it < 16 ? 4 : 3, n0 = bj * 448 + (it < 16 ? 0 : 256);
                    if (it < 3) {
                        const int i = it * 3 >> 1;
                        mbar_wait(e5 + 8 * i, (p5 >> i) & 1);
                        mbar_wait(e5 + 8 * i + 8, (p5 >> (i + 1)) & 1);
                    }
                    mbar_wait(e4 + 8 * s4, p4);
                    uint32_t sa = sbase + s4 * (it < 16 ? R4_STAGE : R4B_STAGE), full = f4 + 8 * s4;
                    mbar_expect_tx(full, (it < 2 ? 0 : 16384) + nb * 8192);
#pragma unroll 1
                    for (int j = (it ^ rank) & 1; j < nb; j += 2) tma_load_2d_mc(sa + 16384 + j * 8192, &tm.w3, full, n0 + j * 64, kc);
                    if (it == 3 || it == 9) {
                        wait_flag(flag_ptr(layer, FL_X1 + (it >> 3), bi), 8);
                        DP(8 * (FL_X1 + (it >> 3)) + 3);
                        fence_proxy_async();
                        DP(8 * (FL_X1 + (it >> 3)) + 4);
                        if (it == 3) tma_load_2d(sbase + 2 * R4_STAGE, &tm.act, f4 + 16, own_first(2), R_X1 + tb);
                    }
                    if (it >= 3) tma_load_2d(sa, &tm.act, full, kc, R_X1 + tb);
                    if (++s4 == R4_N) { s4 = 0; p4 ^= 1; }
                }
                wait_flag(flag_ptr(layer, FL_H2, bi), 8);
                fence_proxy_async();
                s5 = 0;
#pragma unroll 1
                for (int j = 0; j < 7; j++) {
                    if (j > 0 && (j & 1) == 0) {
                        mbar_wait(b_h2 + 4 * j, layer);
                        fence_proxy_async();
                    }
                    const int ra = R_H2 + (j >> 1) * 256 + tb;
#pragma unroll 1
                    for (int b = 0; b < 8; b++) {
                        if (j == 0 && b < R4_N) mbar_wait(e4 + 8 * b, p4);
                        putB(&tm.w4, (7 * b + j) * BK, R5_STAGE);
                        putA(((j & 1) * 8 + b) * BK, ra);
                    }
                }
            }
        } } else {
            pdl_wait();
#pragma unroll 1
            for (int layer = 0; layer < 2; layer++) {
                if (warp == 10) {
#pragma unroll 1
                    for (int kind = 0; kind < 6; kind += 2) {
                        const uint32_t src = kind == FL_H ? s_stg : s_epi;
                        const int r = kind == FL_H ? R_H + layer * R_HP + m0 : (kind == FL_XA ? R_XA : R_X1) + tb;
#pragma unroll 1
                        for (int hf = 0; hf < 2; hf++) {
                            named_bar_sync(5 + hf, 288);
                            if (lane == 0) {
                                DP(8 * (kind + hf));
                                tma_store_2d(&tm.act, src + hf * 16384, bj * 128 + hf * 64, r);
                                asm volatile("cp.async.bulk.commit_group;" ::: "memory");
                            }
                            __syncwarp();
                        }
                        if (lane == 0) {
#pragma unroll 1
                            for (int hf = 0; hf < 2; hf++) {
                                if (hf == 0) asm volatile("cp.async.bulk.wait_group 1;" ::: "memory");
                                else asm volatile("cp.async.bulk.wait_group 0;" ::: "memory");
                                DP(8 * (kind + hf) + 1);
                                DP(8 * (kind + hf) + 2);
                                unsigned int* fp = flag_ptr(layer, kind + hf, bi);
                                asm volatile("red.relaxed.gpu.global.add.u32 [%0], 1;" ::"l"(fp) : "memory");
                                if (kind == FL_H) {
                                    if (bi > 0) asm volatile("red.relaxed.gpu.global.add.u32 [%0], 1;" ::"l"(fp - FL_PITCH) : "memory");
                                    if (bi < 15) asm volatile("red.relaxed.gpu.global.add.u32 [%0], 1;" ::"l"(fp + FL_PITCH) : "memory");
                                }
                            }
                        }
                        __syncwarp();
                    }
                } else if (warp == 9) {
                    uint32_t* rs = reinterpret_cast<uint32_t*>(sgen + OFF_RS);
                    float* cs = reinterpret_cast<float*>(sgen + OFF_CS);
#pragma unroll 1
                    for (int which = 0; which < 2; which++) {
                        if (lane == 0 && (layer | which)) wait_flag(flag_ptr(layer, which == 0 ? FL_XA : FL_X1, bi), 8);
                        __syncwarp();
#pragma unroll 1
                        for (int c = (which == 0 && layer == 0 ? 0 : 256) + lane * 4; c < (which == 0 ? 384 : 448); c += 128) {
                            const float* cp = g_cpart + (which == 0 && c >= 256 ? F_ + bj * 128 - 256 : bj * 448) + c;
                            float4 a = make_float4(0.f, 0.f, 0.f, 0.f);
#pragma unroll
                            for (int r0 = 0; r0 < 16; r0 += 8) {
                                float4 v[8];
#pragma unroll
                                for (int r = 0; r < 8; r++) v[r] = __ldcg(reinterpret_cast<const float4*>(cp + (r0 + r) * (F_ + D_)));
#pragma unroll
                                for (int r = 0; r < 8; r++) { a.x += v[r].x; a.y += v[r].y; a.z += v[r].z; a.w += v[r].w; }
                            }
                            *reinterpret_cast<float4*>(cs + c) = a;
                        }
#pragma unroll 1
                        for (int i = 0; i < 4; i++) {
                            const int r = i * 32 + lane;
                            float mean, var;
                            row_stats(g_stats + (3 * layer + 1 + which) * S_ * 8 + bi * 1024 + r, mean, var);
                            const uint32_t c0 = pack2(mean, fsqrt(bfr(bfr(var) + 1e-5f)));
                            rs[r] = c0;
                            const float rd = frcp(hi2f(c0));
                            rs[128 + r] = pack2((mean - lo2f(c0)) * rd, fsqrt(bfr(bfr(var * rd * rd) + 1e-5f)));
                        }
                        __syncwarp();
                        named_bar_arrive(3, 288);
                    }
                }
                const uint32_t s_cnt = s_bar + 224;
                auto ticket = [&](uint32_t a) {
                    uint32_t v = 0;
                    if (lane == 0) asm volatile("atom.acq_rel.cta.shared.add.u32 %0, [%1], 1;" : "=r"(v) : "r"(a) : "memory");
                    return v;
                };
                mbar_wait(b_stg, 0);
                int u = __shfl_sync(0xffffffffu, ticket(s_cnt + 16 + 4 * layer), 0), step = 0;
#pragma unroll 1
                while (true) {
#pragma unroll 1
                    for (; step < 5 && u >= (int)((0x3830201810ull >> (8 * step)) & 255); step++) {
                        if (step == 1) { named_bar_arrive(4, 352); continue; }
                        const int part = step ? step - 1 : 0;
                        __syncwarp();
                        if (ticket(s_cnt + 4 * part) == 3 * layer + 2) {
                            asm volatile("fence.release.gpu;" ::: "memory");
                            unsigned int* fp = flag_ptr(layer, FL_H2 + part, bi);
                            asm volatile("red.relaxed.gpu.global.add.u32 [%0], 1;" ::"l"(fp) : "memory");
                            if (part > 0) { wait_flag(fp, 8); mbar_arrive(b_h2 + 8 * part); }
                        }
                        __syncwarp();
                        if (step == 2) mbar_wait(b_stg, 1);
                    }
                    if (u >= 56) break;
                    const uint32_t un = ticket(s_cnt + 16 + 4 * layer);
                    const int job = u >> 3, r = (u & 7) * 16 + (lane >> 3);
                    const uint32_t sp = sbase + ((job & 2) ? OFF_STG5 : OFF_EPI) + r * 256 + (job & 1) * 128;
                    bf16* gp = act + (size_t)(R_H2 + (job >> 1) * 256 + tb + r) * D_ + ((job & 1) * 8 + bj) * 64 + (lane & 7) * 8;
                    uint4 v[4];
#pragma unroll
                    for (int e = 0; e < 4; e++) v[e] = lds128(sp + e * 1024 + (((lane & 7) ^ ((r + 4 * e) & 7)) << 4));
#pragma unroll
                    for (int e = 0; e < 4; e++) stg128(gp + 4 * e * D_, gelu8h(v[e]));
                    u = __shfl_sync(0xffffffffu, un, 0);
                }
            }
        }
        __syncwarp();
        asm volatile("barrier.cluster.arrive.relaxed.aligned;\nbarrier.cluster.wait.acquire.aligned; // helpers" ::: "memory");
    } else {
        asm volatile("setmaxnreg.inc.sync.aligned.u32 216;");
        const int tid = threadIdx.x;
        const int wg = warp >> 2;
        const bool rel_on = (tid & 95) == 0;
        const uint32_t rel5 = mapa_u32(e5, (warp & 1) ^ rank), rel4 = rel5 + (e4 - e5);
        const uint32_t da0 = desc_a(sbase + wg * 8192), db0 = desc_b(sbase + BM * BK * 2), dae = da0 + OFF_EPI / 16;
        auto skip5 = [&](RingState& rs) {
            if (rel_on) mbar_arrive_cluster(rel5 + 8 * rs.st);
            rs.st++;
        };
        const int t = lane & 3;
        const int row = warp * 16 + (lane >> 2);
        const uint32_t st_w = (uint32_t)((warp * 16 + ((lane >> 3) & 1) * 8 + (lane & 7)) * 256 + (((lane >> 4) ^ (lane & 7)) << 4));
        const uint32_t fr = (uint32_t)((warp * 16 + ((lane >> 3) & 1) * 8 + (lane & 7)) * 128 + (((lane >> 4) ^ (lane & 7)) << 4));
        auto copy_out = [&](bf16* dst, uint32_t src) {
            const int r = warp * 16 + (lane >> 4);
            bf16* ox = dst + (size_t)(m0 + r) * D_ + bj * 128 + (lane & 15) * 8;
            const uint32_t ra = src + ((lane & 15) >> 3) * 16384 + r * 128;
            uint4 v[8];
#pragma unroll
            for (int it = 0; it < 8; it++) v[it] = lds128(ra + it * 256 + (((lane & 7) ^ ((2 * it + (lane >> 4)) & 7)) << 4));
#pragma unroll
            for (int it = 0; it < 8; it++) *reinterpret_cast<uint4*>(ox + (size_t)it * 2 * D_) = v[it];
        };
        auto put_stats = [&](const uint32_t (&w)[32], int which) {
            float sm[2] = {0.f, 0.f}, sq[2] = {0.f, 0.f};
#pragma unroll
            for (int e = 0; e < 32; e++) {
                const float e0 = lo2f(w[e]), e1 = hi2f(w[e]);
                sm[e & 1] += e0 + e1; sq[e & 1] = fmaf(e0, e0, fmaf(e1, e1, sq[e & 1]));
            }
#pragma unroll
            for (int of = 1; of < 4; of <<= 1)
#pragma unroll
                for (int e = 0; e < 2; e++) { sm[e] += __shfl_xor_sync(0xffffffffu, sm[e], of); sq[e] += __shfl_xor_sync(0xffffffffu, sq[e], of); }
            if (t < 2) {
                const float s1 = t ? sm[1] : sm[0], q1 = t ? sq[1] : sq[0], mu = s1 * (1.0f / 128);
                asm volatile("{\n.reg .b64 t;\nmov.b64 t, {%1, %2};\nst.relaxed.gpu.global.b64 [%0], t;\n}"
                             ::"l"(g_stats + which * S_ * 8 + (bi * 8 + bj) * 128 + row + 8 * t), "f"(mu), "f"(fmaxf(q1 - s1 * mu, 0.f)) : "memory");
            }
        };
        const float* csp = reinterpret_cast<const float*>(sgen + OFF_CS) + 2 * t;
        float mrow[2], rrow[2];
        const uint32_t* rsp = reinterpret_cast<const uint32_t*>(sgen + OFF_RS) + row;
        auto row_consts = [&](bool twice) {
#pragma unroll
            for (int e = 0; e < 2; e++) {
                const uint32_t q0 = rsp[8 * e], q1 = rsp[128 + 8 * e];
                mrow[e] = twice ? fmaf(lo2f(q1), hi2f(q0), lo2f(q0)) : lo2f(q0);
                rrow[e] = 0.5f * frcp(twice ? hi2f(q0) * hi2f(q1) : hi2f(q0));
            }
        };
        auto stage = [&](const float* acc, uint32_t dst, int j0, float2 (&cs)[8], const float* cnext) {
            float2 cn[8];
#pragma unroll
            for (int e = 0; e < 8; e++) cn[e] = *reinterpret_cast<const float2*>(cnext + 8 * e);
#pragma unroll
            for (int j = 0; j < 8; j += 2) {
                uint32_t w[4];
#pragma unroll
                for (int e = 0; e < 2; e++) {
                    const float* a = acc + 4 * (j + e);
                    w[2 * e] = pack2(fmaf(-mrow[0], cs[j + e].x, a[0]) * rrow[0], fmaf(-mrow[0], cs[j + e].y, a[1]) * rrow[0]);
                    w[2 * e + 1] = pack2(fmaf(-mrow[1], cs[j + e].x, a[2]) * rrow[1], fmaf(-mrow[1], cs[j + e].y, a[3]) * rrow[1]);
                }
                stsm4((dst + st_w) ^ (((j0 + j) & 15) << 4), w[0], w[1], w[2], w[3]);
            }
#pragma unroll
            for (int e = 0; e < 8; e++) cs[e] = cn[e];
        };
        RingState r5{0, 0}, r4{0, 0};
        skip5(r5);
        DT(1);
        uint32_t x[32];
        mbar_wait(b_rfull, 0);
#pragma unroll
        for (int jp = 0; jp < 8; jp++) ldsm4(x[4 * jp], x[4 * jp + 1], x[4 * jp + 2], x[4 * jp + 3], s_epi + (fr ^ ((jp & 3) << 5)) + (jp >> 2) * 16384);
#pragma unroll 1
        for (int layer = 0; layer < 2; layer++) {
            {
                DT(2 + 24 * layer);
                if (layer == 1) put_stats(x, 3);
                else pdl_wait();
                DT(20 + 24 * layer);
                DT(22 + 24 * layer);
                uint32_t mb[2];
                float rd[2];
                {
                    float mean, var;
                    row_stats(g_stats + 3 * layer * S_ * 8 + bi * 1024 + warp * 16 + (lane & 15), mean, var);
                    __syncwarp();
                    const float r1 = frcp(bfr(fsqrt(bfr(bfr(var) + 1e-5f))));
                    const uint32_t m1 = pack2(mean, mean);
#pragma unroll
                    for (int e = 0; e < 2; e++) { mb[e] = __shfl_sync(0xffffffffu, m1, (lane >> 2) + 8 * e); rd[e] = __shfl_sync(0xffffffffu, r1, (lane >> 2) + 8 * e); }
                }
                DT(21 + 24 * layer);
                mbar_wait(f5 + 8, r5.ph);
                if (layer == 0) GT(3);
                const uint32_t ya = sbase + R5_STAGE + wg * 16384 + ((lane >> 4) * 8 + (lane & 7)) * 128 + ((((warp & 3) * 2 + ((lane >> 3) & 1)) ^ (lane & 7)) << 4);
                uint32_t y[16];
#pragma unroll
                for (int e = 0; e < 32; e++) {
                    if ((e & 15) == 0) {
#pragma unroll
                        for (int jp = 0; jp < 4; jp++) ldsm4t(y[4 * jp], y[4 * jp + 1], y[4 * jp + 2], y[4 * jp + 3], ya + jp * 2048 + e * 512);
                    }
                    const uint32_t d = bsub2(x[e], mb[e & 1]);
                    x[e] = badd2(x[e], bmul2(pack2(lo2f(d) * rd[e & 1], hi2f(d) * rd[e & 1]), y[e & 15]));
                    if ((e & 3) == 3) stsm4(s_epi + (fr ^ (((e >> 2) & 3) << 5)) + (e >> 4) * 16384, x[e - 3], x[e - 2], x[e - 1], x[e]);
                    if ((e & 15) == 15) { fence_async_smem(); named_bar_arrive(5 + (e >> 4), 288); }
                }
                DT(19 + 24 * layer);
                named_bar_sync(9 + wg, 128);
                skip5(r5);
                DT(3 + 24 * layer);
            }
            {
                float acc[64];
                zero_acc(acc);
                kblock<128, R5_N>(acc, dae, db0 + 2 * (R5_STAGE / 16), f5, r5);
                kblock<128, R5_N>(acc, dae + 1024, db0 + 3 * (R5_STAGE / 16), f5, r5);
                put_stats(x, 3 * layer + 1);
                wgmma_wait<1>();
                if (rel_on) mbar_arrive_cluster(rel5 + 16);
                mainloop<128, R5_N, R5_STAGE>(acc, 14, da0, db0, f5, rel5, rel_on, r5, 15 + 24 * layer);
                DT(4 + 24 * layer);
                named_bar_sync(3, 288);
                row_consts(true);
                float2 cs[8];
#pragma unroll
                for (int j = 0; j < 16; j += 2) {
                    if ((j & 7) == 0) {
#pragma unroll
                        for (int e = 0; e < 8; e++) cs[e] = *reinterpret_cast<const float2*>(csp + 256 + 8 * (j + e));
                    }
                    uint32_t w[4];
#pragma unroll
                    for (int e = 0; e < 4; e++) {
                        const float* a = acc + 4 * j + 2 * e;
                        const float2 c = cs[(j & 7) + (e >> 1)];
                        w[e] = pack2(gelu_tanh_h(fmaf(-mrow[e & 1], c.x, a[0]) * rrow[e & 1]), gelu_tanh_h(fmaf(-mrow[e & 1], c.y, a[1]) * rrow[e & 1]));
                    }
                    stsm4(s_stg + (fr ^ ((j & 7) << 4)) + (j >> 3) * 16384, w[0], w[1], w[2], w[3]);
                    if ((j & 7) == 6) { fence_async_smem(); named_bar_arrive(5 + (j >> 3), 288); }
                }
                DT(5 + 24 * layer);
            }
            {
                float acc[64];
                zero_acc(acc);
                mbar_wait(f5 + 24, r5.ph);
                skip5(r5);
                kblock<128, R5_N>(acc, da0 + 4 * (R5_STAGE / 16), db0 + 4 * (R5_STAGE / 16), f5, r5);
                DT(16 + 24 * layer);
                mainloop<128, R5_N, R5_STAGE>(acc, 15, da0, db0, f5, rel5, rel_on, r5, -1);
                DT(6 + 24 * layer);
                uint32_t mb[2];
                float rd[2];
#pragma unroll
                for (int j = 0; j < 16; j += 2) {
                    if ((j & 7) == 0) {
#pragma unroll
                        for (int e = 0; e < 2; e++) { const uint32_t q0 = rsp[8 * e]; mb[e] = (q0 & 0xffffu) * 0x10001u; rd[e] = frcp(hi2f(q0)); }
                    }
                    uint32_t w[4];
#pragma unroll
                    for (int e = 0; e < 4; e++) {
                        const uint32_t d = bsub2(x[2 * j + e], mb[e & 1]);
                        w[e] = badd2(pack2(lo2f(d) * rd[e & 1], hi2f(d) * rd[e & 1]), pack2(acc[4 * j + 2 * e], acc[4 * j + 2 * e + 1]));
                        x[2 * j + e] = badd2(x[2 * j + e], w[e]);
                    }
                    stsm4(s_epi + (fr ^ ((j & 7) << 4)) + (j >> 3) * 16384, w[0], w[1], w[2], w[3]);
                    if ((j & 7) == 6) { fence_async_smem(); named_bar_arrive(5 + (j >> 3), 288); }
                }
                named_bar_sync(9 + wg, 128);
                DT(7 + 24 * layer);
                if (layer == 0) GT(7);
            }
            {
                float2 cs[8];
                {
                    float acc[128];
                    zero_acc(acc);
                    kblock<256, R4_N>(acc, dae, db0, f4, r4);
                    kblock<256, R4_N>(acc, dae + 1024, db0 + R4_STAGE / 16, f4, r4);
                    {
                        uint32_t w[32];
#pragma unroll
                        for (int jp = 0; jp < 8; jp++) ldsm4(w[4 * jp], w[4 * jp + 1], w[4 * jp + 2], w[4 * jp + 3], s_epi + (fr ^ ((jp & 3) << 5)) + (jp >> 2) * 16384);
                        put_stats(w, 3 * layer + 2);
                    }
                    wgmma_wait<1>();
                    if (rel_on) mbar_arrive_cluster(rel4);
                    mainloop<256, R4_N, R4_STAGE>(acc, 14, da0, db0, f4, rel4, rel_on, r4, 17 + 24 * layer);
                    DT(8 + 24 * layer);
                    named_bar_sync(3, 288);
                    row_consts(false);
#pragma unroll
                    for (int e = 0; e < 8; e++) cs[e] = *reinterpret_cast<const float2*>(csp + 8 * e);
#pragma unroll
                    for (int j = 0; j < 32; j += 8) stage(acc + 4 * j, j < 16 ? s_epi : s_stg, j, cs, csp + 8 * (j + 8));
                    __syncwarp();
                if (lane == 0) mbar_arrive(b_stg);
                }
                DT(9 + 24 * layer);
                float acc[96];
                zero_acc(acc);
                kblock<192, R4_N>(acc, da0, db0, f4, r4);
                mainloop<192, R4_N, R4B_STAGE>(acc, 15, da0, db0, f4, rel4, rel_on, r4, -1);
                DT(10 + 24 * layer);
                named_bar_sync(4, 352);
#pragma unroll
                for (int j = 0; j < 24; j += 8) stage(acc + 4 * j, j < 16 ? s_epi : s_stg, j, cs, csp + 256 + 8 * (j < 16 ? j + 8 : 0));
                __syncwarp();
                if (lane == 0) mbar_arrive(b_stg);
                DT(11 + 24 * layer);
            }
            {
                float acc[64];
#pragma unroll
                for (int i = 0; i < 32; i++) asm volatile("shl.b32 %0, %2, 16;\nand.b32 %1, %2, 0xffff0000;" : "=f"(acc[2 * i]), "=f"(acc[2 * i + 1]) : "r"(x[i]));
                kblock<128, R5_N>(acc, da0, db0, f5, r5);
                DT(18 + 24 * layer);
                mainloop<128, R5_N, R5_STAGE>(acc, 55, da0, db0, f5, rel5, rel_on, r5, 62 - 40 * (layer ^ 1));
                DT(12 + 24 * layer);
#pragma unroll
                for (int i = 0; i < 32; i++) x[i] = pack2(acc[2 * i], acc[2 * i + 1]);
                DT(13 + 24 * layer);
                if (layer == 0) GT(6);
                DT(14 + 24 * layer);
            }
        }
#pragma unroll
        for (int jp = 0; jp < 8; jp++) stsm4(s_epi + (fr ^ ((jp & 3) << 5)) + (jp >> 2) * 16384, x[4 * jp], x[4 * jp + 1], x[4 * jp + 2], x[4 * jp + 3]);
        __syncwarp();
        copy_out(outp, s_epi);
        DT(38);
        GT(4);
        cluster_arrive_relaxed();
        cluster_wait();
    }
}

constexpr int CV_CH = 8;
constexpr int CV_UPITCH = 72;
constexpr int CV_UROWS = 40;
constexpr int CV_U_BYTES = CV_UROWS * CV_UPITCH * 2;
constexpr int CV_P_WORDS = 2048 + 16;
constexpr int CV_P_BYTES = CV_P_WORDS * 4;
constexpr int CV_Y_BYTES = 8 * CV_UPITCH * 2;
constexpr int CV_SMEM = CV_CH * (CV_U_BYTES + CV_P_BYTES + CV_Y_BYTES) + 2 * 8 * 16 * 32 * 4 + 128 + (128 + 2048 * 16) + 2048 * 16;

__device__ __forceinline__ void mma16816(float (&d)[4], uint32_t a0, uint32_t a1, uint32_t a2, uint32_t a3, uint32_t b0, uint32_t b1) {
    asm volatile("mma.sync.aligned.m16n8k16.row.col.f32.bf16.bf16.f32 {%0,%1,%2,%3}, {%4,%5,%6,%7}, {%8,%9}, {%0,%1,%2,%3};"
                 : "+f"(d[0]), "+f"(d[1]), "+f"(d[2]), "+f"(d[3]) : "r"(a0), "r"(a1), "r"(a2), "r"(a3), "r"(b0), "r"(b1));
}
__device__ __forceinline__ void stsm4t(uint32_t addr, uint32_t r0, uint32_t r1, uint32_t r2, uint32_t r3) {
    asm volatile("stmatrix.sync.aligned.m8n8.x4.trans.shared.b16 [%0], {%1,%2,%3,%4};" ::"r"(addr), "r"(r0), "r"(r1), "r"(r2), "r"(r3) : "memory");
}
__device__ __forceinline__ void ldsm4c(uint32_t& r0, uint32_t& r1, uint32_t& r2, uint32_t& r3, uint32_t addr) {
    asm volatile("ldmatrix.sync.aligned.m8n8.x4.shared.b16 {%0,%1,%2,%3}, [%4];" : "=r"(r0), "=r"(r1), "=r"(r2), "=r"(r3) : "r"(addr));
}
__global__ void __launch_bounds__(640, 1)
conv_kernel(const __grid_constant__ CUtensorMap tmK, const __grid_constant__ CUtensorMap tmV, const bf16* __restrict__ kp,
            const bf16* __restrict__ vp, const bf16* __restrict__ shk,
            const bf16* __restrict__ ssk, const bf16* __restrict__ ssD, const bf16* __restrict__ w1p, const bf16* __restrict__ w3p,
            const bf16* __restrict__ xq, bf16* act) {
    extern __shared__ __align__(128) uint8_t sm[];
    uint8_t* sU = sm;
    uint8_t* sP = sm + CV_CH * CV_U_BYTES;
    uint8_t* sY = sP + CV_CH * CV_P_BYTES;
    float* sR = reinterpret_cast<float*>(sY + CV_CH * CV_Y_BYTES);
    const int tid = threadIdx.x, warp = tid >> 5, lane = tid & 31;
    const int d0 = blockIdx.x * CV_CH;
    const uint32_t bar0 = smem_u32(sR + 2 * 8 * 16 * 32);
    const uint8_t* sK = reinterpret_cast<const uint8_t*>(sR + 2 * 8 * 16 * 32) + 128 + 128;
    const uint8_t* sV = sK + 2048 * 16;
    DBG_T(0);
    GT(0);
    auto load_kv = [&](int q) {
        mbar_expect_tx(bar0 + 64 + 8 * q, 4 * 4096);
        for (int i = 0; i < 2; i++) {
            int r0 = 512 * q + 256 * i;
            tma_load_2d(smem_u32(sK) + r0 * 16, &tmK, bar0 + 64 + 8 * q, d0, r0);
            tma_load_2d(smem_u32(sV) + r0 * 16, &tmV, bar0 + 64 + 8 * q, d0, r0);
        }
    };
    uint4 k0, v0;
    if (tid < 512) {
        k0 = __ldg(reinterpret_cast<const uint4*>(kp + (size_t)tid * D_ + d0));
        v0 = __ldg(reinterpret_cast<const uint4*>(vp + (size_t)tid * D_ + d0));
    }
    if (tid == 512) {
        for (int i = 0; i < 4; i++) { mbar_init(bar0 + 8 * i, 4); mbar_init(bar0 + 32 + 8 * i, 4); mbar_init(bar0 + 64 + 8 * i, i == 0 ? 16 : 1); }
        asm volatile("fence.mbarrier_init.release.cluster;" ::: "memory");
        fence_async_smem();
    }
    if (tid >= 32 && tid < 35) *reinterpret_cast<uint4*>(const_cast<uint8_t*>(sK) - 16 * (tid - 31)) = make_uint4(0, 0, 0, 0);
    for (int i = tid; tid < 512 && i < CV_CH * 8 * CV_UPITCH / 8; i += 512) {
        int c2 = i / (8 * CV_UPITCH / 8), r = i % (8 * CV_UPITCH / 8);
        *reinterpret_cast<uint4*>(sU + c2 * CV_U_BYTES + r * 16) = make_uint4(0, 0, 0, 0);
    }
    if (warp < 8 && lane < 16) reinterpret_cast<uint32_t*>(sP + warp * CV_P_BYTES)[lane] = 0;

    if (warp >= 16) {
        const int bt = tid - 512;
        uint32_t wv[4][4];
#pragma unroll
        for (int pr = 0; pr < 4; pr++) {
            uint2 wa = *reinterpret_cast<const uint2*>(shk + (d0 + 2 * pr) * 4);
            uint2 wb = *reinterpret_cast<const uint2*>(shk + (d0 + 2 * pr + 1) * 4);
            wv[0][pr] = (wa.x & 0xffffu) | (wb.x << 16);
            wv[1][pr] = (wa.x >> 16) | (wb.x & 0xffff0000u);
            wv[2][pr] = (wa.y & 0xffffu) | (wb.y << 16);
            wv[3][pr] = (wa.y >> 16) | (wb.y & 0xffff0000u);
        }
        const int pch = bt >> 4, pl = bt & 15;
        const bf16* hrow = ssk + (size_t)(d0 + pch) * S_ + pl * 8;
        uint32_t* Pw = reinterpret_cast<uint32_t*>(sP + pch * CV_P_BYTES) + 16 + pl * 8;
        uint4 pf[4];
        uint32_t hprev[4];
        auto prefetch = [&](int q) {
#pragma unroll
            for (int i = 0; i < 4; i++) {
                int j0 = 512 * q + i * 128;
                pf[i] = __ldg(reinterpret_cast<const uint4*>(hrow + j0));
                hprev[i] = (j0 + pl > 0) ? (uint32_t)__bfloat16_as_ushort(hrow[j0 - 1]) : 0u;
            }
        };
        prefetch(0);
        asm volatile("barrier.sync 0, 640;" ::: "memory");
        pdl_wait();
        if (blockIdx.x == 0) {
            for (int i = bt; i < FL_WORDS / FL_PITCH; i += 128) g_flag[i * FL_PITCH] = 0;
            if (bt < 9) { g_ticket[bt * FL_PITCH] = 0; __threadfence(); }
        }
        __syncwarp();
        if (warp == 16) pdl_launch();
        for (int i = bt; i < 320; i += 128) reinterpret_cast<float4*>(g_stats + S_ * 8)[blockIdx.x * 320 + i] = make_float4(-1.f, -1.f, -1.f, -1.f);
#pragma unroll 1
        for (int q = 0; q < 4; q++) {
#pragma unroll
            for (int i = 0; i < 4; i++) {
                int j0 = 512 * q + i * 128;
                uint32_t x0 = pf[i].x, x1 = pf[i].y, x2 = pf[i].z, x3 = pf[i].w;
                uint4 o0, o1;
                o0.x = (x0 & 0xffffu) | (hprev[i] << 16);
                o0.y = (x0 >> 16) | (x0 << 16);
                o0.z = (x1 & 0xffffu) | (x0 & 0xffff0000u);
                o0.w = (x1 >> 16) | (x1 << 16);
                o1.x = (x2 & 0xffffu) | (x1 & 0xffff0000u);
                o1.y = (x2 >> 16) | (x2 << 16);
                o1.z = (x3 & 0xffffu) | (x2 & 0xffff0000u);
                o1.w = (x3 >> 16) | (x3 << 16);
                *reinterpret_cast<uint4*>(Pw + j0) = o0;
                *reinterpret_cast<uint4*>(Pw + j0 + 4) = o1;
            }
            DBG_T(1 + 3 * q);
            mbar_wait(bar0 + 64 + 8 * q, 0);
            if (q < 3) {
                if (bt == 0) load_kv(q + 1);
                prefetch(q + 1);
            }
            DBG_T(2 + 3 * q);
#pragma unroll 1
            for (int hf = 0; hf < 2; hf++) {
                const int s0 = 512 * q + 256 * hf + 2 * bt;
                const int a = s0 >> 6, b = s0 & 63;
                uint4 kf[7];
#pragma unroll
                for (int i = 0; i < 5; i++) kf[i] = *reinterpret_cast<const uint4*>(sK + (s0 - 3 + i) * 16);
#pragma unroll
                for (int i = 0; i < 2; i++) kf[5 + i] = *reinterpret_cast<const uint4*>(sV + (s0 + i) * 16);
#pragma unroll
                for (int pr = 0; pr < 4; pr++) {
                    uint32_t k0 = reinterpret_cast<const uint32_t*>(&kf[0])[pr], k1 = reinterpret_cast<const uint32_t*>(&kf[1])[pr],
                             k2 = reinterpret_cast<const uint32_t*>(&kf[2])[pr], k3 = reinterpret_cast<const uint32_t*>(&kf[3])[pr],
                             k4 = reinterpret_cast<const uint32_t*>(&kf[4])[pr];
                    uint32_t r0 = bmul2(k0, wv[3][pr]);
                    r0 = badd2(r0, bmul2(k1, wv[2][pr]));
                    r0 = badd2(r0, bmul2(k2, wv[1][pr]));
                    r0 = badd2(r0, bmul2(k3, wv[0][pr]));
                    r0 = bmul2(r0, reinterpret_cast<const uint32_t*>(&kf[5])[pr]);
                    uint32_t r1 = bmul2(k1, wv[3][pr]);
                    r1 = badd2(r1, bmul2(k2, wv[2][pr]));
                    r1 = badd2(r1, bmul2(k3, wv[1][pr]));
                    r1 = badd2(r1, bmul2(k4, wv[0][pr]));
                    r1 = bmul2(r1, reinterpret_cast<const uint32_t*>(&kf[6])[pr]);
                    uint32_t c0 = (r0 & 0xffffu) | (r1 << 16), c1 = (r0 >> 16) | (r1 & 0xffff0000u);
                    *reinterpret_cast<uint32_t*>(sU + (2 * pr) * CV_U_BYTES + ((8 + a) * CV_UPITCH + b) * 2) = c0;
                    *reinterpret_cast<uint32_t*>(sU + (2 * pr + 1) * CV_U_BYTES + ((8 + a) * CV_UPITCH + b) * 2) = c1;
                }
            }
            __syncwarp();
            if (lane == 0) mbar_arrive(bar0 + 8 * q);
            DBG_T(3 + 3 * q);
        }
        {
            const int bi = blockIdx.x >> 3, bj = blockIdx.x & 7;
            const bool is3 = bt < 112;
            const int cg = is3 ? bt % 56 : bt - 112, pitch = is3 ? F_ : D_, col = is3 ? bj * 448 + cg * 8 : bj * 128 + cg * 8;
            const int r1 = is3 ? 32 : 64;
            const bf16* p = (is3 ? w3p + (size_t)(bt >= 56 ? 32 : 0) * F_ : w1p) + (size_t)(bi * 64) * pitch + col;
            float a8[8];
#pragma unroll
            for (int i = 0; i < 8; i++) a8[i] = 0.f;
#pragma unroll 1
            for (int r0 = 0; r0 < r1; r0 += 16) {
                uint4 v[16];
#pragma unroll
                for (int r = 0; r < 16; r++) v[r] = __ldg(reinterpret_cast<const uint4*>(p + (size_t)(r0 + r) * pitch));
#pragma unroll
                for (int r = 0; r < 16; r++) {
                    a8[0] += lo2f(v[r].x); a8[1] += hi2f(v[r].x); a8[2] += lo2f(v[r].y); a8[3] += hi2f(v[r].y);
                    a8[4] += lo2f(v[r].z); a8[5] += hi2f(v[r].z); a8[6] += lo2f(v[r].w); a8[7] += hi2f(v[r].w);
                }
            }
            float* sc = reinterpret_cast<float*>(const_cast<uint8_t*>(sK));
            mbar_wait(bar0, 0);
            if (bt >= 56 && is3) {
#pragma unroll
                for (int i = 0; i < 8; i++) sc[cg * 8 + i] = a8[i];
            }
            __syncwarp();
            if (lane == 0) mbar_arrive(bar0 + 32);
            mbar_wait(bar0 + 32, 0);
            if (bt < 56 || !is3) {
                if (is3) {
#pragma unroll
                    for (int i = 0; i < 8; i++) a8[i] += sc[cg * 8 + i];
                }
                float4* dst = reinterpret_cast<float4*>(g_cpart + bi * (F_ + D_) + (is3 ? 0 : F_) + col);
                dst[0] = make_float4(a8[0], a8[1], a8[2], a8[3]);
                dst[1] = make_float4(a8[4], a8[5], a8[6], a8[7]);
            }
        }
        {
            const int r = blockIdx.x * 16 + (warp - 16) * 4;
            uint4 v[16];
#pragma unroll
            for (int e = 0; e < 16; e++) v[e] = __ldg(reinterpret_cast<const uint4*>(xq + (size_t)r * D_ + e * 256 + lane * 8));
            float sm[4] = {0.f, 0.f, 0.f, 0.f}, sq[4] = {0.f, 0.f, 0.f, 0.f};
#pragma unroll
            for (int e = 0; e < 64; e++) {
                const uint32_t w = reinterpret_cast<const uint32_t*>(v)[e];
                sm[e >> 4] += lo2f(w) + hi2f(w); sq[e >> 4] = fmaf(lo2f(w), lo2f(w), fmaf(hi2f(w), hi2f(w), sq[e >> 4]));
            }
#pragma unroll
            for (int o = 16; o > 0; o >>= 1)
#pragma unroll
                for (int e = 0; e < 4; e++) { sm[e] += __shfl_xor_sync(0xffffffffu, sm[e], o); sq[e] += __shfl_xor_sync(0xffffffffu, sq[e], o); }
            const int e = lane >> 3;
            const float s1 = e == 0 ? sm[0] : e == 1 ? sm[1] : e == 2 ? sm[2] : sm[3], q1 = e == 0 ? sq[0] : e == 1 ? sq[1] : e == 2 ? sq[2] : sq[3];
            const float mu = s1 * (1.0f / D_);
            g_stats[((r >> 7) * 8 + (lane & 7)) * 128 + (r & 127) + e] = make_float2(mu, fmaxf(q1 - s1 * mu, 0.f) * 0.125f);
        }
        DBG_T(13);
        return;
    }

    asm volatile("barrier.sync 0, 640;" ::: "memory");
    *reinterpret_cast<uint4*>(const_cast<uint8_t*>(sK) + tid * 16) = k0;
    *reinterpret_cast<uint4*>(const_cast<uint8_t*>(sV) + tid * 16) = v0;
    __syncwarp();
    if (lane == 0) mbar_arrive(bar0 + 64);
    const int ch = warp & 7, par = warp >> 3;
    const int g = lane >> 2, t = lane & 3;
    const uint32_t* P = reinterpret_cast<const uint32_t*>(sP + ch * CV_P_BYTES) + 16 + (g - 2 * t);
    const uint32_t uB = smem_u32(sU + ch * CV_U_BYTES);
    const int lrow = lane & 7, lmat = lane >> 3;
    const uint32_t Dk2 = (uint32_t)__bfloat16_as_ushort(ssD[d0 + ch]) * 0x10001u;
    pdl_wait();
    GT(5);

#pragma unroll 1
    for (int q = 0; q < 4; q++) {
        mbar_wait(bar0 + 8 * q, 0);
        DBG_T(1 + 3 * q);
        float acc[4][4];
#pragma unroll
        for (int i = 0; i < 4; i++)
#pragma unroll
            for (int k = 0; k < 4; k++) acc[i][k] = 0.f;
        const int c0 = par * (4 * q + 4), c1 = c0 + 4 * q + 4;
        const uint32_t base0 = uB + ((8 + 8 * q + lrow) * CV_UPITCH) * 2 + lmat * 16;
        int c = c0;
        uint32_t pa[15];
        if (par == 0) {
#pragma unroll
            for (int j = 6; j < 15; j++) pa[j] = P[8 * (j - 7)];
            uint32_t b[8];
            ldsm4c(b[0], b[1], b[2], b[3], base0);
            ldsm4c(b[4], b[5], b[6], b[7], base0 + 64);
#pragma unroll
            for (int kk = 0; kk < 4; kk++)
#pragma unroll
                for (int mi = kk; mi < 4; mi++) {
                    int jj = 2 * (mi - kk) + 7;
                    mma16816(acc[mi], pa[jj], pa[jj + 1], pa[jj - 1], pa[jj], b[2 * kk], b[2 * kk + 1]);
                }
            c = 1;
        } else {
#pragma unroll
            for (int j = 8; j < 15; j++) pa[j] = P[8 * (8 * c - 15 + j)];
        }
#pragma unroll 2
        for (; c < c1; c++) {
#pragma unroll
            for (int j = 0; j < 7; j++) pa[j] = pa[j + 8];
#pragma unroll
            for (int j = 7; j < 15; j++) pa[j] = P[8 * (8 * c - 7 + j)];
            uint32_t b[8];
            uint32_t base = base0 - c * (CV_UPITCH * 2);
            ldsm4c(b[0], b[1], b[2], b[3], base);
            ldsm4c(b[4], b[5], b[6], b[7], base + 64);
#pragma unroll
            for (int kk = 3; kk >= 0; kk--)
#pragma unroll
                for (int mi = 0; mi < 4; mi++) {
                    int jj = 2 * (mi - kk) + 7;
                    mma16816(acc[mi], pa[jj], pa[jj + 1], pa[jj - 1], pa[jj], b[2 * kk], b[2 * kk + 1]);
                }
        }
        DBG_T(2 + 3 * q);
        float4* sRq = reinterpret_cast<float4*>(sR) + ((q & 1) * 8 + ch) * 128 + lane;
        if (par == 1) {
#pragma unroll
            for (int mi = 0; mi < 4; mi++) sRq[mi * 32] = make_float4(acc[mi][0], acc[mi][1], acc[mi][2], acc[mi][3]);
            named_bar_arrive(ch + 8 * (q & 1), 64);
        } else {
            uint32_t kv[8];
            ldsm4t(kv[0], kv[1], kv[2], kv[3], base0);
            ldsm4t(kv[4], kv[5], kv[6], kv[7], base0 + 64);
            named_bar_sync(ch + 8 * (q & 1), 64);
#pragma unroll
            for (int mi = 0; mi < 4; mi++) {
                const float4 o = sRq[mi * 32];
                kv[2 * mi] = badd2(pack2(acc[mi][0] + o.x, acc[mi][1] + o.y), bmul2(kv[2 * mi], Dk2));
                kv[2 * mi + 1] = badd2(pack2(acc[mi][2] + o.z, acc[mi][3] + o.w), bmul2(kv[2 * mi + 1], Dk2));
            }
            const uint32_t yb = smem_u32(sY + ch * CV_Y_BYTES);
            __syncwarp();
            stsm4t(yb + lrow * (CV_UPITCH * 2) + lmat * 16, kv[0], kv[1], kv[2], kv[3]);
            stsm4t(yb + lrow * (CV_UPITCH * 2) + lmat * 16 + 64, kv[4], kv[5], kv[6], kv[7]);
            __syncwarp();
            uint4* dst = reinterpret_cast<uint4*>(act + (size_t)(R_Y + q * 4096 + ((d0 + ch) & 255)) * D_ + (d0 & ~255)) + lane;
            const uint4 v0 = lds128(yb + (lane >> 3) * (CV_UPITCH * 2) + (lane & 7) * 16);
            const uint4 v1 = lds128(yb + (4 + (lane >> 3)) * (CV_UPITCH * 2) + (lane & 7) * 16);
            dst[0] = v0;
            dst[2048 * D_ / 8] = v1;
        }
        DBG_T(3 + 3 * q);
    }
    GT(1);
}

typedef CUresult (*PFN_encodeTiled)(CUtensorMap*, CUtensorMapDataType, cuuint32_t, void*, const cuuint64_t*, const cuuint64_t*,
                                    const cuuint32_t*, const cuuint32_t*, CUtensorMapInterleave, CUtensorMapSwizzle,
                                    CUtensorMapL2promotion, CUtensorMapFloatOOBfill);

static CUtensorMap make_map(PFN_encodeTiled enc, const void* ptr, int inner, int outer, int box_inner, int box_outer,
                            CUtensorMapSwizzle swz = CU_TENSOR_MAP_SWIZZLE_128B) {
    CUtensorMap m;
    cuuint64_t dims[2] = {(cuuint64_t)inner, (cuuint64_t)outer};
    cuuint64_t strides[1] = {(cuuint64_t)inner * 2};
    cuuint32_t box[2] = {(cuuint32_t)box_inner, (cuuint32_t)box_outer};
    cuuint32_t es[2] = {1, 1};
    enc(&m, CU_TENSOR_MAP_DATA_TYPE_BFLOAT16, 2, const_cast<void*>(ptr), dims, strides, box, es, CU_TENSOR_MAP_INTERLEAVE_NONE,
        swz, CU_TENSOR_MAP_L2_PROMOTION_L2_256B, CU_TENSOR_MAP_FLOAT_OOB_FILL_NONE);
    return m;
}

extern "C" void kernel_launch(void* const* d_in, const int* in_sizes, int n_in, void* d_out, int out_size) {
    const bf16* A_q = (const bf16*)d_in[0];
    const bf16* A_k = (const bf16*)d_in[1];
    const bf16* A_v = (const bf16*)d_in[2];
    const bf16* A_shk = (const bf16*)d_in[3];
    const bf16* A_ssk = (const bf16*)d_in[4];
    const bf16* A_ssD = (const bf16*)d_in[5];
    const bf16* w1 = (const bf16*)d_in[7];
    const bf16* w2 = (const bf16*)d_in[8];
    const bf16* w3 = (const bf16*)d_in[9];
    const bf16* w4 = (const bf16*)d_in[10];
    bf16* out = (bf16*)d_out;

    static PFN_encodeTiled enc = nullptr;
    static bool attr_done = false;
    if (!enc) {
        void* fn = nullptr;
        cudaDriverEntryPointQueryResult qr;
        cudaGetDriverEntryPoint("cuTensorMapEncodeTiled", &fn, cudaEnableDefault, &qr);
        enc = (PFN_encodeTiled)fn;
    }
    if (!attr_done) {
        cudaFuncSetAttribute(mega_kernel, cudaFuncAttributeMaxDynamicSharedMemorySize, MEGA_SMEM);
        cudaFuncSetAttribute(conv_kernel, cudaFuncAttributeMaxDynamicSharedMemorySize, CV_SMEM);
        attr_done = true;
    }
    void* p_act;
    cudaGetSymbolAddress(&p_act, g_act);
    bf16* act = (bf16*)(((uintptr_t)p_act + 0x1fffff) & ~(uintptr_t)0x1fffff);

    MegaMaps tm;
    tm.q = make_map(enc, A_q, D_, S_, 64, 128);
    tm.act = make_map(enc, act, D_, R_END, 64, 128);
    tm.w1 = make_map(enc, w1, D_, D_, 64, 64);
    tm.w2 = make_map(enc, w2, D_, D_, 64, 64);
    tm.w3 = make_map(enc, w3, F_, D_, 64, 64);
    tm.w4 = make_map(enc, w4, D_, F_, 64, 64);
    CUtensorMap tm_k = make_map(enc, A_k, D_, S_, 8, 256, CU_TENSOR_MAP_SWIZZLE_NONE);
    CUtensorMap tm_v = make_map(enc, A_v, D_, S_, 8, 256, CU_TENSOR_MAP_SWIZZLE_NONE);

    cudaStream_t st = cudaStreamPerThread;
    cudaLaunchAttribute at[2];
    at[0].id = cudaLaunchAttributeProgrammaticStreamSerialization;
    at[0].val.programmaticStreamSerializationAllowed = 1;
    at[1].id = cudaLaunchAttributeClusterDimension;
    at[1].val.clusterDim.x = 2;
    at[1].val.clusterDim.y = 1;
    at[1].val.clusterDim.z = 1;
    {
        cudaLaunchConfig_t cfg = {};
        cfg.gridDim = dim3(D_ / CV_CH);
        cfg.blockDim = dim3(640);
        cfg.dynamicSmemBytes = CV_SMEM;
        cfg.stream = st;
        cfg.attrs = at;
        cfg.numAttrs = 1;
        cudaLaunchKernelEx(&cfg, conv_kernel, tm_k, tm_v, A_k, A_v, A_shk, A_ssk, A_ssD, w1, w3, A_q, act);
    }
    {
        cudaLaunchConfig_t cfg = {};
        cfg.gridDim = dim3(132);
        cfg.blockDim = dim3(384);
        cfg.dynamicSmemBytes = MEGA_SMEM;
        cfg.stream = st;
        cfg.attrs = at;
        cfg.numAttrs = 2;
        cudaLaunchKernelEx(&cfg, mega_kernel, tm, out, act);
    }
}
```

```cpp
#include <cuda_runtime.h>
#include <cuda_bf16.h>
#include <cuda.h>
#include <stdint.h>

typedef __nv_bfloat16 bf16;

constexpr int S_ = 2048;
constexpr int D_ = 1024;
constexpr int F_ = 3584;

constexpr int R_XA = 0, R_X1 = 256, R_H2 = 512, R_Y = 1536, R_H = 16384 + 8, R_HP = S_ + 8, R_END = R_H + 2 * R_HP;
__device__ __align__(1024) bf16 g_act[(size_t)(R_END + 1024) * D_];
__device__ __align__(16) float g_cpart[16 * (F_ + D_)];
__device__ __align__(16) float2 g_stats[6 * S_ * 8];

__device__ __forceinline__ float bfr(float x) { return __bfloat162float(__float2bfloat16_rn(x)); }
__device__ __forceinline__ uint32_t pack2(float lo, float hi) {
    __nv_bfloat162 v = __floats2bfloat162_rn(lo, hi);
    return *reinterpret_cast<uint32_t*>(&v);
}
__device__ __forceinline__ float lo2f(uint32_t v) { return __uint_as_float(v << 16); }
__device__ __forceinline__ float hi2f(uint32_t v) { return __uint_as_float(v & 0xffff0000u); }
__device__ __forceinline__ float frcp(float x) { float r; asm("rcp.approx.f32 %0, %1;" : "=f"(r) : "f"(x)); return r; }
__device__ __forceinline__ float fsqrt(float x) { float r; asm("sqrt.approx.f32 %0, %1;" : "=f"(r) : "f"(x)); return r; }
__device__ __forceinline__ uint32_t smem_u32(const void* p) { return (uint32_t)__cvta_generic_to_shared(p); }

__device__ __forceinline__ void mbar_init(uint32_t bar, uint32_t cnt) {
    asm volatile("mbarrier.init.shared::cta.b64 [%0], %1;" ::"r"(bar), "r"(cnt));
}
__device__ __forceinline__ void mbar_expect_tx(uint32_t bar, uint32_t bytes) {
    asm volatile("mbarrier.arrive.expect_tx.shared::cta.b64 _, [%0], %1;" ::"r"(bar), "r"(bytes) : "memory");
}
__device__ __forceinline__ void mbar_arrive(uint32_t bar) {
    asm volatile("mbarrier.arrive.shared::cta.b64 _, [%0];" ::"r"(bar) : "memory");
}
__device__ __forceinline__ void mbar_wait(uint32_t bar, uint32_t parity) {
    asm volatile(
        "{\n.reg .pred p;\n.reg .u32 n;\n"
        "mbarrier.try_wait.parity.shared::cta.b64 p, [%0], %1;\n"
        "@p bra LD;\n"
        "mov.u32 n, 0;\n"
        "LW:\n"
        "mbarrier.try_wait.parity.shared::cta.b64 p, [%0], %1;\n"
        "@p bra LD;\n"
        "add.u32 n, n, 1;\n"
        "setp.lt.u32 p, n, 0x400000;\n"
        "@p bra LW;\n"
        "LD:\n}\n"
        ::"r"(bar), "r"(parity) : "memory");
}
__device__ __forceinline__ void tma_load_2d(uint32_t dst, const CUtensorMap* tm, uint32_t bar, int c0, int c1) {
    asm volatile(
        "cp.async.bulk.tensor.2d.shared::cluster.global.mbarrier::complete_tx::bytes [%0], [%1, {%3, %4}], [%2];"
        ::"r"(dst), "l"((uint64_t)tm), "r"(bar), "r"(c0), "r"(c1) : "memory");
}
__device__ __forceinline__ void tma_load_2d_mc(uint32_t dst, const CUtensorMap* tm, uint32_t bar, int c0, int c1) {
    asm volatile(
        "cp.async.bulk.tensor.2d.shared::cluster.global.mbarrier::complete_tx::bytes.multicast::cluster [%0], [%1, {%3, %4}], [%2], %5;"
        ::"r"(dst), "l"((uint64_t)tm), "r"(bar), "r"(c0), "r"(c1), "h"((uint16_t)3) : "memory");
}
__device__ __forceinline__ void tma_prefetch_2d(const CUtensorMap* tm, int c0, int c1) {
    asm volatile("cp.async.bulk.prefetch.tensor.2d.L2.global.tile [%0, {%1, %2}];" ::"l"((uint64_t)tm), "r"(c0), "r"(c1) : "memory");
}
__device__ __forceinline__ void tma_store_2d(const CUtensorMap* tm, uint32_t src, int c0, int c1) {
    asm volatile("cp.async.bulk.tensor.2d.global.shared::cta.bulk_group [%0, {%2, %3}], [%1];"
                 ::"l"((uint64_t)tm), "r"(src), "r"(c0), "r"(c1) : "memory");
}
__device__ __forceinline__ void wgmma_fence() { asm volatile("wgmma.fence.sync.aligned;" ::: "memory"); }
__device__ __forceinline__ void wgmma_commit() { asm volatile("wgmma.commit_group.sync.aligned;" ::: "memory"); }
template <int N> __device__ __forceinline__ void wgmma_wait() { asm volatile("wgmma.wait_group.sync.aligned %0;" ::"n"(N) : "memory"); }
__device__ __forceinline__ void named_bar_arrive(int id, int n) { asm volatile("bar.arrive %0, %1;" ::"r"(id), "r"(n) : "memory"); }
__device__ __forceinline__ void named_bar_sync(int id, int n) { asm volatile("bar.sync %0, %1;" ::"r"(id), "r"(n) : "memory"); }

__device__ __forceinline__ void pdl_wait() { asm volatile("griddepcontrol.wait;" ::: "memory"); }
__device__ __forceinline__ void pdl_launch() { asm volatile("griddepcontrol.launch_dependents;" ::: "memory"); }

__device__ __forceinline__ uint32_t desc_a(uint32_t addr) { return ((addr & 0x3FFFF) >> 4) | (1u << 16); }
__device__ __forceinline__ uint32_t desc_b(uint32_t addr) { return ((addr & 0x3FFFF) >> 4) | (512u << 16); }

__device__ __forceinline__ void wgmma_m64n192k16(float (&d)[96], uint32_t descA, uint32_t descB) {
  asm volatile("{\n.reg .pred p;\n.reg .b64 da, db;\nsetp.eq.b32 p, 0, 0;\nmov.b64 da, {%96, %98};\nmov.b64 db, {%97, %98};\n"
    "wgmma.mma_async.sync.aligned.m64n192k16.f32.bf16.bf16 "
    "{%0, %1, %2, %3, %4, %5, %6, %7, %8, %9, %10, %11, %12, %13, %14, %15, %16, %17, %18, %19, %20, %21, %22, %23, %24, %25, %26, %27, %28, %29, %30, %31, %32, %33, %34, %35, %36, %37, %38, %39, %40, %41, %42, %43, %44, %45, %46, %47, %48, %49, %50, %51, %52, %53, %54, %55, %56, %57, %58, %59, %60, %61, %62, %63, %64, %65, %66, %67, %68, %69, %70, %71, %72, %73, %74, %75, %76, %77, %78, %79, %80, %81, %82, %83, %84, %85, %86, %87, %88, %89, %90, %91, %92, %93, %94, %95}, "
    "da, db, p, 1, 1, 0, 1;\n}\n"
    : "+f"(d[0]), "+f"(d[1]), "+f"(d[2]), "+f"(d[3]), "+f"(d[4]), "+f"(d[5]), "+f"(d[6]), "+f"(d[7]), "+f"(d[8]), "+f"(d[9]), "+f"(d[10]), "+f"(d[11]), "+f"(d[12]), "+f"(d[13]), "+f"(d[14]), "+f"(d[15]), "+f"(d[16]), "+f"(d[17]), "+f"(d[18]), "+f"(d[19]), "+f"(d[20]), "+f"(d[21]), "+f"(d[22]), "+f"(d[23]), "+f"(d[24]), "+f"(d[25]), "+f"(d[26]), "+f"(d[27]), "+f"(d[28]), "+f"(d[29]), "+f"(d[30]), "+f"(d[31]), "+f"(d[32]), "+f"(d[33]), "+f"(d[34]), "+f"(d[35]), "+f"(d[36]), "+f"(d[37]), "+f"(d[38]), "+f"(d[39]), "+f"(d[40]), "+f"(d[41]), "+f"(d[42]), "+f"(d[43]), "+f"(d[44]), "+f"(d[45]), "+f"(d[46]), "+f"(d[47]), "+f"(d[48]), "+f"(d[49]), "+f"(d[50]), "+f"(d[51]), "+f"(d[52]), "+f"(d[53]), "+f"(d[54]), "+f"(d[55]), "+f"(d[56]), "+f"(d[57]), "+f"(d[58]), "+f"(d[59]), "+f"(d[60]), "+f"(d[61]), "+f"(d[62]), "+f"(d[63]), "+f"(d[64]), "+f"(d[65]), "+f"(d[66]), "+f"(d[67]), "+f"(d[68]), "+f"(d[69]), "+f"(d[70]), "+f"(d[71]), "+f"(d[72]), "+f"(d[73]), "+f"(d[74]), "+f"(d[75]), "+f"(d[76]), "+f"(d[77]), "+f"(d[78]), "+f"(d[79]), "+f"(d[80]), "+f"(d[81]), "+f"(d[82]), "+f"(d[83]), "+f"(d[84]), "+f"(d[85]), "+f"(d[86]), "+f"(d[87]), "+f"(d[88]), "+f"(d[89]), "+f"(d[90]), "+f"(d[91]), "+f"(d[92]), "+f"(d[93]), "+f"(d[94]), "+f"(d[95])
    : "r"(descA), "r"(descB), "r"(0x40000040u));
}

__device__ __forceinline__ void wgmma_m64n256k16(float (&d)[128], uint32_t descA, uint32_t descB) {
  asm volatile("{\n.reg .pred p;\n.reg .b64 da, db;\nsetp.eq.b32 p, 0, 0;\nmov.b64 da, {%128, %130};\nmov.b64 db, {%129, %130};\n"
    "wgmma.mma_async.sync.aligned.m64n256k16.f32.bf16.bf16 "
    "{%0, %1, %2, %3, %4, %5, %6, %7, %8, %9, %10, %11, %12, %13, %14, %15, %16, %17, %18, %19, %20, %21, %22, %23, %24, %25, %26, %27, %28, %29, %30, %31, %32, %33, %34, %35, %36, %37, %38, %39, %40, %41, %42, %43, %44, %45, %46, %47, %48, %49, %50, %51, %52, %53, %54, %55, %56, %57, %58, %59, %60, %61, %62, %63, %64, %65, %66, %67, %68, %69, %70, %71, %72, %73, %74, %75, %76, %77, %78, %79, %80, %81, %82, %83, %84, %85, %86, %87, %88, %89, %90, %91, %92, %93, %94, %95, %96, %97, %98, %99, %100, %101, %102, %103, %104, %105, %106, %107, %108, %109, %110, %111, %112, %113, %114, %115, %116, %117, %118, %119, %120, %121, %122, %123, %124, %125, %126, %127}, "
    "da, db, p, 1, 1, 0, 1;\n}\n"
    : "+f"(d[0]), "+f"(d[1]), "+f"(d[2]), "+f"(d[3]), "+f"(d[4]), "+f"(d[5]), "+f"(d[6]), "+f"(d[7]), "+f"(d[8]), "+f"(d[9]), "+f"(d[10]), "+f"(d[11]), "+f"(d[12]), "+f"(d[13]), "+f"(d[14]), "+f"(d[15]), "+f"(d[16]), "+f"(d[17]), "+f"(d[18]), "+f"(d[19]), "+f"(d[20]), "+f"(d[21]), "+f"(d[22]), "+f"(d[23]), "+f"(d[24]), "+f"(d[25]), "+f"(d[26]), "+f"(d[27]), "+f"(d[28]), "+f"(d[29]), "+f"(d[30]), "+f"(d[31]), "+f"(d[32]), "+f"(d[33]), "+f"(d[34]), "+f"(d[35]), "+f"(d[36]), "+f"(d[37]), "+f"(d[38]), "+f"(d[39]), "+f"(d[40]), "+f"(d[41]), "+f"(d[42]), "+f"(d[43]), "+f"(d[44]), "+f"(d[45]), "+f"(d[46]), "+f"(d[47]), "+f"(d[48]), "+f"(d[49]), "+f"(d[50]), "+f"(d[51]), "+f"(d[52]), "+f"(d[53]), "+f"(d[54]), "+f"(d[55]), "+f"(d[56]), "+f"(d[57]), "+f"(d[58]), "+f"(d[59]), "+f"(d[60]), "+f"(d[61]), "+f"(d[62]), "+f"(d[63]), "+f"(d[64]), "+f"(d[65]), "+f"(d[66]), "+f"(d[67]), "+f"(d[68]), "+f"(d[69]), "+f"(d[70]), "+f"(d[71]), "+f"(d[72]), "+f"(d[73]), "+f"(d[74]), "+f"(d[75]), "+f"(d[76]), "+f"(d[77]), "+f"(d[78]), "+f"(d[79]), "+f"(d[80]), "+f"(d[81]), "+f"(d[82]), "+f"(d[83]), "+f"(d[84]), "+f"(d[85]), "+f"(d[86]), "+f"(d[87]), "+f"(d[88]), "+f"(d[89]), "+f"(d[90]), "+f"(d[91]), "+f"(d[92]), "+f"(d[93]), "+f"(d[94]), "+f"(d[95]), "+f"(d[96]), "+f"(d[97]), "+f"(d[98]), "+f"(d[99]), "+f"(d[100]), "+f"(d[101]), "+f"(d[102]), "+f"(d[103]), "+f"(d[104]), "+f"(d[105]), "+f"(d[106]), "+f"(d[107]), "+f"(d[108]), "+f"(d[109]), "+f"(d[110]), "+f"(d[111]), "+f"(d[112]), "+f"(d[113]), "+f"(d[114]), "+f"(d[115]), "+f"(d[116]), "+f"(d[117]), "+f"(d[118]), "+f"(d[119]), "+f"(d[120]), "+f"(d[121]), "+f"(d[122]), "+f"(d[123]), "+f"(d[124]), "+f"(d[125]), "+f"(d[126]), "+f"(d[127])
    : "r"(descA), "r"(descB), "r"(0x40000040u));
}

__device__ __forceinline__ void wgmma_m64n128k16(float (&d)[64], uint32_t descA, uint32_t descB) {
  asm volatile("{\n.reg .pred p;\n.reg .b64 da, db;\nsetp.eq.b32 p, 0, 0;\nmov.b64 da, {%64, %66};\nmov.b64 db, {%65, %66};\n"
    "wgmma.mma_async.sync.aligned.m64n128k16.f32.bf16.bf16 "
    "{%0, %1, %2, %3, %4, %5, %6, %7, %8, %9, %10, %11, %12, %13, %14, %15, %16, %17, %18, %19, %20, %21, %22, %23, %24, %25, %26, %27, %28, %29, %30, %31, %32, %33, %34, %35, %36, %37, %38, %39, %40, %41, %42, %43, %44, %45, %46, %47, %48, %49, %50, %51, %52, %53, %54, %55, %56, %57, %58, %59, %60, %61, %62, %63}, "
    "da, db, p, 1, 1, 0, 1;\n}\n"
    : "+f"(d[0]), "+f"(d[1]), "+f"(d[2]), "+f"(d[3]), "+f"(d[4]), "+f"(d[5]), "+f"(d[6]), "+f"(d[7]), "+f"(d[8]), "+f"(d[9]), "+f"(d[10]), "+f"(d[11]), "+f"(d[12]), "+f"(d[13]), "+f"(d[14]), "+f"(d[15]), "+f"(d[16]), "+f"(d[17]), "+f"(d[18]), "+f"(d[19]), "+f"(d[20]), "+f"(d[21]), "+f"(d[22]), "+f"(d[23]), "+f"(d[24]), "+f"(d[25]), "+f"(d[26]), "+f"(d[27]), "+f"(d[28]), "+f"(d[29]), "+f"(d[30]), "+f"(d[31]), "+f"(d[32]), "+f"(d[33]), "+f"(d[34]), "+f"(d[35]), "+f"(d[36]), "+f"(d[37]), "+f"(d[38]), "+f"(d[39]), "+f"(d[40]), "+f"(d[41]), "+f"(d[42]), "+f"(d[43]), "+f"(d[44]), "+f"(d[45]), "+f"(d[46]), "+f"(d[47]), "+f"(d[48]), "+f"(d[49]), "+f"(d[50]), "+f"(d[51]), "+f"(d[52]), "+f"(d[53]), "+f"(d[54]), "+f"(d[55]), "+f"(d[56]), "+f"(d[57]), "+f"(d[58]), "+f"(d[59]), "+f"(d[60]), "+f"(d[61]), "+f"(d[62]), "+f"(d[63])
    : "r"(descA), "r"(descB), "r"(0x40000040u));
}

template <int BN> struct WG;
template <> struct WG<128> { static __device__ __forceinline__ void mma(float (&d)[64], uint32_t a, uint32_t b) { wgmma_m64n128k16(d, a, b); } };
template <> struct WG<256> { static __device__ __forceinline__ void mma(float (&d)[128], uint32_t a, uint32_t b) { wgmma_m64n256k16(d, a, b); } };
template <> struct WG<192> { static __device__ __forceinline__ void mma(float (&d)[96], uint32_t a, uint32_t b) { wgmma_m64n192k16(d, a, b); } };

#define DBG_T(i)
__device__ __forceinline__ void fence_async_smem() { asm volatile("fence.proxy.async.shared::cta;" ::: "memory"); }
__device__ __forceinline__ void prefetch_tmap(const CUtensorMap* tm) { asm volatile("prefetch.tensormap [%0];" ::"l"((uint64_t)tm) : "memory"); }
__device__ __forceinline__ uint32_t mapa_u32(uint32_t addr, uint32_t cta) {
    uint32_t r;
    asm volatile("mapa.shared::cluster.u32 %0, %1, %2;" : "=r"(r) : "r"(addr), "r"(cta));
    return r;
}
__device__ __forceinline__ void mbar_arrive_cluster(uint32_t cluster_addr) {
    asm volatile("mbarrier.arrive.shared::cluster.b64 _, [%0];" ::"r"(cluster_addr) : "memory");
}
__device__ __forceinline__ bool elect_one() {
    uint32_t p;
    asm volatile("{\n.reg .pred P;\nelect.sync _|P, 0xffffffff;\nselp.u32 %0, 1, 0, P;\n}\n" : "=r"(p));
    return p != 0;
}
__device__ __forceinline__ void cluster_arrive_relaxed() { asm volatile("barrier.cluster.arrive.relaxed.aligned;" ::: "memory"); }
__device__ __forceinline__ void cluster_wait() { asm volatile("barrier.cluster.wait.acquire.aligned;" ::: "memory"); }

__device__ __forceinline__ uint32_t bsub2(uint32_t a, uint32_t b) {
    __nv_bfloat162 r = __hsub2(*reinterpret_cast<__nv_bfloat162*>(&a), *reinterpret_cast<__nv_bfloat162*>(&b));
    return *reinterpret_cast<uint32_t*>(&r);
}
__device__ __forceinline__ uint32_t bmul2(uint32_t a, uint32_t b) {
    __nv_bfloat162 r = __hmul2(*reinterpret_cast<__nv_bfloat162*>(&a), *reinterpret_cast<__nv_bfloat162*>(&b));
    return *reinterpret_cast<uint32_t*>(&r);
}
__device__ __forceinline__ uint32_t badd2(uint32_t a, uint32_t b) {
    __nv_bfloat162 r = __hadd2(*reinterpret_cast<__nv_bfloat162*>(&a), *reinterpret_cast<__nv_bfloat162*>(&b));
    return *reinterpret_cast<uint32_t*>(&r);
}
constexpr int BM = 128, BK = 64;
constexpr int R5_STAGE = 32768, R5_N = 5;
constexpr int R4_STAGE = 49152, R4_N = 4;
constexpr int R4B_STAGE = 40960;
constexpr int OFF_STG5 = 0, OFF_R = 32768;
constexpr int OFF_EPI = 196608;
constexpr int OFF_BAR = OFF_EPI + 32768;
constexpr int OFF_RS = OFF_BAR + 256;
constexpr int OFF_CS = OFF_RS + 1024;
constexpr int MEGA_SMEM = OFF_CS + 1792;
enum { FL_XA = 0, FL_H = 2, FL_X1 = 4, FL_H2 = 6, FL_KINDS = 10 };
constexpr int FL_PITCH = 64;
constexpr int FL_WORDS = 2 * FL_KINDS * 16 * FL_PITCH;
__device__ unsigned int g_flag[FL_WORDS];
__device__ unsigned int g_ticket[9 * FL_PITCH];
__device__ __forceinline__ unsigned int* flag_ptr(int layer, int kind, int i) { return g_flag + ((layer * FL_KINDS + kind) * 16 + i) * FL_PITCH; }

__device__ __forceinline__ void wait_flag(const unsigned int* p, unsigned int target) {
    long long t0 = clock64();
    while (true) {
        unsigned int v;
        asm volatile("ld.relaxed.gpu.global.u32 %0, [%1];" : "=r"(v) : "l"(p) : "memory");
        if (v >= target) break;
        if (clock64() - t0 > 2000000000LL) break;
    }
    asm volatile("fence.acquire.gpu;" ::: "memory");
}
__device__ __forceinline__ void fence_proxy_async() {
    asm volatile("fence.proxy.async.global;" ::: "memory");
    asm volatile("fence.proxy.async.shared::cta;" ::: "memory");
}
__device__ __forceinline__ void stsm4(uint32_t addr, uint32_t r0, uint32_t r1, uint32_t r2, uint32_t r3) {
    asm volatile("stmatrix.sync.aligned.m8n8.x4.shared.b16 [%0], {%1,%2,%3,%4};" ::"r"(addr), "r"(r0), "r"(r1), "r"(r2), "r"(r3));
}
__device__ __forceinline__ uint4 lds128(uint32_t a) {
    uint4 v;
    asm volatile("ld.shared.v4.b32 {%0,%1,%2,%3}, [%4];" : "=r"(v.x), "=r"(v.y), "=r"(v.z), "=r"(v.w) : "r"(a) : "memory");
    return v;
}
__device__ __forceinline__ void stg128(void* p, uint4 v) {
    asm volatile("st.global.v4.b32 [%0], {%1,%2,%3,%4};" ::"l"(p), "r"(v.x), "r"(v.y), "r"(v.z), "r"(v.w) : "memory");
}
__device__ __forceinline__ float gelu_tanh_h(float hx) {
    float z = hx * fmaf(hx * hx, 8.0f * 0.035677408136300125f, 2.0f * 0.7978845608028654f);
    float t;
    asm("tanh.approx.f32 %0, %1;" : "=f"(t) : "f"(z));
    return fmaf(hx, t, hx);
}
__device__ __forceinline__ uint32_t gelu2h(uint32_t p) { return pack2(gelu_tanh_h(lo2f(p)), gelu_tanh_h(hi2f(p))); }
__device__ __forceinline__ uint4 gelu8h(uint4 v) { return make_uint4(gelu2h(v.x), gelu2h(v.y), gelu2h(v.z), gelu2h(v.w)); }

__device__ __forceinline__ void row_stats(const float2* p, float& mean, float& var) {
    float2 v[8];
#pragma unroll 1
    for (int n = 0; n < (1 << 20); n++) {
#pragma unroll
        for (int i = 0; i < 8; i++)
            asm volatile("{\n.reg .b64 t;\nld.relaxed.gpu.global.b64 t, [%2];\nmov.b64 {%0, %1}, t;\n}" : "=f"(v[i].x), "=f"(v[i].y) : "l"(p + 128 * i) : "memory");
        if (fminf(fminf(fminf(v[0].y, v[1].y), fminf(v[2].y, v[3].y)), fminf(fminf(v[4].y, v[5].y), fminf(v[6].y, v[7].y))) >= 0.f) break;
    }
    mean = (((v[0].x + v[1].x) + (v[2].x + v[3].x)) + ((v[4].x + v[5].x) + (v[6].x + v[7].x))) * 0.125f;
    float m2 = 0.f, d2 = 0.f;
#pragma unroll
    for (int i = 0; i < 8; i++) { m2 += v[i].y; d2 = fmaf(v[i].x - mean, v[i].x - mean, d2); }
    var = fmaf(128.0f, d2, m2) * (1.0f / D_);
}
struct RingState { uint32_t st, ph; };

#define DT(i)
#define DP(i)
#define GT(i)

template <int BN, int NST>
__device__ __forceinline__ void kblock(float (&acc)[BN / 2], uint32_t da, uint32_t db, uint32_t bfull, RingState& rs) {
    mbar_wait(bfull + 8 * rs.st, rs.ph);
    wgmma_fence();
#pragma unroll
    for (int k = 0; k < 4; k++) WG<BN>::mma(acc, da + k * 2, db + k * 128);
    wgmma_commit();
    if (++rs.st == NST) { rs.st = 0; rs.ph ^= 1; }
}
template <int BN, int NST, int STAGE>
__device__ __forceinline__ void mainloop(float (&acc)[BN / 2], int KB, uint32_t da0, uint32_t db0, uint32_t bfull, uint32_t rel, bool rel_on,
                                         RingState& rs, int dbg) {
    uint32_t prev = rs.st ? rs.st - 1 : NST - 1;
#pragma unroll 1
    for (int kk = 0; kk < KB; kk++) {
        const uint32_t cur = rs.st;
        kblock<BN, NST>(acc, da0 + cur * (STAGE / 16), db0 + cur * (STAGE / 16), bfull, rs);
        wgmma_wait<1>();
        if (rel_on) mbar_arrive_cluster(rel + 8 * prev);
        prev = cur;
    }
    wgmma_wait<0>();
#pragma unroll
    for (int i = 0; i < BN / 2; i++) asm volatile("" : "+f"(acc[i])::"memory");
    if (rel_on) mbar_arrive_cluster(rel + 8 * prev);
}
template <int N> __device__ __forceinline__ void zero_acc(float (&acc)[N]) {
#pragma unroll
    for (int i = 0; i < N; i++) acc[i] = 0.f;
}
__device__ __forceinline__ void ldsm4(uint32_t& r0, uint32_t& r1, uint32_t& r2, uint32_t& r3, uint32_t addr) {
    asm volatile("ldmatrix.sync.aligned.m8n8.x4.shared.b16 {%0,%1,%2,%3}, [%4];" : "=r"(r0), "=r"(r1), "=r"(r2), "=r"(r3) : "r"(addr));
}

__device__ __forceinline__ void ldsm4t(uint32_t& r0, uint32_t& r1, uint32_t& r2, uint32_t& r3, uint32_t addr) {
    asm volatile("ldmatrix.sync.aligned.m8n8.x4.trans.shared.b16 {%0,%1,%2,%3}, [%4];" : "=r"(r0), "=r"(r1), "=r"(r2), "=r"(r3) : "r"(addr));
}

struct MegaMaps {
    CUtensorMap q, act;
    CUtensorMap w1, w2, w3, w4;
};

__global__ void __cluster_dims__(2, 1, 1) __launch_bounds__(384, 1)
mega_kernel(const __grid_constant__ MegaMaps tm, bf16* __restrict__ outp, bf16* act) {
    extern __shared__ __align__(1024) uint8_t sgen[];
    const uint32_t sbase = smem_u32(sgen);
    DT(0);
    GT(2);
    const int warp = __shfl_sync(0xffffffffu, threadIdx.x >> 5, 0), lane = threadIdx.x & 31;
    const int rank = blockIdx.x & 1;
    const uint32_t s_bar = sbase + OFF_BAR;
    const uint32_t f5 = s_bar, e5 = s_bar + 48, f4 = s_bar + 96, e4 = s_bar + 128;
    const uint32_t b_rfull = s_bar + 176, b_stg = s_bar + 184, b_h2 = s_bar + 192;
    const uint32_t s_epi = sbase + OFF_EPI, s_stg = sbase + OFF_STG5, s_r = sbase + OFF_R;

    if (threadIdx.x == 256) {
        for (int i = 0; i < R5_N; i++) { mbar_init(f5 + 8 * i, 1); mbar_init(e5 + 8 * i, 4); }
        for (int i = 0; i < R4_N; i++) { mbar_init(f4 + 8 * i, 1); mbar_init(e4 + 8 * i, 4); }
        mbar_init(b_rfull, 1); mbar_init(b_stg, 8);
        for (int i = 1; i < 4; i++) mbar_init(b_h2 + 8 * i, 1);
        for (int i = 0; i < 6; i++) reinterpret_cast<uint32_t*>(sgen + OFF_BAR + 224)[i] = 0;
        asm volatile("fence.mbarrier_init.release.cluster;" ::: "memory");
        fence_async_smem();
        prefetch_tmap(&tm.act);
    }
    if (threadIdx.x == 288 && rank == 0) {
        uint32_t smid;
        asm volatile("mov.u32 %0, %%smid;" : "=r"(smid));
        const int t = smid >> 1;
        int team = t < 32 ? t & 7 : t < 60 ? 1 + (t - 32) % 7 : t < 62 ? t - 54 : 0;
        int slot = atomicAdd(g_ticket + team * FL_PITCH, 1u);
        atomicAdd(g_ticket + 8 * FL_PITCH, 1u);
        if (slot >= 8) {
            const long long t0 = clock64();
            while (*(volatile unsigned int*)(g_ticket + 8 * FL_PITCH) < gridDim.x / 2 && clock64() - t0 < 100000) {}
            for (team = 0; team < 8; team++)
                if ((slot = atomicAdd(g_ticket + team * FL_PITCH, 1u)) < 8) break;
        }
        const uint32_t role = team * 8 + slot, ra = s_bar + 192;
        asm volatile("st.shared::cluster.u32 [%0], %1;" ::"r"(mapa_u32(ra, 0)), "r"(role) : "memory");
        asm volatile("st.shared::cluster.u32 [%0], %1;" ::"r"(mapa_u32(ra, 1)), "r"(role) : "memory");
        asm volatile("fence.acq_rel.cluster;" ::: "memory");
    }
    __syncwarp();
    cluster_arrive_relaxed();
    cluster_wait();
    const int role = *reinterpret_cast<const volatile int*>(sgen + OFF_BAR + 192);
    if (role >= 64) return;
    const int bi = (role >> 3) * 2 + rank, bj = role & 7, m0 = bi * BM, tb = (role >> 3) * 2048 + rank * 128;
    if (threadIdx.x == 256) {
        mbar_expect_tx(b_rfull, 32768);
        tma_load_2d(s_epi, &tm.q, b_rfull, bj * 128, m0);
        tma_load_2d(s_epi + 16384, &tm.q, b_rfull, bj * 128 + 64, m0);
    }

    if (warp >= 8) {
        asm volatile("setmaxnreg.dec.sync.aligned.u32 72;");
        if (warp == 8) { if (elect_one()) {
            int s5 = 0, s4 = 0;
            uint32_t p5 = 31, p4 = 1;
            auto putB = [&](const CUtensorMap* tB, int kc, uint32_t bytes) {
                const uint32_t full = f5 + 8 * s5;
                mbar_wait(full + 48, (p5 >> s5) & 1);
                mbar_expect_tx(full, bytes);
                tma_load_2d_mc(s_r + 16384 + rank * 8192 + s5 * R5_STAGE, tB, full, bj * 128 + rank * 64, kc);
                p5 ^= 1u << s5;
            };
            auto putA = [&](int c, int r) {
                tma_load_2d(s_r + s5 * R5_STAGE, &tm.act, f5 + 8 * s5, c, r);
                if (++s5 == R5_N) s5 = 0;
            };
            pdl_wait();
            prefetch_tmap(&tm.w1); prefetch_tmap(&tm.w2); prefetch_tmap(&tm.w3); prefetch_tmap(&tm.w4);
            auto own_first = [&](int it) {
                const int hf = it >= 9, c = it - 2 - 7 * hf;
                return (it < 2 ? 2 * bj + it : 2 * (c + (c >= bj)) + hf) * BK;
            };
            const unsigned int nh = (bi == 0 || bi == 15) ? 16 : 24;
#pragma unroll 1
            for (int layer = 0; layer < 2; layer++) {
                if (layer == 0) { mbar_arrive(f5); p5 ^= 1; }
                mbar_wait(e5 + 8, (p5 >> 1) & 1);
                mbar_expect_tx(f5 + 8, 32768);
                tma_load_2d(s_r + R5_STAGE, &tm.act, f5 + 8, (bj >> 1) * 256 + rank * 128, R_Y + (tb & ~255) + (bj & 1) * 128);
                tma_load_2d(s_r + R5_STAGE + 16384, &tm.act, f5 + 8, (bj >> 1) * 256 + rank * 128 + 64, R_Y + (tb & ~255) + (bj & 1) * 128);
                p5 ^= 2;
                s5 = 2;
#pragma unroll 1
                for (int kk = 0; kk < 4; kk++) { putB(&tm.w1, own_first(kk), kk < 2 ? 16384 : R5_STAGE); if (++s5 == R5_N) s5 = 0; }
                s5 = 4;
#pragma unroll 1
                for (int kk = 2; kk < 16; kk++) {
                    const int kc = own_first(kk);
                    if (kk >= 4) putB(&tm.w1, kc, R5_STAGE);
                    if (kk == 2 || kk == 9) {
                        wait_flag(flag_ptr(layer, FL_XA + (kk & 1), bi), 8);
                        DP(8 * (FL_XA + (kk & 1)) + 3);
                        fence_proxy_async();
                        DP(8 * (FL_XA + (kk & 1)) + 4);
                    }
                    putA(kc, R_XA + tb);
                }
                mbar_wait(e5 + 24, (p5 >> 3) & 1);
                mbar_arrive(f5 + 24);
                p5 ^= 8;
                s5 = 4;
#pragma unroll 1
                for (int kk = 0; kk < 5; kk++) { putB(&tm.w2, kk * 2 * BK, R5_STAGE); if (++s5 == R5_N) s5 = 0; }
#pragma unroll 1
                for (int kk = 0; kk < 16; kk++) {
                    const int kc = ((kk & 7) * 2 + (kk >> 3)) * BK;
                    if (kk >= 5) putB(&tm.w2, kc, R5_STAGE);
                    if ((kk & 7) == 0) {
                        wait_flag(flag_ptr(layer, FL_H + (kk >> 3), bi), nh);
                        DP(8 * (FL_H + (kk >> 3)) + 3);
                        fence_proxy_async();
                        DP(8 * (FL_H + (kk >> 3)) + 4);
                    }
                    putA(kc, R_H + layer * R_HP + m0 + (int)((0x4031u >> ((kk & 6) << 1)) & 7) - 2);
                }
#pragma unroll 1
                for (int it = 0; it < 32; it++) {
                    const int kc = it >= 16 ? (it - 16) * BK : own_first(it);
                    const int nb = it < 16 ? 4 : 3, n0 = bj * 448 + (it < 16 ? 0 : 256);
                    if (it > 0 && it < 4) {
                        const int i = (it - 1) * 3 >> 1;
                        mbar_wait(e5 + 8 * i, (p5 >> i) & 1);
                        mbar_wait(e5 + 8 * i + 8, (p5 >> (i + 1)) & 1);
                    }
                    mbar_wait(e4 + 8 * s4, p4);
                    if (it >= 16 && it < 19) mbar_wait(e4 + 8 * s4 + 8, p4);
                    uint32_t sa = s_r + s4 * (it < 16 ? R4_STAGE : R4B_STAGE), full = f4 + 8 * s4;
                    mbar_expect_tx(full, (it < 2 ? 0 : 16384) + nb * 8192);
#pragma unroll 1
                    for (int j = (it ^ rank) & 1; j < nb; j += 2) tma_load_2d_mc(sa + (it < 16 ? -32768 : 16384) + j * 8192, &tm.w3, full, n0 + j * 64, kc);
                    if (it == 3 || it == 9) {
                        wait_flag(flag_ptr(layer, FL_X1 + (it >> 3), bi), 8);
                        DP(8 * (FL_X1 + (it >> 3)) + 3);
                        fence_proxy_async();
                        DP(8 * (FL_X1 + (it >> 3)) + 4);
                        if (it == 3) tma_load_2d(s_r + 2 * R4_STAGE, &tm.act, f4 + 16, own_first(2), R_X1 + tb);
                    }
                    if (it >= 3) tma_load_2d(sa, &tm.act, full, kc, R_X1 + tb);
                    if (++s4 == R4_N) { s4 = 0; p4 ^= 1; }
                }
                wait_flag(flag_ptr(layer, FL_H2, bi), 8);
                fence_proxy_async();
                s5 = 0;
#pragma unroll 1
                for (int j = 0; j < 7; j++) {
                    if (j > 0 && (j & 1) == 0) {
                        mbar_wait(b_h2 + 4 * j, layer);
                        fence_proxy_async();
                    }
                    const int ra = R_H2 + (j >> 1) * 256 + tb;
#pragma unroll 1
                    for (int b = 0; b < 8; b++) {
                        if (j == 0 && b < R4_N) mbar_wait(e4 + 8 * b, p4);
                        putB(&tm.w4, (7 * b + j) * BK, R5_STAGE);
                        putA(((j & 1) * 8 + b) * BK, ra);
                    }
                }
            }
        } } else {
            pdl_wait();
#pragma unroll 1
            for (int layer = 0; layer < 2; layer++) {
                if (warp == 10) {
#pragma unroll 1
                    for (int kind = 0; kind < 6; kind += 2) {
                        const uint32_t src = kind == FL_H ? s_stg : s_epi;
                        const int r = kind == FL_H ? R_H + layer * R_HP + m0 : (kind == FL_XA ? R_XA : R_X1) + tb;
#pragma unroll 1
                        for (int hf = 0; hf < 2; hf++) {
                            named_bar_sync(5 + hf, 288);
                            if (lane == 0) {
                                DP(8 * (kind + hf));
                                tma_store_2d(&tm.act, src + hf * 16384, bj * 128 + hf * 64, r);
                                asm volatile("cp.async.bulk.commit_group;" ::: "memory");
                                asm volatile("cp.async.bulk.wait_group 0;" ::: "memory");
                                DP(8 * (kind + hf) + 1);
                                DP(8 * (kind + hf) + 2);
                                unsigned int* fp = flag_ptr(layer, kind + hf, bi);
                                asm volatile("red.relaxed.gpu.global.add.u32 [%0], 1;" ::"l"(fp) : "memory");
                                if (kind == FL_H) {
                                    if (bi > 0) asm volatile("red.relaxed.gpu.global.add.u32 [%0], 1;" ::"l"(fp - FL_PITCH) : "memory");
                                    if (bi < 15) asm volatile("red.relaxed.gpu.global.add.u32 [%0], 1;" ::"l"(fp + FL_PITCH) : "memory");
                                }
                            }
                            __syncwarp();
                        }
                    }
                } else if (warp == 9) {
                    uint32_t* rs = reinterpret_cast<uint32_t*>(sgen + OFF_RS);
                    float* cs = reinterpret_cast<float*>(sgen + OFF_CS);
#pragma unroll 1
                    for (int which = 0; which < 2; which++) {
                        if (lane == 0 && (layer | which)) wait_flag(flag_ptr(layer, which == 0 ? FL_XA : FL_X1, bi), 8);
                        __syncwarp();
#pragma unroll 1
                        for (int c = (which == 0 && layer == 0 ? 0 : 256) + lane * 4; c < (which == 0 ? 384 : 448); c += 128) {
                            const float* cp = g_cpart + (which == 0 && c >= 256 ? F_ + bj * 128 - 256 : bj * 448) + c;
                            float4 a = make_float4(0.f, 0.f, 0.f, 0.f);
#pragma unroll
                            for (int r0 = 0; r0 < 16; r0 += 8) {
                                float4 v[8];
#pragma unroll
                                for (int r = 0; r < 8; r++) v[r] = __ldcg(reinterpret_cast<const float4*>(cp + (r0 + r) * (F_ + D_)));
#pragma unroll
                                for (int r = 0; r < 8; r++) { a.x += v[r].x; a.y += v[r].y; a.z += v[r].z; a.w += v[r].w; }
                            }
                            *reinterpret_cast<float4*>(cs + c) = a;
                        }
#pragma unroll 1
                        for (int i = 0; i < 4; i++) {
                            const int r = i * 32 + lane;
                            float mean, var;
                            row_stats(g_stats + (3 * layer + 1 + which) * S_ * 8 + bi * 1024 + r, mean, var);
                            const uint32_t c0 = pack2(mean, fsqrt(bfr(bfr(var) + 1e-5f)));
                            rs[r] = c0;
                            const float rd = frcp(hi2f(c0));
                            rs[128 + r] = pack2((mean - lo2f(c0)) * rd, fsqrt(bfr(bfr(var * rd * rd) + 1e-5f)));
                        }
                        __syncwarp();
                        named_bar_arrive(3, 288);
                    }
                }
                const uint32_t s_cnt = s_bar + 224;
                auto ticket = [&](uint32_t a) {
                    uint32_t v = 0;
                    if (lane == 0) asm volatile("atom.acq_rel.cta.shared.add.u32 %0, [%1], 1;" : "=r"(v) : "r"(a) : "memory");
                    return v;
                };
                mbar_wait(b_stg, 0);
                int u = __shfl_sync(0xffffffffu, ticket(s_cnt + 16 + 4 * layer), 0), step = 0;
#pragma unroll 1
                while (true) {
#pragma unroll 1
                    for (; step < 5 && u >= (int)((0x3830201810ull >> (8 * step)) & 255); step++) {
                        if (step == 1) { named_bar_arrive(4, 352); continue; }
                        const int part = step ? step - 1 : 0;
                        __syncwarp();
                        if (ticket(s_cnt + 4 * part) == 3 * layer + 2) {
                            asm volatile("fence.release.gpu;" ::: "memory");
                            unsigned int* fp = flag_ptr(layer, FL_H2 + part, bi);
                            asm volatile("red.relaxed.gpu.global.add.u32 [%0], 1;" ::"l"(fp) : "memory");
                            if (part > 0) { wait_flag(fp, 8); mbar_arrive(b_h2 + 8 * part); }
                        }
                        __syncwarp();
                        if (step == 2) mbar_wait(b_stg, 1);
                    }
                    if (u >= 56) break;
                    const uint32_t un = ticket(s_cnt + 16 + 4 * layer);
                    const int job = u >> 3, r = (u & 7) * 16 + (lane >> 3);
                    const uint32_t sp = sbase + ((job & 2) ? OFF_STG5 : OFF_EPI) + r * 256 + (job & 1) * 128;
                    bf16* gp = act + (size_t)(R_H2 + (job >> 1) * 256 + tb + r) * D_ + ((job & 1) * 8 + bj) * 64 + (lane & 7) * 8;
                    uint4 v[4];
#pragma unroll
                    for (int e = 0; e < 4; e++) v[e] = lds128(sp + e * 1024 + (((lane & 7) ^ ((r + 4 * e) & 7)) << 4));
#pragma unroll
                    for (int e = 0; e < 4; e++) stg128(gp + 4 * e * D_, gelu8h(v[e]));
                    u = __shfl_sync(0xffffffffu, un, 0);
                }
                if (layer == 0 && warp == 11) {
                    const char* ps = reinterpret_cast<const char*>(g_stats + 3 * S_ * 8 + bi * 1024) + lane * 128;
                    const char* py = reinterpret_cast<const char*>(act + (size_t)(R_Y + (tb & ~255) + (bj & 1) * 128 + (lane >> 1)) * D_ + (bj >> 1) * 256 + rank * 128) + (lane & 1) * 128;
#pragma unroll 1
                    for (int i = 0; i < 8; i++) {
                        asm volatile("prefetch.global.L2 [%0];" ::"l"(py + (size_t)i * 16 * D_ * 2) : "memory");
                        if (i >= 6) asm volatile("prefetch.global.L2 [%0];" ::"l"(ps + (i & 1) * 4096) : "memory");
                        __nanosleep(400);
                    }
                }
            }
        }
        __syncwarp();
        asm volatile("barrier.cluster.arrive.relaxed.aligned;\nbarrier.cluster.wait.acquire.aligned; // helpers" ::: "memory");
    } else {
        asm volatile("setmaxnreg.inc.sync.aligned.u32 216;");
        const int tid = threadIdx.x;
        const int wg = warp >> 2;
        const bool rel_on = (tid & 95) == 0;
        const uint32_t rel5 = mapa_u32(e5, (warp & 1) ^ rank), rel4 = rel5 + (e4 - e5);
        const uint32_t da0 = desc_a(s_r + wg * 8192), db0 = desc_b(s_r + BM * BK * 2), dae = da0 + (OFF_EPI - OFF_R) / 16, db4 = db0 - 49152 / 16;
        auto skip5 = [&](RingState& rs) {
            if (rel_on) mbar_arrive_cluster(rel5 + 8 * rs.st);
            rs.st++;
        };
        const int t = lane & 3;
        const int row = warp * 16 + (lane >> 2);
        const uint32_t st_w = (uint32_t)((warp * 16 + ((lane >> 3) & 1) * 8 + (lane & 7)) * 256 + (((lane >> 4) ^ (lane & 7)) << 4));
        const uint32_t fr = (uint32_t)((warp * 16 + ((lane >> 3) & 1) * 8 + (lane & 7)) * 128 + (((lane >> 4) ^ (lane & 7)) << 4));
        auto copy_out = [&](bf16* dst, uint32_t src) {
            const int r = warp * 16 + (lane >> 4);
            bf16* ox = dst + (size_t)(m0 + r) * D_ + bj * 128 + (lane & 15) * 8;
            const uint32_t ra = src + ((lane & 15) >> 3) * 16384 + r * 128;
            uint4 v[8];
#pragma unroll
            for (int it = 0; it < 8; it++) v[it] = lds128(ra + it * 256 + (((lane & 7) ^ ((2 * it + (lane >> 4)) & 7)) << 4));
#pragma unroll
            for (int it = 0; it < 8; it++) *reinterpret_cast<uint4*>(ox + (size_t)it * 2 * D_) = v[it];
        };
        auto put_stats = [&](const uint32_t (&w)[32], int which) {
            float sm[2] = {0.f, 0.f}, sq[2] = {0.f, 0.f};
#pragma unroll
            for (int e = 0; e < 32; e++) {
                const float e0 = lo2f(w[e]), e1 = hi2f(w[e]);
                sm[e & 1] += e0 + e1; sq[e & 1] = fmaf(e0, e0, fmaf(e1, e1, sq[e & 1]));
            }
#pragma unroll
            for (int of = 1; of < 4; of <<= 1)
#pragma unroll
                for (int e = 0; e < 2; e++) { sm[e] += __shfl_xor_sync(0xffffffffu, sm[e], of); sq[e] += __shfl_xor_sync(0xffffffffu, sq[e], of); }
            if (t < 2) {
                const float s1 = t ? sm[1] : sm[0], q1 = t ? sq[1] : sq[0], mu = s1 * (1.0f / 128);
                asm volatile("{\n.reg .b64 t;\nmov.b64 t, {%1, %2};\nst.relaxed.gpu.global.b64 [%0], t;\n}"
                             ::"l"(g_stats + which * S_ * 8 + (bi * 8 + bj) * 128 + row + 8 * t), "f"(mu), "f"(fmaxf(q1 - s1 * mu, 0.f)) : "memory");
            }
        };
        const float* csp = reinterpret_cast<const float*>(sgen + OFF_CS) + 2 * t;
        float mrow[2], rrow[2];
        const uint32_t* rsp = reinterpret_cast<const uint32_t*>(sgen + OFF_RS) + row;
        auto row_consts = [&](bool twice) {
#pragma unroll
            for (int e = 0; e < 2; e++) {
                const uint32_t q0 = rsp[8 * e], q1 = rsp[128 + 8 * e];
                mrow[e] = twice ? fmaf(lo2f(q1), hi2f(q0), lo2f(q0)) : lo2f(q0);
                rrow[e] = 0.5f * frcp(twice ? hi2f(q0) * hi2f(q1) : hi2f(q0));
            }
        };
        auto stage = [&](const float* acc, uint32_t dst, int j0, float2 (&cs)[8], const float* cnext) {
            float2 cn[8];
#pragma unroll
            for (int e = 0; e < 8; e++) cn[e] = *reinterpret_cast<const float2*>(cnext + 8 * e);
#pragma unroll
            for (int j = 0; j < 8; j += 2) {
                uint32_t w[4];
#pragma unroll
                for (int e = 0; e < 2; e++) {
                    const float* a = acc + 4 * (j + e);
                    w[2 * e] = pack2(fmaf(-mrow[0], cs[j + e].x, a[0]) * rrow[0], fmaf(-mrow[0], cs[j + e].y, a[1]) * rrow[0]);
                    w[2 * e + 1] = pack2(fmaf(-mrow[1], cs[j + e].x, a[2]) * rrow[1], fmaf(-mrow[1], cs[j + e].y, a[3]) * rrow[1]);
                }
                stsm4((dst + st_w) ^ (((j0 + j) & 15) << 4), w[0], w[1], w[2], w[3]);
            }
#pragma unroll
            for (int e = 0; e < 8; e++) cs[e] = cn[e];
        };
        RingState r5{0, 0}, r4{0, 0};
        skip5(r5);
        DT(1);
        uint32_t x[32];
        mbar_wait(b_rfull, 0);
#pragma unroll
        for (int jp = 0; jp < 8; jp++) ldsm4(x[4 * jp], x[4 * jp + 1], x[4 * jp + 2], x[4 * jp + 3], s_epi + (fr ^ ((jp & 3) << 5)) + (jp >> 2) * 16384);
#pragma unroll 1
        for (int layer = 0; layer < 2; layer++) {
            {
                DT(2 + 24 * layer);
                if (layer == 1) put_stats(x, 3);
                else pdl_wait();
                DT(20 + 24 * layer);
                DT(22 + 24 * layer);
                uint32_t mb[2];
                float rd[2];
                {
                    float mean, var;
                    row_stats(g_stats + 3 * layer * S_ * 8 + bi * 1024 + warp * 16 + (lane & 15), mean, var);
                    __syncwarp();
                    const float r1 = frcp(bfr(fsqrt(bfr(bfr(var) + 1e-5f))));
                    const uint32_t m1 = pack2(mean, mean);
#pragma unroll
                    for (int e = 0; e < 2; e++) { mb[e] = __shfl_sync(0xffffffffu, m1, (lane >> 2) + 8 * e); rd[e] = __shfl_sync(0xffffffffu, r1, (lane >> 2) + 8 * e); }
                }
                DT(21 + 24 * layer);
                mbar_wait(f5 + 8, r5.ph);
                if (layer == 0) GT(3);
                const uint32_t ya = s_r + R5_STAGE + wg * 16384 + ((lane >> 4) * 8 + (lane & 7)) * 128 + ((((warp & 3) * 2 + ((lane >> 3) & 1)) ^ (lane & 7)) << 4);
                uint32_t y[16];
#pragma unroll
                for (int e = 0; e < 32; e++) {
                    if ((e & 15) == 0) {
#pragma unroll
                        for (int jp = 0; jp < 4; jp++) ldsm4t(y[4 * jp], y[4 * jp + 1], y[4 * jp + 2], y[4 * jp + 3], ya + jp * 2048 + e * 512);
                    }
                    const uint32_t d = bsub2(x[e], mb[e & 1]);
                    x[e] = badd2(x[e], bmul2(pack2(lo2f(d) * rd[e & 1], hi2f(d) * rd[e & 1]), y[e & 15]));
                    if ((e & 3) == 3) stsm4(s_epi + (fr ^ (((e >> 2) & 3) << 5)) + (e >> 4) * 16384, x[e - 3], x[e - 2], x[e - 1], x[e]);
                    if ((e & 15) == 15) { fence_async_smem(); named_bar_arrive(5 + (e >> 4), 288); }
                }
                DT(19 + 24 * layer);
                named_bar_sync(9 + wg, 128);
                skip5(r5);
                DT(3 + 24 * layer);
            }
            {
                float acc[64];
                zero_acc(acc);
                kblock<128, R5_N>(acc, dae, db0 + 2 * (R5_STAGE / 16), f5, r5);
                kblock<128, R5_N>(acc, dae + 1024, db0 + 3 * (R5_STAGE / 16), f5, r5);
                put_stats(x, 3 * layer + 1);
                wgmma_wait<1>();
                if (rel_on) mbar_arrive_cluster(rel5 + 16);
                mainloop<128, R5_N, R5_STAGE>(acc, 14, da0, db0, f5, rel5, rel_on, r5, 15 + 24 * layer);
                DT(4 + 24 * layer);
                named_bar_sync(3, 288);
                row_consts(true);
                float2 cs[8];
#pragma unroll
                for (int j = 0; j < 16; j += 2) {
                    if ((j & 7) == 0) {
#pragma unroll
                        for (int e = 0; e < 8; e++) cs[e] = *reinterpret_cast<const float2*>(csp + 256 + 8 * (j + e));
                    }
                    uint32_t w[4];
#pragma unroll
                    for (int e = 0; e < 4; e++) {
                        const float* a = acc + 4 * j + 2 * e;
                        const float2 c = cs[(j & 7) + (e >> 1)];
                        w[e] = pack2(gelu_tanh_h(fmaf(-mrow[e & 1], c.x, a[0]) * rrow[e & 1]), gelu_tanh_h(fmaf(-mrow[e & 1], c.y, a[1]) * rrow[e & 1]));
                    }
                    stsm4(s_stg + (fr ^ ((j & 7) << 4)) + (j >> 3) * 16384, w[0], w[1], w[2], w[3]);
                    if ((j & 7) == 6) { fence_async_smem(); named_bar_arrive(5 + (j >> 3), 288); }
                }
                DT(5 + 24 * layer);
            }
            {
                float acc[64];
                zero_acc(acc);
                uint32_t u[32];
                {
                    uint32_t mb[2];
                    float rd[2];
#pragma unroll
                    for (int e = 0; e < 2; e++) { const uint32_t q0 = rsp[8 * e]; mb[e] = (q0 & 0xffffu) * 0x10001u; rd[e] = frcp(hi2f(q0)); }
#pragma unroll
                    for (int e = 0; e < 32; e++) {
                        const uint32_t d = bsub2(x[e], mb[e & 1]);
                        u[e] = pack2(lo2f(d) * rd[e & 1], hi2f(d) * rd[e & 1]);
                        asm volatile("" : "+r"(u[e]));
                    }
                }
                mbar_wait(f5 + 24, r5.ph);
                skip5(r5);
                kblock<128, R5_N>(acc, da0 + 4 * (R5_STAGE / 16), db0 + 4 * (R5_STAGE / 16), f5, r5);
                DT(16 + 24 * layer);
                mainloop<128, R5_N, R5_STAGE>(acc, 15, da0, db0, f5, rel5, rel_on, r5, -1);
                DT(6 + 24 * layer);
#pragma unroll
                for (int j = 0; j < 16; j += 2) {
#pragma unroll
                    for (int e = 0; e < 4; e++) u[2 * j + e] = badd2(u[2 * j + e], pack2(acc[4 * j + 2 * e], acc[4 * j + 2 * e + 1]));
                    stsm4(s_epi + (fr ^ ((j & 7) << 4)) + (j >> 3) * 16384, u[2 * j], u[2 * j + 1], u[2 * j + 2], u[2 * j + 3]);
                    if ((j & 7) == 6) { fence_async_smem(); named_bar_arrive(5 + (j >> 3), 288); }
                }
#pragma unroll
                for (int e = 0; e < 32; e++) x[e] = badd2(x[e], u[e]);
                named_bar_sync(9 + wg, 128);
                DT(7 + 24 * layer);
                if (layer == 0) GT(7);
            }
            {
                float2 cs[8];
                {
                    float acc[128];
                    zero_acc(acc);
                    kblock<256, R4_N>(acc, dae, db4, f4, r4);
                    kblock<256, R4_N>(acc, dae + 1024, db4 + R4_STAGE / 16, f4, r4);
                    {
                        uint32_t w[32];
#pragma unroll
                        for (int jp = 0; jp < 8; jp++) ldsm4(w[4 * jp], w[4 * jp + 1], w[4 * jp + 2], w[4 * jp + 3], s_epi + (fr ^ ((jp & 3) << 5)) + (jp >> 2) * 16384);
                        put_stats(w, 3 * layer + 2);
                    }
                    wgmma_wait<1>();
                    if (rel_on) mbar_arrive_cluster(rel4);
                    mainloop<256, R4_N, R4_STAGE>(acc, 14, da0, db4, f4, rel4, rel_on, r4, 17 + 24 * layer);
                    DT(8 + 24 * layer);
                    named_bar_sync(3, 288);
                    row_consts(false);
#pragma unroll
                    for (int e = 0; e < 8; e++) cs[e] = *reinterpret_cast<const float2*>(csp + 8 * e);
#pragma unroll
                    for (int j = 0; j < 32; j += 8) stage(acc + 4 * j, j < 16 ? s_epi : s_stg, j, cs, csp + 8 * (j + 8));
                    __syncwarp();
                if (lane == 0) mbar_arrive(b_stg);
                }
                DT(9 + 24 * layer);
                float acc[96];
                zero_acc(acc);
                kblock<192, R4_N>(acc, da0, db0, f4, r4);
                mainloop<192, R4_N, R4B_STAGE>(acc, 15, da0, db0, f4, rel4, rel_on, r4, -1);
                DT(10 + 24 * layer);
                named_bar_sync(4, 352);
#pragma unroll
                for (int j = 0; j < 24; j += 8) stage(acc + 4 * j, j < 16 ? s_epi : s_stg, j, cs, csp + 256 + 8 * (j < 16 ? j + 8 : 0));
                __syncwarp();
                if (lane == 0) mbar_arrive(b_stg);
                DT(11 + 24 * layer);
            }
            {
                float acc[64];
#pragma unroll
                for (int i = 0; i < 32; i++) asm volatile("shl.b32 %0, %2, 16;\nand.b32 %1, %2, 0xffff0000;" : "=f"(acc[2 * i]), "=f"(acc[2 * i + 1]) : "r"(x[i]));
                kblock<128, R5_N>(acc, da0, db0, f5, r5);
                DT(18 + 24 * layer);
                mainloop<128, R5_N, R5_STAGE>(acc, 55, da0, db0, f5, rel5, rel_on, r5, 62 - 40 * (layer ^ 1));
                DT(12 + 24 * layer);
#pragma unroll
                for (int i = 0; i < 32; i++) x[i] = pack2(acc[2 * i], acc[2 * i + 1]);
                DT(13 + 24 * layer);
                if (layer == 0) GT(6);
                DT(14 + 24 * layer);
            }
        }
#pragma unroll
        for (int jp = 0; jp < 8; jp++) stsm4(s_epi + (fr ^ ((jp & 3) << 5)) + (jp >> 2) * 16384, x[4 * jp], x[4 * jp + 1], x[4 * jp + 2], x[4 * jp + 3]);
        __syncwarp();
        copy_out(outp, s_epi);
        DT(38);
        GT(4);
        cluster_arrive_relaxed();
        cluster_wait();
    }
}

constexpr int CV_CH = 8;
constexpr int CV_UPITCH = 72;
constexpr int CV_UROWS = 40;
constexpr int CV_U_BYTES = CV_UROWS * CV_UPITCH * 2;
constexpr int CV_P_WORDS = 2048 + 16;
constexpr int CV_P_BYTES = CV_P_WORDS * 4;
constexpr int CV_Y_BYTES = 8 * CV_UPITCH * 2;
constexpr int CV_SMEM = CV_CH * (CV_U_BYTES + CV_P_BYTES + CV_Y_BYTES) + 2 * 8 * 16 * 32 * 4 + 128 + (128 + 2048 * 16) + 2048 * 16;

__device__ __forceinline__ void mma16816(float (&d)[4], uint32_t a0, uint32_t a1, uint32_t a2, uint32_t a3, uint32_t b0, uint32_t b1) {
    asm volatile("mma.sync.aligned.m16n8k16.row.col.f32.bf16.bf16.f32 {%0,%1,%2,%3}, {%4,%5,%6,%7}, {%8,%9}, {%0,%1,%2,%3};"
                 : "+f"(d[0]), "+f"(d[1]), "+f"(d[2]), "+f"(d[3]) : "r"(a0), "r"(a1), "r"(a2), "r"(a3), "r"(b0), "r"(b1));
}
__device__ __forceinline__ void stsm4t(uint32_t addr, uint32_t r0, uint32_t r1, uint32_t r2, uint32_t r3) {
    asm volatile("stmatrix.sync.aligned.m8n8.x4.trans.shared.b16 [%0], {%1,%2,%3,%4};" ::"r"(addr), "r"(r0), "r"(r1), "r"(r2), "r"(r3) : "memory");
}
__device__ __forceinline__ void ldsm4c(uint32_t& r0, uint32_t& r1, uint32_t& r2, uint32_t& r3, uint32_t addr) {
    asm volatile("ldmatrix.sync.aligned.m8n8.x4.shared.b16 {%0,%1,%2,%3}, [%4];" : "=r"(r0), "=r"(r1), "=r"(r2), "=r"(r3) : "r"(addr));
}
__global__ void __launch_bounds__(640, 1)
conv_kernel(const __grid_constant__ CUtensorMap tmK, const __grid_constant__ CUtensorMap tmV, const bf16* __restrict__ kp,
            const bf16* __restrict__ vp, const bf16* __restrict__ shk,
            const bf16* __restrict__ ssk, const bf16* __restrict__ ssD, const bf16* __restrict__ w1p, const bf16* __restrict__ w3p,
            const bf16* __restrict__ xq, bf16* act) {
    extern __shared__ __align__(128) uint8_t sm[];
    uint8_t* sU = sm;
    uint8_t* sP = sm + CV_CH * CV_U_BYTES;
    uint8_t* sY = sP + CV_CH * CV_P_BYTES;
    float* sR = reinterpret_cast<float*>(sY + CV_CH * CV_Y_BYTES);
    const int tid = threadIdx.x, warp = tid >> 5, lane = tid & 31;
    const int d0 = blockIdx.x * CV_CH;
    const uint32_t bar0 = smem_u32(sR + 2 * 8 * 16 * 32);
    const uint8_t* sK = reinterpret_cast<const uint8_t*>(sR + 2 * 8 * 16 * 32) + 128 + 128;
    const uint8_t* sV = sK + 2048 * 16;
    DBG_T(0);
    GT(0);
    auto load_kv = [&](int q) {
        mbar_expect_tx(bar0 + 64 + 8 * q, 4 * 4096);
        for (int i = 0; i < 2; i++) {
            int r0 = 512 * q + 256 * i;
            tma_load_2d(smem_u32(sK) + r0 * 16, &tmK, bar0 + 64 + 8 * q, d0, r0);
            tma_load_2d(smem_u32(sV) + r0 * 16, &tmV, bar0 + 64 + 8 * q, d0, r0);
        }
    };
    uint4 k0, v0;
    if (tid < 512) {
        k0 = __ldg(reinterpret_cast<const uint4*>(kp + (size_t)tid * D_ + d0));
        v0 = __ldg(reinterpret_cast<const uint4*>(vp + (size_t)tid * D_ + d0));
    }
    if (tid == 512) {
        for (int i = 0; i < 4; i++) { mbar_init(bar0 + 8 * i, 4); mbar_init(bar0 + 32 + 8 * i, 4); mbar_init(bar0 + 64 + 8 * i, i == 0 ? 16 : 1); }
        asm volatile("fence.mbarrier_init.release.cluster;" ::: "memory");
        fence_async_smem();
    }
    if (tid >= 32 && tid < 35) *reinterpret_cast<uint4*>(const_cast<uint8_t*>(sK) - 16 * (tid - 31)) = make_uint4(0, 0, 0, 0);
    for (int i = tid; tid < 512 && i < CV_CH * 8 * CV_UPITCH / 8; i += 512) {
        int c2 = i / (8 * CV_UPITCH / 8), r = i % (8 * CV_UPITCH / 8);
        *reinterpret_cast<uint4*>(sU + c2 * CV_U_BYTES + r * 16) = make_uint4(0, 0, 0, 0);
    }
    if (warp < 8 && lane < 16) reinterpret_cast<uint32_t*>(sP + warp * CV_P_BYTES)[lane] = 0;

    if (warp >= 16) {
        const int bt = tid - 512;
        uint32_t wv[4][4];
#pragma unroll
        for (int pr = 0; pr < 4; pr++) {
            uint2 wa = *reinterpret_cast<const uint2*>(shk + (d0 + 2 * pr) * 4);
            uint2 wb = *reinterpret_cast<const uint2*>(shk + (d0 + 2 * pr + 1) * 4);
            wv[0][pr] = (wa.x & 0xffffu) | (wb.x << 16);
            wv[1][pr] = (wa.x >> 16) | (wb.x & 0xffff0000u);
            wv[2][pr] = (wa.y & 0xffffu) | (wb.y << 16);
            wv[3][pr] = (wa.y >> 16) | (wb.y & 0xffff0000u);
        }
        const int pch = bt >> 4, pl = bt & 15;
        const bf16* hrow = ssk + (size_t)(d0 + pch) * S_ + pl * 8;
        uint32_t* Pw = reinterpret_cast<uint32_t*>(sP + pch * CV_P_BYTES) + 16 + pl * 8;
        uint4 pf[4];
        uint32_t hprev[4];
        auto prefetch = [&](int q) {
#pragma unroll
            for (int i = 0; i < 4; i++) {
                int j0 = 512 * q + i * 128;
                pf[i] = __ldg(reinterpret_cast<const uint4*>(hrow + j0));
                hprev[i] = (j0 + pl > 0) ? (uint32_t)__bfloat16_as_ushort(hrow[j0 - 1]) : 0u;
            }
        };
        prefetch(0);
        asm volatile("barrier.sync 0, 640;" ::: "memory");
        pdl_wait();
        if (blockIdx.x == 0) {
            for (int i = bt; i < FL_WORDS / FL_PITCH; i += 128) g_flag[i * FL_PITCH] = 0;
            if (bt < 9) { g_ticket[bt * FL_PITCH] = 0; __threadfence(); }
        }
        __syncwarp();
        if (warp == 16) pdl_launch();
        for (int i = bt; i < 320; i += 128) reinterpret_cast<float4*>(g_stats + S_ * 8)[blockIdx.x * 320 + i] = make_float4(-1.f, -1.f, -1.f, -1.f);
#pragma unroll 1
        for (int q = 0; q < 4; q++) {
#pragma unroll
            for (int i = 0; i < 4; i++) {
                int j0 = 512 * q + i * 128;
                uint32_t x0 = pf[i].x, x1 = pf[i].y, x2 = pf[i].z, x3 = pf[i].w;
                uint4 o0, o1;
                o0.x = (x0 & 0xffffu) | (hprev[i] << 16);
                o0.y = (x0 >> 16) | (x0 << 16);
                o0.z = (x1 & 0xffffu) | (x0 & 0xffff0000u);
                o0.w = (x1 >> 16) | (x1 << 16);
                o1.x = (x2 & 0xffffu) | (x1 & 0xffff0000u);
                o1.y = (x2 >> 16) | (x2 << 16);
                o1.z = (x3 & 0xffffu) | (x2 & 0xffff0000u);
                o1.w = (x3 >> 16) | (x3 << 16);
                *reinterpret_cast<uint4*>(Pw + j0) = o0;
                *reinterpret_cast<uint4*>(Pw + j0 + 4) = o1;
            }
            DBG_T(1 + 3 * q);
            mbar_wait(bar0 + 64 + 8 * q, 0);
            if (q < 3) {
                if (bt == 0) load_kv(q + 1);
                prefetch(q + 1);
            }
            DBG_T(2 + 3 * q);
#pragma unroll 1
            for (int hf = 0; hf < 2; hf++) {
                const int s0 = 512 * q + 256 * hf + 2 * bt;
                const int a = s0 >> 6, b = s0 & 63;
                uint4 kf[7];
#pragma unroll
                for (int i = 0; i < 5; i++) kf[i] = *reinterpret_cast<const uint4*>(sK + (s0 - 3 + i) * 16);
#pragma unroll
                for (int i = 0; i < 2; i++) kf[5 + i] = *reinterpret_cast<const uint4*>(sV + (s0 + i) * 16);
#pragma unroll
                for (int pr = 0; pr < 4; pr++) {
                    uint32_t k0 = reinterpret_cast<const uint32_t*>(&kf[0])[pr], k1 = reinterpret_cast<const uint32_t*>(&kf[1])[pr],
                             k2 = reinterpret_cast<const uint32_t*>(&kf[2])[pr], k3 = reinterpret_cast<const uint32_t*>(&kf[3])[pr],
                             k4 = reinterpret_cast<const uint32_t*>(&kf[4])[pr];
                    uint32_t r0 = bmul2(k0, wv[3][pr]);
                    r0 = badd2(r0, bmul2(k1, wv[2][pr]));
                    r0 = badd2(r0, bmul2(k2, wv[1][pr]));
                    r0 = badd2(r0, bmul2(k3, wv[0][pr]));
                    r0 = bmul2(r0, reinterpret_cast<const uint32_t*>(&kf[5])[pr]);
                    uint32_t r1 = bmul2(k1, wv[3][pr]);
                    r1 = badd2(r1, bmul2(k2, wv[2][pr]));
                    r1 = badd2(r1, bmul2(k3, wv[1][pr]));
                    r1 = badd2(r1, bmul2(k4, wv[0][pr]));
                    r1 = bmul2(r1, reinterpret_cast<const uint32_t*>(&kf[6])[pr]);
                    uint32_t c0 = (r0 & 0xffffu) | (r1 << 16), c1 = (r0 >> 16) | (r1 & 0xffff0000u);
                    *reinterpret_cast<uint32_t*>(sU + (2 * pr) * CV_U_BYTES + ((8 + a) * CV_UPITCH + b) * 2) = c0;
                    *reinterpret_cast<uint32_t*>(sU + (2 * pr + 1) * CV_U_BYTES + ((8 + a) * CV_UPITCH + b) * 2) = c1;
                }
            }
            __syncwarp();
            if (lane == 0) mbar_arrive(bar0 + 8 * q);
            DBG_T(3 + 3 * q);
        }
        {
            const int bi = blockIdx.x >> 3, bj = blockIdx.x & 7;
            const bool is3 = bt < 112;
            const int cg = is3 ? bt % 56 : bt - 112, pitch = is3 ? F_ : D_, col = is3 ? bj * 448 + cg * 8 : bj * 128 + cg * 8;
            const int r1 = is3 ? 32 : 64;
            const bf16* p = (is3 ? w3p + (size_t)(bt >= 56 ? 32 : 0) * F_ : w1p) + (size_t)(bi * 64) * pitch + col;
            float a8[8];
#pragma unroll
            for (int i = 0; i < 8; i++) a8[i] = 0.f;
#pragma unroll 1
            for (int r0 = 0; r0 < r1; r0 += 16) {
                uint4 v[16];
#pragma unroll
                for (int r = 0; r < 16; r++) v[r] = __ldg(reinterpret_cast<const uint4*>(p + (size_t)(r0 + r) * pitch));
#pragma unroll
                for (int r = 0; r < 16; r++) {
                    a8[0] += lo2f(v[r].x); a8[1] += hi2f(v[r].x); a8[2] += lo2f(v[r].y); a8[3] += hi2f(v[r].y);
                    a8[4] += lo2f(v[r].z); a8[5] += hi2f(v[r].z); a8[6] += lo2f(v[r].w); a8[7] += hi2f(v[r].w);
                }
            }
            float* sc = reinterpret_cast<float*>(const_cast<uint8_t*>(sK));
            mbar_wait(bar0, 0);
            if (bt >= 56 && is3) {
#pragma unroll
                for (int i = 0; i < 8; i++) sc[cg * 8 + i] = a8[i];
            }
            __syncwarp();
            if (lane == 0) mbar_arrive(bar0 + 32);
            mbar_wait(bar0 + 32, 0);
            if (bt < 56 || !is3) {
                if (is3) {
#pragma unroll
                    for (int i = 0; i < 8; i++) a8[i] += sc[cg * 8 + i];
                }
                float4* dst = reinterpret_cast<float4*>(g_cpart + bi * (F_ + D_) + (is3 ? 0 : F_) + col);
                dst[0] = make_float4(a8[0], a8[1], a8[2], a8[3]);
                dst[1] = make_float4(a8[4], a8[5], a8[6], a8[7]);
            }
        }
        {
            const int r = blockIdx.x * 16 + (warp - 16) * 4;
            uint4 v[16];
#pragma unroll
            for (int e = 0; e < 16; e++) v[e] = __ldg(reinterpret_cast<const uint4*>(xq + (size_t)r * D_ + e * 256 + lane * 8));
            float sm[4] = {0.f, 0.f, 0.f, 0.f}, sq[4] = {0.f, 0.f, 0.f, 0.f};
#pragma unroll
            for (int e = 0; e < 64; e++) {
                const uint32_t w = reinterpret_cast<const uint32_t*>(v)[e];
                sm[e >> 4] += lo2f(w) + hi2f(w); sq[e >> 4] = fmaf(lo2f(w), lo2f(w), fmaf(hi2f(w), hi2f(w), sq[e >> 4]));
            }
#pragma unroll
            for (int o = 16; o > 0; o >>= 1)
#pragma unroll
                for (int e = 0; e < 4; e++) { sm[e] += __shfl_xor_sync(0xffffffffu, sm[e], o); sq[e] += __shfl_xor_sync(0xffffffffu, sq[e], o); }
            const int e = lane >> 3;
            const float s1 = e == 0 ? sm[0] : e == 1 ? sm[1] : e == 2 ? sm[2] : sm[3], q1 = e == 0 ? sq[0] : e == 1 ? sq[1] : e == 2 ? sq[2] : sq[3];
            const float mu = s1 * (1.0f / D_);
            g_stats[((r >> 7) * 8 + (lane & 7)) * 128 + (r & 127) + e] = make_float2(mu, fmaxf(q1 - s1 * mu, 0.f) * 0.125f);
        }
        DBG_T(13);
        return;
    }

    asm volatile("barrier.sync 0, 640;" ::: "memory");
    *reinterpret_cast<uint4*>(const_cast<uint8_t*>(sK) + tid * 16) = k0;
    *reinterpret_cast<uint4*>(const_cast<uint8_t*>(sV) + tid * 16) = v0;
    __syncwarp();
    if (lane == 0) mbar_arrive(bar0 + 64);
    const int ch = warp & 7, par = warp >> 3;
    const int g = lane >> 2, t = lane & 3;
    const uint32_t* P = reinterpret_cast<const uint32_t*>(sP + ch * CV_P_BYTES) + 16 + (g - 2 * t);
    const uint32_t uB = smem_u32(sU + ch * CV_U_BYTES);
    const int lrow = lane & 7, lmat = lane >> 3;
    const uint32_t Dk2 = (uint32_t)__bfloat16_as_ushort(ssD[d0 + ch]) * 0x10001u;
    pdl_wait();
    GT(5);

#pragma unroll 1
    for (int q = 0; q < 4; q++) {
        mbar_wait(bar0 + 8 * q, 0);
        DBG_T(1 + 3 * q);
        float acc[4][4];
#pragma unroll
        for (int i = 0; i < 4; i++)
#pragma unroll
            for (int k = 0; k < 4; k++) acc[i][k] = 0.f;
        const int c0 = par * (4 * q + 4), c1 = c0 + 4 * q + 4;
        const uint32_t base0 = uB + ((8 + 8 * q + lrow) * CV_UPITCH) * 2 + lmat * 16;
        int c = c0;
        uint32_t pa[15];
        if (par == 0) {
#pragma unroll
            for (int j = 6; j < 15; j++) pa[j] = P[8 * (j - 7)];
            uint32_t b[8];
            ldsm4c(b[0], b[1], b[2], b[3], base0);
            ldsm4c(b[4], b[5], b[6], b[7], base0 + 64);
#pragma unroll
            for (int kk = 0; kk < 4; kk++)
#pragma unroll
                for (int mi = kk; mi < 4; mi++) {
                    int jj = 2 * (mi - kk) + 7;
                    mma16816(acc[mi], pa[jj], pa[jj + 1], pa[jj - 1], pa[jj], b[2 * kk], b[2 * kk + 1]);
                }
            c = 1;
        } else {
#pragma unroll
            for (int j = 8; j < 15; j++) pa[j] = P[8 * (8 * c - 15 + j)];
        }
#pragma unroll 2
        for (; c < c1; c++) {
#pragma unroll
            for (int j = 0; j < 7; j++) pa[j] = pa[j + 8];
#pragma unroll
            for (int j = 7; j < 15; j++) pa[j] = P[8 * (8 * c - 7 + j)];
            uint32_t b[8];
            uint32_t base = base0 - c * (CV_UPITCH * 2);
            ldsm4c(b[0], b[1], b[2], b[3], base);
            ldsm4c(b[4], b[5], b[6], b[7], base + 64);
#pragma unroll
            for (int kk = 3; kk >= 0; kk--)
#pragma unroll
                for (int mi = 0; mi < 4; mi++) {
                    int jj = 2 * (mi - kk) + 7;
                    mma16816(acc[mi], pa[jj], pa[jj + 1], pa[jj - 1], pa[jj], b[2 * kk], b[2 * kk + 1]);
                }
        }
        DBG_T(2 + 3 * q);
        float4* sRq = reinterpret_cast<float4*>(sR) + ((q & 1) * 8 + ch) * 128 + lane;
        if (par == 1) {
#pragma unroll
            for (int mi = 0; mi < 4; mi++) sRq[mi * 32] = make_float4(acc[mi][0], acc[mi][1], acc[mi][2], acc[mi][3]);
            named_bar_arrive(ch + 8 * (q & 1), 64);
        } else {
            uint32_t kv[8];
            ldsm4t(kv[0], kv[1], kv[2], kv[3], base0);
            ldsm4t(kv[4], kv[5], kv[6], kv[7], base0 + 64);
            named_bar_sync(ch + 8 * (q & 1), 64);
#pragma unroll
            for (int mi = 0; mi < 4; mi++) {
                const float4 o = sRq[mi * 32];
                kv[2 * mi] = badd2(pack2(acc[mi][0] + o.x, acc[mi][1] + o.y), bmul2(kv[2 * mi], Dk2));
                kv[2 * mi + 1] = badd2(pack2(acc[mi][2] + o.z, acc[mi][3] + o.w), bmul2(kv[2 * mi + 1], Dk2));
            }
            const uint32_t yb = smem_u32(sY + ch * CV_Y_BYTES);
            __syncwarp();
            stsm4t(yb + lrow * (CV_UPITCH * 2) + lmat * 16, kv[0], kv[1], kv[2], kv[3]);
            stsm4t(yb + lrow * (CV_UPITCH * 2) + lmat * 16 + 64, kv[4], kv[5], kv[6], kv[7]);
            __syncwarp();
            uint4* dst = reinterpret_cast<uint4*>(act + (size_t)(R_Y + q * 4096 + ((d0 + ch) & 255)) * D_ + (d0 & ~255)) + lane;
            const uint4 v0 = lds128(yb + (lane >> 3) * (CV_UPITCH * 2) + (lane & 7) * 16);
            const uint4 v1 = lds128(yb + (4 + (lane >> 3)) * (CV_UPITCH * 2) + (lane & 7) * 16);
            dst[0] = v0;
            dst[2048 * D_ / 8] = v1;
        }
        DBG_T(3 + 3 * q);
    }
    GT(1);
}

typedef CUresult (*PFN_encodeTiled)(CUtensorMap*, CUtensorMapDataType, cuuint32_t, void*, const cuuint64_t*, const cuuint64_t*,
                                    const cuuint32_t*, const cuuint32_t*, CUtensorMapInterleave, CUtensorMapSwizzle,
                                    CUtensorMapL2promotion, CUtensorMapFloatOOBfill);

static CUtensorMap make_map(PFN_encodeTiled enc, const void* ptr, int inner, int outer, int box_inner, int box_outer,
                            CUtensorMapSwizzle swz = CU_TENSOR_MAP_SWIZZLE_128B) {
    CUtensorMap m;
    cuuint64_t dims[2] = {(cuuint64_t)inner, (cuuint64_t)outer};
    cuuint64_t strides[1] = {(cuuint64_t)inner * 2};
    cuuint32_t box[2] = {(cuuint32_t)box_inner, (cuuint32_t)box_outer};
    cuuint32_t es[2] = {1, 1};
    enc(&m, CU_TENSOR_MAP_DATA_TYPE_BFLOAT16, 2, const_cast<void*>(ptr), dims, strides, box, es, CU_TENSOR_MAP_INTERLEAVE_NONE,
        swz, CU_TENSOR_MAP_L2_PROMOTION_L2_256B, CU_TENSOR_MAP_FLOAT_OOB_FILL_NONE);
    return m;
}

extern "C" void kernel_launch(void* const* d_in, const int* in_sizes, int n_in, void* d_out, int out_size) {
    const bf16* A_q = (const bf16*)d_in[0];
    const bf16* A_k = (const bf16*)d_in[1];
    const bf16* A_v = (const bf16*)d_in[2];
    const bf16* A_shk = (const bf16*)d_in[3];
    const bf16* A_ssk = (const bf16*)d_in[4];
    const bf16* A_ssD = (const bf16*)d_in[5];
    const bf16* w1 = (const bf16*)d_in[7];
    const bf16* w2 = (const bf16*)d_in[8];
    const bf16* w3 = (const bf16*)d_in[9];
    const bf16* w4 = (const bf16*)d_in[10];
    bf16* out = (bf16*)d_out;

    static PFN_encodeTiled enc = nullptr;
    static bool attr_done = false;
    if (!enc) {
        void* fn = nullptr;
        cudaDriverEntryPointQueryResult qr;
        cudaGetDriverEntryPoint("cuTensorMapEncodeTiled", &fn, cudaEnableDefault, &qr);
        enc = (PFN_encodeTiled)fn;
    }
    if (!attr_done) {
        cudaFuncSetAttribute(mega_kernel, cudaFuncAttributeMaxDynamicSharedMemorySize, MEGA_SMEM);
        cudaFuncSetAttribute(conv_kernel, cudaFuncAttributeMaxDynamicSharedMemorySize, CV_SMEM);
        attr_done = true;
    }
    void* p_act;
    cudaGetSymbolAddress(&p_act, g_act);
    bf16* act = (bf16*)(((uintptr_t)p_act + 0x1fffff) & ~(uintptr_t)0x1fffff);

    MegaMaps tm;
    tm.q = make_map(enc, A_q, D_, S_, 64, 128);
    tm.act = make_map(enc, act, D_, R_END, 64, 128);
    tm.w1 = make_map(enc, w1, D_, D_, 64, 64);
    tm.w2 = make_map(enc, w2, D_, D_, 64, 64);
    tm.w3 = make_map(enc, w3, F_, D_, 64, 64);
    tm.w4 = make_map(enc, w4, D_, F_, 64, 64);
    CUtensorMap tm_k = make_map(enc, A_k, D_, S_, 8, 256, CU_TENSOR_MAP_SWIZZLE_NONE);
    CUtensorMap tm_v = make_map(enc, A_v, D_, S_, 8, 256, CU_TENSOR_MAP_SWIZZLE_NONE);

    cudaStream_t st = cudaStreamPerThread;
    cudaLaunchAttribute at[2];
    at[0].id = cudaLaunchAttributeProgrammaticStreamSerialization;
    at[0].val.programmaticStreamSerializationAllowed = 1;
    at[1].id = cudaLaunchAttributeClusterDimension;
    at[1].val.clusterDim.x = 2;
    at[1].val.clusterDim.y = 1;
    at[1].val.clusterDim.z = 1;
    {
        cudaLaunchConfig_t cfg = {};
        cfg.gridDim = dim3(D_ / CV_CH);
        cfg.blockDim = dim3(640);
        cfg.dynamicSmemBytes = CV_SMEM;
        cfg.stream = st;
        cfg.attrs = at;
        cfg.numAttrs = 1;
        cudaLaunchKernelEx(&cfg, conv_kernel, tm_k, tm_v, A_k, A_v, A_shk, A_ssk, A_ssD, w1, w3, A_q, act);
    }
    {
        cudaLaunchConfig_t cfg = {};
        cfg.gridDim = dim3(132);
        cfg.blockDim = dim3(384);
        cfg.dynamicSmemBytes = MEGA_SMEM;
        cfg.stream = st;
        cfg.attrs = at;
        cfg.numAttrs = 2;
        cudaLaunchKernelEx(&cfg, mega_kernel, tm, out, act);
    }
}
```

```cpp
#include <cuda_runtime.h>
#include <cuda_bf16.h>
#include <cuda.h>
#include <stdint.h>

typedef __nv_bfloat16 bf16;

constexpr int S_ = 2048;
constexpr int D_ = 1024;
constexpr int F_ = 3584;

constexpr int R_XA = 0, R_X1 = 256, R_H2 = 512, R_Y = 1536, R_H = 16384 + 8, R_HP = S_ + 8, R_END = R_H + 2 * R_HP;
__device__ __align__(1024) bf16 g_act[(size_t)(R_END + 1024) * D_];
__device__ __align__(16) float g_cpart[16 * (F_ + D_)];
__device__ __align__(16) float2 g_stats[6 * S_ * 8];

__device__ __forceinline__ float bfr(float x) { return __bfloat162float(__float2bfloat16_rn(x)); }
__device__ __forceinline__ uint32_t pack2(float lo, float hi) {
    __nv_bfloat162 v = __floats2bfloat162_rn(lo, hi);
    return *reinterpret_cast<uint32_t*>(&v);
}
__device__ __forceinline__ float lo2f(uint32_t v) { return __uint_as_float(v << 16); }
__device__ __forceinline__ float hi2f(uint32_t v) { return __uint_as_float(v & 0xffff0000u); }
__device__ __forceinline__ float frcp(float x) { float r; asm("rcp.approx.f32 %0, %1;" : "=f"(r) : "f"(x)); return r; }
__device__ __forceinline__ float fsqrt(float x) { float r; asm("sqrt.approx.f32 %0, %1;" : "=f"(r) : "f"(x)); return r; }
__device__ __forceinline__ uint32_t smem_u32(const void* p) { return (uint32_t)__cvta_generic_to_shared(p); }

__device__ __forceinline__ void mbar_init(uint32_t bar, uint32_t cnt) {
    asm volatile("mbarrier.init.shared::cta.b64 [%0], %1;" ::"r"(bar), "r"(cnt));
}
__device__ __forceinline__ void mbar_expect_tx(uint32_t bar, uint32_t bytes) {
    asm volatile("mbarrier.arrive.expect_tx.shared::cta.b64 _, [%0], %1;" ::"r"(bar), "r"(bytes) : "memory");
}
__device__ __forceinline__ void mbar_arrive(uint32_t bar) {
    asm volatile("mbarrier.arrive.shared::cta.b64 _, [%0];" ::"r"(bar) : "memory");
}
__device__ __forceinline__ void mbar_wait(uint32_t bar, uint32_t parity) {
    asm volatile(
        "{\n.reg .pred p;\n.reg .u32 n;\n"
        "mbarrier.try_wait.parity.shared::cta.b64 p, [%0], %1;\n"
        "@p bra LD;\n"
        "mov.u32 n, 0;\n"
        "LW:\n"
        "mbarrier.try_wait.parity.shared::cta.b64 p, [%0], %1;\n"
        "@p bra LD;\n"
        "add.u32 n, n, 1;\n"
        "setp.lt.u32 p, n, 0x400000;\n"
        "@p bra LW;\n"
        "LD:\n}\n"
        ::"r"(bar), "r"(parity) : "memory");
}
__device__ __forceinline__ void tma_load_2d(uint32_t dst, const CUtensorMap* tm, uint32_t bar, int c0, int c1) {
    asm volatile(
        "cp.async.bulk.tensor.2d.shared::cluster.global.mbarrier::complete_tx::bytes [%0], [%1, {%3, %4}], [%2];"
        ::"r"(dst), "l"((uint64_t)tm), "r"(bar), "r"(c0), "r"(c1) : "memory");
}
__device__ __forceinline__ void tma_load_2d_mc(uint32_t dst, const CUtensorMap* tm, uint32_t bar, int c0, int c1) {
    asm volatile(
        "cp.async.bulk.tensor.2d.shared::cluster.global.mbarrier::complete_tx::bytes.multicast::cluster [%0], [%1, {%3, %4}], [%2], %5;"
        ::"r"(dst), "l"((uint64_t)tm), "r"(bar), "r"(c0), "r"(c1), "h"((uint16_t)3) : "memory");
}
__device__ __forceinline__ void tma_prefetch_2d(const CUtensorMap* tm, int c0, int c1) {
    asm volatile("cp.async.bulk.prefetch.tensor.2d.L2.global.tile [%0, {%1, %2}];" ::"l"((uint64_t)tm), "r"(c0), "r"(c1) : "memory");
}
__device__ __forceinline__ void tma_store_2d(const CUtensorMap* tm, uint32_t src, int c0, int c1) {
    asm volatile("cp.async.bulk.tensor.2d.global.shared::cta.bulk_group [%0, {%2, %3}], [%1];"
                 ::"l"((uint64_t)tm), "r"(src), "r"(c0), "r"(c1) : "memory");
}
__device__ __forceinline__ void wgmma_fence() { asm volatile("wgmma.fence.sync.aligned;" ::: "memory"); }
__device__ __forceinline__ void wgmma_commit() { asm volatile("wgmma.commit_group.sync.aligned;" ::: "memory"); }
template <int N> __device__ __forceinline__ void wgmma_wait() { asm volatile("wgmma.wait_group.sync.aligned %0;" ::"n"(N) : "memory"); }
__device__ __forceinline__ void named_bar_arrive(int id, int n) { asm volatile("bar.arrive %0, %1;" ::"r"(id), "r"(n) : "memory"); }
__device__ __forceinline__ void named_bar_sync(int id, int n) { asm volatile("bar.sync %0, %1;" ::"r"(id), "r"(n) : "memory"); }

__device__ __forceinline__ void pdl_wait() { asm volatile("griddepcontrol.wait;" ::: "memory"); }
__device__ __forceinline__ void pdl_launch() { asm volatile("griddepcontrol.launch_dependents;" ::: "memory"); }

__device__ __forceinline__ uint32_t desc_a(uint32_t addr) { return ((addr & 0x3FFFF) >> 4) | (1u << 16); }
__device__ __forceinline__ uint32_t desc_b(uint32_t addr) { return ((addr & 0x3FFFF) >> 4) | (512u << 16); }

__device__ __forceinline__ void wgmma_m64n192k16(float (&d)[96], uint32_t descA, uint32_t descB) {
  asm volatile("{\n.reg .pred p;\n.reg .b64 da, db;\nsetp.eq.b32 p, 0, 0;\nmov.b64 da, {%96, %98};\nmov.b64 db, {%97, %98};\n"
    "wgmma.mma_async.sync.aligned.m64n192k16.f32.bf16.bf16 "
    "{%0, %1, %2, %3, %4, %5, %6, %7, %8, %9, %10, %11, %12, %13, %14, %15, %16, %17, %18, %19, %20, %21, %22, %23, %24, %25, %26, %27, %28, %29, %30, %31, %32, %33, %34, %35, %36, %37, %38, %39, %40, %41, %42, %43, %44, %45, %46, %47, %48, %49, %50, %51, %52, %53, %54, %55, %56, %57, %58, %59, %60, %61, %62, %63, %64, %65, %66, %67, %68, %69, %70, %71, %72, %73, %74, %75, %76, %77, %78, %79, %80, %81, %82, %83, %84, %85, %86, %87, %88, %89, %90, %91, %92, %93, %94, %95}, "
    "da, db, p, 1, 1, 0, 1;\n}\n"
    : "+f"(d[0]), "+f"(d[1]), "+f"(d[2]), "+f"(d[3]), "+f"(d[4]), "+f"(d[5]), "+f"(d[6]), "+f"(d[7]), "+f"(d[8]), "+f"(d[9]), "+f"(d[10]), "+f"(d[11]), "+f"(d[12]), "+f"(d[13]), "+f"(d[14]), "+f"(d[15]), "+f"(d[16]), "+f"(d[17]), "+f"(d[18]), "+f"(d[19]), "+f"(d[20]), "+f"(d[21]), "+f"(d[22]), "+f"(d[23]), "+f"(d[24]), "+f"(d[25]), "+f"(d[26]), "+f"(d[27]), "+f"(d[28]), "+f"(d[29]), "+f"(d[30]), "+f"(d[31]), "+f"(d[32]), "+f"(d[33]), "+f"(d[34]), "+f"(d[35]), "+f"(d[36]), "+f"(d[37]), "+f"(d[38]), "+f"(d[39]), "+f"(d[40]), "+f"(d[41]), "+f"(d[42]), "+f"(d[43]), "+f"(d[44]), "+f"(d[45]), "+f"(d[46]), "+f"(d[47]), "+f"(d[48]), "+f"(d[49]), "+f"(d[50]), "+f"(d[51]), "+f"(d[52]), "+f"(d[53]), "+f"(d[54]), "+f"(d[55]), "+f"(d[56]), "+f"(d[57]), "+f"(d[58]), "+f"(d[59]), "+f"(d[60]), "+f"(d[61]), "+f"(d[62]), "+f"(d[63]), "+f"(d[64]), "+f"(d[65]), "+f"(d[66]), "+f"(d[67]), "+f"(d[68]), "+f"(d[69]), "+f"(d[70]), "+f"(d[71]), "+f"(d[72]), "+f"(d[73]), "+f"(d[74]), "+f"(d[75]), "+f"(d[76]), "+f"(d[77]), "+f"(d[78]), "+f"(d[79]), "+f"(d[80]), "+f"(d[81]), "+f"(d[82]), "+f"(d[83]), "+f"(d[84]), "+f"(d[85]), "+f"(d[86]), "+f"(d[87]), "+f"(d[88]), "+f"(d[89]), "+f"(d[90]), "+f"(d[91]), "+f"(d[92]), "+f"(d[93]), "+f"(d[94]), "+f"(d[95])
    : "r"(descA), "r"(descB), "r"(0x40000040u));
}

__device__ __forceinline__ void wgmma_m64n256k16(float (&d)[128], uint32_t descA, uint32_t descB) {
  asm volatile("{\n.reg .pred p;\n.reg .b64 da, db;\nsetp.eq.b32 p, 0, 0;\nmov.b64 da, {%128, %130};\nmov.b64 db, {%129, %130};\n"
    "wgmma.mma_async.sync.aligned.m64n256k16.f32.bf16.bf16 "
    "{%0, %1, %2, %3, %4, %5, %6, %7, %8, %9, %10, %11, %12, %13, %14, %15, %16, %17, %18, %19, %20, %21, %22, %23, %24, %25, %26, %27, %28, %29, %30, %31, %32, %33, %34, %35, %36, %37, %38, %39, %40, %41, %42, %43, %44, %45, %46, %47, %48, %49, %50, %51, %52, %53, %54, %55, %56, %57, %58, %59, %60, %61, %62, %63, %64, %65, %66, %67, %68, %69, %70, %71, %72, %73, %74, %75, %76, %77, %78, %79, %80, %81, %82, %83, %84, %85, %86, %87, %88, %89, %90, %91, %92, %93, %94, %95, %96, %97, %98, %99, %100, %101, %102, %103, %104, %105, %106, %107, %108, %109, %110, %111, %112, %113, %114, %115, %116, %117, %118, %119, %120, %121, %122, %123, %124, %125, %126, %127}, "
    "da, db, p, 1, 1, 0, 1;\n}\n"
    : "+f"(d[0]), "+f"(d[1]), "+f"(d[2]), "+f"(d[3]), "+f"(d[4]), "+f"(d[5]), "+f"(d[6]), "+f"(d[7]), "+f"(d[8]), "+f"(d[9]), "+f"(d[10]), "+f"(d[11]), "+f"(d[12]), "+f"(d[13]), "+f"(d[14]), "+f"(d[15]), "+f"(d[16]), "+f"(d[17]), "+f"(d[18]), "+f"(d[19]), "+f"(d[20]), "+f"(d[21]), "+f"(d[22]), "+f"(d[23]), "+f"(d[24]), "+f"(d[25]), "+f"(d[26]), "+f"(d[27]), "+f"(d[28]), "+f"(d[29]), "+f"(d[30]), "+f"(d[31]), "+f"(d[32]), "+f"(d[33]), "+f"(d[34]), "+f"(d[35]), "+f"(d[36]), "+f"(d[37]), "+f"(d[38]), "+f"(d[39]), "+f"(d[40]), "+f"(d[41]), "+f"(d[42]), "+f"(d[43]), "+f"(d[44]), "+f"(d[45]), "+f"(d[46]), "+f"(d[47]), "+f"(d[48]), "+f"(d[49]), "+f"(d[50]), "+f"(d[51]), "+f"(d[52]), "+f"(d[53]), "+f"(d[54]), "+f"(d[55]), "+f"(d[56]), "+f"(d[57]), "+f"(d[58]), "+f"(d[59]), "+f"(d[60]), "+f"(d[61]), "+f"(d[62]), "+f"(d[63]), "+f"(d[64]), "+f"(d[65]), "+f"(d[66]), "+f"(d[67]), "+f"(d[68]), "+f"(d[69]), "+f"(d[70]), "+f"(d[71]), "+f"(d[72]), "+f"(d[73]), "+f"(d[74]), "+f"(d[75]), "+f"(d[76]), "+f"(d[77]), "+f"(d[78]), "+f"(d[79]), "+f"(d[80]), "+f"(d[81]), "+f"(d[82]), "+f"(d[83]), "+f"(d[84]), "+f"(d[85]), "+f"(d[86]), "+f"(d[87]), "+f"(d[88]), "+f"(d[89]), "+f"(d[90]), "+f"(d[91]), "+f"(d[92]), "+f"(d[93]), "+f"(d[94]), "+f"(d[95]), "+f"(d[96]), "+f"(d[97]), "+f"(d[98]), "+f"(d[99]), "+f"(d[100]), "+f"(d[101]), "+f"(d[102]), "+f"(d[103]), "+f"(d[104]), "+f"(d[105]), "+f"(d[106]), "+f"(d[107]), "+f"(d[108]), "+f"(d[109]), "+f"(d[110]), "+f"(d[111]), "+f"(d[112]), "+f"(d[113]), "+f"(d[114]), "+f"(d[115]), "+f"(d[116]), "+f"(d[117]), "+f"(d[118]), "+f"(d[119]), "+f"(d[120]), "+f"(d[121]), "+f"(d[122]), "+f"(d[123]), "+f"(d[124]), "+f"(d[125]), "+f"(d[126]), "+f"(d[127])
    : "r"(descA), "r"(descB), "r"(0x40000040u));
}

__device__ __forceinline__ void wgmma_m64n128k16(float (&d)[64], uint32_t descA, uint32_t descB) {
  asm volatile("{\n.reg .pred p;\n.reg .b64 da, db;\nsetp.eq.b32 p, 0, 0;\nmov.b64 da, {%64, %66};\nmov.b64 db, {%65, %66};\n"
    "wgmma.mma_async.sync.aligned.m64n128k16.f32.bf16.bf16 "
    "{%0, %1, %2, %3, %4, %5, %6, %7, %8, %9, %10, %11, %12, %13, %14, %15, %16, %17, %18, %19, %20, %21, %22, %23, %24, %25, %26, %27, %28, %29, %30, %31, %32, %33, %34, %35, %36, %37, %38, %39, %40, %41, %42, %43, %44, %45, %46, %47, %48, %49, %50, %51, %52, %53, %54, %55, %56, %57, %58, %59, %60, %61, %62, %63}, "
    "da, db, p, 1, 1, 0, 1;\n}\n"
    : "+f"(d[0]), "+f"(d[1]), "+f"(d[2]), "+f"(d[3]), "+f"(d[4]), "+f"(d[5]), "+f"(d[6]), "+f"(d[7]), "+f"(d[8]), "+f"(d[9]), "+f"(d[10]), "+f"(d[11]), "+f"(d[12]), "+f"(d[13]), "+f"(d[14]), "+f"(d[15]), "+f"(d[16]), "+f"(d[17]), "+f"(d[18]), "+f"(d[19]), "+f"(d[20]), "+f"(d[21]), "+f"(d[22]), "+f"(d[23]), "+f"(d[24]), "+f"(d[25]), "+f"(d[26]), "+f"(d[27]), "+f"(d[28]), "+f"(d[29]), "+f"(d[30]), "+f"(d[31]), "+f"(d[32]), "+f"(d[33]), "+f"(d[34]), "+f"(d[35]), "+f"(d[36]), "+f"(d[37]), "+f"(d[38]), "+f"(d[39]), "+f"(d[40]), "+f"(d[41]), "+f"(d[42]), "+f"(d[43]), "+f"(d[44]), "+f"(d[45]), "+f"(d[46]), "+f"(d[47]), "+f"(d[48]), "+f"(d[49]), "+f"(d[50]), "+f"(d[51]), "+f"(d[52]), "+f"(d[53]), "+f"(d[54]), "+f"(d[55]), "+f"(d[56]), "+f"(d[57]), "+f"(d[58]), "+f"(d[59]), "+f"(d[60]), "+f"(d[61]), "+f"(d[62]), "+f"(d[63])
    : "r"(descA), "r"(descB), "r"(0x40000040u));
}

template <int BN> struct WG;
template <> struct WG<128> { static __device__ __forceinline__ void mma(float (&d)[64], uint32_t a, uint32_t b) { wgmma_m64n128k16(d, a, b); } };
template <> struct WG<256> { static __device__ __forceinline__ void mma(float (&d)[128], uint32_t a, uint32_t b) { wgmma_m64n256k16(d, a, b); } };
template <> struct WG<192> { static __device__ __forceinline__ void mma(float (&d)[96], uint32_t a, uint32_t b) { wgmma_m64n192k16(d, a, b); } };

#define DBG_T(i)
__device__ __forceinline__ void fence_async_smem() { asm volatile("fence.proxy.async.shared::cta;" ::: "memory"); }
__device__ __forceinline__ void prefetch_tmap(const CUtensorMap* tm) { asm volatile("prefetch.tensormap [%0];" ::"l"((uint64_t)tm) : "memory"); }
__device__ __forceinline__ uint32_t mapa_u32(uint32_t addr, uint32_t cta) {
    uint32_t r;
    asm volatile("mapa.shared::cluster.u32 %0, %1, %2;" : "=r"(r) : "r"(addr), "r"(cta));
    return r;
}
__device__ __forceinline__ void mbar_arrive_cluster(uint32_t cluster_addr) {
    asm volatile("mbarrier.arrive.shared::cluster.b64 _, [%0];" ::"r"(cluster_addr) : "memory");
}
__device__ __forceinline__ bool elect_one() {
    uint32_t p;
    asm volatile("{\n.reg .pred P;\nelect.sync _|P, 0xffffffff;\nselp.u32 %0, 1, 0, P;\n}\n" : "=r"(p));
    return p != 0;
}
__device__ __forceinline__ void cluster_arrive_relaxed() { asm volatile("barrier.cluster.arrive.relaxed.aligned;" ::: "memory"); }
__device__ __forceinline__ void cluster_wait() { asm volatile("barrier.cluster.wait.acquire.aligned;" ::: "memory"); }

__device__ __forceinline__ uint32_t bsub2(uint32_t a, uint32_t b) {
    __nv_bfloat162 r = __hsub2(*reinterpret_cast<__nv_bfloat162*>(&a), *reinterpret_cast<__nv_bfloat162*>(&b));
    return *reinterpret_cast<uint32_t*>(&r);
}
__device__ __forceinline__ uint32_t bmul2(uint32_t a, uint32_t b) {
    __nv_bfloat162 r = __hmul2(*reinterpret_cast<__nv_bfloat162*>(&a), *reinterpret_cast<__nv_bfloat162*>(&b));
    return *reinterpret_cast<uint32_t*>(&r);
}
__device__ __forceinline__ uint32_t badd2(uint32_t a, uint32_t b) {
    __nv_bfloat162 r = __hadd2(*reinterpret_cast<__nv_bfloat162*>(&a), *reinterpret_cast<__nv_bfloat162*>(&b));
    return *reinterpret_cast<uint32_t*>(&r);
}
constexpr int BM = 128, BK = 64;
constexpr int R5_STAGE = 32768, R5_N = 5;
constexpr int R4_STAGE = 49152, R4_N = 4;
constexpr int R4B_STAGE = 40960;
constexpr int OFF_STG5 = 0, OFF_R = 32768;
constexpr int OFF_EPI = 196608;
constexpr int OFF_BAR = OFF_EPI + 32768;
constexpr int OFF_RS = OFF_BAR + 256;
constexpr int OFF_CS = OFF_RS + 1024;
constexpr int MEGA_SMEM = OFF_CS + 1792;
enum { FL_XA = 0, FL_H = 2, FL_X1 = 4, FL_H2 = 6, FL_KINDS = 10 };
constexpr int FL_PITCH = 64;
constexpr int FL_WORDS = 2 * FL_KINDS * 16 * FL_PITCH;
__device__ unsigned int g_flag[FL_WORDS];
__device__ unsigned int g_ticket[9 * FL_PITCH];
__device__ __forceinline__ unsigned int* flag_ptr(int layer, int kind, int i) { return g_flag + ((layer * FL_KINDS + kind) * 16 + i) * FL_PITCH; }

__device__ __forceinline__ void wait_flag(const unsigned int* p, unsigned int target) {
    long long t0 = clock64();
    while (true) {
        unsigned int v;
        asm volatile("ld.relaxed.gpu.global.u32 %0, [%1];" : "=r"(v) : "l"(p) : "memory");
        if (v >= target) break;
        if (clock64() - t0 > 2000000000LL) break;
    }
    asm volatile("fence.acquire.gpu;" ::: "memory");
}
__device__ __forceinline__ void fence_proxy_async() {
    asm volatile("fence.proxy.async.global;" ::: "memory");
    asm volatile("fence.proxy.async.shared::cta;" ::: "memory");
}
__device__ __forceinline__ void stsm4(uint32_t addr, uint32_t r0, uint32_t r1, uint32_t r2, uint32_t r3) {
    asm volatile("stmatrix.sync.aligned.m8n8.x4.shared.b16 [%0], {%1,%2,%3,%4};" ::"r"(addr), "r"(r0), "r"(r1), "r"(r2), "r"(r3));
}
__device__ __forceinline__ uint4 lds128(uint32_t a) {
    uint4 v;
    asm volatile("ld.shared.v4.b32 {%0,%1,%2,%3}, [%4];" : "=r"(v.x), "=r"(v.y), "=r"(v.z), "=r"(v.w) : "r"(a) : "memory");
    return v;
}
__device__ __forceinline__ void stg128(void* p, uint4 v) {
    asm volatile("st.global.v4.b32 [%0], {%1,%2,%3,%4};" ::"l"(p), "r"(v.x), "r"(v.y), "r"(v.z), "r"(v.w) : "memory");
}
__device__ __forceinline__ float gelu_tanh_h(float hx) {
    float z = hx * fmaf(hx * hx, 8.0f * 0.035677408136300125f, 2.0f * 0.7978845608028654f);
    float t;
    asm("tanh.approx.f32 %0, %1;" : "=f"(t) : "f"(z));
    return fmaf(hx, t, hx);
}
__device__ __forceinline__ uint32_t gelu2h(uint32_t p) { return pack2(gelu_tanh_h(lo2f(p)), gelu_tanh_h(hi2f(p))); }
__device__ __forceinline__ uint4 gelu8h(uint4 v) { return make_uint4(gelu2h(v.x), gelu2h(v.y), gelu2h(v.z), gelu2h(v.w)); }

__device__ __forceinline__ void row_stats(const float2* p, float& mean, float& var) {
    float2 v[8];
#pragma unroll 1
    for (int n = 0; n < (1 << 20); n++) {
#pragma unroll
        for (int i = 0; i < 8; i++)
            asm volatile("{\n.reg .b64 t;\nld.relaxed.gpu.global.b64 t, [%2];\nmov.b64 {%0, %1}, t;\n}" : "=f"(v[i].x), "=f"(v[i].y) : "l"(p + 128 * i) : "memory");
        if (fminf(fminf(fminf(v[0].y, v[1].y), fminf(v[2].y, v[3].y)), fminf(fminf(v[4].y, v[5].y), fminf(v[6].y, v[7].y))) >= 0.f) break;
    }
    mean = (((v[0].x + v[1].x) + (v[2].x + v[3].x)) + ((v[4].x + v[5].x) + (v[6].x + v[7].x))) * 0.125f;
    float m2 = 0.f, d2 = 0.f;
#pragma unroll
    for (int i = 0; i < 8; i++) { m2 += v[i].y; d2 = fmaf(v[i].x - mean, v[i].x - mean, d2); }
    var = fmaf(128.0f, d2, m2) * (1.0f / D_);
}
struct RingState { uint32_t st, ph; };

#define DT(i)
#define DP(i)
#define GT(i)

template <int BN, int NST>
__device__ __forceinline__ void kblock(float (&acc)[BN / 2], uint32_t da, uint32_t db, uint32_t bfull, RingState& rs) {
    mbar_wait(bfull + 8 * rs.st, rs.ph);
    wgmma_fence();
#pragma unroll
    for (int k = 0; k < 4; k++) WG<BN>::mma(acc, da + k * 2, db + k * 128);
    wgmma_commit();
    if (++rs.st == NST) { rs.st = 0; rs.ph ^= 1; }
}
template <int BN, int NST, int STAGE>
__device__ __forceinline__ void mainloop(float (&acc)[BN / 2], int KB, uint32_t da0, uint32_t db0, uint32_t bfull, uint32_t rel, bool rel_on,
                                         RingState& rs, int dbg) {
    uint32_t prev = rs.st ? rs.st - 1 : NST - 1;
#pragma unroll 1
    for (int kk = 0; kk < KB; kk++) {
        const uint32_t cur = rs.st;
        kblock<BN, NST>(acc, da0 + cur * (STAGE / 16), db0 + cur * (STAGE / 16), bfull, rs);
        wgmma_wait<1>();
        if (rel_on) mbar_arrive_cluster(rel + 8 * prev);
        prev = cur;
    }
    wgmma_wait<0>();
#pragma unroll
    for (int i = 0; i < BN / 2; i++) asm volatile("" : "+f"(acc[i])::"memory");
    if (rel_on) mbar_arrive_cluster(rel + 8 * prev);
}
template <int N> __device__ __forceinline__ void zero_acc(float (&acc)[N]) {
#pragma unroll
    for (int i = 0; i < N; i++) acc[i] = 0.f;
}
__device__ __forceinline__ void ldsm4(uint32_t& r0, uint32_t& r1, uint32_t& r2, uint32_t& r3, uint32_t addr) {
    asm volatile("ldmatrix.sync.aligned.m8n8.x4.shared.b16 {%0,%1,%2,%3}, [%4];" : "=r"(r0), "=r"(r1), "=r"(r2), "=r"(r3) : "r"(addr));
}

__device__ __forceinline__ void ldsm4t(uint32_t& r0, uint32_t& r1, uint32_t& r2, uint32_t& r3, uint32_t addr) {
    asm volatile("ldmatrix.sync.aligned.m8n8.x4.trans.shared.b16 {%0,%1,%2,%3}, [%4];" : "=r"(r0), "=r"(r1), "=r"(r2), "=r"(r3) : "r"(addr));
}

struct MegaMaps {
    CUtensorMap q, act;
    CUtensorMap w1, w2, w3, w4;
};

__global__ void __cluster_dims__(2, 1, 1) __launch_bounds__(384, 1)
mega_kernel(const __grid_constant__ MegaMaps tm, bf16* __restrict__ outp, bf16* act) {
    extern __shared__ __align__(1024) uint8_t sgen[];
    const uint32_t sbase = smem_u32(sgen);
    DT(0);
    GT(2);
    const int warp = __shfl_sync(0xffffffffu, threadIdx.x >> 5, 0), lane = threadIdx.x & 31;
    const int rank = blockIdx.x & 1;
    const uint32_t s_bar = sbase + OFF_BAR;
    const uint32_t f5 = s_bar, e5 = s_bar + 48, f4 = s_bar + 96, e4 = s_bar + 128;
    const uint32_t b_rfull = s_bar + 176, b_stg = s_bar + 184, b_h2 = s_bar + 192;
    const uint32_t s_epi = sbase + OFF_EPI, s_stg = sbase + OFF_STG5, s_r = sbase + OFF_R;

    cluster_arrive_relaxed();
    if (threadIdx.x == 256) {
        for (int i = 0; i < R5_N; i++) { mbar_init(f5 + 8 * i, 1); mbar_init(e5 + 8 * i, 4); }
        for (int i = 0; i < R4_N; i++) { mbar_init(f4 + 8 * i, 1); mbar_init(e4 + 8 * i, 4); }
        mbar_init(b_rfull, 1); mbar_init(b_stg, 8);
        mbar_arrive(f5);
        for (int i = 1; i < 4; i++) mbar_init(b_h2 + 8 * i, 1);
        for (int i = 0; i < 6; i++) reinterpret_cast<uint32_t*>(sgen + OFF_BAR + 224)[i] = 0;
        asm volatile("fence.mbarrier_init.release.cluster;" ::: "memory");
        fence_async_smem();
        prefetch_tmap(&tm.act);
    }
    uint32_t role_w = 0;
    if (threadIdx.x == 288 && rank == 0) {
        uint32_t smid;
        asm volatile("mov.u32 %0, %%smid;" : "=r"(smid));
        const int t = smid >> 1;
        int team = t < 32 ? t & 7 : t < 60 ? 1 + (t - 32) % 7 : t < 62 ? t - 54 : 0;
        int slot = atomicAdd(g_ticket + team * FL_PITCH, 1u);
        atomicAdd(g_ticket + 8 * FL_PITCH, 1u);
        if (slot >= 8) {
            const long long t0 = clock64();
            while (*(volatile unsigned int*)(g_ticket + 8 * FL_PITCH) < gridDim.x / 2 && clock64() - t0 < 100000) {}
            for (team = 0; team < 8; team++)
                if ((slot = atomicAdd(g_ticket + team * FL_PITCH, 1u)) < 8) break;
        }
        role_w = team * 8 + slot;
    }
    __syncwarp();
    cluster_wait();
    if (threadIdx.x == 288 && rank == 0) {
        asm volatile("st.shared::cluster.u32 [%0], %1;" ::"r"(mapa_u32(s_bar + 192, 0)), "r"(role_w) : "memory");
        asm volatile("st.shared::cluster.u32 [%0], %1;" ::"r"(mapa_u32(s_bar + 192, 1)), "r"(role_w) : "memory");
        asm volatile("fence.acq_rel.cluster;" ::: "memory");
    }
    __syncwarp();
    cluster_arrive_relaxed();
    cluster_wait();
    const int role = *reinterpret_cast<const volatile int*>(sgen + OFF_BAR + 192);
    if (role >= 64) return;
    const int bi = (role >> 3) * 2 + rank, bj = role & 7, m0 = bi * BM, tb = (role >> 3) * 2048 + rank * 128;
    if (threadIdx.x == 256) {
        mbar_expect_tx(b_rfull, 32768);
        tma_load_2d(s_epi, &tm.q, b_rfull, bj * 128, m0);
        tma_load_2d(s_epi + 16384, &tm.q, b_rfull, bj * 128 + 64, m0);
    }

    if (warp >= 8) {
        asm volatile("setmaxnreg.dec.sync.aligned.u32 72;");
        if (warp == 8) { if (elect_one()) {
            int s5 = 0, s4 = 0;
            uint32_t p5 = 30, p4 = 1;
            auto putB = [&](const CUtensorMap* tB, int kc, uint32_t bytes) {
                const uint32_t full = f5 + 8 * s5;
                mbar_wait(full + 48, (p5 >> s5) & 1);
                mbar_expect_tx(full, bytes);
                tma_load_2d_mc(s_r + 16384 + rank * 8192 + s5 * R5_STAGE, tB, full, bj * 128 + rank * 64, kc);
                p5 ^= 1u << s5;
            };
            auto putA = [&](int c, int r) {
                tma_load_2d(s_r + s5 * R5_STAGE, &tm.act, f5 + 8 * s5, c, r);
                if (++s5 == R5_N) s5 = 0;
            };
            pdl_wait();
            prefetch_tmap(&tm.w1); prefetch_tmap(&tm.w2); prefetch_tmap(&tm.w3); prefetch_tmap(&tm.w4);
            auto own_first = [&](int it) {
                const int hf = it >= 9, c = it - 2 - 7 * hf;
                return (it < 2 ? 2 * bj + it : 2 * (c + (c >= bj)) + hf) * BK;
            };
            const unsigned int nh = (bi == 0 || bi == 15) ? 16 : 24;
#pragma unroll 1
            for (int layer = 0; layer < 2; layer++) {
                mbar_wait(e5 + 8, (p5 >> 1) & 1);
                mbar_expect_tx(f5 + 8, 32768);
                tma_load_2d(s_r + R5_STAGE, &tm.act, f5 + 8, (bj >> 1) * 256 + rank * 128, R_Y + (tb & ~255) + (bj & 1) * 128);
                tma_load_2d(s_r + R5_STAGE + 16384, &tm.act, f5 + 8, (bj >> 1) * 256 + rank * 128 + 64, R_Y + (tb & ~255) + (bj & 1) * 128);
                p5 ^= 2;
                s5 = 2;
#pragma unroll 1
                for (int kk = 0; kk < 4; kk++) { putB(&tm.w1, own_first(kk), kk < 2 ? 16384 : R5_STAGE); if (++s5 == R5_N) s5 = 0; }
                s5 = 4;
#pragma unroll 1
                for (int kk = 2; kk < 16; kk++) {
                    const int kc = own_first(kk);
                    if (kk >= 4) putB(&tm.w1, kc, R5_STAGE);
                    if (kk == 2 || kk == 9) {
                        wait_flag(flag_ptr(layer, FL_XA + (kk & 1), bi), 8);
                        DP(8 * (FL_XA + (kk & 1)) + 3);
                        fence_proxy_async();
                        DP(8 * (FL_XA + (kk & 1)) + 4);
                    }
                    putA(kc, R_XA + tb);
                }
                mbar_wait(e5 + 24, (p5 >> 3) & 1);
                mbar_arrive(f5 + 24);
                p5 ^= 8;
                s5 = 4;
#pragma unroll 1
                for (int kk = 0; kk < 5; kk++) { putB(&tm.w2, kk * 2 * BK, R5_STAGE); if (++s5 == R5_N) s5 = 0; }
#pragma unroll 1
                for (int kk = 0; kk < 16; kk++) {
                    const int kc = ((kk & 7) * 2 + (kk >> 3)) * BK;
                    if (kk >= 5) putB(&tm.w2, kc, R5_STAGE);
                    if ((kk & 7) == 0) {
                        wait_flag(flag_ptr(layer, FL_H + (kk >> 3), bi), nh);
                        DP(8 * (FL_H + (kk >> 3)) + 3);
                        fence_proxy_async();
                        DP(8 * (FL_H + (kk >> 3)) + 4);
                    }
                    putA(kc, R_H + layer * R_HP + m0 + (int)((0x4031u >> ((kk & 6) << 1)) & 7) - 2);
                }
#pragma unroll 1
                for (int it = 0; it < 32; it++) {
                    const int kc = it >= 16 ? (it - 16) * BK : own_first(it);
                    const int nb = it < 16 ? 4 : 3, n0 = bj * 448 + (it < 16 ? 0 : 256);
                    if (it > 0 && it < 4) {
                        const int i = (it - 1) * 3 >> 1;
                        mbar_wait(e5 + 8 * i, (p5 >> i) & 1);
                        mbar_wait(e5 + 8 * i + 8, (p5 >> (i + 1)) & 1);
                    }
                    mbar_wait(e4 + 8 * s4, p4);
                    if (it >= 16 && it < 19) mbar_wait(e4 + 8 * s4 + 8, p4);
                    uint32_t sa = s_r + s4 * (it < 16 ? R4_STAGE : R4B_STAGE), full = f4 + 8 * s4;
                    mbar_expect_tx(full, (it < 2 ? 0 : 16384) + nb * 8192);
#pragma unroll 1
                    for (int j = (it ^ rank) & 1; j < nb; j += 2) tma_load_2d_mc(sa + (it < 16 ? -32768 : 16384) + j * 8192, &tm.w3, full, n0 + j * 64, kc);
                    if (it == 3 || it == 9) {
                        wait_flag(flag_ptr(layer, FL_X1 + (it >> 3), bi), 8);
                        DP(8 * (FL_X1 + (it >> 3)) + 3);
                        fence_proxy_async();
                        DP(8 * (FL_X1 + (it >> 3)) + 4);
                        if (it == 3) tma_load_2d(s_r + 2 * R4_STAGE, &tm.act, f4 + 16, own_first(2), R_X1 + tb);
                    }
                    if (it >= 3) tma_load_2d(sa, &tm.act, full, kc, R_X1 + tb);
                    if (++s4 == R4_N) { s4 = 0; p4 ^= 1; }
                }
                wait_flag(flag_ptr(layer, FL_H2, bi), 8);
                fence_proxy_async();
                s5 = 0;
#pragma unroll 1
                for (int j = 0; j < 7; j++) {
                    if (j > 0 && (j & 1) == 0) {
                        mbar_wait(b_h2 + 4 * j, layer);
                        fence_proxy_async();
                    }
                    const int ra = R_H2 + (j >> 1) * 256 + tb;
#pragma unroll 1
                    for (int b = 0; b < 8; b++) {
                        if (j == 0 && b < R4_N) mbar_wait(e4 + 8 * b, p4);
                        putB(&tm.w4, (7 * b + j) * BK, R5_STAGE);
                        putA(((j & 1) * 8 + b) * BK, ra);
                    }
                }
            }
        } } else {
            pdl_wait();
#pragma unroll 1
            for (int layer = 0; layer < 2; layer++) {
                if (warp == 10) {
#pragma unroll 1
                    for (int kind = 0; kind < 6; kind += 2) {
                        const uint32_t src = kind == FL_H ? s_stg : s_epi;
                        const int r = kind == FL_H ? R_H + layer * R_HP + m0 : (kind == FL_XA ? R_XA : R_X1) + tb;
#pragma unroll 1
                        for (int hf = 0; hf < 2; hf++) {
                            named_bar_sync(5 + hf, 288);
                            if (lane == 0) {
                                DP(8 * (kind + hf));
                                tma_store_2d(&tm.act, src + hf * 16384, bj * 128 + hf * 64, r);
                                asm volatile("cp.async.bulk.commit_group;" ::: "memory");
                                asm volatile("cp.async.bulk.wait_group 0;" ::: "memory");
                                DP(8 * (kind + hf) + 1);
                                DP(8 * (kind + hf) + 2);
                                unsigned int* fp = flag_ptr(layer, kind + hf, bi);
                                asm volatile("red.relaxed.gpu.global.add.u32 [%0], 1;" ::"l"(fp) : "memory");
                                if (kind == FL_H) {
                                    if (bi > 0) asm volatile("red.relaxed.gpu.global.add.u32 [%0], 1;" ::"l"(fp - FL_PITCH) : "memory");
                                    if (bi < 15) asm volatile("red.relaxed.gpu.global.add.u32 [%0], 1;" ::"l"(fp + FL_PITCH) : "memory");
                                }
                            }
                            __syncwarp();
                        }
                    }
                } else if (warp == 9) {
                    uint32_t* rs = reinterpret_cast<uint32_t*>(sgen + OFF_RS);
                    float* cs = reinterpret_cast<float*>(sgen + OFF_CS);
#pragma unroll 1
                    for (int which = 0; which < 2; which++) {
                        if (lane == 0 && (layer | which)) wait_flag(flag_ptr(layer, which == 0 ? FL_XA : FL_X1, bi), 8);
                        __syncwarp();
#pragma unroll 1
                        for (int c = (which == 0 && layer == 0 ? 0 : 256) + lane * 4; c < (which == 0 ? 384 : 448); c += 128) {
                            const float* cp = g_cpart + (which == 0 && c >= 256 ? F_ + bj * 128 - 256 : bj * 448) + c;
                            float4 a = make_float4(0.f, 0.f, 0.f, 0.f);
#pragma unroll
                            for (int r0 = 0; r0 < 16; r0 += 8) {
                                float4 v[8];
#pragma unroll
                                for (int r = 0; r < 8; r++) v[r] = __ldcg(reinterpret_cast<const float4*>(cp + (r0 + r) * (F_ + D_)));
#pragma unroll
                                for (int r = 0; r < 8; r++) { a.x += v[r].x; a.y += v[r].y; a.z += v[r].z; a.w += v[r].w; }
                            }
                            *reinterpret_cast<float4*>(cs + c) = a;
                        }
#pragma unroll 1
                        for (int i = 0; i < 4; i++) {
                            const int r = i * 32 + lane;
                            float mean, var;
                            row_stats(g_stats + (3 * layer + 1 + which) * S_ * 8 + bi * 1024 + r, mean, var);
                            const uint32_t c0 = pack2(mean, fsqrt(bfr(bfr(var) + 1e-5f)));
                            rs[r] = c0;
                            const float rd = frcp(hi2f(c0));
                            rs[128 + r] = pack2((mean - lo2f(c0)) * rd, fsqrt(bfr(bfr(var * rd * rd) + 1e-5f)));
                        }
                        __syncwarp();
                        named_bar_arrive(3, 288);
                    }
                }
                const uint32_t s_cnt = s_bar + 224;
                auto ticket = [&](uint32_t a) {
                    uint32_t v = 0;
                    if (lane == 0) asm volatile("atom.acq_rel.cta.shared.add.u32 %0, [%1], 1;" : "=r"(v) : "r"(a) : "memory");
                    return v;
                };
                mbar_wait(b_stg, 0);
                int u = __shfl_sync(0xffffffffu, ticket(s_cnt + 16 + 4 * layer), 0), step = 0;
#pragma unroll 1
                while (true) {
#pragma unroll 1
                    for (; step < 5 && u >= (int)((0x3830201810ull >> (8 * step)) & 255); step++) {
                        if (step == 1) { named_bar_arrive(4, 352); continue; }
                        const int part = step ? step - 1 : 0;
                        __syncwarp();
                        if (ticket(s_cnt + 4 * part) == 3 * layer + 2) {
                            asm volatile("fence.release.gpu;" ::: "memory");
                            unsigned int* fp = flag_ptr(layer, FL_H2 + part, bi);
                            asm volatile("red.relaxed.gpu.global.add.u32 [%0], 1;" ::"l"(fp) : "memory");
                            if (part > 0) { wait_flag(fp, 8); mbar_arrive(b_h2 + 8 * part); }
                        }
                        __syncwarp();
                        if (step == 2) mbar_wait(b_stg, 1);
                    }
                    if (u >= 56) break;
                    const uint32_t un = ticket(s_cnt + 16 + 4 * layer);
                    const int job = u >> 3, r = (u & 7) * 16 + (lane >> 3);
                    const uint32_t sp = sbase + ((job & 2) ? OFF_STG5 : OFF_EPI) + r * 256 + (job & 1) * 128;
                    bf16* gp = act + (size_t)(R_H2 + (job >> 1) * 256 + tb + r) * D_ + ((job & 1) * 8 + bj) * 64 + (lane & 7) * 8;
                    uint4 v[4];
#pragma unroll
                    for (int e = 0; e < 4; e++) v[e] = lds128(sp + e * 1024 + (((lane & 7) ^ ((r + 4 * e) & 7)) << 4));
#pragma unroll
                    for (int e = 0; e < 4; e++) stg128(gp + 4 * e * D_, gelu8h(v[e]));
                    u = __shfl_sync(0xffffffffu, un, 0);
                }
                if (layer == 0 && warp == 11) {
                    const char* ps = reinterpret_cast<const char*>(g_stats + 3 * S_ * 8 + bi * 1024) + lane * 128;
                    const char* py = reinterpret_cast<const char*>(act + (size_t)(R_Y + (tb & ~255) + (bj & 1) * 128 + (lane >> 1)) * D_ + (bj >> 1) * 256 + rank * 128) + (lane & 1) * 128;
#pragma unroll 1
                    for (int i = 0; i < 8; i++) {
                        asm volatile("prefetch.global.L2 [%0];" ::"l"(py + (size_t)i * 16 * D_ * 2) : "memory");
                        if (i >= 6) asm volatile("prefetch.global.L2 [%0];" ::"l"(ps + (i & 1) * 4096) : "memory");
                        __nanosleep(400);
                    }
                }
            }
        }
        __syncwarp();
        asm volatile("barrier.cluster.arrive.relaxed.aligned;\nbarrier.cluster.wait.acquire.aligned; // helpers" ::: "memory");
    } else {
        asm volatile("setmaxnreg.inc.sync.aligned.u32 216;");
        const int tid = threadIdx.x;
        const int wg = warp >> 2;
        const bool rel_on = (tid & 95) == 0;
        const uint32_t rel5 = mapa_u32(e5, (warp & 1) ^ rank), rel4 = rel5 + (e4 - e5);
        const uint32_t da0 = desc_a(s_r + wg * 8192), db0 = desc_b(s_r + BM * BK * 2), dae = da0 + (OFF_EPI - OFF_R) / 16, db4 = db0 - 49152 / 16;
        auto skip5 = [&](RingState& rs) {
            if (rel_on) mbar_arrive_cluster(rel5 + 8 * rs.st);
            rs.st++;
        };
        const int t = lane & 3;
        const int row = warp * 16 + (lane >> 2);
        const uint32_t st_w = (uint32_t)((warp * 16 + ((lane >> 3) & 1) * 8 + (lane & 7)) * 256 + (((lane >> 4) ^ (lane & 7)) << 4));
        const uint32_t fr = (uint32_t)((warp * 16 + ((lane >> 3) & 1) * 8 + (lane & 7)) * 128 + (((lane >> 4) ^ (lane & 7)) << 4));
        auto copy_out = [&](bf16* dst, uint32_t src) {
            const int r = warp * 16 + (lane >> 4);
            bf16* ox = dst + (size_t)(m0 + r) * D_ + bj * 128 + (lane & 15) * 8;
            const uint32_t ra = src + ((lane & 15) >> 3) * 16384 + r * 128;
            uint4 v[8];
#pragma unroll
            for (int it = 0; it < 8; it++) v[it] = lds128(ra + it * 256 + (((lane & 7) ^ ((2 * it + (lane >> 4)) & 7)) << 4));
#pragma unroll
            for (int it = 0; it < 8; it++) *reinterpret_cast<uint4*>(ox + (size_t)it * 2 * D_) = v[it];
        };
        auto put_stats = [&](const uint32_t (&w)[32], int which) {
            float sm[2] = {0.f, 0.f}, sq[2] = {0.f, 0.f};
#pragma unroll
            for (int e = 0; e < 32; e++) {
                const float e0 = lo2f(w[e]), e1 = hi2f(w[e]);
                sm[e & 1] += e0 + e1; sq[e & 1] = fmaf(e0, e0, fmaf(e1, e1, sq[e & 1]));
            }
#pragma unroll
            for (int of = 1; of < 4; of <<= 1)
#pragma unroll
                for (int e = 0; e < 2; e++) { sm[e] += __shfl_xor_sync(0xffffffffu, sm[e], of); sq[e] += __shfl_xor_sync(0xffffffffu, sq[e], of); }
            if (t < 2) {
                const float s1 = t ? sm[1] : sm[0], q1 = t ? sq[1] : sq[0], mu = s1 * (1.0f / 128);
                asm volatile("{\n.reg .b64 t;\nmov.b64 t, {%1, %2};\nst.relaxed.gpu.global.b64 [%0], t;\n}"
                             ::"l"(g_stats + which * S_ * 8 + (bi * 8 + bj) * 128 + row + 8 * t), "f"(mu), "f"(fmaxf(q1 - s1 * mu, 0.f)) : "memory");
            }
        };
        const float* csp = reinterpret_cast<const float*>(sgen + OFF_CS) + 2 * t;
        float mrow[2], rrow[2];
        const uint32_t* rsp = reinterpret_cast<const uint32_t*>(sgen + OFF_RS) + row;
        auto row_consts = [&](bool twice) {
#pragma unroll
            for (int e = 0; e < 2; e++) {
                const uint32_t q0 = rsp[8 * e], q1 = rsp[128 + 8 * e];
                mrow[e] = twice ? fmaf(lo2f(q1), hi2f(q0), lo2f(q0)) : lo2f(q0);
                rrow[e] = 0.5f * frcp(twice ? hi2f(q0) * hi2f(q1) : hi2f(q0));
            }
        };
        auto stage = [&](const float* acc, uint32_t dst, int j0, float2 (&cs)[8], const float* cnext) {
            float2 cn[8];
#pragma unroll
            for (int e = 0; e < 8; e++) cn[e] = *reinterpret_cast<const float2*>(cnext + 8 * e);
#pragma unroll
            for (int j = 0; j < 8; j += 2) {
                uint32_t w[4];
#pragma unroll
                for (int e = 0; e < 2; e++) {
                    const float* a = acc + 4 * (j + e);
                    w[2 * e] = pack2(fmaf(-mrow[0], cs[j + e].x, a[0]) * rrow[0], fmaf(-mrow[0], cs[j + e].y, a[1]) * rrow[0]);
                    w[2 * e + 1] = pack2(fmaf(-mrow[1], cs[j + e].x, a[2]) * rrow[1], fmaf(-mrow[1], cs[j + e].y, a[3]) * rrow[1]);
                }
                stsm4((dst + st_w) ^ (((j0 + j) & 15) << 4), w[0], w[1], w[2], w[3]);
            }
#pragma unroll
            for (int e = 0; e < 8; e++) cs[e] = cn[e];
        };
        RingState r5{0, 0}, r4{0, 0};
        skip5(r5);
        DT(1);
        uint32_t x[32];
        mbar_wait(b_rfull, 0);
#pragma unroll
        for (int jp = 0; jp < 8; jp++) ldsm4(x[4 * jp], x[4 * jp + 1], x[4 * jp + 2], x[4 * jp + 3], s_epi + (fr ^ ((jp & 3) << 5)) + (jp >> 2) * 16384);
#pragma unroll 1
        for (int layer = 0; layer < 2; layer++) {
            {
                DT(2 + 24 * layer);
                if (layer == 1) put_stats(x, 3);
                else pdl_wait();
                DT(20 + 24 * layer);
                DT(22 + 24 * layer);
                uint32_t mb[2];
                float rd[2];
                {
                    float mean, var;
                    row_stats(g_stats + 3 * layer * S_ * 8 + bi * 1024 + warp * 16 + (lane & 15), mean, var);
                    __syncwarp();
                    const float r1 = frcp(bfr(fsqrt(bfr(bfr(var) + 1e-5f))));
                    const uint32_t m1 = pack2(mean, mean);
#pragma unroll
                    for (int e = 0; e < 2; e++) { mb[e] = __shfl_sync(0xffffffffu, m1, (lane >> 2) + 8 * e); rd[e] = __shfl_sync(0xffffffffu, r1, (lane >> 2) + 8 * e); }
                }
                DT(21 + 24 * layer);
                mbar_wait(f5 + 8, r5.ph);
                if (layer == 0) GT(3);
                const uint32_t ya = s_r + R5_STAGE + wg * 16384 + ((lane >> 4) * 8 + (lane & 7)) * 128 + ((((warp & 3) * 2 + ((lane >> 3) & 1)) ^ (lane & 7)) << 4);
                uint32_t y[16];
#pragma unroll
                for (int e = 0; e < 32; e++) {
                    if ((e & 15) == 0) {
#pragma unroll
                        for (int jp = 0; jp < 4; jp++) ldsm4t(y[4 * jp], y[4 * jp + 1], y[4 * jp + 2], y[4 * jp + 3], ya + jp * 2048 + e * 512);
                    }
                    const uint32_t d = bsub2(x[e], mb[e & 1]);
                    x[e] = badd2(x[e], bmul2(pack2(lo2f(d) * rd[e & 1], hi2f(d) * rd[e & 1]), y[e & 15]));
                    if ((e & 3) == 3) stsm4(s_epi + (fr ^ (((e >> 2) & 3) << 5)) + (e >> 4) * 16384, x[e - 3], x[e - 2], x[e - 1], x[e]);
                    if ((e & 15) == 15) { fence_async_smem(); named_bar_arrive(5 + (e >> 4), 288); }
                }
                DT(19 + 24 * layer);
                named_bar_sync(9 + wg, 128);
                skip5(r5);
                DT(3 + 24 * layer);
            }
            {
                float acc[64];
                zero_acc(acc);
                kblock<128, R5_N>(acc, dae, db0 + 2 * (R5_STAGE / 16), f5, r5);
                kblock<128, R5_N>(acc, dae + 1024, db0 + 3 * (R5_STAGE / 16), f5, r5);
                put_stats(x, 3 * layer + 1);
                wgmma_wait<1>();
                if (rel_on) mbar_arrive_cluster(rel5 + 16);
                mainloop<128, R5_N, R5_STAGE>(acc, 14, da0, db0, f5, rel5, rel_on, r5, 15 + 24 * layer);
                DT(4 + 24 * layer);
                named_bar_sync(3, 288);
                row_consts(true);
                float2 cs[8];
#pragma unroll
                for (int j = 0; j < 16; j += 2) {
                    if ((j & 7) == 0) {
#pragma unroll
                        for (int e = 0; e < 8; e++) cs[e] = *reinterpret_cast<const float2*>(csp + 256 + 8 * (j + e));
                    }
                    uint32_t w[4];
#pragma unroll
                    for (int e = 0; e < 4; e++) {
                        const float* a = acc + 4 * j + 2 * e;
                        const float2 c = cs[(j & 7) + (e >> 1)];
                        w[e] = pack2(gelu_tanh_h(fmaf(-mrow[e & 1], c.x, a[0]) * rrow[e & 1]), gelu_tanh_h(fmaf(-mrow[e & 1], c.y, a[1]) * rrow[e & 1]));
                    }
                    stsm4(s_stg + (fr ^ ((j & 7) << 4)) + (j >> 3) * 16384, w[0], w[1], w[2], w[3]);
                    if ((j & 7) == 6) { fence_async_smem(); named_bar_arrive(5 + (j >> 3), 288); }
                }
                DT(5 + 24 * layer);
            }
            {
                float acc[64];
                zero_acc(acc);
                uint32_t u[32];
                {
                    uint32_t mb[2];
                    float rd[2];
#pragma unroll
                    for (int e = 0; e < 2; e++) { const uint32_t q0 = rsp[8 * e]; mb[e] = (q0 & 0xffffu) * 0x10001u; rd[e] = frcp(hi2f(q0)); }
#pragma unroll
                    for (int e = 0; e < 32; e++) {
                        const uint32_t d = bsub2(x[e], mb[e & 1]);
                        u[e] = pack2(lo2f(d) * rd[e & 1], hi2f(d) * rd[e & 1]);
                        asm volatile("" : "+r"(u[e]));
                    }
                }
                mbar_wait(f5 + 24, r5.ph);
                skip5(r5);
                kblock<128, R5_N>(acc, da0 + 4 * (R5_STAGE / 16), db0 + 4 * (R5_STAGE / 16), f5, r5);
                DT(16 + 24 * layer);
                mainloop<128, R5_N, R5_STAGE>(acc, 15, da0, db0, f5, rel5, rel_on, r5, -1);
                DT(6 + 24 * layer);
#pragma unroll
                for (int j = 0; j < 16; j += 2) {
#pragma unroll
                    for (int e = 0; e < 4; e++) u[2 * j + e] = badd2(u[2 * j + e], pack2(acc[4 * j + 2 * e], acc[4 * j + 2 * e + 1]));
                    stsm4(s_epi + (fr ^ ((j & 7) << 4)) + (j >> 3) * 16384, u[2 * j], u[2 * j + 1], u[2 * j + 2], u[2 * j + 3]);
                    if ((j & 7) == 6) { fence_async_smem(); named_bar_arrive(5 + (j >> 3), 288); }
                }
#pragma unroll
                for (int e = 0; e < 32; e++) x[e] = badd2(x[e], u[e]);
                named_bar_sync(9 + wg, 128);
                DT(7 + 24 * layer);
                if (layer == 0) GT(7);
            }
            {
                float2 cs[8];
                {
                    float acc[128];
                    zero_acc(acc);
                    kblock<256, R4_N>(acc, dae, db4, f4, r4);
                    kblock<256, R4_N>(acc, dae + 1024, db4 + R4_STAGE / 16, f4, r4);
                    {
                        uint32_t w[32];
#pragma unroll
                        for (int jp = 0; jp < 8; jp++) ldsm4(w[4 * jp], w[4 * jp + 1], w[4 * jp + 2], w[4 * jp + 3], s_epi + (fr ^ ((jp & 3) << 5)) + (jp >> 2) * 16384);
                        put_stats(w, 3 * layer + 2);
                    }
                    wgmma_wait<1>();
                    if (rel_on) mbar_arrive_cluster(rel4);
                    mainloop<256, R4_N, R4_STAGE>(acc, 14, da0, db4, f4, rel4, rel_on, r4, 17 + 24 * layer);
                    DT(8 + 24 * layer);
                    named_bar_sync(3, 288);
                    row_consts(false);
#pragma unroll
                    for (int e = 0; e < 8; e++) cs[e] = *reinterpret_cast<const float2*>(csp + 8 * e);
#pragma unroll
                    for (int j = 0; j < 32; j += 8) stage(acc + 4 * j, j < 16 ? s_epi : s_stg, j, cs, csp + 8 * (j + 8));
                    __syncwarp();
                if (lane == 0) mbar_arrive(b_stg);
                }
                DT(9 + 24 * layer);
                float acc[96];
                zero_acc(acc);
                kblock<192, R4_N>(acc, da0, db0, f4, r4);
                mainloop<192, R4_N, R4B_STAGE>(acc, 15, da0, db0, f4, rel4, rel_on, r4, -1);
                DT(10 + 24 * layer);
                named_bar_sync(4, 352);
#pragma unroll
                for (int j = 0; j < 24; j += 8) stage(acc + 4 * j, j < 16 ? s_epi : s_stg, j, cs, csp + 256 + 8 * (j < 16 ? j + 8 : 0));
                __syncwarp();
                if (lane == 0) mbar_arrive(b_stg);
                DT(11 + 24 * layer);
            }
            {
                float acc[64];
#pragma unroll
                for (int i = 0; i < 32; i++) asm volatile("shl.b32 %0, %2, 16;\nand.b32 %1, %2, 0xffff0000;" : "=f"(acc[2 * i]), "=f"(acc[2 * i + 1]) : "r"(x[i]));
                kblock<128, R5_N>(acc, da0, db0, f5, r5);
                DT(18 + 24 * layer);
                mainloop<128, R5_N, R5_STAGE>(acc, 55, da0, db0, f5, rel5, rel_on, r5, 62 - 40 * (layer ^ 1));
                DT(12 + 24 * layer);
#pragma unroll
                for (int i = 0; i < 32; i++) x[i] = pack2(acc[2 * i], acc[2 * i + 1]);
                DT(13 + 24 * layer);
                if (layer == 0) GT(6);
                DT(14 + 24 * layer);
            }
        }
#pragma unroll
        for (int jp = 0; jp < 8; jp++) stsm4(s_epi + (fr ^ ((jp & 3) << 5)) + (jp >> 2) * 16384, x[4 * jp], x[4 * jp + 1], x[4 * jp + 2], x[4 * jp + 3]);
        __syncwarp();
        copy_out(outp, s_epi);
        DT(38);
        GT(4);
        cluster_arrive_relaxed();
        cluster_wait();
    }
}

constexpr int CV_CH = 8;
constexpr int CV_UPITCH = 72;
constexpr int CV_UROWS = 40;
constexpr int CV_U_BYTES = CV_UROWS * CV_UPITCH * 2;
constexpr int CV_P_WORDS = 2048 + 16;
constexpr int CV_P_BYTES = CV_P_WORDS * 4;
constexpr int CV_Y_BYTES = 8 * CV_UPITCH * 2;
constexpr int CV_SMEM = CV_CH * (CV_U_BYTES + CV_P_BYTES + CV_Y_BYTES) + 2 * 8 * 16 * 32 * 4 + 128 + (128 + 2048 * 16) + 2048 * 16;

__device__ __forceinline__ void mma16816(float (&d)[4], uint32_t a0, uint32_t a1, uint32_t a2, uint32_t a3, uint32_t b0, uint32_t b1) {
    asm volatile("mma.sync.aligned.m16n8k16.row.col.f32.bf16.bf16.f32 {%0,%1,%2,%3}, {%4,%5,%6,%7}, {%8,%9}, {%0,%1,%2,%3};"
                 : "+f"(d[0]), "+f"(d[1]), "+f"(d[2]), "+f"(d[3]) : "r"(a0), "r"(a1), "r"(a2), "r"(a3), "r"(b0), "r"(b1));
}
__device__ __forceinline__ void stsm4t(uint32_t addr, uint32_t r0, uint32_t r1, uint32_t r2, uint32_t r3) {
    asm volatile("stmatrix.sync.aligned.m8n8.x4.trans.shared.b16 [%0], {%1,%2,%3,%4};" ::"r"(addr), "r"(r0), "r"(r1), "r"(r2), "r"(r3) : "memory");
}
__device__ __forceinline__ void ldsm4c(uint32_t& r0, uint32_t& r1, uint32_t& r2, uint32_t& r3, uint32_t addr) {
    asm volatile("ldmatrix.sync.aligned.m8n8.x4.shared.b16 {%0,%1,%2,%3}, [%4];" : "=r"(r0), "=r"(r1), "=r"(r2), "=r"(r3) : "r"(addr));
}
__global__ void __launch_bounds__(640, 1)
conv_kernel(const __grid_constant__ CUtensorMap tmK, const __grid_constant__ CUtensorMap tmV, const bf16* __restrict__ kp,
            const bf16* __restrict__ vp, const bf16* __restrict__ shk,
            const bf16* __restrict__ ssk, const bf16* __restrict__ ssD, const bf16* __restrict__ w1p, const bf16* __restrict__ w3p,
            const bf16* __restrict__ xq, bf16* act) {
    extern __shared__ __align__(128) uint8_t sm[];
    uint8_t* sU = sm;
    uint8_t* sP = sm + CV_CH * CV_U_BYTES;
    uint8_t* sY = sP + CV_CH * CV_P_BYTES;
    float* sR = reinterpret_cast<float*>(sY + CV_CH * CV_Y_BYTES);
    const int tid = threadIdx.x, warp = tid >> 5, lane = tid & 31;
    const int d0 = blockIdx.x * CV_CH;
    const uint32_t bar0 = smem_u32(sR + 2 * 8 * 16 * 32);
    const uint8_t* sK = reinterpret_cast<const uint8_t*>(sR + 2 * 8 * 16 * 32) + 128 + 128;
    const uint8_t* sV = sK + 2048 * 16;
    DBG_T(0);
    GT(0);
    auto load_kv = [&](int q) {
        mbar_expect_tx(bar0 + 64 + 8 * q, 4 * 4096);
        for (int i = 0; i < 2; i++) {
            int r0 = 512 * q + 256 * i;
            tma_load_2d(smem_u32(sK) + r0 * 16, &tmK, bar0 + 64 + 8 * q, d0, r0);
            tma_load_2d(smem_u32(sV) + r0 * 16, &tmV, bar0 + 64 + 8 * q, d0, r0);
        }
    };
    uint4 k0, v0;
    if (tid < 512) {
        k0 = __ldg(reinterpret_cast<const uint4*>(kp + (size_t)tid * D_ + d0));
        v0 = __ldg(reinterpret_cast<const uint4*>(vp + (size_t)tid * D_ + d0));
    }
    if (tid == 512) {
        for (int i = 0; i < 4; i++) { mbar_init(bar0 + 8 * i, 4); mbar_init(bar0 + 32 + 8 * i, 4); mbar_init(bar0 + 64 + 8 * i, i == 0 ? 16 : 1); }
        asm volatile("fence.mbarrier_init.release.cluster;" ::: "memory");
        fence_async_smem();
    }
    if (tid >= 32 && tid < 35) *reinterpret_cast<uint4*>(const_cast<uint8_t*>(sK) - 16 * (tid - 31)) = make_uint4(0, 0, 0, 0);
    for (int i = tid; tid < 512 && i < CV_CH * 8 * CV_UPITCH / 8; i += 512) {
        int c2 = i / (8 * CV_UPITCH / 8), r = i % (8 * CV_UPITCH / 8);
        *reinterpret_cast<uint4*>(sU + c2 * CV_U_BYTES + r * 16) = make_uint4(0, 0, 0, 0);
    }
    if (warp < 8 && lane < 16) reinterpret_cast<uint32_t*>(sP + warp * CV_P_BYTES)[lane] = 0;

    if (warp >= 16) {
        const int bt = tid - 512;
        uint32_t wv[4][4];
#pragma unroll
        for (int pr = 0; pr < 4; pr++) {
            uint2 wa = *reinterpret_cast<const uint2*>(shk + (d0 + 2 * pr) * 4);
            uint2 wb = *reinterpret_cast<const uint2*>(shk + (d0 + 2 * pr + 1) * 4);
            wv[0][pr] = (wa.x & 0xffffu) | (wb.x << 16);
            wv[1][pr] = (wa.x >> 16) | (wb.x & 0xffff0000u);
            wv[2][pr] = (wa.y & 0xffffu) | (wb.y << 16);
            wv[3][pr] = (wa.y >> 16) | (wb.y & 0xffff0000u);
        }
        const int pch = bt >> 4, pl = bt & 15;
        const bf16* hrow = ssk + (size_t)(d0 + pch) * S_ + pl * 8;
        uint32_t* Pw = reinterpret_cast<uint32_t*>(sP + pch * CV_P_BYTES) + 16 + pl * 8;
        uint4 pf[4];
        uint32_t hprev[4];
        auto prefetch = [&](int q) {
#pragma unroll
            for (int i = 0; i < 4; i++) {
                int j0 = 512 * q + i * 128;
                pf[i] = __ldg(reinterpret_cast<const uint4*>(hrow + j0));
                hprev[i] = (j0 + pl > 0) ? (uint32_t)__bfloat16_as_ushort(hrow[j0 - 1]) : 0u;
            }
        };
        prefetch(0);
        asm volatile("barrier.sync 0, 640;" ::: "memory");
        pdl_wait();
        if (blockIdx.x == 0) {
            for (int i = bt; i < FL_WORDS / FL_PITCH; i += 128) g_flag[i * FL_PITCH] = 0;
            if (bt < 9) { g_ticket[bt * FL_PITCH] = 0; __threadfence(); }
        }
        __syncwarp();
        if (warp == 16) pdl_launch();
        for (int i = bt; i < 320; i += 128) reinterpret_cast<float4*>(g_stats + S_ * 8)[blockIdx.x * 320 + i] = make_float4(-1.f, -1.f, -1.f, -1.f);
#pragma unroll 1
        for (int q = 0; q < 4; q++) {
#pragma unroll
            for (int i = 0; i < 4; i++) {
                int j0 = 512 * q + i * 128;
                uint32_t x0 = pf[i].x, x1 = pf[i].y, x2 = pf[i].z, x3 = pf[i].w;
                uint4 o0, o1;
                o0.x = (x0 & 0xffffu) | (hprev[i] << 16);
                o0.y = (x0 >> 16) | (x0 << 16);
                o0.z = (x1 & 0xffffu) | (x0 & 0xffff0000u);
                o0.w = (x1 >> 16) | (x1 << 16);
                o1.x = (x2 & 0xffffu) | (x1 & 0xffff0000u);
                o1.y = (x2 >> 16) | (x2 << 16);
                o1.z = (x3 & 0xffffu) | (x2 & 0xffff0000u);
                o1.w = (x3 >> 16) | (x3 << 16);
                *reinterpret_cast<uint4*>(Pw + j0) = o0;
                *reinterpret_cast<uint4*>(Pw + j0 + 4) = o1;
            }
            DBG_T(1 + 3 * q);
            mbar_wait(bar0 + 64 + 8 * q, 0);
            if (q < 3) {
                if (bt == 0) load_kv(q + 1);
                prefetch(q + 1);
            }
            DBG_T(2 + 3 * q);
#pragma unroll 1
            for (int hf = 0; hf < 2; hf++) {
                const int s0 = 512 * q + 256 * hf + 2 * bt;
                const int a = s0 >> 6, b = s0 & 63;
                uint4 kf[7];
#pragma unroll
                for (int i = 0; i < 5; i++) kf[i] = *reinterpret_cast<const uint4*>(sK + (s0 - 3 + i) * 16);
#pragma unroll
                for (int i = 0; i < 2; i++) kf[5 + i] = *reinterpret_cast<const uint4*>(sV + (s0 + i) * 16);
#pragma unroll
                for (int pr = 0; pr < 4; pr++) {
                    uint32_t k0 = reinterpret_cast<const uint32_t*>(&kf[0])[pr], k1 = reinterpret_cast<const uint32_t*>(&kf[1])[pr],
                             k2 = reinterpret_cast<const uint32_t*>(&kf[2])[pr], k3 = reinterpret_cast<const uint32_t*>(&kf[3])[pr],
                             k4 = reinterpret_cast<const uint32_t*>(&kf[4])[pr];
                    uint32_t r0 = bmul2(k0, wv[3][pr]);
                    r0 = badd2(r0, bmul2(k1, wv[2][pr]));
                    r0 = badd2(r0, bmul2(k2, wv[1][pr]));
                    r0 = badd2(r0, bmul2(k3, wv[0][pr]));
                    r0 = bmul2(r0, reinterpret_cast<const uint32_t*>(&kf[5])[pr]);
                    uint32_t r1 = bmul2(k1, wv[3][pr]);
                    r1 = badd2(r1, bmul2(k2, wv[2][pr]));
                    r1 = badd2(r1, bmul2(k3, wv[1][pr]));
                    r1 = badd2(r1, bmul2(k4, wv[0][pr]));
                    r1 = bmul2(r1, reinterpret_cast<const uint32_t*>(&kf[6])[pr]);
                    uint32_t c0 = (r0 & 0xffffu) | (r1 << 16), c1 = (r0 >> 16) | (r1 & 0xffff0000u);
                    *reinterpret_cast<uint32_t*>(sU + (2 * pr) * CV_U_BYTES + ((8 + a) * CV_UPITCH + b) * 2) = c0;
                    *reinterpret_cast<uint32_t*>(sU + (2 * pr + 1) * CV_U_BYTES + ((8 + a) * CV_UPITCH + b) * 2) = c1;
                }
            }
            __syncwarp();
            if (lane == 0) mbar_arrive(bar0 + 8 * q);
            DBG_T(3 + 3 * q);
        }
        {
            const int bi = blockIdx.x >> 3, bj = blockIdx.x & 7;
            const bool is3 = bt < 112;
            const int cg = is3 ? bt % 56 : bt - 112, pitch = is3 ? F_ : D_, col = is3 ? bj * 448 + cg * 8 : bj * 128 + cg * 8;
            const int r1 = is3 ? 32 : 64;
            const bf16* p = (is3 ? w3p + (size_t)(bt >= 56 ? 32 : 0) * F_ : w1p) + (size_t)(bi * 64) * pitch + col;
            float a8[8];
#pragma unroll
            for (int i = 0; i < 8; i++) a8[i] = 0.f;
#pragma unroll 1
            for (int r0 = 0; r0 < r1; r0 += 16) {
                uint4 v[16];
#pragma unroll
                for (int r = 0; r < 16; r++) v[r] = __ldg(reinterpret_cast<const uint4*>(p + (size_t)(r0 + r) * pitch));
#pragma unroll
                for (int r = 0; r < 16; r++) {
                    a8[0] += lo2f(v[r].x); a8[1] += hi2f(v[r].x); a8[2] += lo2f(v[r].y); a8[3] += hi2f(v[r].y);
                    a8[4] += lo2f(v[r].z); a8[5] += hi2f(v[r].z); a8[6] += lo2f(v[r].w); a8[7] += hi2f(v[r].w);
                }
            }
            float* sc = reinterpret_cast<float*>(const_cast<uint8_t*>(sK));
            mbar_wait(bar0, 0);
            if (bt >= 56 && is3) {
#pragma unroll
                for (int i = 0; i < 8; i++) sc[cg * 8 + i] = a8[i];
            }
            __syncwarp();
            if (lane == 0) mbar_arrive(bar0 + 32);
            mbar_wait(bar0 + 32, 0);
            if (bt < 56 || !is3) {
                if (is3) {
#pragma unroll
                    for (int i = 0; i < 8; i++) a8[i] += sc[cg * 8 + i];
                }
                float4* dst = reinterpret_cast<float4*>(g_cpart + bi * (F_ + D_) + (is3 ? 0 : F_) + col);
                dst[0] = make_float4(a8[0], a8[1], a8[2], a8[3]);
                dst[1] = make_float4(a8[4], a8[5], a8[6], a8[7]);
            }
        }
        {
            const int r = blockIdx.x * 16 + (warp - 16) * 4;
            uint4 v[16];
#pragma unroll
            for (int e = 0; e < 16; e++) v[e] = __ldg(reinterpret_cast<const uint4*>(xq + (size_t)r * D_ + e * 256 + lane * 8));
            float sm[4] = {0.f, 0.f, 0.f, 0.f}, sq[4] = {0.f, 0.f, 0.f, 0.f};
#pragma unroll
            for (int e = 0; e < 64; e++) {
                const uint32_t w = reinterpret_cast<const uint32_t*>(v)[e];
                sm[e >> 4] += lo2f(w) + hi2f(w); sq[e >> 4] = fmaf(lo2f(w), lo2f(w), fmaf(hi2f(w), hi2f(w), sq[e >> 4]));
            }
#pragma unroll
            for (int o = 16; o > 0; o >>= 1)
#pragma unroll
                for (int e = 0; e < 4; e++) { sm[e] += __shfl_xor_sync(0xffffffffu, sm[e], o); sq[e] += __shfl_xor_sync(0xffffffffu, sq[e], o); }
            const int e = lane >> 3;
            const float s1 = e == 0 ? sm[0] : e == 1 ? sm[1] : e == 2 ? sm[2] : sm[3], q1 = e == 0 ? sq[0] : e == 1 ? sq[1] : e == 2 ? sq[2] : sq[3];
            const float mu = s1 * (1.0f / D_);
            g_stats[((r >> 7) * 8 + (lane & 7)) * 128 + (r & 127) + e] = make_float2(mu, fmaxf(q1 - s1 * mu, 0.f) * 0.125f);
        }
        DBG_T(13);
        return;
    }

    asm volatile("barrier.sync 0, 640;" ::: "memory");
    *reinterpret_cast<uint4*>(const_cast<uint8_t*>(sK) + tid * 16) = k0;
    *reinterpret_cast<uint4*>(const_cast<uint8_t*>(sV) + tid * 16) = v0;
    __syncwarp();
    if (lane == 0) mbar_arrive(bar0 + 64);
    const int ch = warp & 7, par = warp >> 3;
    const int g = lane >> 2, t = lane & 3;
    const uint32_t* P = reinterpret_cast<const uint32_t*>(sP + ch * CV_P_BYTES) + 16 + (g - 2 * t);
    const uint32_t uB = smem_u32(sU + ch * CV_U_BYTES);
    const int lrow = lane & 7, lmat = lane >> 3;
    const uint32_t Dk2 = (uint32_t)__bfloat16_as_ushort(ssD[d0 + ch]) * 0x10001u;
    pdl_wait();
    GT(5);

#pragma unroll 1
    for (int q = 0; q < 4; q++) {
        mbar_wait(bar0 + 8 * q, 0);
        DBG_T(1 + 3 * q);
        float acc[4][4];
#pragma unroll
        for (int i = 0; i < 4; i++)
#pragma unroll
            for (int k = 0; k < 4; k++) acc[i][k] = 0.f;
        const int c0 = par * (4 * q + 4), c1 = c0 + 4 * q + 4;
        const uint32_t base0 = uB + ((8 + 8 * q + lrow) * CV_UPITCH) * 2 + lmat * 16;
        int c = c0;
        uint32_t pa[15];
        if (par == 0) {
#pragma unroll
            for (int j = 6; j < 15; j++) pa[j] = P[8 * (j - 7)];
            uint32_t b[8];
            ldsm4c(b[0], b[1], b[2], b[3], base0);
            ldsm4c(b[4], b[5], b[6], b[7], base0 + 64);
#pragma unroll
            for (int kk = 0; kk < 4; kk++)
#pragma unroll
                for (int mi = kk; mi < 4; mi++) {
                    int jj = 2 * (mi - kk) + 7;
                    mma16816(acc[mi], pa[jj], pa[jj + 1], pa[jj - 1], pa[jj], b[2 * kk], b[2 * kk + 1]);
                }
            c = 1;
        } else {
#pragma unroll
            for (int j = 8; j < 15; j++) pa[j] = P[8 * (8 * c - 15 + j)];
        }
#pragma unroll 2
        for (; c < c1; c++) {
#pragma unroll
            for (int j = 0; j < 7; j++) pa[j] = pa[j + 8];
#pragma unroll
            for (int j = 7; j < 15; j++) pa[j] = P[8 * (8 * c - 7 + j)];
            uint32_t b[8];
            uint32_t base = base0 - c * (CV_UPITCH * 2);
            ldsm4c(b[0], b[1], b[2], b[3], base);
            ldsm4c(b[4], b[5], b[6], b[7], base + 64);
#pragma unroll
            for (int kk = 3; kk >= 0; kk--)
#pragma unroll
                for (int mi = 0; mi < 4; mi++) {
                    int jj = 2 * (mi - kk) + 7;
                    mma16816(acc[mi], pa[jj], pa[jj + 1], pa[jj - 1], pa[jj], b[2 * kk], b[2 * kk + 1]);
                }
        }
        DBG_T(2 + 3 * q);
        float4* sRq = reinterpret_cast<float4*>(sR) + ((q & 1) * 8 + ch) * 128 + lane;
        if (par == 1) {
#pragma unroll
            for (int mi = 0; mi < 4; mi++) sRq[mi * 32] = make_float4(acc[mi][0], acc[mi][1], acc[mi][2], acc[mi][3]);
            named_bar_arrive(ch + 8 * (q & 1), 64);
        } else {
            uint32_t kv[8];
            ldsm4t(kv[0], kv[1], kv[2], kv[3], base0);
            ldsm4t(kv[4], kv[5], kv[6], kv[7], base0 + 64);
            named_bar_sync(ch + 8 * (q & 1), 64);
#pragma unroll
            for (int mi = 0; mi < 4; mi++) {
                const float4 o = sRq[mi * 32];
                kv[2 * mi] = badd2(pack2(acc[mi][0] + o.x, acc[mi][1] + o.y), bmul2(kv[2 * mi], Dk2));
                kv[2 * mi + 1] = badd2(pack2(acc[mi][2] + o.z, acc[mi][3] + o.w), bmul2(kv[2 * mi + 1], Dk2));
            }
            const uint32_t yb = smem_u32(sY + ch * CV_Y_BYTES);
            __syncwarp();
            stsm4t(yb + lrow * (CV_UPITCH * 2) + lmat * 16, kv[0], kv[1], kv[2], kv[3]);
            stsm4t(yb + lrow * (CV_UPITCH * 2) + lmat * 16 + 64, kv[4], kv[5], kv[6], kv[7]);
            __syncwarp();
            uint4* dst = reinterpret_cast<uint4*>(act + (size_t)(R_Y + q * 4096 + ((d0 + ch) & 255)) * D_ + (d0 & ~255)) + lane;
            const uint4 v0 = lds128(yb + (lane >> 3) * (CV_UPITCH * 2) + (lane & 7) * 16);
            const uint4 v1 = lds128(yb + (4 + (lane >> 3)) * (CV_UPITCH * 2) + (lane & 7) * 16);
            dst[0] = v0;
            dst[2048 * D_ / 8] = v1;
        }
        DBG_T(3 + 3 * q);
    }
    GT(1);
}

typedef CUresult (*PFN_encodeTiled)(CUtensorMap*, CUtensorMapDataType, cuuint32_t, void*, const cuuint64_t*, const cuuint64_t*,
                                    const cuuint32_t*, const cuuint32_t*, CUtensorMapInterleave, CUtensorMapSwizzle,
                                    CUtensorMapL2promotion, CUtensorMapFloatOOBfill);

static CUtensorMap make_map(PFN_encodeTiled enc, const void* ptr, int inner, int outer, int box_inner, int box_outer,
                            CUtensorMapSwizzle swz = CU_TENSOR_MAP_SWIZZLE_128B) {
    CUtensorMap m;
    cuuint64_t dims[2] = {(cuuint64_t)inner, (cuuint64_t)outer};
    cuuint64_t strides[1] = {(cuuint64_t)inner * 2};
    cuuint32_t box[2] = {(cuuint32_t)box_inner, (cuuint32_t)box_outer};
    cuuint32_t es[2] = {1, 1};
    enc(&m, CU_TENSOR_MAP_DATA_TYPE_BFLOAT16, 2, const_cast<void*>(ptr), dims, strides, box, es, CU_TENSOR_MAP_INTERLEAVE_NONE,
        swz, CU_TENSOR_MAP_L2_PROMOTION_L2_256B, CU_TENSOR_MAP_FLOAT_OOB_FILL_NONE);
    return m;
}

extern "C" void kernel_launch(void* const* d_in, const int* in_sizes, int n_in, void* d_out, int out_size) {
    const bf16* A_q = (const bf16*)d_in[0];
    const bf16* A_k = (const bf16*)d_in[1];
    const bf16* A_v = (const bf16*)d_in[2];
    const bf16* A_shk = (const bf16*)d_in[3];
    const bf16* A_ssk = (const bf16*)d_in[4];
    const bf16* A_ssD = (const bf16*)d_in[5];
    const bf16* w1 = (const bf16*)d_in[7];
    const bf16* w2 = (const bf16*)d_in[8];
    const bf16* w3 = (const bf16*)d_in[9];
    const bf16* w4 = (const bf16*)d_in[10];
    bf16* out = (bf16*)d_out;

    static PFN_encodeTiled enc = nullptr;
    static bool attr_done = false;
    if (!enc) {
        void* fn = nullptr;
        cudaDriverEntryPointQueryResult qr;
        cudaGetDriverEntryPoint("cuTensorMapEncodeTiled", &fn, cudaEnableDefault, &qr);
        enc = (PFN_encodeTiled)fn;
    }
    if (!attr_done) {
        cudaFuncSetAttribute(mega_kernel, cudaFuncAttributeMaxDynamicSharedMemorySize, MEGA_SMEM);
        cudaFuncSetAttribute(conv_kernel, cudaFuncAttributeMaxDynamicSharedMemorySize, CV_SMEM);
        attr_done = true;
    }
    void* p_act;
    cudaGetSymbolAddress(&p_act, g_act);
    bf16* act = (bf16*)(((uintptr_t)p_act + 0x1fffff) & ~(uintptr_t)0x1fffff);

    MegaMaps tm;
    tm.q = make_map(enc, A_q, D_, S_, 64, 128);
    tm.act = make_map(enc, act, D_, R_END, 64, 128);
    tm.w1 = make_map(enc, w1, D_, D_, 64, 64);
    tm.w2 = make_map(enc, w2, D_, D_, 64, 64);
    tm.w3 = make_map(enc, w3, F_, D_, 64, 64);
    tm.w4 = make_map(enc, w4, D_, F_, 64, 64);
    CUtensorMap tm_k = make_map(enc, A_k, D_, S_, 8, 256, CU_TENSOR_MAP_SWIZZLE_NONE);
    CUtensorMap tm_v = make_map(enc, A_v, D_, S_, 8, 256, CU_TENSOR_MAP_SWIZZLE_NONE);

    cudaStream_t st = cudaStreamPerThread;
    cudaLaunchAttribute at[2];
    at[0].id = cudaLaunchAttributeProgrammaticStreamSerialization;
    at[0].val.programmaticStreamSerializationAllowed = 1;
    at[1].id = cudaLaunchAttributeClusterDimension;
    at[1].val.clusterDim.x = 2;
    at[1].val.clusterDim.y = 1;
    at[1].val.clusterDim.z = 1;
    {
        cudaLaunchConfig_t cfg = {};
        cfg.gridDim = dim3(D_ / CV_CH);
        cfg.blockDim = dim3(640);
        cfg.dynamicSmemBytes = CV_SMEM;
        cfg.stream = st;
        cfg.attrs = at;
        cfg.numAttrs = 1;
        cudaLaunchKernelEx(&cfg, conv_kernel, tm_k, tm_v, A_k, A_v, A_shk, A_ssk, A_ssD, w1, w3, A_q, act);
    }
    {
        cudaLaunchConfig_t cfg = {};
        cfg.gridDim = dim3(132);
        cfg.blockDim = dim3(384);
        cfg.dynamicSmemBytes = MEGA_SMEM;
        cfg.stream = st;
        cfg.attrs = at;
        cfg.numAttrs = 2;
        cudaLaunchKernelEx(&cfg, mega_kernel, tm, out, act);
    }
}
```

```cpp
#include <cuda_runtime.h>
#include <cuda_bf16.h>
#include <cuda.h>
#include <stdint.h>

typedef __nv_bfloat16 bf16;

constexpr int S_ = 2048;
constexpr int D_ = 1024;
constexpr int F_ = 3584;

constexpr int R_XA = 0, R_X1 = 256, R_H2 = 512, R_Y = 1536, R_H = 16384 + 8, R_HP = S_ + 8, R_END = R_H + 2 * R_HP;
__device__ __align__(1024) bf16 g_act[(size_t)(R_END + 1024) * D_];
__device__ __align__(16) float g_cpart[16 * (F_ + D_)];
__device__ __align__(16) float2 g_stats[6 * S_ * 8];

__device__ __forceinline__ float bfr(float x) { return __bfloat162float(__float2bfloat16_rn(x)); }
__device__ __forceinline__ uint32_t pack2(float lo, float hi) {
    __nv_bfloat162 v = __floats2bfloat162_rn(lo, hi);
    return *reinterpret_cast<uint32_t*>(&v);
}
__device__ __forceinline__ float lo2f(uint32_t v) { return __uint_as_float(v << 16); }
__device__ __forceinline__ float hi2f(uint32_t v) { return __uint_as_float(v & 0xffff0000u); }
__device__ __forceinline__ float frcp(float x) { float r; asm("rcp.approx.f32 %0, %1;" : "=f"(r) : "f"(x)); return r; }
__device__ __forceinline__ float fsqrt(float x) { float r; asm("sqrt.approx.f32 %0, %1;" : "=f"(r) : "f"(x)); return r; }
__device__ __forceinline__ uint32_t smem_u32(const void* p) { return (uint32_t)__cvta_generic_to_shared(p); }

__device__ __forceinline__ void mbar_init(uint32_t bar, uint32_t cnt) {
    asm volatile("mbarrier.init.shared::cta.b64 [%0], %1;" ::"r"(bar), "r"(cnt));
}
__device__ __forceinline__ void mbar_expect_tx(uint32_t bar, uint32_t bytes) {
    asm volatile("mbarrier.arrive.expect_tx.shared::cta.b64 _, [%0], %1;" ::"r"(bar), "r"(bytes) : "memory");
}
__device__ __forceinline__ void mbar_arrive(uint32_t bar) {
    asm volatile("mbarrier.arrive.shared::cta.b64 _, [%0];" ::"r"(bar) : "memory");
}
__device__ __forceinline__ void mbar_wait(uint32_t bar, uint32_t parity) {
    asm volatile(
        "{\n.reg .pred p;\n.reg .u32 n;\n"
        "mbarrier.try_wait.parity.shared::cta.b64 p, [%0], %1;\n"
        "@p bra LD;\n"
        "mov.u32 n, 0;\n"
        "LW:\n"
        "mbarrier.try_wait.parity.shared::cta.b64 p, [%0], %1;\n"
        "@p bra LD;\n"
        "add.u32 n, n, 1;\n"
        "setp.lt.u32 p, n, 0x400000;\n"
        "@p bra LW;\n"
        "LD:\n}\n"
        ::"r"(bar), "r"(parity) : "memory");
}
__device__ __forceinline__ void tma_load_2d(uint32_t dst, const CUtensorMap* tm, uint32_t bar, int c0, int c1) {
    asm volatile(
        "cp.async.bulk.tensor.2d.shared::cluster.global.mbarrier::complete_tx::bytes [%0], [%1, {%3, %4}], [%2];"
        ::"r"(dst), "l"((uint64_t)tm), "r"(bar), "r"(c0), "r"(c1) : "memory");
}
__device__ __forceinline__ void tma_load_2d_mc(uint32_t dst, const CUtensorMap* tm, uint32_t bar, int c0, int c1) {
    asm volatile(
        "cp.async.bulk.tensor.2d.shared::cluster.global.mbarrier::complete_tx::bytes.multicast::cluster [%0], [%1, {%3, %4}], [%2], %5;"
        ::"r"(dst), "l"((uint64_t)tm), "r"(bar), "r"(c0), "r"(c1), "h"((uint16_t)3) : "memory");
}
__device__ __forceinline__ void tma_prefetch_2d(const CUtensorMap* tm, int c0, int c1) {
    asm volatile("cp.async.bulk.prefetch.tensor.2d.L2.global.tile [%0, {%1, %2}];" ::"l"((uint64_t)tm), "r"(c0), "r"(c1) : "memory");
}
__device__ __forceinline__ void tma_store_2d(const CUtensorMap* tm, uint32_t src, int c0, int c1) {
    asm volatile("cp.async.bulk.tensor.2d.global.shared::cta.bulk_group [%0, {%2, %3}], [%1];"
                 ::"l"((uint64_t)tm), "r"(src), "r"(c0), "r"(c1) : "memory");
}
__device__ __forceinline__ void wgmma_fence() { asm volatile("wgmma.fence.sync.aligned;" ::: "memory"); }
__device__ __forceinline__ void wgmma_commit() { asm volatile("wgmma.commit_group.sync.aligned;" ::: "memory"); }
template <int N> __device__ __forceinline__ void wgmma_wait() { asm volatile("wgmma.wait_group.sync.aligned %0;" ::"n"(N) : "memory"); }
__device__ __forceinline__ void named_bar_arrive(int id, int n) { asm volatile("bar.arrive %0, %1;" ::"r"(id), "r"(n) : "memory"); }
__device__ __forceinline__ void named_bar_sync(int id, int n) { asm volatile("bar.sync %0, %1;" ::"r"(id), "r"(n) : "memory"); }

__device__ __forceinline__ void pdl_wait() { asm volatile("griddepcontrol.wait;" ::: "memory"); }
__device__ __forceinline__ void pdl_launch() { asm volatile("griddepcontrol.launch_dependents;" ::: "memory"); }

__device__ __forceinline__ uint32_t desc_a(uint32_t addr) { return ((addr & 0x3FFFF) >> 4) | (1u << 16); }
__device__ __forceinline__ uint32_t desc_b(uint32_t addr) { return ((addr & 0x3FFFF) >> 4) | (512u << 16); }

__device__ __forceinline__ void wgmma_m64n192k16(float (&d)[96], uint32_t descA, uint32_t descB) {
  asm volatile("{\n.reg .pred p;\n.reg .b64 da, db;\nsetp.eq.b32 p, 0, 0;\nmov.b64 da, {%96, %98};\nmov.b64 db, {%97, %98};\n"
    "wgmma.mma_async.sync.aligned.m64n192k16.f32.bf16.bf16 "
    "{%0, %1, %2, %3, %4, %5, %6, %7, %8, %9, %10, %11, %12, %13, %14, %15, %16, %17, %18, %19, %20, %21, %22, %23, %24, %25, %26, %27, %28, %29, %30, %31, %32, %33, %34, %35, %36, %37, %38, %39, %40, %41, %42, %43, %44, %45, %46, %47, %48, %49, %50, %51, %52, %53, %54, %55, %56, %57, %58, %59, %60, %61, %62, %63, %64, %65, %66, %67, %68, %69, %70, %71, %72, %73, %74, %75, %76, %77, %78, %79, %80, %81, %82, %83, %84, %85, %86, %87, %88, %89, %90, %91, %92, %93, %94, %95}, "
    "da, db, p, 1, 1, 0, 1;\n}\n"
    : "+f"(d[0]), "+f"(d[1]), "+f"(d[2]), "+f"(d[3]), "+f"(d[4]), "+f"(d[5]), "+f"(d[6]), "+f"(d[7]), "+f"(d[8]), "+f"(d[9]), "+f"(d[10]), "+f"(d[11]), "+f"(d[12]), "+f"(d[13]), "+f"(d[14]), "+f"(d[15]), "+f"(d[16]), "+f"(d[17]), "+f"(d[18]), "+f"(d[19]), "+f"(d[20]), "+f"(d[21]), "+f"(d[22]), "+f"(d[23]), "+f"(d[24]), "+f"(d[25]), "+f"(d[26]), "+f"(d[27]), "+f"(d[28]), "+f"(d[29]), "+f"(d[30]), "+f"(d[31]), "+f"(d[32]), "+f"(d[33]), "+f"(d[34]), "+f"(d[35]), "+f"(d[36]), "+f"(d[37]), "+f"(d[38]), "+f"(d[39]), "+f"(d[40]), "+f"(d[41]), "+f"(d[42]), "+f"(d[43]), "+f"(d[44]), "+f"(d[45]), "+f"(d[46]), "+f"(d[47]), "+f"(d[48]), "+f"(d[49]), "+f"(d[50]), "+f"(d[51]), "+f"(d[52]), "+f"(d[53]), "+f"(d[54]), "+f"(d[55]), "+f"(d[56]), "+f"(d[57]), "+f"(d[58]), "+f"(d[59]), "+f"(d[60]), "+f"(d[61]), "+f"(d[62]), "+f"(d[63]), "+f"(d[64]), "+f"(d[65]), "+f"(d[66]), "+f"(d[67]), "+f"(d[68]), "+f"(d[69]), "+f"(d[70]), "+f"(d[71]), "+f"(d[72]), "+f"(d[73]), "+f"(d[74]), "+f"(d[75]), "+f"(d[76]), "+f"(d[77]), "+f"(d[78]), "+f"(d[79]), "+f"(d[80]), "+f"(d[81]), "+f"(d[82]), "+f"(d[83]), "+f"(d[84]), "+f"(d[85]), "+f"(d[86]), "+f"(d[87]), "+f"(d[88]), "+f"(d[89]), "+f"(d[90]), "+f"(d[91]), "+f"(d[92]), "+f"(d[93]), "+f"(d[94]), "+f"(d[95])
    : "r"(descA), "r"(descB), "r"(0x40000040u));
}

__device__ __forceinline__ void wgmma_m64n256k16(float (&d)[128], uint32_t descA, uint32_t descB) {
  asm volatile("{\n.reg .pred p;\n.reg .b64 da, db;\nsetp.eq.b32 p, 0, 0;\nmov.b64 da, {%128, %130};\nmov.b64 db, {%129, %130};\n"
    "wgmma.mma_async.sync.aligned.m64n256k16.f32.bf16.bf16 "
    "{%0, %1, %2, %3, %4, %5, %6, %7, %8, %9, %10, %11, %12, %13, %14, %15, %16, %17, %18, %19, %20, %21, %22, %23, %24, %25, %26, %27, %28, %29, %30, %31, %32, %33, %34, %35, %36, %37, %38, %39, %40, %41, %42, %43, %44, %45, %46, %47, %48, %49, %50, %51, %52, %53, %54, %55, %56, %57, %58, %59, %60, %61, %62, %63, %64, %65, %66, %67, %68, %69, %70, %71, %72, %73, %74, %75, %76, %77, %78, %79, %80, %81, %82, %83, %84, %85, %86, %87, %88, %89, %90, %91, %92, %93, %94, %95, %96, %97, %98, %99, %100, %101, %102, %103, %104, %105, %106, %107, %108, %109, %110, %111, %112, %113, %114, %115, %116, %117, %118, %119, %120, %121, %122, %123, %124, %125, %126, %127}, "
    "da, db, p, 1, 1, 0, 1;\n}\n"
    : "+f"(d[0]), "+f"(d[1]), "+f"(d[2]), "+f"(d[3]), "+f"(d[4]), "+f"(d[5]), "+f"(d[6]), "+f"(d[7]), "+f"(d[8]), "+f"(d[9]), "+f"(d[10]), "+f"(d[11]), "+f"(d[12]), "+f"(d[13]), "+f"(d[14]), "+f"(d[15]), "+f"(d[16]), "+f"(d[17]), "+f"(d[18]), "+f"(d[19]), "+f"(d[20]), "+f"(d[21]), "+f"(d[22]), "+f"(d[23]), "+f"(d[24]), "+f"(d[25]), "+f"(d[26]), "+f"(d[27]), "+f"(d[28]), "+f"(d[29]), "+f"(d[30]), "+f"(d[31]), "+f"(d[32]), "+f"(d[33]), "+f"(d[34]), "+f"(d[35]), "+f"(d[36]), "+f"(d[37]), "+f"(d[38]), "+f"(d[39]), "+f"(d[40]), "+f"(d[41]), "+f"(d[42]), "+f"(d[43]), "+f"(d[44]), "+f"(d[45]), "+f"(d[46]), "+f"(d[47]), "+f"(d[48]), "+f"(d[49]), "+f"(d[50]), "+f"(d[51]), "+f"(d[52]), "+f"(d[53]), "+f"(d[54]), "+f"(d[55]), "+f"(d[56]), "+f"(d[57]), "+f"(d[58]), "+f"(d[59]), "+f"(d[60]), "+f"(d[61]), "+f"(d[62]), "+f"(d[63]), "+f"(d[64]), "+f"(d[65]), "+f"(d[66]), "+f"(d[67]), "+f"(d[68]), "+f"(d[69]), "+f"(d[70]), "+f"(d[71]), "+f"(d[72]), "+f"(d[73]), "+f"(d[74]), "+f"(d[75]), "+f"(d[76]), "+f"(d[77]), "+f"(d[78]), "+f"(d[79]), "+f"(d[80]), "+f"(d[81]), "+f"(d[82]), "+f"(d[83]), "+f"(d[84]), "+f"(d[85]), "+f"(d[86]), "+f"(d[87]), "+f"(d[88]), "+f"(d[89]), "+f"(d[90]), "+f"(d[91]), "+f"(d[92]), "+f"(d[93]), "+f"(d[94]), "+f"(d[95]), "+f"(d[96]), "+f"(d[97]), "+f"(d[98]), "+f"(d[99]), "+f"(d[100]), "+f"(d[101]), "+f"(d[102]), "+f"(d[103]), "+f"(d[104]), "+f"(d[105]), "+f"(d[106]), "+f"(d[107]), "+f"(d[108]), "+f"(d[109]), "+f"(d[110]), "+f"(d[111]), "+f"(d[112]), "+f"(d[113]), "+f"(d[114]), "+f"(d[115]), "+f"(d[116]), "+f"(d[117]), "+f"(d[118]), "+f"(d[119]), "+f"(d[120]), "+f"(d[121]), "+f"(d[122]), "+f"(d[123]), "+f"(d[124]), "+f"(d[125]), "+f"(d[126]), "+f"(d[127])
    : "r"(descA), "r"(descB), "r"(0x40000040u));
}

__device__ __forceinline__ void wgmma_m64n128k16(float (&d)[64], uint32_t descA, uint32_t descB) {
  asm volatile("{\n.reg .pred p;\n.reg .b64 da, db;\nsetp.eq.b32 p, 0, 0;\nmov.b64 da, {%64, %66};\nmov.b64 db, {%65, %66};\n"
    "wgmma.mma_async.sync.aligned.m64n128k16.f32.bf16.bf16 "
    "{%0, %1, %2, %3, %4, %5, %6, %7, %8, %9, %10, %11, %12, %13, %14, %15, %16, %17, %18, %19, %20, %21, %22, %23, %24, %25, %26, %27, %28, %29, %30, %31, %32, %33, %34, %35, %36, %37, %38, %39, %40, %41, %42, %43, %44, %45, %46, %47, %48, %49, %50, %51, %52, %53, %54, %55, %56, %57, %58, %59, %60, %61, %62, %63}, "
    "da, db, p, 1, 1, 0, 1;\n}\n"
    : "+f"(d[0]), "+f"(d[1]), "+f"(d[2]), "+f"(d[3]), "+f"(d[4]), "+f"(d[5]), "+f"(d[6]), "+f"(d[7]), "+f"(d[8]), "+f"(d[9]), "+f"(d[10]), "+f"(d[11]), "+f"(d[12]), "+f"(d[13]), "+f"(d[14]), "+f"(d[15]), "+f"(d[16]), "+f"(d[17]), "+f"(d[18]), "+f"(d[19]), "+f"(d[20]), "+f"(d[21]), "+f"(d[22]), "+f"(d[23]), "+f"(d[24]), "+f"(d[25]), "+f"(d[26]), "+f"(d[27]), "+f"(d[28]), "+f"(d[29]), "+f"(d[30]), "+f"(d[31]), "+f"(d[32]), "+f"(d[33]), "+f"(d[34]), "+f"(d[35]), "+f"(d[36]), "+f"(d[37]), "+f"(d[38]), "+f"(d[39]), "+f"(d[40]), "+f"(d[41]), "+f"(d[42]), "+f"(d[43]), "+f"(d[44]), "+f"(d[45]), "+f"(d[46]), "+f"(d[47]), "+f"(d[48]), "+f"(d[49]), "+f"(d[50]), "+f"(d[51]), "+f"(d[52]), "+f"(d[53]), "+f"(d[54]), "+f"(d[55]), "+f"(d[56]), "+f"(d[57]), "+f"(d[58]), "+f"(d[59]), "+f"(d[60]), "+f"(d[61]), "+f"(d[62]), "+f"(d[63])
    : "r"(descA), "r"(descB), "r"(0x40000040u));
}

template <int BN> struct WG;
template <> struct WG<128> { static __device__ __forceinline__ void mma(float (&d)[64], uint32_t a, uint32_t b) { wgmma_m64n128k16(d, a, b); } };
template <> struct WG<256> { static __device__ __forceinline__ void mma(float (&d)[128], uint32_t a, uint32_t b) { wgmma_m64n256k16(d, a, b); } };
template <> struct WG<192> { static __device__ __forceinline__ void mma(float (&d)[96], uint32_t a, uint32_t b) { wgmma_m64n192k16(d, a, b); } };

#define DBG_T(i)
__device__ __forceinline__ void fence_async_smem() { asm volatile("fence.proxy.async.shared::cta;" ::: "memory"); }
__device__ __forceinline__ void prefetch_tmap(const CUtensorMap* tm) { asm volatile("prefetch.tensormap [%0];" ::"l"((uint64_t)tm) : "memory"); }
__device__ __forceinline__ uint32_t mapa_u32(uint32_t addr, uint32_t cta) {
    uint32_t r;
    asm volatile("mapa.shared::cluster.u32 %0, %1, %2;" : "=r"(r) : "r"(addr), "r"(cta));
    return r;
}
__device__ __forceinline__ void mbar_arrive_cluster(uint32_t cluster_addr) {
    asm volatile("mbarrier.arrive.shared::cluster.b64 _, [%0];" ::"r"(cluster_addr) : "memory");
}
__device__ __forceinline__ bool elect_one() {
    uint32_t p;
    asm volatile("{\n.reg .pred P;\nelect.sync _|P, 0xffffffff;\nselp.u32 %0, 1, 0, P;\n}\n" : "=r"(p));
    return p != 0;
}
__device__ __forceinline__ void cluster_arrive_relaxed() { asm volatile("barrier.cluster.arrive.relaxed.aligned;" ::: "memory"); }
__device__ __forceinline__ void cluster_wait() { asm volatile("barrier.cluster.wait.acquire.aligned;" ::: "memory"); }

__device__ __forceinline__ uint32_t bsub2(uint32_t a, uint32_t b) {
    __nv_bfloat162 r = __hsub2(*reinterpret_cast<__nv_bfloat162*>(&a), *reinterpret_cast<__nv_bfloat162*>(&b));
    return *reinterpret_cast<uint32_t*>(&r);
}
__device__ __forceinline__ uint32_t bmul2(uint32_t a, uint32_t b) {
    __nv_bfloat162 r = __hmul2(*reinterpret_cast<__nv_bfloat162*>(&a), *reinterpret_cast<__nv_bfloat162*>(&b));
    return *reinterpret_cast<uint32_t*>(&r);
}
__device__ __forceinline__ uint32_t badd2(uint32_t a, uint32_t b) {
    __nv_bfloat162 r = __hadd2(*reinterpret_cast<__nv_bfloat162*>(&a), *reinterpret_cast<__nv_bfloat162*>(&b));
    return *reinterpret_cast<uint32_t*>(&r);
}
constexpr int BM = 128, BK = 64;
constexpr int R5_STAGE = 32768, R5_N = 5;
constexpr int R4_STAGE = 49152, R4_N = 4;
constexpr int R4B_STAGE = 40960;
constexpr int OFF_STG5 = 0, OFF_R = 32768;
constexpr int OFF_EPI = 196608;
constexpr int OFF_BAR = OFF_EPI + 32768;
constexpr int OFF_RS = OFF_BAR + 256;
constexpr int OFF_CS = OFF_RS + 1024;
constexpr int MEGA_SMEM = OFF_CS + 1792;
enum { FL_XA = 0, FL_H = 2, FL_X1 = 4, FL_H2 = 6, FL_CS = 10, FL_KINDS = 11 };
constexpr int FL_PITCH = 64;
constexpr int FL_WORDS = 2 * FL_KINDS * 16 * FL_PITCH;
__device__ unsigned int g_flag[FL_WORDS];
__device__ unsigned int g_ticket[9 * FL_PITCH];
__device__ __forceinline__ unsigned int* flag_ptr(int layer, int kind, int i) { return g_flag + ((layer * FL_KINDS + kind) * 16 + i) * FL_PITCH; }

__device__ __forceinline__ void wait_flag(const unsigned int* p, unsigned int target) {
    long long t0 = clock64();
    while (true) {
        unsigned int v;
        asm volatile("ld.relaxed.gpu.global.u32 %0, [%1];" : "=r"(v) : "l"(p) : "memory");
        if (v >= target) break;
        if (clock64() - t0 > 2000000000LL) break;
    }
    asm volatile("fence.acquire.gpu;" ::: "memory");
}
__device__ __forceinline__ void fence_proxy_async() {
    asm volatile("fence.proxy.async.global;" ::: "memory");
    asm volatile("fence.proxy.async.shared::cta;" ::: "memory");
}
__device__ __forceinline__ void stsm4(uint32_t addr, uint32_t r0, uint32_t r1, uint32_t r2, uint32_t r3) {
    asm volatile("stmatrix.sync.aligned.m8n8.x4.shared.b16 [%0], {%1,%2,%3,%4};" ::"r"(addr), "r"(r0), "r"(r1), "r"(r2), "r"(r3));
}
__device__ __forceinline__ uint4 lds128(uint32_t a) {
    uint4 v;
    asm volatile("ld.shared.v4.b32 {%0,%1,%2,%3}, [%4];" : "=r"(v.x), "=r"(v.y), "=r"(v.z), "=r"(v.w) : "r"(a) : "memory");
    return v;
}
__device__ __forceinline__ void stg128(void* p, uint4 v) {
    asm volatile("st.global.v4.b32 [%0], {%1,%2,%3,%4};" ::"l"(p), "r"(v.x), "r"(v.y), "r"(v.z), "r"(v.w) : "memory");
}
__device__ __forceinline__ float gelu_tanh_h(float hx) {
    float z = hx * fmaf(hx * hx, 8.0f * 0.035677408136300125f, 2.0f * 0.7978845608028654f);
    float t;
    asm("tanh.approx.f32 %0, %1;" : "=f"(t) : "f"(z));
    return fmaf(hx, t, hx);
}
__device__ __forceinline__ uint32_t gelu2h(uint32_t p) { return pack2(gelu_tanh_h(lo2f(p)), gelu_tanh_h(hi2f(p))); }
__device__ __forceinline__ uint4 gelu8h(uint4 v) { return make_uint4(gelu2h(v.x), gelu2h(v.y), gelu2h(v.z), gelu2h(v.w)); }

__device__ __forceinline__ void row_stats(const float2* p, float& mean, float& var) {
    float2 v[8];
#pragma unroll 1
    for (int n = 0; n < (1 << 20); n++) {
#pragma unroll
        for (int i = 0; i < 8; i++)
            asm volatile("{\n.reg .b64 t;\nld.relaxed.gpu.global.b64 t, [%2];\nmov.b64 {%0, %1}, t;\n}" : "=f"(v[i].x), "=f"(v[i].y) : "l"(p + 128 * i) : "memory");
        if (fminf(fminf(fminf(v[0].y, v[1].y), fminf(v[2].y, v[3].y)), fminf(fminf(v[4].y, v[5].y), fminf(v[6].y, v[7].y))) >= 0.f) break;
    }
    mean = (((v[0].x + v[1].x) + (v[2].x + v[3].x)) + ((v[4].x + v[5].x) + (v[6].x + v[7].x))) * 0.125f;
    float m2 = 0.f, d2 = 0.f;
#pragma unroll
    for (int i = 0; i < 8; i++) { m2 += v[i].y; d2 = fmaf(v[i].x - mean, v[i].x - mean, d2); }
    var = fmaf(128.0f, d2, m2) * (1.0f / D_);
}
struct RingState { uint32_t st, ph; };

#define DT(i)
#define DP(i)
#define GT(i)

template <int BN, int NST>
__device__ __forceinline__ void kblock(float (&acc)[BN / 2], uint32_t da, uint32_t db, uint32_t bfull, RingState& rs) {
    mbar_wait(bfull + 8 * rs.st, rs.ph);
    wgmma_fence();
#pragma unroll
    for (int k = 0; k < 4; k++) WG<BN>::mma(acc, da + k * 2, db + k * 128);
    wgmma_commit();
    if (++rs.st == NST) { rs.st = 0; rs.ph ^= 1; }
}
template <int BN, int NST, int STAGE>
__device__ __forceinline__ void mainloop(float (&acc)[BN / 2], int KB, uint32_t da0, uint32_t db0, uint32_t bfull, uint32_t rel, bool rel_on,
                                         RingState& rs, int dbg) {
    uint32_t prev = rs.st ? rs.st - 1 : NST - 1;
#pragma unroll 1
    for (int kk = 0; kk < KB; kk++) {
        const uint32_t cur = rs.st;
        kblock<BN, NST>(acc, da0 + cur * (STAGE / 16), db0 + cur * (STAGE / 16), bfull, rs);
        wgmma_wait<1>();
        if (rel_on) mbar_arrive_cluster(rel + 8 * prev);
        prev = cur;
    }
    wgmma_wait<0>();
#pragma unroll
    for (int i = 0; i < BN / 2; i++) asm volatile("" : "+f"(acc[i])::"memory");
    if (rel_on) mbar_arrive_cluster(rel + 8 * prev);
}
template <int N> __device__ __forceinline__ void zero_acc(float (&acc)[N]) {
#pragma unroll
    for (int i = 0; i < N; i++) acc[i] = 0.f;
}
__device__ __forceinline__ void ldsm4(uint32_t& r0, uint32_t& r1, uint32_t& r2, uint32_t& r3, uint32_t addr) {
    asm volatile("ldmatrix.sync.aligned.m8n8.x4.shared.b16 {%0,%1,%2,%3}, [%4];" : "=r"(r0), "=r"(r1), "=r"(r2), "=r"(r3) : "r"(addr));
}

__device__ __forceinline__ void ldsm4t(uint32_t& r0, uint32_t& r1, uint32_t& r2, uint32_t& r3, uint32_t addr) {
    asm volatile("ldmatrix.sync.aligned.m8n8.x4.trans.shared.b16 {%0,%1,%2,%3}, [%4];" : "=r"(r0), "=r"(r1), "=r"(r2), "=r"(r3) : "r"(addr));
}

struct MegaMaps {
    CUtensorMap q, act;
    CUtensorMap w1, w2, w3, w4;
};

__global__ void __cluster_dims__(2, 1, 1) __launch_bounds__(384, 1)
mega_kernel(const __grid_constant__ MegaMaps tm, bf16* __restrict__ outp, bf16* act, const bf16* __restrict__ w1p, const bf16* __restrict__ w3p) {
    extern __shared__ __align__(1024) uint8_t sgen[];
    const uint32_t sbase = smem_u32(sgen);
    DT(0);
    GT(2);
    const int warp = __shfl_sync(0xffffffffu, threadIdx.x >> 5, 0), lane = threadIdx.x & 31;
    const int rank = blockIdx.x & 1;
    const uint32_t s_bar = sbase + OFF_BAR;
    const uint32_t f5 = s_bar, e5 = s_bar + 48, f4 = s_bar + 96, e4 = s_bar + 128;
    const uint32_t b_rfull = s_bar + 176, b_stg = s_bar + 184, b_h2 = s_bar + 192;
    const uint32_t s_epi = sbase + OFF_EPI, s_stg = sbase + OFF_STG5, s_r = sbase + OFF_R;

    cluster_arrive_relaxed();
    if (threadIdx.x == 256) {
        for (int i = 0; i < R5_N; i++) { mbar_init(f5 + 8 * i, 1); mbar_init(e5 + 8 * i, 4); }
        for (int i = 0; i < R4_N; i++) { mbar_init(f4 + 8 * i, 1); mbar_init(e4 + 8 * i, 4); }
        mbar_init(b_rfull, 1); mbar_init(b_stg, 8);
        mbar_arrive(f5);
        for (int i = 1; i < 4; i++) mbar_init(b_h2 + 8 * i, 1);
        for (int i = 0; i < 6; i++) reinterpret_cast<uint32_t*>(sgen + OFF_BAR + 224)[i] = 0;
        asm volatile("fence.mbarrier_init.release.cluster;" ::: "memory");
        fence_async_smem();
        prefetch_tmap(&tm.act);
    }
    uint32_t role_w = 0;
    if (threadIdx.x == 288 && rank == 0) {
        uint32_t smid;
        asm volatile("mov.u32 %0, %%smid;" : "=r"(smid));
        const int t = smid >> 1;
        int team = t < 32 ? t & 7 : t < 60 ? 1 + (t - 32) % 7 : t < 62 ? t - 54 : 0;
        int slot = atomicAdd(g_ticket + team * FL_PITCH, 1u);
        atomicAdd(g_ticket + 8 * FL_PITCH, 1u);
        if (slot >= 8) {
            const long long t0 = clock64();
            while (*(volatile unsigned int*)(g_ticket + 8 * FL_PITCH) < gridDim.x / 2 && clock64() - t0 < 100000) {}
            for (team = 0; team < 8; team++)
                if ((slot = atomicAdd(g_ticket + team * FL_PITCH, 1u)) < 8) break;
        }
        role_w = team * 8 + slot;
    }
    __syncwarp();
    cluster_wait();
    if (threadIdx.x == 288 && rank == 0) {
        asm volatile("st.shared::cluster.u32 [%0], %1;" ::"r"(mapa_u32(s_bar + 192, 0)), "r"(role_w) : "memory");
        asm volatile("st.shared::cluster.u32 [%0], %1;" ::"r"(mapa_u32(s_bar + 192, 1)), "r"(role_w) : "memory");
        asm volatile("fence.acq_rel.cluster;" ::: "memory");
    }
    __syncwarp();
    cluster_arrive_relaxed();
    cluster_wait();
    const int role = *reinterpret_cast<const volatile int*>(sgen + OFF_BAR + 192);
    if (role >= 64) return;
    const int bi = (role >> 3) * 2 + rank, bj = role & 7, m0 = bi * BM, tb = (role >> 3) * 2048 + rank * 128;
    if (threadIdx.x == 256) {
        mbar_expect_tx(b_rfull, 32768);
        tma_load_2d(s_epi, &tm.q, b_rfull, bj * 128, m0);
        tma_load_2d(s_epi + 16384, &tm.q, b_rfull, bj * 128 + 64, m0);
    }

    if (warp >= 8) {
        asm volatile("setmaxnreg.dec.sync.aligned.u32 72;");
        if (warp == 8) { if (elect_one()) {
            int s5 = 0, s4 = 0;
            uint32_t p5 = 30, p4 = 1;
            auto putB = [&](const CUtensorMap* tB, int kc, uint32_t bytes) {
                const uint32_t full = f5 + 8 * s5;
                mbar_wait(full + 48, (p5 >> s5) & 1);
                mbar_expect_tx(full, bytes);
                tma_load_2d_mc(s_r + 16384 + rank * 8192 + s5 * R5_STAGE, tB, full, bj * 128 + rank * 64, kc);
                p5 ^= 1u << s5;
            };
            auto putA = [&](int c, int r) {
                tma_load_2d(s_r + s5 * R5_STAGE, &tm.act, f5 + 8 * s5, c, r);
                if (++s5 == R5_N) s5 = 0;
            };
            pdl_wait();
            prefetch_tmap(&tm.w1); prefetch_tmap(&tm.w2); prefetch_tmap(&tm.w3); prefetch_tmap(&tm.w4);
            auto own_first = [&](int it) {
                const int hf = it >= 9, c = it - 2 - 7 * hf;
                return (it < 2 ? 2 * bj + it : 2 * (c + (c >= bj)) + hf) * BK;
            };
            const unsigned int nh = (bi == 0 || bi == 15) ? 16 : 24;
#pragma unroll 1
            for (int layer = 0; layer < 2; layer++) {
                mbar_wait(e5 + 8, (p5 >> 1) & 1);
                mbar_expect_tx(f5 + 8, 32768);
                tma_load_2d(s_r + R5_STAGE, &tm.act, f5 + 8, (bj >> 1) * 256 + rank * 128, R_Y + (tb & ~255) + (bj & 1) * 128);
                tma_load_2d(s_r + R5_STAGE + 16384, &tm.act, f5 + 8, (bj >> 1) * 256 + rank * 128 + 64, R_Y + (tb & ~255) + (bj & 1) * 128);
                p5 ^= 2;
                s5 = 2;
#pragma unroll 1
                for (int kk = 0; kk < 4; kk++) { putB(&tm.w1, own_first(kk), kk < 2 ? 16384 : R5_STAGE); if (++s5 == R5_N) s5 = 0; }
                s5 = 4;
#pragma unroll 1
                for (int kk = 2; kk < 16; kk++) {
                    const int kc = own_first(kk);
                    if (kk >= 4) putB(&tm.w1, kc, R5_STAGE);
                    if (kk == 2 || kk == 9) {
                        wait_flag(flag_ptr(layer, FL_XA + (kk & 1), bi), 8);
                        DP(8 * (FL_XA + (kk & 1)) + 3);
                        fence_proxy_async();
                        DP(8 * (FL_XA + (kk & 1)) + 4);
                    }
                    putA(kc, R_XA + tb);
                }
                mbar_wait(e5 + 24, (p5 >> 3) & 1);
                mbar_arrive(f5 + 24);
                p5 ^= 8;
                s5 = 4;
#pragma unroll 1
                for (int kk = 0; kk < 5; kk++) { putB(&tm.w2, kk * 2 * BK, R5_STAGE); if (++s5 == R5_N) s5 = 0; }
#pragma unroll 1
                for (int kk = 0; kk < 16; kk++) {
                    const int kc = ((kk & 7) * 2 + (kk >> 3)) * BK;
                    if (kk >= 5) putB(&tm.w2, kc, R5_STAGE);
                    if ((kk & 7) == 0) {
                        wait_flag(flag_ptr(layer, FL_H + (kk >> 3), bi), nh);
                        DP(8 * (FL_H + (kk >> 3)) + 3);
                        fence_proxy_async();
                        DP(8 * (FL_H + (kk >> 3)) + 4);
                    }
                    putA(kc, R_H + layer * R_HP + m0 + (int)((0x4031u >> ((kk & 6) << 1)) & 7) - 2);
                }
#pragma unroll 1
                for (int it = 0; it < 32; it++) {
                    const int kc = it >= 16 ? (it - 16) * BK : own_first(it);
                    const int nb = it < 16 ? 4 : 3, n0 = bj * 448 + (it < 16 ? 0 : 256);
                    if (it > 0 && it < 4) {
                        const int i = (it - 1) * 3 >> 1;
                        mbar_wait(e5 + 8 * i, (p5 >> i) & 1);
                        mbar_wait(e5 + 8 * i + 8, (p5 >> (i + 1)) & 1);
                    }
                    mbar_wait(e4 + 8 * s4, p4);
                    if (it >= 16 && it < 19) mbar_wait(e4 + 8 * s4 + 8, p4);
                    uint32_t sa = s_r + s4 * (it < 16 ? R4_STAGE : R4B_STAGE), full = f4 + 8 * s4;
                    mbar_expect_tx(full, (it < 2 ? 0 : 16384) + nb * 8192);
#pragma unroll 1
                    for (int j = (it ^ rank) & 1; j < nb; j += 2) tma_load_2d_mc(sa + (it < 16 ? -32768 : 16384) + j * 8192, &tm.w3, full, n0 + j * 64, kc);
                    if (it == 3 || it == 9) {
                        wait_flag(flag_ptr(layer, FL_X1 + (it >> 3), bi), 8);
                        DP(8 * (FL_X1 + (it >> 3)) + 3);
                        fence_proxy_async();
                        DP(8 * (FL_X1 + (it >> 3)) + 4);
                        if (it == 3) tma_load_2d(s_r + 2 * R4_STAGE, &tm.act, f4 + 16, own_first(2), R_X1 + tb);
                    }
                    if (it >= 3) tma_load_2d(sa, &tm.act, full, kc, R_X1 + tb);
                    if (++s4 == R4_N) { s4 = 0; p4 ^= 1; }
                }
                wait_flag(flag_ptr(layer, FL_H2, bi), 8);
                fence_proxy_async();
                s5 = 0;
#pragma unroll 1
                for (int j = 0; j < 7; j++) {
                    if (j > 0 && (j & 1) == 0) {
                        mbar_wait(b_h2 + 4 * j, layer);
                        fence_proxy_async();
                    }
                    const int ra = R_H2 + (j >> 1) * 256 + tb;
#pragma unroll 1
                    for (int b = 0; b < 8; b++) {
                        if (j == 0 && b < R4_N) mbar_wait(e4 + 8 * b, p4);
                        putB(&tm.w4, (7 * b + j) * BK, R5_STAGE);
                        putA(((j & 1) * 8 + b) * BK, ra);
                    }
                }
            }
        } } else {
            {
                const bool is1 = warp == 10;
                const int pitch = is1 ? D_ : F_, c = is1 ? bj * 128 + (lane & 15) * 8 : bj * 448 + min((warp & 2) * 128 + lane * 8, 440);
                const bf16* p = (is1 ? w1p + (lane >> 4) * 32 * D_ : w3p) + (size_t)bi * 64 * pitch + c;
                float a[8];
#pragma unroll
                for (int i = 0; i < 8; i++) a[i] = 0.f;
#pragma unroll 1
                for (int r0 = is1 ? 32 : 0; r0 < 64; r0 += 8) {
                    uint4 v[8];
#pragma unroll
                    for (int r = 0; r < 8; r++, p += pitch) v[r] = __ldg(reinterpret_cast<const uint4*>(p));
#pragma unroll
                    for (int r = 0; r < 8; r++) {
                        a[0] += lo2f(v[r].x); a[1] += hi2f(v[r].x); a[2] += lo2f(v[r].y); a[3] += hi2f(v[r].y);
                        a[4] += lo2f(v[r].z); a[5] += hi2f(v[r].z); a[6] += lo2f(v[r].w); a[7] += hi2f(v[r].w);
                    }
                }
                if (is1) {
#pragma unroll
                    for (int i = 0; i < 8; i++) a[i] += __shfl_xor_sync(0xffffffffu, a[i], 16);
                }
                float4* dst = reinterpret_cast<float4*>(g_cpart + bi * (F_ + D_) + (is1 ? F_ : 0) + c);
                dst[0] = make_float4(a[0], a[1], a[2], a[3]);
                dst[1] = make_float4(a[4], a[5], a[6], a[7]);
                asm volatile("fence.release.gpu;" ::: "memory");
                __syncwarp();
                if (lane == 0) asm volatile("red.relaxed.gpu.global.add.u32 [%0], 1;" ::"l"(flag_ptr(!is1, FL_CS, bj)) : "memory");
            }
            float4 keep[2];
            pdl_wait();
#pragma unroll 1
            for (int layer = 0; layer < 2; layer++) {
                if (warp == 10) {
#pragma unroll 1
                    for (int kind = 0; kind < 6; kind += 2) {
                        const uint32_t src = kind == FL_H ? s_stg : s_epi;
                        const int r = kind == FL_H ? R_H + layer * R_HP + m0 : (kind == FL_XA ? R_XA : R_X1) + tb;
#pragma unroll 1
                        for (int hf = 0; hf < 2; hf++) {
                            named_bar_sync(5 + hf, 288);
                            if (lane == 0) {
                                DP(8 * (kind + hf));
                                tma_store_2d(&tm.act, src + hf * 16384, bj * 128 + hf * 64, r);
                                asm volatile("cp.async.bulk.commit_group;" ::: "memory");
                                asm volatile("cp.async.bulk.wait_group 0;" ::: "memory");
                                DP(8 * (kind + hf) + 1);
                                DP(8 * (kind + hf) + 2);
                                unsigned int* fp = flag_ptr(layer, kind + hf, bi);
                                asm volatile("red.relaxed.gpu.global.add.u32 [%0], 1;" ::"l"(fp) : "memory");
                                if (kind == FL_H) {
                                    if (bi > 0) asm volatile("red.relaxed.gpu.global.add.u32 [%0], 1;" ::"l"(fp - FL_PITCH) : "memory");
                                    if (bi < 15) asm volatile("red.relaxed.gpu.global.add.u32 [%0], 1;" ::"l"(fp + FL_PITCH) : "memory");
                                }
                            }
                            __syncwarp();
                        }
                    }
                } else if (warp == 9) {
                    uint32_t* rs = reinterpret_cast<uint32_t*>(sgen + OFF_RS);
                    float* cs = reinterpret_cast<float*>(sgen + OFF_CS);
#pragma unroll 1
                    for (int which = 0; which < 2; which++) {
                        if (layer == 0) {
                            if (lane == 0) wait_flag(flag_ptr(which, FL_CS, bj), 16 << which);
                            __syncwarp();
#pragma unroll 1
                            for (int c = (which ? 384 : 768) + lane * 4; c < 896; c += 128) {
                                const float* cp = g_cpart + (which ? bj * 448 + min(c & 511, 444) : F_ + bj * 128 + lane * 4);
                                float4 a = make_float4(0.f, 0.f, 0.f, 0.f);
#pragma unroll
                                for (int r0 = 0; r0 < 16; r0 += 8) {
                                    float4 v[8];
#pragma unroll
                                    for (int r = 0; r < 8; r++) v[r] = __ldcg(reinterpret_cast<const float4*>(cp + (r0 + r) * (F_ + D_)));
#pragma unroll
                                    for (int r = 0; r < 8; r++) { a.x += v[r].x; a.y += v[r].y; a.z += v[r].z; a.w += v[r].w; }
                                }
                                if (c < 768) *reinterpret_cast<float4*>(cs + min(c & 511, 444)) = a;
                                keep[0] = a;
                            }
                        }
                        if (lane == 0 && (layer | which)) wait_flag(flag_ptr(layer, which == 0 ? FL_XA : FL_X1, bi), 8);
                        __syncwarp();
                        *reinterpret_cast<float4*>(cs + 256 + lane * 4) = keep[0];
                        { const float4 k0 = keep[0]; keep[0] = keep[1]; keep[1] = k0; }
#pragma unroll 1
                        for (int i = 0; i < 4; i++) {
                            const int r = i * 32 + lane;
                            float mean, var;
                            row_stats(g_stats + (3 * layer + 1 + which) * S_ * 8 + bi * 1024 + r, mean, var);
                            const uint32_t c0 = pack2(mean, fsqrt(bfr(bfr(var) + 1e-5f)));
                            rs[r] = c0;
                            const float rd = frcp(hi2f(c0));
                            rs[128 + r] = pack2((mean - lo2f(c0)) * rd, fsqrt(bfr(bfr(var * rd * rd) + 1e-5f)));
                        }
                        __syncwarp();
                        named_bar_arrive(3, 288);
                    }
                }
                const uint32_t s_cnt = s_bar + 224;
                auto ticket = [&](uint32_t a) {
                    uint32_t v = 0;
                    if (lane == 0) asm volatile("atom.acq_rel.cta.shared.add.u32 %0, [%1], 1;" : "=r"(v) : "r"(a) : "memory");
                    return v;
                };
                mbar_wait(b_stg, 0);
                int u = __shfl_sync(0xffffffffu, ticket(s_cnt + 16 + 4 * layer), 0), step = 0;
#pragma unroll 1
                while (true) {
#pragma unroll 1
                    for (; step < 5 && u >= (int)((0x3830201810ull >> (8 * step)) & 255); step++) {
                        if (step == 1) { named_bar_arrive(4, 352); continue; }
                        const int part = step ? step - 1 : 0;
                        __syncwarp();
                        if (ticket(s_cnt + 4 * part) == 3 * layer + 2) {
                            asm volatile("fence.release.gpu;" ::: "memory");
                            unsigned int* fp = flag_ptr(layer, FL_H2 + part, bi);
                            asm volatile("red.relaxed.gpu.global.add.u32 [%0], 1;" ::"l"(fp) : "memory");
                            if (part > 0) { wait_flag(fp, 8); mbar_arrive(b_h2 + 8 * part); }
                        }
                        __syncwarp();
                        if (step == 2) mbar_wait(b_stg, 1);
                    }
                    if (u >= 56) break;
                    const uint32_t un = ticket(s_cnt + 16 + 4 * layer);
                    const int job = u >> 3, r = (u & 7) * 16 + (lane >> 3);
                    const uint32_t sp = sbase + ((job & 2) ? OFF_STG5 : OFF_EPI) + r * 256 + (job & 1) * 128;
                    bf16* gp = act + (size_t)(R_H2 + (job >> 1) * 256 + tb + r) * D_ + ((job & 1) * 8 + bj) * 64 + (lane & 7) * 8;
                    uint4 v[4];
#pragma unroll
                    for (int e = 0; e < 4; e++) v[e] = lds128(sp + e * 1024 + (((lane & 7) ^ ((r + 4 * e) & 7)) << 4));
#pragma unroll
                    for (int e = 0; e < 4; e++) stg128(gp + 4 * e * D_, gelu8h(v[e]));
                    u = __shfl_sync(0xffffffffu, un, 0);
                }
                if (layer == 0 && warp == 11) {
                    const char* ps = reinterpret_cast<const char*>(g_stats + 3 * S_ * 8 + bi * 1024) + lane * 128;
                    const char* py = reinterpret_cast<const char*>(act + (size_t)(R_Y + (tb & ~255) + (bj & 1) * 128 + (lane >> 1)) * D_ + (bj >> 1) * 256 + rank * 128) + (lane & 1) * 128;
#pragma unroll 1
                    for (int i = 0; i < 8; i++) {
                        asm volatile("prefetch.global.L2 [%0];" ::"l"(py + (size_t)i * 16 * D_ * 2) : "memory");
                        if (i >= 6) asm volatile("prefetch.global.L2 [%0];" ::"l"(ps + (i & 1) * 4096) : "memory");
                        __nanosleep(400);
                    }
                }
            }
        }
        __syncwarp();
        asm volatile("barrier.cluster.arrive.relaxed.aligned;\nbarrier.cluster.wait.acquire.aligned; // helpers" ::: "memory");
    } else {
        asm volatile("setmaxnreg.inc.sync.aligned.u32 216;");
        const int tid = threadIdx.x;
        const int wg = warp >> 2;
        const bool rel_on = (tid & 95) == 0;
        const uint32_t rel5 = mapa_u32(e5, (warp & 1) ^ rank), rel4 = rel5 + (e4 - e5);
        const uint32_t da0 = desc_a(s_r + wg * 8192), db0 = desc_b(s_r + BM * BK * 2), dae = da0 + (OFF_EPI - OFF_R) / 16, db4 = db0 - 49152 / 16;
        auto skip5 = [&](RingState& rs) {
            if (rel_on) mbar_arrive_cluster(rel5 + 8 * rs.st);
            rs.st++;
        };
        const int t = lane & 3;
        const int row = warp * 16 + (lane >> 2);
        const uint32_t st_w = (uint32_t)((warp * 16 + ((lane >> 3) & 1) * 8 + (lane & 7)) * 256 + (((lane >> 4) ^ (lane & 7)) << 4));
        const uint32_t fr = (uint32_t)((warp * 16 + ((lane >> 3) & 1) * 8 + (lane & 7)) * 128 + (((lane >> 4) ^ (lane & 7)) << 4));
        auto copy_out = [&](bf16* dst, uint32_t src) {
            const int r = warp * 16 + (lane >> 4);
            bf16* ox = dst + (size_t)(m0 + r) * D_ + bj * 128 + (lane & 15) * 8;
            const uint32_t ra = src + ((lane & 15) >> 3) * 16384 + r * 128;
            uint4 v[8];
#pragma unroll
            for (int it = 0; it < 8; it++) v[it] = lds128(ra + it * 256 + (((lane & 7) ^ ((2 * it + (lane >> 4)) & 7)) << 4));
#pragma unroll
            for (int it = 0; it < 8; it++) *reinterpret_cast<uint4*>(ox + (size_t)it * 2 * D_) = v[it];
        };
        auto put_stats = [&](const uint32_t (&w)[32], int which) {
            float sm[2] = {0.f, 0.f}, sq[2] = {0.f, 0.f};
#pragma unroll
            for (int e = 0; e < 32; e++) {
                const float e0 = lo2f(w[e]), e1 = hi2f(w[e]);
                sm[e & 1] += e0 + e1; sq[e & 1] = fmaf(e0, e0, fmaf(e1, e1, sq[e & 1]));
            }
#pragma unroll
            for (int of = 1; of < 4; of <<= 1)
#pragma unroll
                for (int e = 0; e < 2; e++) { sm[e] += __shfl_xor_sync(0xffffffffu, sm[e], of); sq[e] += __shfl_xor_sync(0xffffffffu, sq[e], of); }
            if (t < 2) {
                const float s1 = t ? sm[1] : sm[0], q1 = t ? sq[1] : sq[0], mu = s1 * (1.0f / 128);
                asm volatile("{\n.reg .b64 t;\nmov.b64 t, {%1, %2};\nst.relaxed.gpu.global.b64 [%0], t;\n}"
                             ::"l"(g_stats + which * S_ * 8 + (bi * 8 + bj) * 128 + row + 8 * t), "f"(mu), "f"(fmaxf(q1 - s1 * mu, 0.f)) : "memory");
            }
        };
        const float* csp = reinterpret_cast<const float*>(sgen + OFF_CS) + 2 * t;
        float mrow[2], rrow[2];
        const uint32_t* rsp = reinterpret_cast<const uint32_t*>(sgen + OFF_RS) + row;
        auto row_consts = [&](bool twice) {
#pragma unroll
            for (int e = 0; e < 2; e++) {
                const uint32_t q0 = rsp[8 * e], q1 = rsp[128 + 8 * e];
                mrow[e] = twice ? fmaf(lo2f(q1), hi2f(q0), lo2f(q0)) : lo2f(q0);
                rrow[e] = 0.5f * frcp(twice ? hi2f(q0) * hi2f(q1) : hi2f(q0));
            }
        };
        auto stage = [&](const float* acc, uint32_t dst, int j0, float2 (&cs)[8], const float* cnext) {
            float2 cn[8];
#pragma unroll
            for (int e = 0; e < 8; e++) cn[e] = *reinterpret_cast<const float2*>(cnext + 8 * e);
#pragma unroll
            for (int j = 0; j < 8; j += 2) {
                uint32_t w[4];
#pragma unroll
                for (int e = 0; e < 2; e++) {
                    const float* a = acc + 4 * (j + e);
                    w[2 * e] = pack2(fmaf(-mrow[0], cs[j + e].x, a[0]) * rrow[0], fmaf(-mrow[0], cs[j + e].y, a[1]) * rrow[0]);
                    w[2 * e + 1] = pack2(fmaf(-mrow[1], cs[j + e].x, a[2]) * rrow[1], fmaf(-mrow[1], cs[j + e].y, a[3]) * rrow[1]);
                }
                stsm4((dst + st_w) ^ (((j0 + j) & 15) << 4), w[0], w[1], w[2], w[3]);
            }
#pragma unroll
            for (int e = 0; e < 8; e++) cs[e] = cn[e];
        };
        RingState r5{0, 0}, r4{0, 0};
        skip5(r5);
        DT(1);
        uint32_t x[32];
        mbar_wait(b_rfull, 0);
#pragma unroll
        for (int jp = 0; jp < 8; jp++) ldsm4(x[4 * jp], x[4 * jp + 1], x[4 * jp + 2], x[4 * jp + 3], s_epi + (fr ^ ((jp & 3) << 5)) + (jp >> 2) * 16384);
#pragma unroll 1
        for (int layer = 0; layer < 2; layer++) {
            {
                DT(2 + 24 * layer);
                put_stats(x, 3 * layer);
                DT(20 + 24 * layer);
                DT(22 + 24 * layer);
                uint32_t mb[2];
                float rd[2];
                {
                    float mean, var;
                    row_stats(g_stats + 3 * layer * S_ * 8 + bi * 1024 + warp * 16 + (lane & 15), mean, var);
                    __syncwarp();
                    const float r1 = frcp(bfr(fsqrt(bfr(bfr(var) + 1e-5f))));
                    const uint32_t m1 = pack2(mean, mean);
#pragma unroll
                    for (int e = 0; e < 2; e++) { mb[e] = __shfl_sync(0xffffffffu, m1, (lane >> 2) + 8 * e); rd[e] = __shfl_sync(0xffffffffu, r1, (lane >> 2) + 8 * e); }
                }
                DT(21 + 24 * layer);
                mbar_wait(f5 + 8, r5.ph);
                if (layer == 0) GT(3);
                const uint32_t ya = s_r + R5_STAGE + wg * 16384 + ((lane >> 4) * 8 + (lane & 7)) * 128 + ((((warp & 3) * 2 + ((lane >> 3) & 1)) ^ (lane & 7)) << 4);
                uint32_t y[16];
#pragma unroll
                for (int e = 0; e < 32; e++) {
                    if ((e & 15) == 0) {
#pragma unroll
                        for (int jp = 0; jp < 4; jp++) ldsm4t(y[4 * jp], y[4 * jp + 1], y[4 * jp + 2], y[4 * jp + 3], ya + jp * 2048 + e * 512);
                    }
                    const uint32_t d = bsub2(x[e], mb[e & 1]);
                    x[e] = badd2(x[e], bmul2(pack2(lo2f(d) * rd[e & 1], hi2f(d) * rd[e & 1]), y[e & 15]));
                    if ((e & 3) == 3) stsm4(s_epi + (fr ^ (((e >> 2) & 3) << 5)) + (e >> 4) * 16384, x[e - 3], x[e - 2], x[e - 1], x[e]);
                    if ((e & 15) == 15) { fence_async_smem(); named_bar_arrive(5 + (e >> 4), 288); }
                }
                DT(19 + 24 * layer);
                named_bar_sync(9 + wg, 128);
                skip5(r5);
                DT(3 + 24 * layer);
            }
            {
                float acc[64];
                zero_acc(acc);
                kblock<128, R5_N>(acc, dae, db0 + 2 * (R5_STAGE / 16), f5, r5);
                kblock<128, R5_N>(acc, dae + 1024, db0 + 3 * (R5_STAGE / 16), f5, r5);
                put_stats(x, 3 * layer + 1);
                wgmma_wait<1>();
                if (rel_on) mbar_arrive_cluster(rel5 + 16);
                mainloop<128, R5_N, R5_STAGE>(acc, 14, da0, db0, f5, rel5, rel_on, r5, 15 + 24 * layer);
                DT(4 + 24 * layer);
                named_bar_sync(3, 288);
                row_consts(true);
                float2 cs[8];
#pragma unroll
                for (int j = 0; j < 16; j += 2) {
                    if ((j & 7) == 0) {
#pragma unroll
                        for (int e = 0; e < 8; e++) cs[e] = *reinterpret_cast<const float2*>(csp + 256 + 8 * (j + e));
                    }
                    uint32_t w[4];
#pragma unroll
                    for (int e = 0; e < 4; e++) {
                        const float* a = acc + 4 * j + 2 * e;
                        const float2 c = cs[(j & 7) + (e >> 1)];
                        w[e] = pack2(gelu_tanh_h(fmaf(-mrow[e & 1], c.x, a[0]) * rrow[e & 1]), gelu_tanh_h(fmaf(-mrow[e & 1], c.y, a[1]) * rrow[e & 1]));
                    }
                    stsm4(s_stg + (fr ^ ((j & 7) << 4)) + (j >> 3) * 16384, w[0], w[1], w[2], w[3]);
                    if ((j & 7) == 6) { fence_async_smem(); named_bar_arrive(5 + (j >> 3), 288); }
                }
                DT(5 + 24 * layer);
            }
            {
                float acc[64];
                zero_acc(acc);
                uint32_t u[32];
                {
                    uint32_t mb[2];
                    float rd[2];
#pragma unroll
                    for (int e = 0; e < 2; e++) { const uint32_t q0 = rsp[8 * e]; mb[e] = (q0 & 0xffffu) * 0x10001u; rd[e] = frcp(hi2f(q0)); }
#pragma unroll
                    for (int e = 0; e < 32; e++) {
                        const uint32_t d = bsub2(x[e], mb[e & 1]);
                        u[e] = pack2(lo2f(d) * rd[e & 1], hi2f(d) * rd[e & 1]);
                        asm volatile("" : "+r"(u[e]));
                    }
                }
                mbar_wait(f5 + 24, r5.ph);
                skip5(r5);
                kblock<128, R5_N>(acc, da0 + 4 * (R5_STAGE / 16), db0 + 4 * (R5_STAGE / 16), f5, r5);
                DT(16 + 24 * layer);
                mainloop<128, R5_N, R5_STAGE>(acc, 15, da0, db0, f5, rel5, rel_on, r5, -1);
                DT(6 + 24 * layer);
#pragma unroll
                for (int j = 0; j < 16; j += 2) {
#pragma unroll
                    for (int e = 0; e < 4; e++) u[2 * j + e] = badd2(u[2 * j + e], pack2(acc[4 * j + 2 * e], acc[4 * j + 2 * e + 1]));
                    stsm4(s_epi + (fr ^ ((j & 7) << 4)) + (j >> 3) * 16384, u[2 * j], u[2 * j + 1], u[2 * j + 2], u[2 * j + 3]);
                    if ((j & 7) == 6) { fence_async_smem(); named_bar_arrive(5 + (j >> 3), 288); }
                }
#pragma unroll
                for (int e = 0; e < 32; e++) x[e] = badd2(x[e], u[e]);
                named_bar_sync(9 + wg, 128);
                DT(7 + 24 * layer);
                if (layer == 0) GT(7);
            }
            {
                float2 cs[8];
                {
                    float acc[128];
                    zero_acc(acc);
                    kblock<256, R4_N>(acc, dae, db4, f4, r4);
                    kblock<256, R4_N>(acc, dae + 1024, db4 + R4_STAGE / 16, f4, r4);
                    {
                        uint32_t w[32];
#pragma unroll
                        for (int jp = 0; jp < 8; jp++) ldsm4(w[4 * jp], w[4 * jp + 1], w[4 * jp + 2], w[4 * jp + 3], s_epi + (fr ^ ((jp & 3) << 5)) + (jp >> 2) * 16384);
                        put_stats(w, 3 * layer + 2);
                    }
                    wgmma_wait<1>();
                    if (rel_on) mbar_arrive_cluster(rel4);
                    mainloop<256, R4_N, R4_STAGE>(acc, 14, da0, db4, f4, rel4, rel_on, r4, 17 + 24 * layer);
                    DT(8 + 24 * layer);
                    named_bar_sync(3, 288);
                    row_consts(false);
#pragma unroll
                    for (int e = 0; e < 8; e++) cs[e] = *reinterpret_cast<const float2*>(csp + 8 * e);
#pragma unroll
                    for (int j = 0; j < 32; j += 8) stage(acc + 4 * j, j < 16 ? s_epi : s_stg, j, cs, csp + 8 * (j + 8));
                    __syncwarp();
                if (lane == 0) mbar_arrive(b_stg);
                }
                DT(9 + 24 * layer);
                float acc[96];
                zero_acc(acc);
                kblock<192, R4_N>(acc, da0, db0, f4, r4);
                mainloop<192, R4_N, R4B_STAGE>(acc, 15, da0, db0, f4, rel4, rel_on, r4, -1);
                DT(10 + 24 * layer);
                named_bar_sync(4, 352);
#pragma unroll
                for (int j = 0; j < 24; j += 8) stage(acc + 4 * j, j < 16 ? s_epi : s_stg, j, cs, csp + 256 + 8 * (j < 16 ? j + 8 : 0));
                __syncwarp();
                if (lane == 0) mbar_arrive(b_stg);
                DT(11 + 24 * layer);
            }
            {
                float acc[64];
#pragma unroll
                for (int i = 0; i < 32; i++) asm volatile("shl.b32 %0, %2, 16;\nand.b32 %1, %2, 0xffff0000;" : "=f"(acc[2 * i]), "=f"(acc[2 * i + 1]) : "r"(x[i]));
                kblock<128, R5_N>(acc, da0, db0, f5, r5);
                DT(18 + 24 * layer);
                mainloop<128, R5_N, R5_STAGE>(acc, 55, da0, db0, f5, rel5, rel_on, r5, 62 - 40 * (layer ^ 1));
                DT(12 + 24 * layer);
#pragma unroll
                for (int i = 0; i < 32; i++) x[i] = pack2(acc[2 * i], acc[2 * i + 1]);
                DT(13 + 24 * layer);
                if (layer == 0) GT(6);
                DT(14 + 24 * layer);
            }
        }
#pragma unroll
        for (int jp = 0; jp < 8; jp++) stsm4(s_epi + (fr ^ ((jp & 3) << 5)) + (jp >> 2) * 16384, x[4 * jp], x[4 * jp + 1], x[4 * jp + 2], x[4 * jp + 3]);
        __syncwarp();
        copy_out(outp, s_epi);
        DT(38);
        GT(4);
        cluster_arrive_relaxed();
        cluster_wait();
    }
}

#define DBG_S(i)
#define DBG_OUT(r, o)
#define DBG_F(i)
#define DBG_W(i)
constexpr int CV_CH = 8;
constexpr int CV_SL = 16384;
constexpr int CV_QG = 128 * 8 + 16;
constexpr int CV_HPL = 2048 + 192;
constexpr int CV_X = -32768, CV_H = 9 * CV_SL, CV_BAR = CV_H + CV_CH * 2 * CV_HPL;
constexpr int CV_SMEM = CV_BAR + 448 - CV_X;

template <int K> __device__ __forceinline__ void cv_mma(float (&d)[64], const uint32_t (&a)[4], uint32_t db, int acc);
template <> __device__ __forceinline__ void cv_mma<0>(float (&d)[64], const uint32_t (&a)[4], uint32_t db, int acc) {
    asm volatile("{\n.reg .pred p;\n.reg .b64 b;\nsetp.ne.b32 p, %70, 0;\nmov.b64 b, {%68, %69};\n"
        "wgmma.mma_async.sync.aligned.m64n128k16.f32.bf16.bf16 {%0,%1,%2,%3,%4,%5,%6,%7,%8,%9,%10,%11,%12,%13,%14,%15,%16,%17,%18,%19,%20,%21,%22,%23,%24,%25,%26,%27,%28,%29,%30,%31,%32,%33,%34,%35,%36,%37,%38,%39,%40,%41,%42,%43,%44,%45,%46,%47,%48,%49,%50,%51,%52,%53,%54,%55,%56,%57,%58,%59,%60,%61,%62,%63}, {%64,%65,%66,%67}, b, p, 1, 1, 0;\n}\n"
        : "+f"(d[0]), "+f"(d[1]), "+f"(d[2]), "+f"(d[3]), "+f"(d[4]), "+f"(d[5]), "+f"(d[6]), "+f"(d[7]), "+f"(d[8]), "+f"(d[9]), "+f"(d[10]), "+f"(d[11]), "+f"(d[12]), "+f"(d[13]), "+f"(d[14]), "+f"(d[15]), "+f"(d[16]), "+f"(d[17]), "+f"(d[18]), "+f"(d[19]), "+f"(d[20]), "+f"(d[21]), "+f"(d[22]), "+f"(d[23]), "+f"(d[24]), "+f"(d[25]), "+f"(d[26]), "+f"(d[27]), "+f"(d[28]), "+f"(d[29]), "+f"(d[30]), "+f"(d[31]), "+f"(d[32]), "+f"(d[33]), "+f"(d[34]), "+f"(d[35]), "+f"(d[36]), "+f"(d[37]), "+f"(d[38]), "+f"(d[39]), "+f"(d[40]), "+f"(d[41]), "+f"(d[42]), "+f"(d[43]), "+f"(d[44]), "+f"(d[45]), "+f"(d[46]), "+f"(d[47]), "+f"(d[48]), "+f"(d[49]), "+f"(d[50]), "+f"(d[51]), "+f"(d[52]), "+f"(d[53]), "+f"(d[54]), "+f"(d[55]), "+f"(d[56]), "+f"(d[57]), "+f"(d[58]), "+f"(d[59]), "+f"(d[60]), "+f"(d[61]), "+f"(d[62]), "+f"(d[63])
        : "r"(a[0]), "r"(a[1]), "r"(a[2]), "r"(a[3]), "r"(db), "r"(8u), "r"(acc));
}
template <> __device__ __forceinline__ void cv_mma<1>(float (&d)[64], const uint32_t (&a)[4], uint32_t db, int acc) {
    asm volatile("{\n.reg .pred p;\n.reg .b64 b;\nsetp.ne.b32 p, %62, 0;\nmov.b64 b, {%60, %61};\n"
        "wgmma.mma_async.sync.aligned.m64n112k16.f32.bf16.bf16 {%0,%1,%2,%3,%4,%5,%6,%7,%8,%9,%10,%11,%12,%13,%14,%15,%16,%17,%18,%19,%20,%21,%22,%23,%24,%25,%26,%27,%28,%29,%30,%31,%32,%33,%34,%35,%36,%37,%38,%39,%40,%41,%42,%43,%44,%45,%46,%47,%48,%49,%50,%51,%52,%53,%54,%55}, {%56,%57,%58,%59}, b, p, 1, 1, 0;\n}\n"
        : "+f"(d[0]), "+f"(d[1]), "+f"(d[2]), "+f"(d[3]), "+f"(d[4]), "+f"(d[5]), "+f"(d[6]), "+f"(d[7]), "+f"(d[8]), "+f"(d[9]), "+f"(d[10]), "+f"(d[11]), "+f"(d[12]), "+f"(d[13]), "+f"(d[14]), "+f"(d[15]), "+f"(d[16]), "+f"(d[17]), "+f"(d[18]), "+f"(d[19]), "+f"(d[20]), "+f"(d[21]), "+f"(d[22]), "+f"(d[23]), "+f"(d[24]), "+f"(d[25]), "+f"(d[26]), "+f"(d[27]), "+f"(d[28]), "+f"(d[29]), "+f"(d[30]), "+f"(d[31]), "+f"(d[32]), "+f"(d[33]), "+f"(d[34]), "+f"(d[35]), "+f"(d[36]), "+f"(d[37]), "+f"(d[38]), "+f"(d[39]), "+f"(d[40]), "+f"(d[41]), "+f"(d[42]), "+f"(d[43]), "+f"(d[44]), "+f"(d[45]), "+f"(d[46]), "+f"(d[47]), "+f"(d[48]), "+f"(d[49]), "+f"(d[50]), "+f"(d[51]), "+f"(d[52]), "+f"(d[53]), "+f"(d[54]), "+f"(d[55])
        : "r"(a[0]), "r"(a[1]), "r"(a[2]), "r"(a[3]), "r"(db), "r"(8u), "r"(acc));
}
template <> __device__ __forceinline__ void cv_mma<2>(float (&d)[64], const uint32_t (&a)[4], uint32_t db, int acc) {
    asm volatile("{\n.reg .pred p;\n.reg .b64 b;\nsetp.ne.b32 p, %54, 0;\nmov.b64 b, {%52, %53};\n"
        "wgmma.mma_async.sync.aligned.m64n96k16.f32.bf16.bf16 {%0,%1,%2,%3,%4,%5,%6,%7,%8,%9,%10,%11,%12,%13,%14,%15,%16,%17,%18,%19,%20,%21,%22,%23,%24,%25,%26,%27,%28,%29,%30,%31,%32,%33,%34,%35,%36,%37,%38,%39,%40,%41,%42,%43,%44,%45,%46,%47}, {%48,%49,%50,%51}, b, p, 1, 1, 0;\n}\n"
        : "+f"(d[0]), "+f"(d[1]), "+f"(d[2]), "+f"(d[3]), "+f"(d[4]), "+f"(d[5]), "+f"(d[6]), "+f"(d[7]), "+f"(d[8]), "+f"(d[9]), "+f"(d[10]), "+f"(d[11]), "+f"(d[12]), "+f"(d[13]), "+f"(d[14]), "+f"(d[15]), "+f"(d[16]), "+f"(d[17]), "+f"(d[18]), "+f"(d[19]), "+f"(d[20]), "+f"(d[21]), "+f"(d[22]), "+f"(d[23]), "+f"(d[24]), "+f"(d[25]), "+f"(d[26]), "+f"(d[27]), "+f"(d[28]), "+f"(d[29]), "+f"(d[30]), "+f"(d[31]), "+f"(d[32]), "+f"(d[33]), "+f"(d[34]), "+f"(d[35]), "+f"(d[36]), "+f"(d[37]), "+f"(d[38]), "+f"(d[39]), "+f"(d[40]), "+f"(d[41]), "+f"(d[42]), "+f"(d[43]), "+f"(d[44]), "+f"(d[45]), "+f"(d[46]), "+f"(d[47])
        : "r"(a[0]), "r"(a[1]), "r"(a[2]), "r"(a[3]), "r"(db), "r"(8u), "r"(acc));
}
template <> __device__ __forceinline__ void cv_mma<3>(float (&d)[64], const uint32_t (&a)[4], uint32_t db, int acc) {
    asm volatile("{\n.reg .pred p;\n.reg .b64 b;\nsetp.ne.b32 p, %46, 0;\nmov.b64 b, {%44, %45};\n"
        "wgmma.mma_async.sync.aligned.m64n80k16.f32.bf16.bf16 {%0,%1,%2,%3,%4,%5,%6,%7,%8,%9,%10,%11,%12,%13,%14,%15,%16,%17,%18,%19,%20,%21,%22,%23,%24,%25,%26,%27,%28,%29,%30,%31,%32,%33,%34,%35,%36,%37,%38,%39}, {%40,%41,%42,%43}, b, p, 1, 1, 0;\n}\n"
        : "+f"(d[0]), "+f"(d[1]), "+f"(d[2]), "+f"(d[3]), "+f"(d[4]), "+f"(d[5]), "+f"(d[6]), "+f"(d[7]), "+f"(d[8]), "+f"(d[9]), "+f"(d[10]), "+f"(d[11]), "+f"(d[12]), "+f"(d[13]), "+f"(d[14]), "+f"(d[15]), "+f"(d[16]), "+f"(d[17]), "+f"(d[18]), "+f"(d[19]), "+f"(d[20]), "+f"(d[21]), "+f"(d[22]), "+f"(d[23]), "+f"(d[24]), "+f"(d[25]), "+f"(d[26]), "+f"(d[27]), "+f"(d[28]), "+f"(d[29]), "+f"(d[30]), "+f"(d[31]), "+f"(d[32]), "+f"(d[33]), "+f"(d[34]), "+f"(d[35]), "+f"(d[36]), "+f"(d[37]), "+f"(d[38]), "+f"(d[39])
        : "r"(a[0]), "r"(a[1]), "r"(a[2]), "r"(a[3]), "r"(db), "r"(8u), "r"(acc));
}
template <> __device__ __forceinline__ void cv_mma<4>(float (&d)[64], const uint32_t (&a)[4], uint32_t db, int acc) {
    asm volatile("{\n.reg .pred p;\n.reg .b64 b;\nsetp.ne.b32 p, %38, 0;\nmov.b64 b, {%36, %37};\n"
        "wgmma.mma_async.sync.aligned.m64n64k16.f32.bf16.bf16 {%0,%1,%2,%3,%4,%5,%6,%7,%8,%9,%10,%11,%12,%13,%14,%15,%16,%17,%18,%19,%20,%21,%22,%23,%24,%25,%26,%27,%28,%29,%30,%31}, {%32,%33,%34,%35}, b, p, 1, 1, 0;\n}\n"
        : "+f"(d[0]), "+f"(d[1]), "+f"(d[2]), "+f"(d[3]), "+f"(d[4]), "+f"(d[5]), "+f"(d[6]), "+f"(d[7]), "+f"(d[8]), "+f"(d[9]), "+f"(d[10]), "+f"(d[11]), "+f"(d[12]), "+f"(d[13]), "+f"(d[14]), "+f"(d[15]), "+f"(d[16]), "+f"(d[17]), "+f"(d[18]), "+f"(d[19]), "+f"(d[20]), "+f"(d[21]), "+f"(d[22]), "+f"(d[23]), "+f"(d[24]), "+f"(d[25]), "+f"(d[26]), "+f"(d[27]), "+f"(d[28]), "+f"(d[29]), "+f"(d[30]), "+f"(d[31])
        : "r"(a[0]), "r"(a[1]), "r"(a[2]), "r"(a[3]), "r"(db), "r"(8u), "r"(acc));
}
template <> __device__ __forceinline__ void cv_mma<5>(float (&d)[64], const uint32_t (&a)[4], uint32_t db, int acc) {
    asm volatile("{\n.reg .pred p;\n.reg .b64 b;\nsetp.ne.b32 p, %30, 0;\nmov.b64 b, {%28, %29};\n"
        "wgmma.mma_async.sync.aligned.m64n48k16.f32.bf16.bf16 {%0,%1,%2,%3,%4,%5,%6,%7,%8,%9,%10,%11,%12,%13,%14,%15,%16,%17,%18,%19,%20,%21,%22,%23}, {%24,%25,%26,%27}, b, p, 1, 1, 0;\n}\n"
        : "+f"(d[0]), "+f"(d[1]), "+f"(d[2]), "+f"(d[3]), "+f"(d[4]), "+f"(d[5]), "+f"(d[6]), "+f"(d[7]), "+f"(d[8]), "+f"(d[9]), "+f"(d[10]), "+f"(d[11]), "+f"(d[12]), "+f"(d[13]), "+f"(d[14]), "+f"(d[15]), "+f"(d[16]), "+f"(d[17]), "+f"(d[18]), "+f"(d[19]), "+f"(d[20]), "+f"(d[21]), "+f"(d[22]), "+f"(d[23])
        : "r"(a[0]), "r"(a[1]), "r"(a[2]), "r"(a[3]), "r"(db), "r"(8u), "r"(acc));
}
template <> __device__ __forceinline__ void cv_mma<6>(float (&d)[64], const uint32_t (&a)[4], uint32_t db, int acc) {
    asm volatile("{\n.reg .pred p;\n.reg .b64 b;\nsetp.ne.b32 p, %22, 0;\nmov.b64 b, {%20, %21};\n"
        "wgmma.mma_async.sync.aligned.m64n32k16.f32.bf16.bf16 {%0,%1,%2,%3,%4,%5,%6,%7,%8,%9,%10,%11,%12,%13,%14,%15}, {%16,%17,%18,%19}, b, p, 1, 1, 0;\n}\n"
        : "+f"(d[0]), "+f"(d[1]), "+f"(d[2]), "+f"(d[3]), "+f"(d[4]), "+f"(d[5]), "+f"(d[6]), "+f"(d[7]), "+f"(d[8]), "+f"(d[9]), "+f"(d[10]), "+f"(d[11]), "+f"(d[12]), "+f"(d[13]), "+f"(d[14]), "+f"(d[15])
        : "r"(a[0]), "r"(a[1]), "r"(a[2]), "r"(a[3]), "r"(db), "r"(8u), "r"(acc));
}
template <> __device__ __forceinline__ void cv_mma<7>(float (&d)[64], const uint32_t (&a)[4], uint32_t db, int acc) {
    asm volatile("{\n.reg .pred p;\n.reg .b64 b;\nsetp.ne.b32 p, %14, 0;\nmov.b64 b, {%12, %13};\n"
        "wgmma.mma_async.sync.aligned.m64n16k16.f32.bf16.bf16 {%0,%1,%2,%3,%4,%5,%6,%7}, {%8,%9,%10,%11}, b, p, 1, 1, 0;\n}\n"
        : "+f"(d[0]), "+f"(d[1]), "+f"(d[2]), "+f"(d[3]), "+f"(d[4]), "+f"(d[5]), "+f"(d[6]), "+f"(d[7])
        : "r"(a[0]), "r"(a[1]), "r"(a[2]), "r"(a[3]), "r"(db), "r"(8u), "r"(acc));
}
__device__ __forceinline__ void stsm4t(uint32_t addr, uint32_t r0, uint32_t r1, uint32_t r2, uint32_t r3) {
    asm volatile("stmatrix.sync.aligned.m8n8.x4.trans.shared.b16 [%0], {%1,%2,%3,%4};" ::"r"(addr), "r"(r0), "r"(r1), "r"(r2), "r"(r3) : "memory");
}
__device__ __forceinline__ void cp16(uint32_t dst, const void* src, int n = 16) {
    asm volatile("cp.async.cg.shared.global.L2::128B [%0], [%1], 16, %2;" ::"r"(dst), "l"(src), "r"(n) : "memory");
}
__device__ __forceinline__ void cp_arrive(uint32_t bar) { asm volatile("cp.async.mbarrier.arrive.noinc.shared::cta.b64 [%0];" ::"r"(bar) : "memory"); }
__device__ __forceinline__ void lds64(uint32_t& x, uint32_t& y, uint32_t a) { asm volatile("ld.shared.v2.b32 {%0,%1}, [%2];" : "=r"(x), "=r"(y) : "r"(a) : "memory"); }
__device__ __forceinline__ void sts128(uint32_t a, uint32_t x, uint32_t y, uint32_t z, uint32_t w) {
    asm volatile("st.shared.v4.b32 [%0], {%1,%2,%3,%4};" ::"r"(a), "r"(x), "r"(y), "r"(z), "r"(w) : "memory");
}
__device__ __forceinline__ uint32_t bfma2(uint32_t a, uint32_t b, uint32_t c) {
    uint32_t r;
    asm("fma.rn.bf16x2 %0, %1, %2, %3;" : "=r"(r) : "r"(a), "r"(b), "r"(c));
    return r;
}
#define CV_NS 4
#define CV_W 1
constexpr int CV_GC = 8 / CV_NS, CV_NA = (CV_W + 2) * CV_NS;
struct CvAddr { uint32_t pa[2], p0[4], db, rdy, xw, xr, bar; bool wrap, neg[2]; };
template <int G> __device__ __forceinline__ void cv_load(uint32_t (&a)[CV_NA][4], const CvAddr& p) {
    if constexpr (G % CV_GC == 0) mbar_wait(p.rdy + 8 * (G / CV_GC), 0);
#pragma unroll
    for (int i = G * CV_NS; i < (G + 1) * CV_NS; i++) {
        const int of = (i / 2 % 2) * CV_QG + (i / 8) * CV_SL + 256 * (i % 2 + (i / 2 & 2));
        if ((i & 5) == 0) {
#pragma unroll
            for (int e = 0; e < 4; e++) asm volatile("ld.shared.b32 %0, [%1];" : "=r"(a[i % CV_NA][e]) : "r"(p.p0[e] + of) : "memory");
            if (i < 8) { if (p.neg[0]) a[i % CV_NA][0] = 0; if (p.neg[1]) a[i % CV_NA][2] = 0; }
        } else {
            lds64(a[i % CV_NA][0], a[i % CV_NA][1], p.pa[0] + of - 256);
            lds64(a[i % CV_NA][2], a[i % CV_NA][3], p.pa[1] + of - 256);
        }
    }
}
__device__ __forceinline__ float vadd(float a, float b) {
    float r;
    asm volatile("add.f32 %0, %1, %2;" : "=f"(r) : "f"(a), "f"(b));
    return r;
}
template <int K> __device__ __forceinline__ uint32_t cv_tail(float (&d)[64], bool wrap) {
    float* z = d + 56 - 8 * K;
    z[4] = vadd(z[4], K > 0 ? z[10] : 0.f);
    if constexpr (K > 0) z[5] = vadd(z[5], z[11]);
    z[0] = vadd(z[0], z[6]);
    z[1] = vadd(z[1], z[7]);
    return pack2(wrap ? (K > 0 ? z[8] : 0.f) : z[4], wrap ? z[4] : z[0]);
}
template <int K> __device__ __forceinline__ uint32_t cv_fin(const float (&d)[64], uint32_t x) { return pack2(d[61 - 8 * K] + lo2f(x), d[57 - 8 * K] + hi2f(x)); }
template <int G>
__device__ __forceinline__ void cv_steps(float (&d)[2][64], uint32_t (&a)[CV_NA][4], uint32_t (&tv)[2][8], const CvAddr& p) {
    constexpr int K = G / CV_GC, GN = 8 * CV_GC;
    constexpr int T = G - CV_W - CV_GC, F = T - 1, TK = T / CV_GC, FK = F / CV_GC;
    if constexpr (G == 0) cv_load<0>(a, p);
    if constexpr (G < GN) {
        wgmma_fence();
#pragma unroll
        for (int i = G * CV_NS; i < (G + 1) * CV_NS; i++)
            cv_mma<K>(d[i / 2 % 2], a[i % CV_NA], p.db + (i / 2 % 2) * (CV_HPL / 8) + 16 * K + 2 * (i % 2 + (i / 2 & 2)), i & ~2 ? 1 : p.bar >> 8);
        wgmma_commit();
    }
    if constexpr (G < GN - 1) cv_load<G + 1>(a, p);
    if constexpr (T >= 0 && T % CV_GC == 0) {
        tv[0][TK] = cv_tail<TK>(d[0], p.wrap);
        tv[1][TK] = cv_tail<TK>(d[1], p.wrap);
        if constexpr (TK & 1) sts128(p.xw + TK / 2 * 512, tv[0][TK - 1], tv[0][TK], tv[1][TK - 1], tv[1][TK]);
    }
    if constexpr (F >= 0 && F % (2 * CV_GC) == CV_GC) {
        const uint4 x = lds128(p.xr + FK / 2 * 512);
        tv[0][FK - 1] = cv_fin<FK - 1>(d[0], x.x); tv[0][FK] = cv_fin<FK>(d[0], x.y);
        tv[1][FK - 1] = cv_fin<FK - 1>(d[1], x.z); tv[1][FK] = cv_fin<FK>(d[1], x.w);
    }
    if constexpr (G < GN - 1) wgmma_wait<CV_W>();
    if constexpr (G == GN - 1) wgmma_wait<0>();
    if constexpr (T >= 0 && T % (2 * CV_GC) == CV_GC) named_bar_sync(p.bar, 128);
    if constexpr (F < GN - CV_GC) cv_steps<G + 1>(d, a, tv, p);
}

#define CV_PF 15
__global__ void __cluster_dims__(2, 1, 1) __launch_bounds__(384, 1)
conv_kernel(const __grid_constant__ CUtensorMap tmK, const __grid_constant__ CUtensorMap tmV, const __grid_constant__ CUtensorMap tmY, const bf16* __restrict__ kp, const bf16* __restrict__ vp, const bf16* __restrict__ shk,
            const bf16* __restrict__ ssk, const bf16* __restrict__ ssD, const bf16* __restrict__ w1p, const bf16* __restrict__ w2p, const bf16* __restrict__ w3p,
            const bf16* __restrict__ xq, unsigned int* p_flag, unsigned int* p_ticket, float2* p_stats, float* p_cpart) {
    extern __shared__ __align__(1024) uint8_t sm0[];
    uint8_t* sm = sm0 - CV_X;
    const uint32_t sb = smem_u32(sm);
    const int tid = threadIdx.x, warp = __shfl_sync(0xffffffffu, tid >> 5, 0), lane = tid & 31;
    const int wg = warp >> 2, w = warp & 3, rank = blockIdx.x & 1;
    const int d0 = blockIdx.x * CV_CH;
    const uint32_t b_full = sb + CV_BAR, b_rdy = b_full + 64, b_h = b_full + 128;
    GT(0);
    auto row_at = [&](int r) { return sb + CV_SL + (r < 0 ? -8192 : 0) + ((r & 127) >> 5) * 1024 + (r & 7) * 128 + ((r >> 3) & 3) * 32 + ((r ^ rank) & 1) * 16; };
    auto load_kv = [&](int c) {
#pragma unroll
        for (int i = 0; i < 2; i++)
            asm volatile("cp.async.bulk.tensor.4d.shared::cluster.global.mbarrier::complete_tx::bytes.multicast::cluster [%0], [%1, {%3, %4, %4, %5}], [%2], %6;"
                         ::"r"(sb + (c + 1) * CV_SL + rank * 8192 + i * 4096), "l"((uint64_t)(i ? &tmV : &tmK)), "r"(b_full + 8 * c), "r"(d0 & ~15), "r"(0),
                         "r"(8 * c + 4 * rank), "h"((uint16_t)3) : "memory");
    };
    auto bulk = [&](uint32_t dst, const void* src, uint32_t n, uint32_t bar) {
        asm volatile("cp.async.bulk.shared::cluster.global.mbarrier::complete_tx::bytes [%0], [%1], %2, [%3];" ::"r"(dst), "l"(src), "r"(n), "r"(bar) : "memory");
    };
    auto put_h = [&](int ch) {
        const uint32_t dk = (tid & 127) ? 0 : *reinterpret_cast<const volatile uint32_t*>(sm + CV_BAR + 160 + 16 * wg + 2 * ch);
        uint4 v[4];
#pragma unroll
        for (int i = 0; i < 4; i++) v[i] = lds128(sb + CV_X + ch * 4096 + i * 2048 + (tid & 127) * 16);
        v[0].x = pack2(lo2f(v[0].x) + lo2f(dk), hi2f(v[0].x));
        v[2].x = pack2(lo2f(v[2].x) + hi2f(dk), hi2f(v[2].x));
#pragma unroll
        for (int i = 0; i < 4; i++)
            sts128(sb + CV_H + (2 * ch + (i & 2) + (tid & 1)) * CV_HPL + (127 - ((tid & 127) >> 1)) * 16 - (i & 1) * 1024, v[i].x, v[i].y, v[i].z, v[i].w);
    };
    if (wg == 2) {
        asm volatile("setmaxnreg.dec.sync.aligned.u32 88;");
        const int bt = tid - 256, g = lane >> 2, t = lane & 3;
        cluster_arrive_relaxed();
        if (bt < 16) sts128(row_at((bt & 7) - 8) + (bt >> 3) * 4096, 0, 0, 0, 0);
#pragma unroll
        for (int i = 0; i < 4; i++)
            cp16(row_at(bt) + i * 4096, (i & 1 ? vp : kp) + (size_t)(bt + (i >> 1) * 128) * D_ + d0);
        DBG_S(16 + (3));
        uint2 wa;
        asm volatile("ld.global.nc.v2.b32 {%0,%1}, [%2];" : "=r"(wa.x), "=r"(wa.y) : "l"(shk + (d0 + g) * 4));
        const int mi = lane >> 3, r0 = 32 * w + 8 * ((lane >> 1) & 3) - (lane & 1);
        const uint32_t ka0 = row_at(r0 + 2 * mi - 3), ka1 = row_at(r0 + 2 * (mi & 1) + 5) + (mi >> 1) * 8192;
        const uint32_t va0 = row_at(r0 + 2 * mi + 1) + 4096, va1 = row_at(r0 - 1) + 4096 + (mi & 1) * 8192;
        const uint32_t qd = sb + g * CV_QG + (32 * w + 8 * t) * 8, qd0 = qd + (t & 2) * 16, qd1 = qd + (~t & 2) * 16;
        const uint32_t w0 = __byte_perm(wa.x, 0, 0x1010), w1 = __byte_perm(wa.x, 0, 0x3232), w2 = __byte_perm(wa.y, 0, 0x1010), w3 = __byte_perm(wa.y, 0, 0x3232);
        cluster_wait();
        DBG_S(16 + (5));
        asm volatile("cp.async.wait_all;" ::: "memory");
        named_bar_sync(5, 128);
        DBG_S(16 + (1));
        struct KV { uint32_t k[2][6], v[2][5]; };
        auto get = [&](KV& x, uint32_t so) {
            ldsm4t(x.k[0][0], x.k[0][1], x.k[0][2], x.k[0][3], ka0 + so);
            ldsm4t(x.k[0][4], x.k[0][5], x.k[1][4], x.k[1][5], ka1 + so);
            ldsm4t(x.k[1][0], x.k[1][1], x.k[1][2], x.k[1][3], ka0 + so + 8192);
            asm volatile("ldmatrix.sync.aligned.m8n8.x2.trans.shared.b16 {%0,%1}, [%2];" : "=r"(x.v[0][0]), "=r"(x.v[1][0]) : "r"(va1 + so));
            ldsm4t(x.v[0][1], x.v[0][2], x.v[0][3], x.v[0][4], va0 + so);
            ldsm4t(x.v[1][1], x.v[1][2], x.v[1][3], x.v[1][4], va0 + so + 8192);
        };
        auto build = [&](int c, const KV& x, KV& nx) {
            const uint32_t so = c * CV_SL;
            DBG_F(1);
            uint32_t early;
            asm volatile("{\n.reg .pred p;\nmbarrier.test_wait.parity.shared::cta.b64 p, [%1], 0;\nvote.sync.all.pred p, p, -1;\nselp.u32 %0, 1, 0, p;\n}"
                         : "=r"(early) : "r"(b_full + 8 * (c < 7 ? c + 1 : c)) : "memory");
            if (early) get(nx, so + CV_SL);
            DBG_F(2);
            uint32_t p[8][2];
#pragma unroll
            for (int sg = 0; sg < 2; sg++) {
                uint32_t u[5], ke[6];
#pragma unroll
                for (int i = 0; i < 6; i++) ke[i] = __byte_perm(x.k[sg][i], x.k[sg][i ? i - 1 : 0], 0x5432);
#pragma unroll
                for (int i = 0; i < 5; i++) {
                    u[i] = bmul2(bfma2(x.k[sg][i + 1], w0, bfma2(ke[i + 1], w1, bfma2(x.k[sg][i], w2, bmul2(ke[i], w3)))), x.v[sg][i]);
                    if (i) { p[2 * i - 1][sg] = u[i]; p[2 * i - 2][sg] = __byte_perm(u[i], u[i - 1], 0x5432); }
                }
            }
            DBG_F(3);
#pragma unroll
            for (int j = 0; j < 4; j++) sts128((j & 2 ? qd1 : qd0) + so + 16 * (j & 1), p[2 * j][0], p[2 * j][1], p[2 * j + 1][0], p[2 * j + 1][1]);
            __syncwarp();
            DBG_F(4);
            if (lane == 0) {
                mbar_arrive(b_rdy + 8 * c);
                if (c == w) {
                    if (c < 3) load_kv(c + 5);
                    else { bulk(sb + CV_X + 16384, ssk + (size_t)(d0 + 4) * S_, 16384, b_h + 16); bulk(b_full + 192, ssD + d0, 16, b_h + 16); }
                }
                if (c == w + 4 && (CV_PF >> w & 1)) {
                    const uint32_t n = w == 0 ? 32768 : w == 3 ? 57344 : 16384;
                    const char* src = reinterpret_cast<const char*>(w == 0 ? xq : w == 1 ? w1p : w == 2 ? w2p : w3p) + (size_t)blockIdx.x * n;
                    asm volatile("cp.async.bulk.prefetch.L2.global [%0], %1;" ::"l"(src), "r"(n) : "memory");
                }
            }
            DBG_F(5);
            named_bar_sync(5, 128);
            DBG_F(6);
            DBG_S(16 + (c == 0 ? 4 : 5 + c));
            if (!early) { mbar_wait(b_full + 8 * c + 8, 0); get(nx, so + CV_SL); }
            DBG_F(7);
        };
        KV x0, x1;
        get(x0, 0);
#pragma unroll 1
        for (int c = 0; c < 8; c += 2) { build(c, x0, x1); build(c + 1, x1, x0); }
        mbar_wait(b_h + 16, 0);
        put_h(4); put_h(6);
        fence_async_smem();
        __syncwarp();
        if (lane == 0) mbar_arrive(b_full);
        pdl_wait();
        if (blockIdx.x == 0) {
            for (int i = bt; i < FL_WORDS / FL_PITCH; i += 128) p_flag[i * FL_PITCH] = 0;
            if (bt < 9) p_ticket[bt * FL_PITCH] = 0;
        }
#pragma unroll
        for (int i = 0; i < 3; i++) reinterpret_cast<float4*>(p_stats)[blockIdx.x * 384 + i * 128 + bt] = make_float4(-1.f, -1.f, -1.f, -1.f);
        __threadfence();
        named_bar_sync(5, 128);
        if (w == 0) pdl_launch();
        DBG_S(16 + (13));
        return;
    }

    if (elect_one()) {
        mbar_init(b_full + 8 * warp, warp ? 1 : 4);
        mbar_init(b_rdy + 8 * warp, 4);
        if (warp) mbar_expect_tx(b_full + 8 * warp, 16384);
        if (w == 0) {
            mbar_init(b_h + 8 * wg, 1);
            mbar_expect_tx(b_h + 8 * wg, 8192 + 16);
            fence_async_smem();
            bulk(sb + CV_X + wg * 8192, ssk + (size_t)(d0 + 2 * wg) * S_, 8192, b_h + 8 * wg);
            bulk(b_full + 160 + 16 * wg, ssD + d0, 16, b_h + 8 * wg);
        }
        if (warp == 1) { mbar_init(b_h + 16, 1); mbar_expect_tx(b_h + 16, 16384 + 16); }
        asm volatile("fence.mbarrier_init.release.cluster;" ::: "memory");
        if (warp == 2) { prefetch_tmap(&tmK); prefetch_tmap(&tmV); }
    }
    __syncwarp();
    DBG_W(1);
    cluster_arrive_relaxed();
    asm volatile("setmaxnreg.inc.sync.aligned.u32 208;");
    DBG_W(2);
    const int zi = (tid & 127) - 32;
    if (zi >= 0 && zi < 48) sts128(sb + CV_H + (4 * wg + (zi / 6 & 3) + (zi / 24) * 8) * CV_HPL + 2048 + (zi % 6) * 16, 0, 0, 0, 0);
    DBG_W(3);
    cluster_wait();
    DBG_W(5);
    if (tid == 32) {
#pragma unroll 1
        for (int c = 1; c < 5; c++) load_kv(c);
        prefetch_tmap(&tmY);
    }
    __syncwarp();
    DBG_W(6);
    const int g = lane >> 2, t = lane & 3;
    const int x0 = 32 + 8 * w + g - 2 * t;
    CvAddr p;
    p.rdy = b_rdy;
    p.bar = 1 + wg;
    p.xr = sb + CV_X + (warp ^ 2) * 2048 + lane * 16;
    p.xw = sb + CV_X + warp * 2048 + (g * 4 + ((t - (w >> 1)) & 3)) * 16;
    p.wrap = t == 0 && w >= 2;
    mbar_wait(b_h + 8 * wg, 0);
    DBG_W(4);
    put_h(2 * wg);
    fence_async_smem();
    named_bar_sync(1 + wg, 128);
    float acc[2][64];
    zero_acc(acc[0]); zero_acc(acc[1]);
#pragma unroll 1
    for (int round = 0; round < 2; round++) {
        const int ch = round * 4 + 2 * wg;
        uint32_t a[CV_NA][4], tv[2][8];
#pragma unroll
        for (int e = 0; e < 2; e++) {
            const int x = x0 - 8 * e;
            p.neg[e] = x < 32;
            p.pa[e] = sb + ch * CV_QG + 8 * (x ^ (x >> 2 & 4));
            p.p0[2 * e] = p.pa[e] + (x < 32 ? 768 + 4 - CV_SL : -256);
            p.p0[2 * e + 1] = p.pa[e] + (x < 32 ? 768 : -256 + 4);
        }
        p.db = (((sb + CV_H + ch * 2 * CV_HPL) & 0x3FFFF) >> 4) | ((CV_HPL / 16) << 16);
        if (round) mbar_wait(b_full, 0);
        DBG_S(7 + 3 * round);
        cv_steps<0>(acc, a, tv, p);
        DBG_S(8 + 3 * round);
        const int r128 = 4 * (lane >> 3) + 2 * (lane & 1) + ((~lane >> 2) & 1);
#pragma unroll
        for (int i = 0; i < 2; i++) {
            const uint32_t ta = sb + (ch + i + 1) * CV_SL + 12288 + r128 * 128 + ((((~lane & 2) * 2 + w) ^ (r128 & 7)) << 4);
            stsm4t(ta, tv[i][0], tv[i][1], tv[i][2], tv[i][3]);
            stsm4t(ta + 2048, tv[i][4], tv[i][5], tv[i][6], tv[i][7]);
        }
        fence_async_smem();
        named_bar_sync(1 + wg, 128);
        if ((tid & 127) < 2) {
            if (round == 0) pdl_wait();
            const int d = d0 + ch + (tid & 1);
            asm volatile("cp.async.bulk.tensor.4d.global.shared::cta.bulk_group [%0, {%2, %3, %4, %2}], [%1];"
                         ::"l"((uint64_t)&tmY), "r"(sb + (ch + (tid & 1) + 1) * CV_SL + 12288), "r"(0), "r"(4 * (d >> 8)), "r"(d & 255) : "memory");
            asm volatile("cp.async.bulk.commit_group;" ::: "memory");
        }
        __syncwarp();
        DBG_S(9 + 3 * round);
    }
    asm volatile("cp.async.bulk.wait_group 0;" ::: "memory");
    GT(1);
}

typedef CUresult (*PFN_encodeTiled)(CUtensorMap*, CUtensorMapDataType, cuuint32_t, void*, const cuuint64_t*, const cuuint64_t*,
                                    const cuuint32_t*, const cuuint32_t*, CUtensorMapInterleave, CUtensorMapSwizzle,
                                    CUtensorMapL2promotion, CUtensorMapFloatOOBfill);

static CUtensorMap make_map(PFN_encodeTiled enc, const void* ptr, int inner, int outer, int box_inner, int box_outer,
                            CUtensorMapSwizzle swz = CU_TENSOR_MAP_SWIZZLE_128B) {
    CUtensorMap m;
    cuuint64_t dims[2] = {(cuuint64_t)inner, (cuuint64_t)outer};
    cuuint64_t strides[1] = {(cuuint64_t)inner * 2};
    cuuint32_t box[2] = {(cuuint32_t)box_inner, (cuuint32_t)box_outer};
    cuuint32_t es[2] = {1, 1};
    enc(&m, CU_TENSOR_MAP_DATA_TYPE_BFLOAT16, 2, const_cast<void*>(ptr), dims, strides, box, es, CU_TENSOR_MAP_INTERLEAVE_NONE,
        swz, CU_TENSOR_MAP_L2_PROMOTION_L2_256B, CU_TENSOR_MAP_FLOAT_OOB_FILL_NONE);
    return m;
}

extern "C" void kernel_launch(void* const* d_in, const int* in_sizes, int n_in, void* d_out, int out_size) {
    const bf16* A_q = (const bf16*)d_in[0];
    const bf16* A_k = (const bf16*)d_in[1];
    const bf16* A_v = (const bf16*)d_in[2];
    const bf16* A_shk = (const bf16*)d_in[3];
    const bf16* A_ssk = (const bf16*)d_in[4];
    const bf16* A_ssD = (const bf16*)d_in[5];
    const bf16* w1 = (const bf16*)d_in[7];
    const bf16* w2 = (const bf16*)d_in[8];
    const bf16* w3 = (const bf16*)d_in[9];
    const bf16* w4 = (const bf16*)d_in[10];
    bf16* out = (bf16*)d_out;

    static PFN_encodeTiled enc = nullptr;
    static bool attr_done = false;
    if (!enc) {
        void* fn = nullptr;
        cudaDriverEntryPointQueryResult qr;
        cudaGetDriverEntryPoint("cuTensorMapEncodeTiled", &fn, cudaEnableDefault, &qr);
        enc = (PFN_encodeTiled)fn;
    }
    if (!attr_done) {
        cudaFuncSetAttribute(mega_kernel, cudaFuncAttributeMaxDynamicSharedMemorySize, MEGA_SMEM);
        cudaFuncSetAttribute(conv_kernel, cudaFuncAttributeMaxDynamicSharedMemorySize, CV_SMEM);
        attr_done = true;
    }
    void* p_act;
    cudaGetSymbolAddress(&p_act, g_act);
    bf16* act = (bf16*)(((uintptr_t)p_act + 0x1fffff) & ~(uintptr_t)0x1fffff);

    MegaMaps tm;
    tm.q = make_map(enc, A_q, D_, S_, 64, 128);
    tm.act = make_map(enc, act, D_, R_END, 64, 128);
    tm.w1 = make_map(enc, w1, D_, D_, 64, 64);
    tm.w2 = make_map(enc, w2, D_, D_, 64, 64);
    tm.w3 = make_map(enc, w3, F_, D_, 64, 64);
    tm.w4 = make_map(enc, w4, D_, F_, 64, 64);
    CUtensorMap tm_y;
    {
        cuuint64_t dims[4] = {64, 16, 256, 8}, strides[3] = {128, D_ * 2, (cuuint64_t)2048 * D_ * 2};
        cuuint32_t box[4] = {64, 4, 1, 8}, es[4] = {1, 1, 1, 1};
        enc(&tm_y, CU_TENSOR_MAP_DATA_TYPE_BFLOAT16, 4, act + (size_t)R_Y * D_, dims, strides, box, es, CU_TENSOR_MAP_INTERLEAVE_NONE,
            CU_TENSOR_MAP_SWIZZLE_128B, CU_TENSOR_MAP_L2_PROMOTION_NONE, CU_TENSOR_MAP_FLOAT_OOB_FILL_NONE);
    }
    CUtensorMap tm_kv[2];
    for (int i = 0; i < 2; i++) {
        cuuint64_t dims[4] = {D_, 4, 8, S_ / 32}, strides[3] = {8 * D_ * 2, D_ * 2, 32 * D_ * 2};
        cuuint32_t box[4] = {16, 4, 8, 4}, es[4] = {1, 1, 1, 1};
        enc(&tm_kv[i], CU_TENSOR_MAP_DATA_TYPE_BFLOAT16, 4, (void*)(i ? A_v : A_k), dims, strides, box, es, CU_TENSOR_MAP_INTERLEAVE_NONE,
            CU_TENSOR_MAP_SWIZZLE_32B, CU_TENSOR_MAP_L2_PROMOTION_NONE, CU_TENSOR_MAP_FLOAT_OOB_FILL_NONE);
    }
    void *p_flag, *p_ticket, *p_stats, *p_cpart;
    cudaGetSymbolAddress(&p_flag, g_flag); cudaGetSymbolAddress(&p_ticket, g_ticket); cudaGetSymbolAddress(&p_stats, g_stats); cudaGetSymbolAddress(&p_cpart, g_cpart);

    cudaStream_t st = cudaStreamPerThread;
    cudaLaunchAttribute at[2];
    at[0].id = cudaLaunchAttributeProgrammaticStreamSerialization;
    at[0].val.programmaticStreamSerializationAllowed = 1;
    at[1].id = cudaLaunchAttributeClusterDimension;
    at[1].val.clusterDim.x = 2;
    at[1].val.clusterDim.y = 1;
    at[1].val.clusterDim.z = 1;
    {
        cudaLaunchConfig_t cfg = {};
        cfg.gridDim = dim3(D_ / CV_CH);
        cfg.blockDim = dim3(384);
        cfg.dynamicSmemBytes = CV_SMEM;
        cfg.stream = st;
        cfg.attrs = at;
        cfg.numAttrs = 2;
        cudaLaunchKernelEx(&cfg, conv_kernel, tm_kv[0], tm_kv[1], tm_y, A_k, A_v, A_shk, A_ssk, A_ssD, w1, w2, w3, A_q, (unsigned int*)p_flag, (unsigned int*)p_ticket, (float2*)p_stats, (float*)p_cpart);
    }
    {
        cudaLaunchConfig_t cfg = {};
        cfg.gridDim = dim3(132);
        cfg.blockDim = dim3(384);
        cfg.dynamicSmemBytes = MEGA_SMEM;
        cfg.stream = st;
        cfg.attrs = at;
        cfg.numAttrs = 2;
        cudaLaunchKernelEx(&cfg, mega_kernel, tm, out, act, w1, w3);
    }
}
```

```cpp
#include <cuda_runtime.h>
#include <cuda_bf16.h>
#include <cuda.h>
#include <stdint.h>

typedef __nv_bfloat16 bf16;

constexpr int S_ = 2048;
constexpr int D_ = 1024;
constexpr int F_ = 3584;

constexpr int R_XA = 0, R_X1 = 256, R_H2 = 512, R_Y = 1536, R_H = 16384 + 8, R_HP = S_ + 8, R_END = R_H + 2 * R_HP;
__device__ __align__(1024) bf16 g_act[(size_t)(R_END + 1024) * D_];
__device__ __align__(16) float g_cpart[16 * (F_ + D_)];
__device__ __align__(16) float2 g_stats[6 * S_ * 8];

__device__ __forceinline__ float bfr(float x) { return __bfloat162float(__float2bfloat16_rn(x)); }
__device__ __forceinline__ uint32_t pack2(float lo, float hi) {
    __nv_bfloat162 v = __floats2bfloat162_rn(lo, hi);
    return *reinterpret_cast<uint32_t*>(&v);
}
__device__ __forceinline__ float lo2f(uint32_t v) { return __uint_as_float(v << 16); }
__device__ __forceinline__ float hi2f(uint32_t v) { return __uint_as_float(v & 0xffff0000u); }
__device__ __forceinline__ float frcp(float x) { float r; asm("rcp.approx.f32 %0, %1;" : "=f"(r) : "f"(x)); return r; }
__device__ __forceinline__ float fsqrt(float x) { float r; asm("sqrt.approx.f32 %0, %1;" : "=f"(r) : "f"(x)); return r; }
__device__ __forceinline__ uint32_t smem_u32(const void* p) { return (uint32_t)__cvta_generic_to_shared(p); }

__device__ __forceinline__ void mbar_init(uint32_t bar, uint32_t cnt) {
    asm volatile("mbarrier.init.shared::cta.b64 [%0], %1;" ::"r"(bar), "r"(cnt));
}
__device__ __forceinline__ void mbar_expect_tx(uint32_t bar, uint32_t bytes) {
    asm volatile("mbarrier.arrive.expect_tx.shared::cta.b64 _, [%0], %1;" ::"r"(bar), "r"(bytes) : "memory");
}
__device__ __forceinline__ void mbar_arrive(uint32_t bar) {
    asm volatile("mbarrier.arrive.shared::cta.b64 _, [%0];" ::"r"(bar) : "memory");
}
__device__ __forceinline__ void mbar_wait(uint32_t bar, uint32_t parity) {
    asm volatile(
        "{\n.reg .pred p;\n.reg .u32 n;\n"
        "mbarrier.try_wait.parity.shared::cta.b64 p, [%0], %1;\n"
        "@p bra LD;\n"
        "mov.u32 n, 0;\n"
        "LW:\n"
        "mbarrier.try_wait.parity.shared::cta.b64 p, [%0], %1;\n"
        "@p bra LD;\n"
        "add.u32 n, n, 1;\n"
        "setp.lt.u32 p, n, 0x400000;\n"
        "@p bra LW;\n"
        "LD:\n}\n"
        ::"r"(bar), "r"(parity) : "memory");
}
__device__ __forceinline__ void tma_load_2d(uint32_t dst, const CUtensorMap* tm, uint32_t bar, int c0, int c1) {
    asm volatile(
        "cp.async.bulk.tensor.2d.shared::cluster.global.mbarrier::complete_tx::bytes [%0], [%1, {%3, %4}], [%2];"
        ::"r"(dst), "l"((uint64_t)tm), "r"(bar), "r"(c0), "r"(c1) : "memory");
}
__device__ __forceinline__ void tma_load_2d_mc(uint32_t dst, const CUtensorMap* tm, uint32_t bar, int c0, int c1) {
    asm volatile(
        "cp.async.bulk.tensor.2d.shared::cluster.global.mbarrier::complete_tx::bytes.multicast::cluster [%0], [%1, {%3, %4}], [%2], %5;"
        ::"r"(dst), "l"((uint64_t)tm), "r"(bar), "r"(c0), "r"(c1), "h"((uint16_t)3) : "memory");
}
__device__ __forceinline__ void tma_prefetch_2d(const CUtensorMap* tm, int c0, int c1) {
    asm volatile("cp.async.bulk.prefetch.tensor.2d.L2.global.tile [%0, {%1, %2}];" ::"l"((uint64_t)tm), "r"(c0), "r"(c1) : "memory");
}
__device__ __forceinline__ void tma_store_2d(const CUtensorMap* tm, uint32_t src, int c0, int c1) {
    asm volatile("cp.async.bulk.tensor.2d.global.shared::cta.bulk_group [%0, {%2, %3}], [%1];"
                 ::"l"((uint64_t)tm), "r"(src), "r"(c0), "r"(c1) : "memory");
}
__device__ __forceinline__ void wgmma_fence() { asm volatile("wgmma.fence.sync.aligned;" ::: "memory"); }
__device__ __forceinline__ void wgmma_commit() { asm volatile("wgmma.commit_group.sync.aligned;" ::: "memory"); }
template <int N> __device__ __forceinline__ void wgmma_wait() { asm volatile("wgmma.wait_group.sync.aligned %0;" ::"n"(N) : "memory"); }
__device__ __forceinline__ void named_bar_arrive(int id, int n) { asm volatile("bar.arrive %0, %1;" ::"r"(id), "r"(n) : "memory"); }
__device__ __forceinline__ void named_bar_sync(int id, int n) { asm volatile("bar.sync %0, %1;" ::"r"(id), "r"(n) : "memory"); }

__device__ __forceinline__ uint32_t desc_a(uint32_t addr) { return ((addr & 0x3FFFF) >> 4) | (1u << 16); }
__device__ __forceinline__ uint32_t desc_b(uint32_t addr) { return ((addr & 0x3FFFF) >> 4) | (512u << 16); }

__device__ __forceinline__ void wgmma_m64n192k16(float (&d)[96], uint32_t descA, uint32_t descB) {
  asm volatile("{\n.reg .pred p;\n.reg .b64 da, db;\nsetp.eq.b32 p, 0, 0;\nmov.b64 da, {%96, %98};\nmov.b64 db, {%97, %98};\n"
    "wgmma.mma_async.sync.aligned.m64n192k16.f32.bf16.bf16 "
    "{%0, %1, %2, %3, %4, %5, %6, %7, %8, %9, %10, %11, %12, %13, %14, %15, %16, %17, %18, %19, %20, %21, %22, %23, %24, %25, %26, %27, %28, %29, %30, %31, %32, %33, %34, %35, %36, %37, %38, %39, %40, %41, %42, %43, %44, %45, %46, %47, %48, %49, %50, %51, %52, %53, %54, %55, %56, %57, %58, %59, %60, %61, %62, %63, %64, %65, %66, %67, %68, %69, %70, %71, %72, %73, %74, %75, %76, %77, %78, %79, %80, %81, %82, %83, %84, %85, %86, %87, %88, %89, %90, %91, %92, %93, %94, %95}, "
    "da, db, p, 1, 1, 0, 1;\n}\n"
    : "+f"(d[0]), "+f"(d[1]), "+f"(d[2]), "+f"(d[3]), "+f"(d[4]), "+f"(d[5]), "+f"(d[6]), "+f"(d[7]), "+f"(d[8]), "+f"(d[9]), "+f"(d[10]), "+f"(d[11]), "+f"(d[12]), "+f"(d[13]), "+f"(d[14]), "+f"(d[15]), "+f"(d[16]), "+f"(d[17]), "+f"(d[18]), "+f"(d[19]), "+f"(d[20]), "+f"(d[21]), "+f"(d[22]), "+f"(d[23]), "+f"(d[24]), "+f"(d[25]), "+f"(d[26]), "+f"(d[27]), "+f"(d[28]), "+f"(d[29]), "+f"(d[30]), "+f"(d[31]), "+f"(d[32]), "+f"(d[33]), "+f"(d[34]), "+f"(d[35]), "+f"(d[36]), "+f"(d[37]), "+f"(d[38]), "+f"(d[39]), "+f"(d[40]), "+f"(d[41]), "+f"(d[42]), "+f"(d[43]), "+f"(d[44]), "+f"(d[45]), "+f"(d[46]), "+f"(d[47]), "+f"(d[48]), "+f"(d[49]), "+f"(d[50]), "+f"(d[51]), "+f"(d[52]), "+f"(d[53]), "+f"(d[54]), "+f"(d[55]), "+f"(d[56]), "+f"(d[57]), "+f"(d[58]), "+f"(d[59]), "+f"(d[60]), "+f"(d[61]), "+f"(d[62]), "+f"(d[63]), "+f"(d[64]), "+f"(d[65]), "+f"(d[66]), "+f"(d[67]), "+f"(d[68]), "+f"(d[69]), "+f"(d[70]), "+f"(d[71]), "+f"(d[72]), "+f"(d[73]), "+f"(d[74]), "+f"(d[75]), "+f"(d[76]), "+f"(d[77]), "+f"(d[78]), "+f"(d[79]), "+f"(d[80]), "+f"(d[81]), "+f"(d[82]), "+f"(d[83]), "+f"(d[84]), "+f"(d[85]), "+f"(d[86]), "+f"(d[87]), "+f"(d[88]), "+f"(d[89]), "+f"(d[90]), "+f"(d[91]), "+f"(d[92]), "+f"(d[93]), "+f"(d[94]), "+f"(d[95])
    : "r"(descA), "r"(descB), "r"(0x40000040u));
}

__device__ __forceinline__ void wgmma_m64n256k16(float (&d)[128], uint32_t descA, uint32_t descB) {
  asm volatile("{\n.reg .pred p;\n.reg .b64 da, db;\nsetp.eq.b32 p, 0, 0;\nmov.b64 da, {%128, %130};\nmov.b64 db, {%129, %130};\n"
    "wgmma.mma_async.sync.aligned.m64n256k16.f32.bf16.bf16 "
    "{%0, %1, %2, %3, %4, %5, %6, %7, %8, %9, %10, %11, %12, %13, %14, %15, %16, %17, %18, %19, %20, %21, %22, %23, %24, %25, %26, %27, %28, %29, %30, %31, %32, %33, %34, %35, %36, %37, %38, %39, %40, %41, %42, %43, %44, %45, %46, %47, %48, %49, %50, %51, %52, %53, %54, %55, %56, %57, %58, %59, %60, %61, %62, %63, %64, %65, %66, %67, %68, %69, %70, %71, %72, %73, %74, %75, %76, %77, %78, %79, %80, %81, %82, %83, %84, %85, %86, %87, %88, %89, %90, %91, %92, %93, %94, %95, %96, %97, %98, %99, %100, %101, %102, %103, %104, %105, %106, %107, %108, %109, %110, %111, %112, %113, %114, %115, %116, %117, %118, %119, %120, %121, %122, %123, %124, %125, %126, %127}, "
    "da, db, p, 1, 1, 0, 1;\n}\n"
    : "+f"(d[0]), "+f"(d[1]), "+f"(d[2]), "+f"(d[3]), "+f"(d[4]), "+f"(d[5]), "+f"(d[6]), "+f"(d[7]), "+f"(d[8]), "+f"(d[9]), "+f"(d[10]), "+f"(d[11]), "+f"(d[12]), "+f"(d[13]), "+f"(d[14]), "+f"(d[15]), "+f"(d[16]), "+f"(d[17]), "+f"(d[18]), "+f"(d[19]), "+f"(d[20]), "+f"(d[21]), "+f"(d[22]), "+f"(d[23]), "+f"(d[24]), "+f"(d[25]), "+f"(d[26]), "+f"(d[27]), "+f"(d[28]), "+f"(d[29]), "+f"(d[30]), "+f"(d[31]), "+f"(d[32]), "+f"(d[33]), "+f"(d[34]), "+f"(d[35]), "+f"(d[36]), "+f"(d[37]), "+f"(d[38]), "+f"(d[39]), "+f"(d[40]), "+f"(d[41]), "+f"(d[42]), "+f"(d[43]), "+f"(d[44]), "+f"(d[45]), "+f"(d[46]), "+f"(d[47]), "+f"(d[48]), "+f"(d[49]), "+f"(d[50]), "+f"(d[51]), "+f"(d[52]), "+f"(d[53]), "+f"(d[54]), "+f"(d[55]), "+f"(d[56]), "+f"(d[57]), "+f"(d[58]), "+f"(d[59]), "+f"(d[60]), "+f"(d[61]), "+f"(d[62]), "+f"(d[63]), "+f"(d[64]), "+f"(d[65]), "+f"(d[66]), "+f"(d[67]), "+f"(d[68]), "+f"(d[69]), "+f"(d[70]), "+f"(d[71]), "+f"(d[72]), "+f"(d[73]), "+f"(d[74]), "+f"(d[75]), "+f"(d[76]), "+f"(d[77]), "+f"(d[78]), "+f"(d[79]), "+f"(d[80]), "+f"(d[81]), "+f"(d[82]), "+f"(d[83]), "+f"(d[84]), "+f"(d[85]), "+f"(d[86]), "+f"(d[87]), "+f"(d[88]), "+f"(d[89]), "+f"(d[90]), "+f"(d[91]), "+f"(d[92]), "+f"(d[93]), "+f"(d[94]), "+f"(d[95]), "+f"(d[96]), "+f"(d[97]), "+f"(d[98]), "+f"(d[99]), "+f"(d[100]), "+f"(d[101]), "+f"(d[102]), "+f"(d[103]), "+f"(d[104]), "+f"(d[105]), "+f"(d[106]), "+f"(d[107]), "+f"(d[108]), "+f"(d[109]), "+f"(d[110]), "+f"(d[111]), "+f"(d[112]), "+f"(d[113]), "+f"(d[114]), "+f"(d[115]), "+f"(d[116]), "+f"(d[117]), "+f"(d[118]), "+f"(d[119]), "+f"(d[120]), "+f"(d[121]), "+f"(d[122]), "+f"(d[123]), "+f"(d[124]), "+f"(d[125]), "+f"(d[126]), "+f"(d[127])
    : "r"(descA), "r"(descB), "r"(0x40000040u));
}

__device__ __forceinline__ void wgmma_m64n128k16(float (&d)[64], uint32_t descA, uint32_t descB) {
  asm volatile("{\n.reg .pred p;\n.reg .b64 da, db;\nsetp.eq.b32 p, 0, 0;\nmov.b64 da, {%64, %66};\nmov.b64 db, {%65, %66};\n"
    "wgmma.mma_async.sync.aligned.m64n128k16.f32.bf16.bf16 "
    "{%0, %1, %2, %3, %4, %5, %6, %7, %8, %9, %10, %11, %12, %13, %14, %15, %16, %17, %18, %19, %20, %21, %22, %23, %24, %25, %26, %27, %28, %29, %30, %31, %32, %33, %34, %35, %36, %37, %38, %39, %40, %41, %42, %43, %44, %45, %46, %47, %48, %49, %50, %51, %52, %53, %54, %55, %56, %57, %58, %59, %60, %61, %62, %63}, "
    "da, db, p, 1, 1, 0, 1;\n}\n"
    : "+f"(d[0]), "+f"(d[1]), "+f"(d[2]), "+f"(d[3]), "+f"(d[4]), "+f"(d[5]), "+f"(d[6]), "+f"(d[7]), "+f"(d[8]), "+f"(d[9]), "+f"(d[10]), "+f"(d[11]), "+f"(d[12]), "+f"(d[13]), "+f"(d[14]), "+f"(d[15]), "+f"(d[16]), "+f"(d[17]), "+f"(d[18]), "+f"(d[19]), "+f"(d[20]), "+f"(d[21]), "+f"(d[22]), "+f"(d[23]), "+f"(d[24]), "+f"(d[25]), "+f"(d[26]), "+f"(d[27]), "+f"(d[28]), "+f"(d[29]), "+f"(d[30]), "+f"(d[31]), "+f"(d[32]), "+f"(d[33]), "+f"(d[34]), "+f"(d[35]), "+f"(d[36]), "+f"(d[37]), "+f"(d[38]), "+f"(d[39]), "+f"(d[40]), "+f"(d[41]), "+f"(d[42]), "+f"(d[43]), "+f"(d[44]), "+f"(d[45]), "+f"(d[46]), "+f"(d[47]), "+f"(d[48]), "+f"(d[49]), "+f"(d[50]), "+f"(d[51]), "+f"(d[52]), "+f"(d[53]), "+f"(d[54]), "+f"(d[55]), "+f"(d[56]), "+f"(d[57]), "+f"(d[58]), "+f"(d[59]), "+f"(d[60]), "+f"(d[61]), "+f"(d[62]), "+f"(d[63])
    : "r"(descA), "r"(descB), "r"(0x40000040u));
}

template <int BN> struct WG;
template <> struct WG<128> { static __device__ __forceinline__ void mma(float (&d)[64], uint32_t a, uint32_t b) { wgmma_m64n128k16(d, a, b); } };
template <> struct WG<256> { static __device__ __forceinline__ void mma(float (&d)[128], uint32_t a, uint32_t b) { wgmma_m64n256k16(d, a, b); } };
template <> struct WG<192> { static __device__ __forceinline__ void mma(float (&d)[96], uint32_t a, uint32_t b) { wgmma_m64n192k16(d, a, b); } };

#define DBG_T(i)
__device__ __forceinline__ void fence_async_smem() { asm volatile("fence.proxy.async.shared::cta;" ::: "memory"); }
__device__ __forceinline__ void prefetch_tmap(const CUtensorMap* tm) { asm volatile("prefetch.tensormap [%0];" ::"l"((uint64_t)tm) : "memory"); }
__device__ __forceinline__ uint32_t mapa_u32(uint32_t addr, uint32_t cta) {
    uint32_t r;
    asm volatile("mapa.shared::cluster.u32 %0, %1, %2;" : "=r"(r) : "r"(addr), "r"(cta));
    return r;
}
__device__ __forceinline__ void mbar_arrive_cluster(uint32_t cluster_addr) {
    asm volatile("mbarrier.arrive.shared::cluster.b64 _, [%0];" ::"r"(cluster_addr) : "memory");
}
__device__ __forceinline__ bool elect_one() {
    uint32_t p;
    asm volatile("{\n.reg .pred P;\nelect.sync _|P, 0xffffffff;\nselp.u32 %0, 1, 0, P;\n}\n" : "=r"(p));
    return p != 0;
}
__device__ __forceinline__ void cluster_arrive_relaxed() { asm volatile("barrier.cluster.arrive.relaxed.aligned;" ::: "memory"); }
__device__ __forceinline__ void cluster_wait() { asm volatile("barrier.cluster.wait.acquire.aligned;" ::: "memory"); }

__device__ __forceinline__ uint32_t bsub2(uint32_t a, uint32_t b) {
    __nv_bfloat162 r = __hsub2(*reinterpret_cast<__nv_bfloat162*>(&a), *reinterpret_cast<__nv_bfloat162*>(&b));
    return *reinterpret_cast<uint32_t*>(&r);
}
__device__ __forceinline__ uint32_t bmul2(uint32_t a, uint32_t b) {
    __nv_bfloat162 r = __hmul2(*reinterpret_cast<__nv_bfloat162*>(&a), *reinterpret_cast<__nv_bfloat162*>(&b));
    return *reinterpret_cast<uint32_t*>(&r);
}
__device__ __forceinline__ uint32_t badd2(uint32_t a, uint32_t b) {
    __nv_bfloat162 r = __hadd2(*reinterpret_cast<__nv_bfloat162*>(&a), *reinterpret_cast<__nv_bfloat162*>(&b));
    return *reinterpret_cast<uint32_t*>(&r);
}
constexpr int BM = 128, BK = 64;
constexpr int R5_STAGE = 32768, R5_N = 5;
constexpr int R4_STAGE = 49152, R4_N = 4;
constexpr int R4B_STAGE = 40960;
constexpr int OFF_STG5 = 0, OFF_R = 32768;
constexpr int OFF_EPI = 196608;
constexpr int OFF_BAR = OFF_EPI + 32768;
constexpr int OFF_RS = OFF_BAR + 256;
constexpr int OFF_CS = OFF_RS + 1024;
constexpr int MEGA_SMEM = OFF_CS + 1792;
enum { FL_XA = 0, FL_H = 2, FL_X1 = 4, FL_H2 = 6, FL_CS = 10, FL_KINDS = 11 };
constexpr int FL_PITCH = 64;
constexpr int FL_WORDS = 2 * FL_KINDS * 16 * FL_PITCH;
__device__ unsigned int g_flag[FL_WORDS];
__device__ __align__(8) unsigned int g_ticket[18 * FL_PITCH];
constexpr int NCL = 66;
__device__ __forceinline__ unsigned int* flag_ptr(int layer, int kind, int i) { return g_flag + ((layer * FL_KINDS + kind) * 16 + i) * FL_PITCH; }

__device__ __forceinline__ void wait_flag(const unsigned int* p, unsigned int target) {
    long long t0 = clock64();
    while (true) {
        unsigned int v;
        asm volatile("ld.relaxed.gpu.global.u32 %0, [%1];" : "=r"(v) : "l"(p) : "memory");
        if ((int)(v - target) >= 0) break;
        if (clock64() - t0 > 2000000000LL) break;
    }
    asm volatile("fence.acquire.gpu;" ::: "memory");
}
__device__ __forceinline__ void fence_proxy_async() {
    asm volatile("fence.proxy.async.global;" ::: "memory");
    asm volatile("fence.proxy.async.shared::cta;" ::: "memory");
}
__device__ __forceinline__ void stsm4(uint32_t addr, uint32_t r0, uint32_t r1, uint32_t r2, uint32_t r3) {
    asm volatile("stmatrix.sync.aligned.m8n8.x4.shared.b16 [%0], {%1,%2,%3,%4};" ::"r"(addr), "r"(r0), "r"(r1), "r"(r2), "r"(r3));
}
__device__ __forceinline__ uint4 lds128(uint32_t a) {
    uint4 v;
    asm volatile("ld.shared.v4.b32 {%0,%1,%2,%3}, [%4];" : "=r"(v.x), "=r"(v.y), "=r"(v.z), "=r"(v.w) : "r"(a) : "memory");
    return v;
}
__device__ __forceinline__ void stg128(void* p, uint4 v) {
    asm volatile("st.global.v4.b32 [%0], {%1,%2,%3,%4};" ::"l"(p), "r"(v.x), "r"(v.y), "r"(v.z), "r"(v.w) : "memory");
}
__device__ __forceinline__ float gelu_tanh_h(float hx) {
    float z = hx * fmaf(hx * hx, 8.0f * 0.035677408136300125f, 2.0f * 0.7978845608028654f);
    float t;
    asm("tanh.approx.f32 %0, %1;" : "=f"(t) : "f"(z));
    return fmaf(hx, t, hx);
}
__device__ __forceinline__ uint32_t gelu2h(uint32_t p) { return pack2(gelu_tanh_h(lo2f(p)), gelu_tanh_h(hi2f(p))); }
__device__ __forceinline__ uint4 gelu8h(uint4 v) { return make_uint4(gelu2h(v.x), gelu2h(v.y), gelu2h(v.z), gelu2h(v.w)); }

__device__ __forceinline__ void row_stats(const float2* p, uint32_t tag, float& mean, float& var) {
    float2 v[8];
#pragma unroll 1
    for (int n = 0; n < (1 << 20); n++) {
#pragma unroll
        for (int i = 0; i < 8; i++)
            asm volatile("{\n.reg .b64 t;\nld.relaxed.gpu.global.b64 t, [%2];\nmov.b64 {%0, %1}, t;\n}" : "=f"(v[i].x), "=f"(v[i].y) : "l"(p + 128 * i) : "memory");
        uint32_t old = 0;
#pragma unroll
        for (int i = 0; i < 8; i++) old |= __float_as_uint(v[i].y) ^ tag;
        if ((int)old >= 0) break;
    }
    mean = (((v[0].x + v[1].x) + (v[2].x + v[3].x)) + ((v[4].x + v[5].x) + (v[6].x + v[7].x))) * 0.125f;
    float m2 = 0.f, d2 = 0.f;
#pragma unroll
    for (int i = 0; i < 8; i++) { m2 += fabsf(v[i].y); d2 = fmaf(v[i].x - mean, v[i].x - mean, d2); }
    var = fmaf(128.0f, d2, m2) * (1.0f / D_);
}
struct RingState { uint32_t st, ph; };

#define DT(i)
#define DP(i)
#define GT(i)

template <int BN, int NST>
__device__ __forceinline__ void kblock(float (&acc)[BN / 2], uint32_t da, uint32_t db, uint32_t bfull, RingState& rs) {
    mbar_wait(bfull + 8 * rs.st, rs.ph);
    wgmma_fence();
#pragma unroll
    for (int k = 0; k < 4; k++) WG<BN>::mma(acc, da + k * 2, db + k * 128);
    wgmma_commit();
    if (++rs.st == NST) { rs.st = 0; rs.ph ^= 1; }
}
template <int BN, int NST, int STAGE>
__device__ __forceinline__ void mainloop(float (&acc)[BN / 2], int KB, uint32_t da0, uint32_t db0, uint32_t bfull, uint32_t rel, bool rel_on,
                                         RingState& rs, int dbg) {
    uint32_t prev = rs.st ? rs.st - 1 : NST - 1;
#pragma unroll 1
    for (int kk = 0; kk < KB; kk++) {
        const uint32_t cur = rs.st;
        kblock<BN, NST>(acc, da0 + cur * (STAGE / 16), db0 + cur * (STAGE / 16), bfull, rs);
        wgmma_wait<1>();
        if (rel_on) mbar_arrive_cluster(rel + 8 * prev);
        prev = cur;
    }
    wgmma_wait<0>();
#pragma unroll
    for (int i = 0; i < BN / 2; i++) asm volatile("" : "+f"(acc[i])::"memory");
    if (rel_on) mbar_arrive_cluster(rel + 8 * prev);
}
template <int N> __device__ __forceinline__ void zero_acc(float (&acc)[N]) {
#pragma unroll
    for (int i = 0; i < N; i++) acc[i] = 0.f;
}
__device__ __forceinline__ void ldsm4(uint32_t& r0, uint32_t& r1, uint32_t& r2, uint32_t& r3, uint32_t addr) {
    asm volatile("ldmatrix.sync.aligned.m8n8.x4.shared.b16 {%0,%1,%2,%3}, [%4];" : "=r"(r0), "=r"(r1), "=r"(r2), "=r"(r3) : "r"(addr));
}

__device__ __forceinline__ void ldsm4t(uint32_t& r0, uint32_t& r1, uint32_t& r2, uint32_t& r3, uint32_t addr) {
    asm volatile("ldmatrix.sync.aligned.m8n8.x4.trans.shared.b16 {%0,%1,%2,%3}, [%4];" : "=r"(r0), "=r"(r1), "=r"(r2), "=r"(r3) : "r"(addr));
}

#define DBG_S(i)
#define DBG_OUT(r, o)
#define DBG_F(i)
#define DBG_W(i)
constexpr int CV_CH = 8;
constexpr int CV_SL = 16384;
constexpr int CV_QG = 128 * 8 + 16;
constexpr int CV_HPL = 2048 + 192;
constexpr int CV_0 = 32768, CV_H = 9 * CV_SL, CV_BAR = OFF_RS - CV_0;

template <int K> __device__ __forceinline__ void cv_mma(float (&d)[64], const uint32_t (&a)[4], uint32_t db, int acc);
template <> __device__ __forceinline__ void cv_mma<0>(float (&d)[64], const uint32_t (&a)[4], uint32_t db, int acc) {
    asm volatile("{\n.reg .pred p;\n.reg .b64 b;\nsetp.ne.b32 p, %70, 0;\nmov.b64 b, {%68, %69};\n"
        "wgmma.mma_async.sync.aligned.m64n128k16.f32.bf16.bf16 {%0,%1,%2,%3,%4,%5,%6,%7,%8,%9,%10,%11,%12,%13,%14,%15,%16,%17,%18,%19,%20,%21,%22,%23,%24,%25,%26,%27,%28,%29,%30,%31,%32,%33,%34,%35,%36,%37,%38,%39,%40,%41,%42,%43,%44,%45,%46,%47,%48,%49,%50,%51,%52,%53,%54,%55,%56,%57,%58,%59,%60,%61,%62,%63}, {%64,%65,%66,%67}, b, p, 1, 1, 0;\n}\n"
        : "+f"(d[0]), "+f"(d[1]), "+f"(d[2]), "+f"(d[3]), "+f"(d[4]), "+f"(d[5]), "+f"(d[6]), "+f"(d[7]), "+f"(d[8]), "+f"(d[9]), "+f"(d[10]), "+f"(d[11]), "+f"(d[12]), "+f"(d[13]), "+f"(d[14]), "+f"(d[15]), "+f"(d[16]), "+f"(d[17]), "+f"(d[18]), "+f"(d[19]), "+f"(d[20]), "+f"(d[21]), "+f"(d[22]), "+f"(d[23]), "+f"(d[24]), "+f"(d[25]), "+f"(d[26]), "+f"(d[27]), "+f"(d[28]), "+f"(d[29]), "+f"(d[30]), "+f"(d[31]), "+f"(d[32]), "+f"(d[33]), "+f"(d[34]), "+f"(d[35]), "+f"(d[36]), "+f"(d[37]), "+f"(d[38]), "+f"(d[39]), "+f"(d[40]), "+f"(d[41]), "+f"(d[42]), "+f"(d[43]), "+f"(d[44]), "+f"(d[45]), "+f"(d[46]), "+f"(d[47]), "+f"(d[48]), "+f"(d[49]), "+f"(d[50]), "+f"(d[51]), "+f"(d[52]), "+f"(d[53]), "+f"(d[54]), "+f"(d[55]), "+f"(d[56]), "+f"(d[57]), "+f"(d[58]), "+f"(d[59]), "+f"(d[60]), "+f"(d[61]), "+f"(d[62]), "+f"(d[63])
        : "r"(a[0]), "r"(a[1]), "r"(a[2]), "r"(a[3]), "r"(db), "r"(8u), "r"(acc));
}
template <> __device__ __forceinline__ void cv_mma<1>(float (&d)[64], const uint32_t (&a)[4], uint32_t db, int acc) {
    asm volatile("{\n.reg .pred p;\n.reg .b64 b;\nsetp.ne.b32 p, %62, 0;\nmov.b64 b, {%60, %61};\n"
        "wgmma.mma_async.sync.aligned.m64n112k16.f32.bf16.bf16 {%0,%1,%2,%3,%4,%5,%6,%7,%8,%9,%10,%11,%12,%13,%14,%15,%16,%17,%18,%19,%20,%21,%22,%23,%24,%25,%26,%27,%28,%29,%30,%31,%32,%33,%34,%35,%36,%37,%38,%39,%40,%41,%42,%43,%44,%45,%46,%47,%48,%49,%50,%51,%52,%53,%54,%55}, {%56,%57,%58,%59}, b, p, 1, 1, 0;\n}\n"
        : "+f"(d[0]), "+f"(d[1]), "+f"(d[2]), "+f"(d[3]), "+f"(d[4]), "+f"(d[5]), "+f"(d[6]), "+f"(d[7]), "+f"(d[8]), "+f"(d[9]), "+f"(d[10]), "+f"(d[11]), "+f"(d[12]), "+f"(d[13]), "+f"(d[14]), "+f"(d[15]), "+f"(d[16]), "+f"(d[17]), "+f"(d[18]), "+f"(d[19]), "+f"(d[20]), "+f"(d[21]), "+f"(d[22]), "+f"(d[23]), "+f"(d[24]), "+f"(d[25]), "+f"(d[26]), "+f"(d[27]), "+f"(d[28]), "+f"(d[29]), "+f"(d[30]), "+f"(d[31]), "+f"(d[32]), "+f"(d[33]), "+f"(d[34]), "+f"(d[35]), "+f"(d[36]), "+f"(d[37]), "+f"(d[38]), "+f"(d[39]), "+f"(d[40]), "+f"(d[41]), "+f"(d[42]), "+f"(d[43]), "+f"(d[44]), "+f"(d[45]), "+f"(d[46]), "+f"(d[47]), "+f"(d[48]), "+f"(d[49]), "+f"(d[50]), "+f"(d[51]), "+f"(d[52]), "+f"(d[53]), "+f"(d[54]), "+f"(d[55])
        : "r"(a[0]), "r"(a[1]), "r"(a[2]), "r"(a[3]), "r"(db), "r"(8u), "r"(acc));
}
template <> __device__ __forceinline__ void cv_mma<2>(float (&d)[64], const uint32_t (&a)[4], uint32_t db, int acc) {
    asm volatile("{\n.reg .pred p;\n.reg .b64 b;\nsetp.ne.b32 p, %54, 0;\nmov.b64 b, {%52, %53};\n"
        "wgmma.mma_async.sync.aligned.m64n96k16.f32.bf16.bf16 {%0,%1,%2,%3,%4,%5,%6,%7,%8,%9,%10,%11,%12,%13,%14,%15,%16,%17,%18,%19,%20,%21,%22,%23,%24,%25,%26,%27,%28,%29,%30,%31,%32,%33,%34,%35,%36,%37,%38,%39,%40,%41,%42,%43,%44,%45,%46,%47}, {%48,%49,%50,%51}, b, p, 1, 1, 0;\n}\n"
        : "+f"(d[0]), "+f"(d[1]), "+f"(d[2]), "+f"(d[3]), "+f"(d[4]), "+f"(d[5]), "+f"(d[6]), "+f"(d[7]), "+f"(d[8]), "+f"(d[9]), "+f"(d[10]), "+f"(d[11]), "+f"(d[12]), "+f"(d[13]), "+f"(d[14]), "+f"(d[15]), "+f"(d[16]), "+f"(d[17]), "+f"(d[18]), "+f"(d[19]), "+f"(d[20]), "+f"(d[21]), "+f"(d[22]), "+f"(d[23]), "+f"(d[24]), "+f"(d[25]), "+f"(d[26]), "+f"(d[27]), "+f"(d[28]), "+f"(d[29]), "+f"(d[30]), "+f"(d[31]), "+f"(d[32]), "+f"(d[33]), "+f"(d[34]), "+f"(d[35]), "+f"(d[36]), "+f"(d[37]), "+f"(d[38]), "+f"(d[39]), "+f"(d[40]), "+f"(d[41]), "+f"(d[42]), "+f"(d[43]), "+f"(d[44]), "+f"(d[45]), "+f"(d[46]), "+f"(d[47])
        : "r"(a[0]), "r"(a[1]), "r"(a[2]), "r"(a[3]), "r"(db), "r"(8u), "r"(acc));
}
template <> __device__ __forceinline__ void cv_mma<3>(float (&d)[64], const uint32_t (&a)[4], uint32_t db, int acc) {
    asm volatile("{\n.reg .pred p;\n.reg .b64 b;\nsetp.ne.b32 p, %46, 0;\nmov.b64 b, {%44, %45};\n"
        "wgmma.mma_async.sync.aligned.m64n80k16.f32.bf16.bf16 {%0,%1,%2,%3,%4,%5,%6,%7,%8,%9,%10,%11,%12,%13,%14,%15,%16,%17,%18,%19,%20,%21,%22,%23,%24,%25,%26,%27,%28,%29,%30,%31,%32,%33,%34,%35,%36,%37,%38,%39}, {%40,%41,%42,%43}, b, p, 1, 1, 0;\n}\n"
        : "+f"(d[0]), "+f"(d[1]), "+f"(d[2]), "+f"(d[3]), "+f"(d[4]), "+f"(d[5]), "+f"(d[6]), "+f"(d[7]), "+f"(d[8]), "+f"(d[9]), "+f"(d[10]), "+f"(d[11]), "+f"(d[12]), "+f"(d[13]), "+f"(d[14]), "+f"(d[15]), "+f"(d[16]), "+f"(d[17]), "+f"(d[18]), "+f"(d[19]), "+f"(d[20]), "+f"(d[21]), "+f"(d[22]), "+f"(d[23]), "+f"(d[24]), "+f"(d[25]), "+f"(d[26]), "+f"(d[27]), "+f"(d[28]), "+f"(d[29]), "+f"(d[30]), "+f"(d[31]), "+f"(d[32]), "+f"(d[33]), "+f"(d[34]), "+f"(d[35]), "+f"(d[36]), "+f"(d[37]), "+f"(d[38]), "+f"(d[39])
        : "r"(a[0]), "r"(a[1]), "r"(a[2]), "r"(a[3]), "r"(db), "r"(8u), "r"(acc));
}
template <> __device__ __forceinline__ void cv_mma<4>(float (&d)[64], const uint32_t (&a)[4], uint32_t db, int acc) {
    asm volatile("{\n.reg .pred p;\n.reg .b64 b;\nsetp.ne.b32 p, %38, 0;\nmov.b64 b, {%36, %37};\n"
        "wgmma.mma_async.sync.aligned.m64n64k16.f32.bf16.bf16 {%0,%1,%2,%3,%4,%5,%6,%7,%8,%9,%10,%11,%12,%13,%14,%15,%16,%17,%18,%19,%20,%21,%22,%23,%24,%25,%26,%27,%28,%29,%30,%31}, {%32,%33,%34,%35}, b, p, 1, 1, 0;\n}\n"
        : "+f"(d[0]), "+f"(d[1]), "+f"(d[2]), "+f"(d[3]), "+f"(d[4]), "+f"(d[5]), "+f"(d[6]), "+f"(d[7]), "+f"(d[8]), "+f"(d[9]), "+f"(d[10]), "+f"(d[11]), "+f"(d[12]), "+f"(d[13]), "+f"(d[14]), "+f"(d[15]), "+f"(d[16]), "+f"(d[17]), "+f"(d[18]), "+f"(d[19]), "+f"(d[20]), "+f"(d[21]), "+f"(d[22]), "+f"(d[23]), "+f"(d[24]), "+f"(d[25]), "+f"(d[26]), "+f"(d[27]), "+f"(d[28]), "+f"(d[29]), "+f"(d[30]), "+f"(d[31])
        : "r"(a[0]), "r"(a[1]), "r"(a[2]), "r"(a[3]), "r"(db), "r"(8u), "r"(acc));
}
template <> __device__ __forceinline__ void cv_mma<5>(float (&d)[64], const uint32_t (&a)[4], uint32_t db, int acc) {
    asm volatile("{\n.reg .pred p;\n.reg .b64 b;\nsetp.ne.b32 p, %30, 0;\nmov.b64 b, {%28, %29};\n"
        "wgmma.mma_async.sync.aligned.m64n48k16.f32.bf16.bf16 {%0,%1,%2,%3,%4,%5,%6,%7,%8,%9,%10,%11,%12,%13,%14,%15,%16,%17,%18,%19,%20,%21,%22,%23}, {%24,%25,%26,%27}, b, p, 1, 1, 0;\n}\n"
        : "+f"(d[0]), "+f"(d[1]), "+f"(d[2]), "+f"(d[3]), "+f"(d[4]), "+f"(d[5]), "+f"(d[6]), "+f"(d[7]), "+f"(d[8]), "+f"(d[9]), "+f"(d[10]), "+f"(d[11]), "+f"(d[12]), "+f"(d[13]), "+f"(d[14]), "+f"(d[15]), "+f"(d[16]), "+f"(d[17]), "+f"(d[18]), "+f"(d[19]), "+f"(d[20]), "+f"(d[21]), "+f"(d[22]), "+f"(d[23])
        : "r"(a[0]), "r"(a[1]), "r"(a[2]), "r"(a[3]), "r"(db), "r"(8u), "r"(acc));
}
template <> __device__ __forceinline__ void cv_mma<6>(float (&d)[64], const uint32_t (&a)[4], uint32_t db, int acc) {
    asm volatile("{\n.reg .pred p;\n.reg .b64 b;\nsetp.ne.b32 p, %22, 0;\nmov.b64 b, {%20, %21};\n"
        "wgmma.mma_async.sync.aligned.m64n32k16.f32.bf16.bf16 {%0,%1,%2,%3,%4,%5,%6,%7,%8,%9,%10,%11,%12,%13,%14,%15}, {%16,%17,%18,%19}, b, p, 1, 1, 0;\n}\n"
        : "+f"(d[0]), "+f"(d[1]), "+f"(d[2]), "+f"(d[3]), "+f"(d[4]), "+f"(d[5]), "+f"(d[6]), "+f"(d[7]), "+f"(d[8]), "+f"(d[9]), "+f"(d[10]), "+f"(d[11]), "+f"(d[12]), "+f"(d[13]), "+f"(d[14]), "+f"(d[15])
        : "r"(a[0]), "r"(a[1]), "r"(a[2]), "r"(a[3]), "r"(db), "r"(8u), "r"(acc));
}
template <> __device__ __forceinline__ void cv_mma<7>(float (&d)[64], const uint32_t (&a)[4], uint32_t db, int acc) {
    asm volatile("{\n.reg .pred p;\n.reg .b64 b;\nsetp.ne.b32 p, %14, 0;\nmov.b64 b, {%12, %13};\n"
        "wgmma.mma_async.sync.aligned.m64n16k16.f32.bf16.bf16 {%0,%1,%2,%3,%4,%5,%6,%7}, {%8,%9,%10,%11}, b, p, 1, 1, 0;\n}\n"
        : "+f"(d[0]), "+f"(d[1]), "+f"(d[2]), "+f"(d[3]), "+f"(d[4]), "+f"(d[5]), "+f"(d[6]), "+f"(d[7])
        : "r"(a[0]), "r"(a[1]), "r"(a[2]), "r"(a[3]), "r"(db), "r"(8u), "r"(acc));
}
__device__ __forceinline__ void stsm4t(uint32_t addr, uint32_t r0, uint32_t r1, uint32_t r2, uint32_t r3) {
    asm volatile("stmatrix.sync.aligned.m8n8.x4.trans.shared.b16 [%0], {%1,%2,%3,%4};" ::"r"(addr), "r"(r0), "r"(r1), "r"(r2), "r"(r3) : "memory");
}
__device__ __forceinline__ void cp16(uint32_t dst, const void* src, int n = 16) {
    asm volatile("cp.async.cg.shared.global.L2::128B [%0], [%1], 16, %2;" ::"r"(dst), "l"(src), "r"(n) : "memory");
}
__device__ __forceinline__ void cp_arrive(uint32_t bar) { asm volatile("cp.async.mbarrier.arrive.noinc.shared::cta.b64 [%0];" ::"r"(bar) : "memory"); }
__device__ __forceinline__ void lds64(uint32_t& x, uint32_t& y, uint32_t a) { asm volatile("ld.shared.v2.b32 {%0,%1}, [%2];" : "=r"(x), "=r"(y) : "r"(a) : "memory"); }
__device__ __forceinline__ void sts128(uint32_t a, uint32_t x, uint32_t y, uint32_t z, uint32_t w) {
    asm volatile("st.shared.v4.b32 [%0], {%1,%2,%3,%4};" ::"r"(a), "r"(x), "r"(y), "r"(z), "r"(w) : "memory");
}
__device__ __forceinline__ uint32_t bfma2(uint32_t a, uint32_t b, uint32_t c) {
    uint32_t r;
    asm("fma.rn.bf16x2 %0, %1, %2, %3;" : "=r"(r) : "r"(a), "r"(b), "r"(c));
    return r;
}
#define CV_NS 4
#define CV_W 1
constexpr int CV_GC = 8 / CV_NS, CV_NA = (CV_W + 2) * CV_NS;
struct CvAddr { uint32_t pa[2], p0[4], db, rdy, xw, xr, bar; bool wrap, neg[2]; };
template <int G> __device__ __forceinline__ void cv_load(uint32_t (&a)[CV_NA][4], const CvAddr& p) {
    if constexpr (G % CV_GC == 0) mbar_wait(p.rdy + 8 * (G / CV_GC), 0);
#pragma unroll
    for (int i = G * CV_NS; i < (G + 1) * CV_NS; i++) {
        const int of = (i / 2 % 2) * CV_QG + (i / 8) * CV_SL + 256 * (i % 2 + (i / 2 & 2));
        if ((i & 5) == 0) {
#pragma unroll
            for (int e = 0; e < 4; e++) asm volatile("ld.shared.b32 %0, [%1];" : "=r"(a[i % CV_NA][e]) : "r"(p.p0[e] + of) : "memory");
            if (i < 8) { if (p.neg[0]) a[i % CV_NA][0] = 0; if (p.neg[1]) a[i % CV_NA][2] = 0; }
        } else {
            lds64(a[i % CV_NA][0], a[i % CV_NA][1], p.pa[0] + of - 256);
            lds64(a[i % CV_NA][2], a[i % CV_NA][3], p.pa[1] + of - 256);
        }
    }
}
__device__ __forceinline__ float vadd(float a, float b) {
    float r;
    asm volatile("add.f32 %0, %1, %2;" : "=f"(r) : "f"(a), "f"(b));
    return r;
}
template <int K> __device__ __forceinline__ uint32_t cv_tail(float (&d)[64], bool wrap) {
    float* z = d + 56 - 8 * K;
    z[4] = vadd(z[4], K > 0 ? z[10] : 0.f);
    if constexpr (K > 0) z[5] = vadd(z[5], z[11]);
    z[0] = vadd(z[0], z[6]);
    z[1] = vadd(z[1], z[7]);
    return pack2(wrap ? (K > 0 ? z[8] : 0.f) : z[4], wrap ? z[4] : z[0]);
}
template <int K> __device__ __forceinline__ uint32_t cv_fin(const float (&d)[64], uint32_t x) { return pack2(d[61 - 8 * K] + lo2f(x), d[57 - 8 * K] + hi2f(x)); }
template <int G>
__device__ __forceinline__ void cv_steps(float (&d)[2][64], uint32_t (&a)[CV_NA][4], uint32_t (&tv)[2][8], const CvAddr& p) {
    constexpr int K = G / CV_GC, GN = 8 * CV_GC;
    constexpr int T = G - CV_W - CV_GC, F = T - 1, TK = T / CV_GC, FK = F / CV_GC;
    if constexpr (G == 0) cv_load<0>(a, p);
    if constexpr (G < GN) {
        wgmma_fence();
#pragma unroll
        for (int i = G * CV_NS; i < (G + 1) * CV_NS; i++)
            cv_mma<K>(d[i / 2 % 2], a[i % CV_NA], p.db + (i / 2 % 2) * (CV_HPL / 8) + 16 * K + 2 * (i % 2 + (i / 2 & 2)), i & ~2 ? 1 : p.bar >> 8);
        wgmma_commit();
    }
    if constexpr (G < GN - 1) cv_load<G + 1>(a, p);
    if constexpr (T >= 0 && T % CV_GC == 0) {
        tv[0][TK] = cv_tail<TK>(d[0], p.wrap);
        tv[1][TK] = cv_tail<TK>(d[1], p.wrap);
        if constexpr (TK & 1) sts128(p.xw + TK / 2 * 512, tv[0][TK - 1], tv[0][TK], tv[1][TK - 1], tv[1][TK]);
    }
    if constexpr (F >= 0 && F % (2 * CV_GC) == CV_GC) {
        const uint4 x = lds128(p.xr + FK / 2 * 512);
        tv[0][FK - 1] = cv_fin<FK - 1>(d[0], x.x); tv[0][FK] = cv_fin<FK>(d[0], x.y);
        tv[1][FK - 1] = cv_fin<FK - 1>(d[1], x.z); tv[1][FK] = cv_fin<FK>(d[1], x.w);
    }
    if constexpr (G < GN - 1) wgmma_wait<CV_W>();
    if constexpr (G == GN - 1) wgmma_wait<0>();
    if constexpr (T >= 0 && T % (2 * CV_GC) == CV_GC) named_bar_sync(p.bar, 128);
    if constexpr (F < GN - CV_GC) cv_steps<G + 1>(d, a, tv, p);
}

#define CV_PF 15
struct MegaMaps {
    CUtensorMap q, act;
    CUtensorMap w1, w2, w3, w4;
    CUtensorMap k, v, y;
};

__global__ void __cluster_dims__(2, 1, 1) __launch_bounds__(384, 1)
mega_kernel(const __grid_constant__ MegaMaps tm, bf16* __restrict__ outp, bf16* act, const bf16* __restrict__ w1p, const bf16* __restrict__ w2p,
            const bf16* __restrict__ w3p, const bf16* __restrict__ xq, const bf16* __restrict__ kp, const bf16* __restrict__ vp,
            const bf16* __restrict__ shk, const bf16* __restrict__ ssk, const bf16* __restrict__ ssD) {
    extern __shared__ __align__(1024) uint8_t sgen[];
    const uint32_t sbase = smem_u32(sgen);
    const int warp = __shfl_sync(0xffffffffu, threadIdx.x >> 5, 0), lane = threadIdx.x & 31;
    const int rank = blockIdx.x & 1;
    const uint32_t s_bar = sbase + OFF_BAR;
    const uint32_t f5 = s_bar, e5 = s_bar + 64, f4 = s_bar + 144, e4 = s_bar + 104;
    const uint32_t b_rfull = s_bar + 176, b_role = s_bar + 184, b_stg = s_bar + 136, b_h2 = s_bar + 32;
    const uint32_t s_epi = sbase + OFF_EPI, s_stg = sbase + OFF_STG5, s_r = sbase + OFF_R;
    uint8_t* sm = sgen + CV_0;
    const uint32_t sb = sbase + CV_0;
    const int tid = threadIdx.x, wg = warp >> 2, w = warp & 3;
    const int d0 = blockIdx.x * CV_CH;
    const bool cv = blockIdx.x < D_ / CV_CH;
    const uint32_t b_full = sb + CV_BAR, b_rdy = b_full + 64, b_h = b_full + 128;
    GT(0);
    auto row_at = [&](int r) { return sb + CV_SL + (r < 0 ? -8192 : 0) + ((r & 127) >> 5) * 1024 + (r & 7) * 128 + ((r >> 3) & 3) * 32 + ((r ^ rank) & 1) * 16; };
    auto load_kv = [&](int c) {
#pragma unroll
        for (int i = 0; i < 2; i++)
            asm volatile("cp.async.bulk.tensor.4d.shared::cluster.global.mbarrier::complete_tx::bytes.multicast::cluster [%0], [%1, {%3, %4, %4, %5}], [%2], %6;"
                         ::"r"(sb + (c + 1) * CV_SL + rank * 8192 + i * 4096), "l"((uint64_t)(i ? &tm.v : &tm.k)), "r"(b_full + 8 * c), "r"(d0 & ~15), "r"(0),
                         "r"(8 * c + 4 * rank), "h"((uint16_t)3) : "memory");
    };
    auto bulk = [&](uint32_t dst, const void* src, uint32_t n, uint32_t bar) {
        asm volatile("cp.async.bulk.shared::cluster.global.mbarrier::complete_tx::bytes [%0], [%1], %2, [%3];" ::"r"(dst), "l"(src), "r"(n), "r"(bar) : "memory");
    };
    auto put_h = [&](int ch) {
        const uint32_t dk = (tid & 127) ? 0 : *reinterpret_cast<const volatile uint32_t*>(sm + CV_BAR + 160 + 16 * wg + 2 * ch);
        uint4 v[4];
#pragma unroll
        for (int i = 0; i < 4; i++) v[i] = lds128(sbase + ch * 4096 + i * 2048 + (tid & 127) * 16);
        v[0].x = pack2(lo2f(v[0].x) + lo2f(dk), hi2f(v[0].x));
        v[2].x = pack2(lo2f(v[2].x) + hi2f(dk), hi2f(v[2].x));
#pragma unroll
        for (int i = 0; i < 4; i++)
            sts128(sb + CV_H + (2 * ch + (i & 2) + (tid & 1)) * CV_HPL + (127 - ((tid & 127) >> 1)) * 16 - (i & 1) * 1024, v[i].x, v[i].y, v[i].z, v[i].w);
    };
    int bi, bj, m0, tb;
    uint32_t ep;
    auto get_role = [&]() {
        mbar_wait(b_role, 0);
        int role;
        asm volatile("ld.shared.v2.b32 {%0,%1}, [%2];" : "=r"(role), "=r"(ep) : "r"(s_bar + 192) : "memory");
        bi = (role >> 3) * 2 + rank; bj = role & 7; m0 = bi * BM; tb = (role >> 3) * 2048 + rank * 128;
        return role < 64;
    };

    if (warp >= 8) {
        asm volatile("setmaxnreg.dec.sync.aligned.u32 88;");
        cluster_arrive_relaxed();
        if (!cv) cluster_wait(); else {
            const int bt = tid - 256, g = lane >> 2, t = lane & 3;
            if (bt < 16) sts128(row_at((bt & 7) - 8) + (bt >> 3) * 4096, 0, 0, 0, 0);
#pragma unroll
            for (int i = 0; i < 4; i++)
                cp16(row_at(bt) + i * 4096, (i & 1 ? vp : kp) + (size_t)(bt + (i >> 1) * 128) * D_ + d0);
            DBG_S(16 + (3));
            uint2 wa;
            asm volatile("ld.global.nc.v2.b32 {%0,%1}, [%2];" : "=r"(wa.x), "=r"(wa.y) : "l"(shk + (d0 + g) * 4));
            const int mi = lane >> 3, r0 = 32 * w + 8 * ((lane >> 1) & 3) - (lane & 1);
            const uint32_t ka0 = row_at(r0 + 2 * mi - 3), ka1 = row_at(r0 + 2 * (mi & 1) + 5) + (mi >> 1) * 8192;
            const uint32_t va0 = row_at(r0 + 2 * mi + 1) + 4096, va1 = row_at(r0 - 1) + 4096 + (mi & 1) * 8192;
            const uint32_t qd = sb + g * CV_QG + (32 * w + 8 * t) * 8, qd0 = qd + (t & 2) * 16, qd1 = qd + (~t & 2) * 16;
            const uint32_t w0 = __byte_perm(wa.x, 0, 0x1010), w1 = __byte_perm(wa.x, 0, 0x3232), w2 = __byte_perm(wa.y, 0, 0x1010), w3 = __byte_perm(wa.y, 0, 0x3232);
            cluster_wait();
            DBG_S(16 + (5));
            asm volatile("cp.async.wait_all;" ::: "memory");
            named_bar_sync(7, 128);
            DBG_S(16 + (1));
            struct KV { uint32_t k[2][6], v[2][5]; };
            auto get = [&](KV& x, uint32_t so) {
                ldsm4t(x.k[0][0], x.k[0][1], x.k[0][2], x.k[0][3], ka0 + so);
                ldsm4t(x.k[0][4], x.k[0][5], x.k[1][4], x.k[1][5], ka1 + so);
                ldsm4t(x.k[1][0], x.k[1][1], x.k[1][2], x.k[1][3], ka0 + so + 8192);
                asm volatile("ldmatrix.sync.aligned.m8n8.x2.trans.shared.b16 {%0,%1}, [%2];" : "=r"(x.v[0][0]), "=r"(x.v[1][0]) : "r"(va1 + so));
                ldsm4t(x.v[0][1], x.v[0][2], x.v[0][3], x.v[0][4], va0 + so);
                ldsm4t(x.v[1][1], x.v[1][2], x.v[1][3], x.v[1][4], va0 + so + 8192);
            };
            auto build = [&](int c, const KV& x, KV& nx) {
                const uint32_t so = c * CV_SL;
                DBG_F(1);
                uint32_t early;
                asm volatile("{\n.reg .pred p;\nmbarrier.test_wait.parity.shared::cta.b64 p, [%1], 0;\nvote.sync.all.pred p, p, -1;\nselp.u32 %0, 1, 0, p;\n}"
                             : "=r"(early) : "r"(b_full + 8 * (c < 7 ? c + 1 : c)) : "memory");
                if (early) get(nx, so + CV_SL);
                DBG_F(2);
                uint32_t p[8][2];
#pragma unroll
                for (int sg = 0; sg < 2; sg++) {
                    uint32_t u[5], ke[6];
#pragma unroll
                    for (int i = 0; i < 6; i++) ke[i] = __byte_perm(x.k[sg][i], x.k[sg][i ? i - 1 : 0], 0x5432);
#pragma unroll
                    for (int i = 0; i < 5; i++) {
                        u[i] = bmul2(bfma2(x.k[sg][i + 1], w0, bfma2(ke[i + 1], w1, bfma2(x.k[sg][i], w2, bmul2(ke[i], w3)))), x.v[sg][i]);
                        if (i) { p[2 * i - 1][sg] = u[i]; p[2 * i - 2][sg] = __byte_perm(u[i], u[i - 1], 0x5432); }
                    }
                }
                DBG_F(3);
#pragma unroll
                for (int j = 0; j < 4; j++) sts128((j & 2 ? qd1 : qd0) + so + 16 * (j & 1), p[2 * j][0], p[2 * j][1], p[2 * j + 1][0], p[2 * j + 1][1]);
                __syncwarp();
                DBG_F(4);
                if (lane == 0) {
                    mbar_arrive(b_rdy + 8 * c);
                    if (c == w) {
                        if (c < 3) load_kv(c + 5);
                        else { bulk(sbase + 16384, ssk + (size_t)(d0 + 4) * S_, 16384, b_h + 16); bulk(b_full + 192, ssD + d0, 16, b_h + 16); }
                    }
                    if (c == w + 4 && (CV_PF >> w & 1)) {
                        const uint32_t n = w == 0 ? 32768 : w == 3 ? 57344 : 16384;
                        const char* src = reinterpret_cast<const char*>(w == 0 ? xq : w == 1 ? w1p : w == 2 ? w2p : w3p) + (size_t)blockIdx.x * n;
                        asm volatile("cp.async.bulk.prefetch.L2.global [%0], %1;" ::"l"(src), "r"(n) : "memory");
                    }
                }
                DBG_F(5);
                named_bar_sync(7, 128);
                DBG_F(6);
                DBG_S(16 + (c == 0 ? 4 : 5 + c));
                if (!early) { mbar_wait(b_full + 8 * c + 8, 0); get(nx, so + CV_SL); }
                DBG_F(7);
            };
            KV x0, x1;
            get(x0, 0);
#pragma unroll 1
            for (int c = 0; c < 8; c += 2) { build(c, x0, x1); build(c + 1, x1, x0); }
            mbar_wait(b_h + 16, 0);
            put_h(4); put_h(6);
            fence_async_smem();
            __syncwarp();
            if (lane == 0) mbar_arrive(b_full);
            named_bar_sync(7, 128);
            DBG_S(16 + (13));
        }
        asm volatile("setmaxnreg.dec.sync.aligned.u32 72;");
        if (warp == 8) { if (elect_one()) {
            if (rank == 0) {
                uint32_t smid;
                asm volatile("mov.u32 %0, %%smid;" : "=r"(smid));
                const int t = smid >> 1;
                int team = t < 32 ? t & 7 : t < 60 ? 1 + (t - 32) % 7 : t < 62 ? t - 54 : 0;
                const unsigned long long arr = atomicAdd(reinterpret_cast<unsigned long long*>(g_ticket + 16 * FL_PITCH), 1ull);
                const uint32_t e1 = (uint32_t)(arr / NCL) + 1;
                unsigned int* tk = g_ticket + (e1 & 1) * 8 * FL_PITCH;
                int slot = atomicAdd(tk + team * FL_PITCH, 1u);
                atomicAdd(g_ticket + 17 * FL_PITCH, 1u);
                if (blockIdx.x < 16) g_ticket[((~e1 & 1) * 8 + (blockIdx.x >> 1)) * FL_PITCH] = 0;
                if (slot >= 8) {
                    const long long t0 = clock64();
                    while ((int)(*(volatile unsigned int*)(g_ticket + 17 * FL_PITCH) - e1 * NCL) < 0 && clock64() - t0 < 100000) {}
                    for (team = 0; team < 8; team++)
                        if ((slot = atomicAdd(tk + team * FL_PITCH, 1u)) < 8) break;
                }
#pragma unroll
                for (int i = 0; i < 2; i++)
                    asm volatile("st.async.weak.shared::cluster.mbarrier::complete_tx::bytes.v2.b32 [%0], {%1, %2}, [%3];"
                                 ::"r"(mapa_u32(s_bar + 192, i)), "r"(team * 8 + slot), "r"(e1), "r"(mapa_u32(b_role, i)) : "memory");
            }
            if (get_role()) {
            mbar_expect_tx(b_rfull, 32768);
            tma_load_2d(sbase + 16384, &tm.q, b_rfull, bj * 128, m0);
            tma_load_2d(sb + 8 * CV_SL, &tm.q, b_rfull, bj * 128 + 64, m0);
            int s5 = 0, s4 = 0;
            uint32_t p5 = 0, p4 = 1;
            auto putB = [&](const CUtensorMap* tB, int kc, uint32_t bytes) {
                const uint32_t full = f5 + 8 * s5;
                mbar_wait(full + 64, (p5 >> s5) & 1);
                mbar_expect_tx(full, bytes);
                tma_load_2d_mc(s_r + 16384 + rank * 8192 + s5 * R5_STAGE, tB, full, bj * 128 + rank * 64, kc);
                p5 ^= 1u << s5;
            };
            auto putA = [&](int c, int r) {
                tma_load_2d(s_r + s5 * R5_STAGE, &tm.act, f5 + 8 * s5, c, r);
                if (++s5 == R5_N) s5 = 0;
            };
            prefetch_tmap(&tm.act); prefetch_tmap(&tm.w1); prefetch_tmap(&tm.w2); prefetch_tmap(&tm.w3); prefetch_tmap(&tm.w4);
            auto own_first = [&](int it) {
                const int hf = it >= 9, c = it - 2 - 7 * hf;
                return (it < 2 ? 2 * bj + it : 2 * (c + (c >= bj)) + hf) * BK;
            };
            const unsigned int n8 = 8 * ep, nh = (bi == 0 || bi == 15) ? 2 * n8 : 3 * n8;
#pragma unroll 1
            for (int layer = 0; layer < 2; layer++) {
                s5 = 2;
#pragma unroll 1
                for (int kk = -layer; kk < 5 - layer; kk++) {
                    if (kk & 4) {
                        if (layer == 0) { wait_flag(flag_ptr(0, FL_CS, 8 + bj), 8 * n8); fence_proxy_async(); }
                        mbar_wait(e5 + 8, (p5 >> 1) & 1);
                        mbar_expect_tx(f5 + 8, 32768);
                        tma_load_2d(s_r + R5_STAGE, &tm.act, f5 + 8, (bj >> 1) * 256 + rank * 128, R_Y + (tb & ~255) + (bj & 1) * 128);
                        tma_load_2d(s_r + R5_STAGE + 16384, &tm.act, f5 + 8, (bj >> 1) * 256 + rank * 128 + 64, R_Y + (tb & ~255) + (bj & 1) * 128);
                        p5 ^= 2;
                    } else {
                        putB(&tm.w1, own_first(kk), kk < 2 ? 16384 : R5_STAGE);
                        if (++s5 == R5_N) s5 = 0;
                    }
                }
                s5 = 4;
#pragma unroll 1
                for (int kk = 2; kk < 16; kk++) {
                    const int kc = own_first(kk);
                    if (kk >= 4) putB(&tm.w1, kc, R5_STAGE);
                    if (kk == 2 || kk == 9) {
                        wait_flag(flag_ptr(layer, FL_XA + (kk & 1), bi), n8);
                        DP(8 * (FL_XA + (kk & 1)) + 3);
                        fence_proxy_async();
                        DP(8 * (FL_XA + (kk & 1)) + 4);
                    }
                    putA(kc, R_XA + tb);
                }
                mbar_wait(e5 + 24, (p5 >> 3) & 1);
                mbar_arrive(f5 + 24);
                p5 ^= 8;
                s5 = 4;
#pragma unroll 1
                for (int kk = 0; kk < 5; kk++) { putB(&tm.w2, kk * 2 * BK, R5_STAGE); if (++s5 == R5_N) s5 = 0; }
#pragma unroll 1
                for (int kk = 0; kk < 16; kk++) {
                    const int kc = ((kk & 7) * 2 + (kk >> 3)) * BK;
                    if (kk >= 5) putB(&tm.w2, kc, R5_STAGE);
                    if ((kk & 7) == 0) {
                        wait_flag(flag_ptr(layer, FL_H + (kk >> 3), bi), nh);
                        DP(8 * (FL_H + (kk >> 3)) + 3);
                        fence_proxy_async();
                        DP(8 * (FL_H + (kk >> 3)) + 4);
                    }
                    putA(kc, R_H + layer * R_HP + m0 + (int)((0x4031u >> ((kk & 6) << 1)) & 7) - 2);
                }
#pragma unroll 1
                for (int it = 0; it < 32; it++) {
                    const int kc = it >= 16 ? (it - 16) * BK : own_first(it);
                    const int nb = it < 16 ? 4 : 3, n0 = bj * 448 + (it < 16 ? 0 : 256);
                    if (it > 0 && it < 4) {
                        const int i = (it - 1) * 3 >> 1;
                        mbar_wait(e5 + 8 * i, (p5 >> i) & 1);
                        mbar_wait(e5 + 8 * i + 8, (p5 >> (i + 1)) & 1);
                    }
                    mbar_wait(e4 + 8 * s4, p4);
                    if (it >= 16 && it < 19) mbar_wait(e4 + 8 * s4 + 8, p4);
                    uint32_t sa = s_r + s4 * (it < 16 ? R4_STAGE : R4B_STAGE), full = f4 + 8 * s4;
                    mbar_expect_tx(full, (it < 2 ? 0 : 16384) + nb * 8192);
#pragma unroll 1
                    for (int j = (it ^ rank) & 1; j < nb; j += 2) tma_load_2d_mc(sa + (it < 16 ? -32768 : 16384) + j * 8192, &tm.w3, full, n0 + j * 64, kc);
                    if (it == 3 || it == 9) {
                        wait_flag(flag_ptr(layer, FL_X1 + (it >> 3), bi), n8);
                        DP(8 * (FL_X1 + (it >> 3)) + 3);
                        fence_proxy_async();
                        DP(8 * (FL_X1 + (it >> 3)) + 4);
                        if (it == 3) tma_load_2d(s_r + 2 * R4_STAGE, &tm.act, f4 + 16, own_first(2), R_X1 + tb);
                    }
                    if (it >= 3) tma_load_2d(sa, &tm.act, full, kc, R_X1 + tb);
                    if (++s4 == R4_N) { s4 = 0; p4 ^= 1; }
                }
                wait_flag(flag_ptr(layer, FL_H2, bi), n8);
                fence_proxy_async();
                s5 = 0;
#pragma unroll 1
                for (int j = 0; j < 7; j++) {
                    if (j > 0 && (j & 1) == 0) {
                        mbar_wait(b_h2 + 4 * j, layer);
                        fence_proxy_async();
                    }
                    const int ra = R_H2 + (j >> 1) * 256 + tb;
#pragma unroll 1
                    for (int b = 0; b < 8; b++) {
                        if (j == 0 && b < R4_N) mbar_wait(e4 + 8 * b, p4);
                        putB(&tm.w4, (7 * b + j) * BK, R5_STAGE);
                        putA(((j & 1) * 8 + b) * BK, ra);
                    }
                }
            }
        } } } else {
            if (cv) {
                const bool is1 = warp == 10;
                const int bi = blockIdx.x >> 3, bj = blockIdx.x & 7;
                const int pitch = is1 ? D_ : F_, c = is1 ? bj * 128 + (lane & 15) * 8 : bj * 448 + min((warp & 2) * 128 + lane * 8, 440);
                const bf16* p = (is1 ? w1p : w3p) + ((bi * 64 + (is1 ? (lane >> 4) * 32 : 0)) * pitch + c);
                float a[8];
#pragma unroll
                for (int i = 0; i < 8; i++) a[i] = 0.f;
#pragma unroll 1
                for (int r0 = is1 ? 32 : 0; r0 < 64; r0 += 8) {
                    uint4 v[8];
#pragma unroll
                    for (int r = 0; r < 8; r++, p += pitch) v[r] = __ldg(reinterpret_cast<const uint4*>(p));
#pragma unroll
                    for (int r = 0; r < 8; r++) {
                        a[0] += lo2f(v[r].x); a[1] += hi2f(v[r].x); a[2] += lo2f(v[r].y); a[3] += hi2f(v[r].y);
                        a[4] += lo2f(v[r].z); a[5] += hi2f(v[r].z); a[6] += lo2f(v[r].w); a[7] += hi2f(v[r].w);
                    }
                }
                if (is1) {
#pragma unroll
                    for (int i = 0; i < 8; i++) a[i] += __shfl_xor_sync(0xffffffffu, a[i], 16);
                }
                float4* dst = reinterpret_cast<float4*>(g_cpart + bi * (F_ + D_) + (is1 ? F_ : 0) + c);
                dst[0] = make_float4(a[0], a[1], a[2], a[3]);
                dst[1] = make_float4(a[4], a[5], a[6], a[7]);
                asm volatile("fence.release.gpu;" ::: "memory");
                __syncwarp();
                if (lane == 0) asm volatile("red.relaxed.gpu.global.add.u32 [%0], 1;" ::"l"(flag_ptr(!is1, FL_CS, bj)) : "memory");
            }
            float4 keep[2];
            const bool on = get_role();
#pragma unroll 1
            for (int layer = on ? 0 : 2; layer < 2; layer++) {
                if (warp == 10) {
#pragma unroll 1
                    for (int kind = 0; kind < 6; kind += 2) {
                        const uint32_t src = kind == FL_H ? s_stg : s_epi;
                        const int r = kind == FL_H ? R_H + layer * R_HP + m0 : (kind == FL_XA ? R_XA : R_X1) + tb;
#pragma unroll 1
                        for (int hf = 0; hf < 2; hf++) {
                            named_bar_sync(5 + hf, 288);
                            if (lane == 0) {
                                DP(8 * (kind + hf));
                                tma_store_2d(&tm.act, src + hf * 16384, bj * 128 + hf * 64, r);
                                asm volatile("cp.async.bulk.commit_group;" ::: "memory");
                                asm volatile("cp.async.bulk.wait_group 0;" ::: "memory");
                                DP(8 * (kind + hf) + 1);
                                DP(8 * (kind + hf) + 2);
                                unsigned int* fp = flag_ptr(layer, kind + hf, bi);
                                asm volatile("red.relaxed.gpu.global.add.u32 [%0], 1;" ::"l"(fp) : "memory");
                                if (kind == FL_H) {
                                    if (bi > 0) asm volatile("red.relaxed.gpu.global.add.u32 [%0], 1;" ::"l"(fp - FL_PITCH) : "memory");
                                    if (bi < 15) asm volatile("red.relaxed.gpu.global.add.u32 [%0], 1;" ::"l"(fp + FL_PITCH) : "memory");
                                }
                            }
                            __syncwarp();
                        }
                    }
                } else if (warp == 9) {
                    uint32_t* rs = reinterpret_cast<uint32_t*>(sgen + OFF_RS);
                    float* cs = reinterpret_cast<float*>(sgen + OFF_CS);
#pragma unroll 1
                    for (int which = 0; which < 2; which++) {
                        if (layer == 0) {
                            if (lane == 0) wait_flag(flag_ptr(which, FL_CS, bj), (16 << which) * ep);
                            __syncwarp();
#pragma unroll 1
                            for (int c = (which ? 384 : 768) + lane * 4; c < 896; c += 128) {
                                const float* cp = g_cpart + (which ? bj * 448 + min(c & 511, 444) : F_ + bj * 128 + lane * 4);
                                float4 a = make_float4(0.f, 0.f, 0.f, 0.f);
#pragma unroll
                                for (int r0 = 0; r0 < 16; r0 += 8) {
                                    float4 v[8];
#pragma unroll
                                    for (int r = 0; r < 8; r++) v[r] = __ldcg(reinterpret_cast<const float4*>(cp + (r0 + r) * (F_ + D_)));
#pragma unroll
                                    for (int r = 0; r < 8; r++) { a.x += v[r].x; a.y += v[r].y; a.z += v[r].z; a.w += v[r].w; }
                                }
                                if (c < 768) *reinterpret_cast<float4*>(cs + min(c & 511, 444)) = a;
                                keep[0] = a;
                            }
                        }
                        if (lane == 0 && (layer | which)) wait_flag(flag_ptr(layer, which == 0 ? FL_XA : FL_X1, bi), 8 * ep);
                        __syncwarp();
                        *reinterpret_cast<float4*>(cs + 256 + lane * 4) = keep[0];
                        { const float4 k0 = keep[0]; keep[0] = keep[1]; keep[1] = k0; }
#pragma unroll 1
                        for (int i = 0; i < 4; i++) {
                            const int r = i * 32 + lane;
                            float mean, var;
                            row_stats(g_stats + (3 * layer + 1 + which) * S_ * 8 + bi * 1024 + r, ep << 31, mean, var);
                            const uint32_t c0 = pack2(mean, fsqrt(bfr(bfr(var) + 1e-5f)));
                            if (lane < 19 && (layer | which | i) == 0) asm volatile("mbarrier.inval.shared::cta.b64 [%0];" ::"r"(b_full + 8 * lane) : "memory");
                            __syncwarp();
                            rs[r] = c0;
                            const float rd = frcp(hi2f(c0));
                            rs[128 + r] = pack2((mean - lo2f(c0)) * rd, fsqrt(bfr(bfr(var * rd * rd) + 1e-5f)));
                        }
                        __syncwarp();
                        named_bar_arrive(3, 288);
                    }
                }
                const uint32_t s_cnt = s_bar + 224;
                auto ticket = [&](uint32_t a) {
                    uint32_t v = 0;
                    if (lane == 0) asm volatile("atom.acq_rel.cta.shared.add.u32 %0, [%1], 1;" : "=r"(v) : "r"(a) : "memory");
                    return v;
                };
                mbar_wait(b_stg, 0);
                int u = __shfl_sync(0xffffffffu, ticket(s_cnt + 16 + 4 * layer), 0), step = 0;
#pragma unroll 1
                while (true) {
#pragma unroll 1
                    for (; step < 5 && u >= (int)((0x3830201810ull >> (8 * step)) & 255); step++) {
                        if (step == 1) { named_bar_arrive(4, 352); continue; }
                        const int part = step ? step - 1 : 0;
                        __syncwarp();
                        if (ticket(s_cnt + 4 * part) == 3 * layer + 2) {
                            asm volatile("fence.release.gpu;" ::: "memory");
                            unsigned int* fp = flag_ptr(layer, FL_H2 + part, bi);
                            asm volatile("red.relaxed.gpu.global.add.u32 [%0], 1;" ::"l"(fp) : "memory");
                            if (part > 0) { wait_flag(fp, 8 * ep); mbar_arrive(b_h2 + 8 * part); }
                        }
                        __syncwarp();
                        if (step == 2) mbar_wait(b_stg, 1);
                    }
                    if (u >= 56) break;
                    const uint32_t un = ticket(s_cnt + 16 + 4 * layer);
                    const int job = u >> 3, r = (u & 7) * 16 + (lane >> 3);
                    const uint32_t sp = sbase + ((job & 2) ? OFF_STG5 : OFF_EPI) + r * 256 + (job & 1) * 128;
                    bf16* gp = act + (size_t)(R_H2 + (job >> 1) * 256 + tb + r) * D_ + ((job & 1) * 8 + bj) * 64 + (lane & 7) * 8;
                    uint4 v[4];
#pragma unroll
                    for (int e = 0; e < 4; e++) v[e] = lds128(sp + e * 1024 + (((lane & 7) ^ ((r + 4 * e) & 7)) << 4));
#pragma unroll
                    for (int e = 0; e < 4; e++) stg128(gp + 4 * e * D_, gelu8h(v[e]));
                    u = __shfl_sync(0xffffffffu, un, 0);
                }
                if (layer == 0 && warp == 11) {
                    const char* ps = reinterpret_cast<const char*>(g_stats + 3 * S_ * 8 + bi * 1024) + lane * 128;
                    const char* py = reinterpret_cast<const char*>(act + (size_t)(R_Y + (tb & ~255) + (bj & 1) * 128 + (lane >> 1)) * D_ + (bj >> 1) * 256 + rank * 128) + (lane & 1) * 128;
#pragma unroll 1
                    for (int i = 0; i < 8; i++) {
                        asm volatile("prefetch.global.L2 [%0];" ::"l"(py + (size_t)i * 16 * D_ * 2) : "memory");
                        if (i >= 6) asm volatile("prefetch.global.L2 [%0];" ::"l"(ps + (i & 1) * 4096) : "memory");
                        __nanosleep(400);
                    }
                }
            }
        }
        __syncwarp();
        asm volatile("barrier.cluster.arrive.relaxed.aligned;\nbarrier.cluster.wait.acquire.aligned; // helpers" ::: "memory");
    } else {
        if (elect_one()) {
            mbar_init(b_full + 8 * warp, warp ? 1 : 4);
            mbar_init(b_rdy + 8 * warp, 4);
            if (warp) mbar_expect_tx(b_full + 8 * warp, 16384);
            if (w == 0 && cv) {
                mbar_init(b_h + 8 * wg, 1);
                mbar_expect_tx(b_h + 8 * wg, 8192 + 16);
                fence_async_smem();
                bulk(sbase + wg * 8192, ssk + (size_t)(d0 + 2 * wg) * S_, 8192, b_h + 8 * wg);
                bulk(b_full + 160 + 16 * wg, ssD + d0, 16, b_h + 8 * wg);
            }
            mbar_init(s_bar + 8 * warp, 1);
            mbar_init(s_bar + 64 + 8 * warp, 4);
            mbar_init(s_bar + 128 + 8 * warp, warp < 2 ? 4 << warp : 1);
            if (warp == 0) mbar_arrive(f5);
            if (warp == 7) mbar_expect_tx(b_role, 8);
            if (warp == 1) { mbar_init(b_h + 16, 1); mbar_expect_tx(b_h + 16, 16384 + 16); }
            if (w == 2) sts128(s_bar + 224 + 16 * wg, 0, 0, 0, 0);
            asm volatile("fence.mbarrier_init.release.cluster;" ::: "memory");
            if (warp == 2) { prefetch_tmap(&tm.k); prefetch_tmap(&tm.v); }
        }
        __syncwarp();
        DBG_W(1);
        cluster_arrive_relaxed();
        asm volatile("setmaxnreg.inc.sync.aligned.u32 208;");
        DBG_W(2);
        const int zi = (tid & 127) - 32;
        if (zi >= 0 && zi < 48) sts128(sb + CV_H + (4 * wg + (zi / 6 & 3) + (zi / 24) * 8) * CV_HPL + 2048 + (zi % 6) * 16, 0, 0, 0, 0);
        DBG_W(3);
        cluster_wait();
        DBG_W(5);
        if (cv) {
            if (tid == 32) {
#pragma unroll 1
                for (int c = 1; c < 5; c++) load_kv(c);
                prefetch_tmap(&tm.y);
            }
            __syncwarp();
            DBG_W(6);
            const int g = lane >> 2, t = lane & 3;
            const int x0 = 32 + 8 * w + g - 2 * t;
            CvAddr p;
            p.rdy = b_rdy;
            p.bar = 1 + wg;
            p.xr = sbase + (warp ^ 2) * 2048 + lane * 16;
            p.xw = sbase + warp * 2048 + (g * 4 + ((t - (w >> 1)) & 3)) * 16;
            p.wrap = t == 0 && w >= 2;
            mbar_wait(b_h + 8 * wg, 0);
            DBG_W(4);
            put_h(2 * wg);
            fence_async_smem();
            named_bar_sync(1 + wg, 128);
            float acc[2][64];
            zero_acc(acc[0]); zero_acc(acc[1]);
#pragma unroll 1
            for (int round = 0; round < 2; round++) {
                const int ch = round * 4 + 2 * wg;
                uint32_t a[CV_NA][4], tv[2][8];
#pragma unroll
                for (int e = 0; e < 2; e++) {
                    const int x = x0 - 8 * e;
                    p.neg[e] = x < 32;
                    p.pa[e] = sb + ch * CV_QG + 8 * (x ^ (x >> 2 & 4));
                    p.p0[2 * e] = p.pa[e] + (x < 32 ? 768 + 4 - CV_SL : -256);
                    p.p0[2 * e + 1] = p.pa[e] + (x < 32 ? 768 : -256 + 4);
                }
                p.db = (((sb + CV_H + ch * 2 * CV_HPL) & 0x3FFFF) >> 4) | ((CV_HPL / 16) << 16);
                if (round) mbar_wait(b_full, 0);
                DBG_S(7 + 3 * round);
                cv_steps<0>(acc, a, tv, p);
                DBG_S(8 + 3 * round);
                const int r128 = 4 * (lane >> 3) + 2 * (lane & 1) + ((~lane >> 2) & 1);
#pragma unroll
                for (int i = 0; i < 2; i++) {
                    const uint32_t ta = sb + ((ch + i + 1) & 7) * CV_SL + 12288 + r128 * 128 + ((((~lane & 2) * 2 + w) ^ (r128 & 7)) << 4);
                    stsm4t(ta, tv[i][0], tv[i][1], tv[i][2], tv[i][3]);
                    stsm4t(ta + 2048, tv[i][4], tv[i][5], tv[i][6], tv[i][7]);
                }
                fence_async_smem();
                named_bar_sync(1 + wg, 128);
                if ((tid & 127) < 2) {
                    const int d = d0 + ch + (tid & 1);
                    asm volatile("cp.async.bulk.tensor.4d.global.shared::cta.bulk_group [%0, {%2, %3, %4, %2}], [%1];"
                                 ::"l"((uint64_t)&tm.y), "r"(sb + ((ch + (tid & 1) + 1) & 7) * CV_SL + 12288), "r"(0), "r"(4 * (d >> 8)), "r"(d & 255) : "memory");
                    asm volatile("cp.async.bulk.commit_group;" ::: "memory");
                }
                __syncwarp();
                DBG_S(9 + 3 * round);
            }
            GT(1);
        }
        DT(0);
        GT(2);
        auto put_y = [&]() {
            if ((tid & 127) < 2 && cv) {
                asm volatile("cp.async.bulk.wait_group 0;" ::: "memory");
                asm volatile("red.relaxed.gpu.global.add.u32 [%0], 1;" ::"l"(flag_ptr(0, FL_CS, 8 + (blockIdx.x >> 4))) : "memory");
            }
            __syncwarp();
        };
        asm volatile("setmaxnreg.inc.sync.aligned.u32 216;");
        if (!get_role()) put_y(); else {
        const bool rel_on = (tid & 95) == 0;
        const uint32_t rel5 = mapa_u32(e5, (warp & 1) ^ rank), rel4 = rel5 + (e4 - e5);
        const uint32_t da0 = desc_a(s_r + wg * 8192), db0 = desc_b(s_r + BM * BK * 2), dae = da0 + (OFF_EPI - OFF_R) / 16, db4 = db0 - 49152 / 16;
        auto skip5 = [&](RingState& rs) {
            if (rel_on) mbar_arrive_cluster(rel5 + 8 * rs.st);
            rs.st++;
        };
        const int t = lane & 3;
        const int row = warp * 16 + (lane >> 2);
        const uint32_t st_w = (uint32_t)((warp * 16 + ((lane >> 3) & 1) * 8 + (lane & 7)) * 256 + (((lane >> 4) ^ (lane & 7)) << 4));
        const uint32_t fr = (uint32_t)((warp * 16 + ((lane >> 3) & 1) * 8 + (lane & 7)) * 128 + (((lane >> 4) ^ (lane & 7)) << 4));
        auto copy_out = [&](bf16* dst, uint32_t src) {
            const int r = warp * 16 + (lane >> 4);
            bf16* ox = dst + (size_t)(m0 + r) * D_ + bj * 128 + (lane & 15) * 8;
            const uint32_t ra = src + ((lane & 15) >> 3) * 16384 + r * 128;
            uint4 v[8];
#pragma unroll
            for (int it = 0; it < 8; it++) v[it] = lds128(ra + it * 256 + (((lane & 7) ^ ((2 * it + (lane >> 4)) & 7)) << 4));
#pragma unroll
            for (int it = 0; it < 8; it++) *reinterpret_cast<uint4*>(ox + (size_t)it * 2 * D_) = v[it];
        };
        auto put_stats = [&](const uint32_t (&w)[32], int which) {
            float sm[2] = {0.f, 0.f}, sq[2] = {0.f, 0.f};
#pragma unroll
            for (int e = 0; e < 32; e++) {
                const float e0 = lo2f(w[e]), e1 = hi2f(w[e]);
                sm[e & 1] += e0 + e1; sq[e & 1] = fmaf(e0, e0, fmaf(e1, e1, sq[e & 1]));
            }
#pragma unroll
            for (int of = 1; of < 4; of <<= 1)
#pragma unroll
                for (int e = 0; e < 2; e++) { sm[e] += __shfl_xor_sync(0xffffffffu, sm[e], of); sq[e] += __shfl_xor_sync(0xffffffffu, sq[e], of); }
            if (t < 2) {
                const float s1 = t ? sm[1] : sm[0], q1 = t ? sq[1] : sq[0], mu = s1 * (1.0f / 128);
                asm volatile("{\n.reg .b64 t;\nmov.b64 t, {%1, %2};\nst.relaxed.gpu.global.b64 [%0], t;\n}"
                             ::"l"(g_stats + which * S_ * 8 + (bi * 8 + bj) * 128 + row + 8 * t), "f"(mu), "r"(__float_as_uint(fmaxf(q1 - s1 * mu, 0.f)) | ep << 31) : "memory");
            }
        };
        const float* csp = reinterpret_cast<const float*>(sgen + OFF_CS) + 2 * t;
        float mrow[2], rrow[2];
        const uint32_t* rsp = reinterpret_cast<const uint32_t*>(sgen + OFF_RS) + row;
        auto row_consts = [&](bool twice) {
#pragma unroll
            for (int e = 0; e < 2; e++) {
                const uint32_t q0 = rsp[8 * e], q1 = rsp[128 + 8 * e];
                mrow[e] = twice ? fmaf(lo2f(q1), hi2f(q0), lo2f(q0)) : lo2f(q0);
                rrow[e] = 0.5f * frcp(twice ? hi2f(q0) * hi2f(q1) : hi2f(q0));
            }
        };
        auto stage = [&](const float* acc, uint32_t dst, int j0, float2 (&cs)[8], const float* cnext) {
            float2 cn[8];
#pragma unroll
            for (int e = 0; e < 8; e++) cn[e] = *reinterpret_cast<const float2*>(cnext + 8 * e);
#pragma unroll
            for (int j = 0; j < 8; j += 2) {
                uint32_t w[4];
#pragma unroll
                for (int e = 0; e < 2; e++) {
                    const float* a = acc + 4 * (j + e);
                    w[2 * e] = pack2(fmaf(-mrow[0], cs[j + e].x, a[0]) * rrow[0], fmaf(-mrow[0], cs[j + e].y, a[1]) * rrow[0]);
                    w[2 * e + 1] = pack2(fmaf(-mrow[1], cs[j + e].x, a[2]) * rrow[1], fmaf(-mrow[1], cs[j + e].y, a[3]) * rrow[1]);
                }
                stsm4((dst + st_w) ^ (((j0 + j) & 15) << 4), w[0], w[1], w[2], w[3]);
            }
#pragma unroll
            for (int e = 0; e < 8; e++) cs[e] = cn[e];
        };
        RingState r5{1, 0}, r4{0, 0};
        DT(1);
        uint32_t x[32];
        mbar_wait(b_rfull, 0);
#pragma unroll
        for (int jp = 0; jp < 8; jp++) ldsm4(x[4 * jp], x[4 * jp + 1], x[4 * jp + 2], x[4 * jp + 3], sbase + 16384 + (fr ^ ((jp & 3) << 5)) + (jp >> 2) * (16384 + 8 * CV_SL));
#pragma unroll 1
        for (int layer = 0; layer < 2; layer++) {
            {
                DT(2 + 24 * layer);
                put_stats(x, 3 * layer);
                if (layer == 0) {
                    put_y();
                    named_bar_sync(9 + wg, 128);
                    if ((tid & 95) < R5_N) mbar_arrive_cluster(rel5 + 8 * lane);
                }
                DT(20 + 24 * layer);
                DT(22 + 24 * layer);
                uint32_t mb[2];
                float rd[2];
                {
                    float mean, var;
                    row_stats(g_stats + 3 * layer * S_ * 8 + bi * 1024 + warp * 16 + (lane & 15), ep << 31, mean, var);
                    __syncwarp();
                    const float r1 = frcp(bfr(fsqrt(bfr(bfr(var) + 1e-5f))));
                    const uint32_t m1 = pack2(mean, mean);
#pragma unroll
                    for (int e = 0; e < 2; e++) { mb[e] = __shfl_sync(0xffffffffu, m1, (lane >> 2) + 8 * e); rd[e] = __shfl_sync(0xffffffffu, r1, (lane >> 2) + 8 * e); }
                }
                DT(21 + 24 * layer);
                mbar_wait(f5 + 8, r5.ph);
                if (layer == 0) GT(3);
                const uint32_t ya = s_r + R5_STAGE + wg * 16384 + ((lane >> 4) * 8 + (lane & 7)) * 128 + ((((warp & 3) * 2 + ((lane >> 3) & 1)) ^ (lane & 7)) << 4);
                uint32_t y[16];
#pragma unroll
                for (int e = 0; e < 32; e++) {
                    if ((e & 15) == 0) {
#pragma unroll
                        for (int jp = 0; jp < 4; jp++) ldsm4t(y[4 * jp], y[4 * jp + 1], y[4 * jp + 2], y[4 * jp + 3], ya + jp * 2048 + e * 512);
                    }
                    const uint32_t d = bsub2(x[e], mb[e & 1]);
                    x[e] = badd2(x[e], bmul2(pack2(lo2f(d) * rd[e & 1], hi2f(d) * rd[e & 1]), y[e & 15]));
                    if ((e & 3) == 3) stsm4(s_epi + (fr ^ (((e >> 2) & 3) << 5)) + (e >> 4) * 16384, x[e - 3], x[e - 2], x[e - 1], x[e]);
                    if ((e & 15) == 15) { fence_async_smem(); named_bar_arrive(5 + (e >> 4), 288); }
                }
                DT(19 + 24 * layer);
                named_bar_sync(9 + wg, 128);
                skip5(r5);
                DT(3 + 24 * layer);
            }
            {
                float acc[64];
                zero_acc(acc);
                kblock<128, R5_N>(acc, dae, db0 + 2 * (R5_STAGE / 16), f5, r5);
                kblock<128, R5_N>(acc, dae + 1024, db0 + 3 * (R5_STAGE / 16), f5, r5);
                put_stats(x, 3 * layer + 1);
                wgmma_wait<1>();
                if (rel_on) mbar_arrive_cluster(rel5 + 16);
                mainloop<128, R5_N, R5_STAGE>(acc, 14, da0, db0, f5, rel5, rel_on, r5, 15 + 24 * layer);
                DT(4 + 24 * layer);
                named_bar_sync(3, 288);
                row_consts(true);
                float2 cs[8];
#pragma unroll
                for (int j = 0; j < 16; j += 2) {
                    if ((j & 7) == 0) {
#pragma unroll
                        for (int e = 0; e < 8; e++) cs[e] = *reinterpret_cast<const float2*>(csp + 256 + 8 * (j + e));
                    }
                    uint32_t w[4];
#pragma unroll
                    for (int e = 0; e < 4; e++) {
                        const float* a = acc + 4 * j + 2 * e;
                        const float2 c = cs[(j & 7) + (e >> 1)];
                        w[e] = pack2(gelu_tanh_h(fmaf(-mrow[e & 1], c.x, a[0]) * rrow[e & 1]), gelu_tanh_h(fmaf(-mrow[e & 1], c.y, a[1]) * rrow[e & 1]));
                    }
                    stsm4(s_stg + (fr ^ ((j & 7) << 4)) + (j >> 3) * 16384, w[0], w[1], w[2], w[3]);
                    if ((j & 7) == 6) { fence_async_smem(); named_bar_arrive(5 + (j >> 3), 288); }
                }
                DT(5 + 24 * layer);
            }
            {
                float acc[64];
                zero_acc(acc);
                uint32_t u[32];
                {
                    uint32_t mb[2];
                    float rd[2];
#pragma unroll
                    for (int e = 0; e < 2; e++) { const uint32_t q0 = rsp[8 * e]; mb[e] = (q0 & 0xffffu) * 0x10001u; rd[e] = frcp(hi2f(q0)); }
#pragma unroll
                    for (int e = 0; e < 32; e++) {
                        const uint32_t d = bsub2(x[e], mb[e & 1]);
                        u[e] = pack2(lo2f(d) * rd[e & 1], hi2f(d) * rd[e & 1]);
                        asm volatile("" : "+r"(u[e]));
                    }
                }
                mbar_wait(f5 + 24, r5.ph);
                skip5(r5);
                kblock<128, R5_N>(acc, da0 + 4 * (R5_STAGE / 16), db0 + 4 * (R5_STAGE / 16), f5, r5);
                DT(16 + 24 * layer);
                mainloop<128, R5_N, R5_STAGE>(acc, 15, da0, db0, f5, rel5, rel_on, r5, -1);
                DT(6 + 24 * layer);
#pragma unroll
                for (int j = 0; j < 16; j += 2) {
#pragma unroll
                    for (int e = 0; e < 4; e++) u[2 * j + e] = badd2(u[2 * j + e], pack2(acc[4 * j + 2 * e], acc[4 * j + 2 * e + 1]));
                    stsm4(s_epi + (fr ^ ((j & 7) << 4)) + (j >> 3) * 16384, u[2 * j], u[2 * j + 1], u[2 * j + 2], u[2 * j + 3]);
                    if ((j & 7) == 6) { fence_async_smem(); named_bar_arrive(5 + (j >> 3), 288); }
                }
#pragma unroll
                for (int e = 0; e < 32; e++) x[e] = badd2(x[e], u[e]);
                named_bar_sync(9 + wg, 128);
                DT(7 + 24 * layer);
                if (layer == 0) GT(7);
            }
            {
                float2 cs[8];
                {
                    float acc[128];
                    zero_acc(acc);
                    kblock<256, R4_N>(acc, dae, db4, f4, r4);
                    kblock<256, R4_N>(acc, dae + 1024, db4 + R4_STAGE / 16, f4, r4);
                    {
                        uint32_t w[32];
#pragma unroll
                        for (int jp = 0; jp < 8; jp++) ldsm4(w[4 * jp], w[4 * jp + 1], w[4 * jp + 2], w[4 * jp + 3], s_epi + (fr ^ ((jp & 3) << 5)) + (jp >> 2) * 16384);
                        put_stats(w, 3 * layer + 2);
                    }
                    wgmma_wait<1>();
                    if (rel_on) mbar_arrive_cluster(rel4);
                    mainloop<256, R4_N, R4_STAGE>(acc, 14, da0, db4, f4, rel4, rel_on, r4, 17 + 24 * layer);
                    DT(8 + 24 * layer);
                    named_bar_sync(3, 288);
                    row_consts(false);
#pragma unroll
                    for (int e = 0; e < 8; e++) cs[e] = *reinterpret_cast<const float2*>(csp + 8 * e);
#pragma unroll
                    for (int j = 0; j < 32; j += 8) stage(acc + 4 * j, j < 16 ? s_epi : s_stg, j, cs, csp + 8 * (j + 8));
                    __syncwarp();
                if (lane == 0) mbar_arrive(b_stg);
                }
                DT(9 + 24 * layer);
                float acc[96];
                zero_acc(acc);
                kblock<192, R4_N>(acc, da0, db0, f4, r4);
                mainloop<192, R4_N, R4B_STAGE>(acc, 15, da0, db0, f4, rel4, rel_on, r4, -1);
                DT(10 + 24 * layer);
                named_bar_sync(4, 352);
#pragma unroll
                for (int j = 0; j < 24; j += 8) stage(acc + 4 * j, j < 16 ? s_epi : s_stg, j, cs, csp + 256 + 8 * (j < 16 ? j + 8 : 0));
                __syncwarp();
                if (lane == 0) mbar_arrive(b_stg);
                DT(11 + 24 * layer);
            }
            {
                float acc[64];
#pragma unroll
                for (int i = 0; i < 32; i++) asm volatile("shl.b32 %0, %2, 16;\nand.b32 %1, %2, 0xffff0000;" : "=f"(acc[2 * i]), "=f"(acc[2 * i + 1]) : "r"(x[i]));
                kblock<128, R5_N>(acc, da0, db0, f5, r5);
                DT(18 + 24 * layer);
                mainloop<128, R5_N, R5_STAGE>(acc, 55, da0, db0, f5, rel5, rel_on, r5, 62 - 40 * (layer ^ 1));
                DT(12 + 24 * layer);
#pragma unroll
                for (int i = 0; i < 32; i++) x[i] = pack2(acc[2 * i], acc[2 * i + 1]);
                DT(13 + 24 * layer);
                if (layer == 0) GT(6);
                DT(14 + 24 * layer);
            }
        }
#pragma unroll
        for (int jp = 0; jp < 8; jp++) stsm4(s_epi + (fr ^ ((jp & 3) << 5)) + (jp >> 2) * 16384, x[4 * jp], x[4 * jp + 1], x[4 * jp + 2], x[4 * jp + 3]);
        __syncwarp();
        copy_out(outp, s_epi);
        DT(38);
        GT(4);
        }
        cluster_arrive_relaxed();
        cluster_wait();
    }
}

typedef CUresult (*PFN_encodeTiled)(CUtensorMap*, CUtensorMapDataType, cuuint32_t, void*, const cuuint64_t*, const cuuint64_t*,
                                    const cuuint32_t*, const cuuint32_t*, CUtensorMapInterleave, CUtensorMapSwizzle,
                                    CUtensorMapL2promotion, CUtensorMapFloatOOBfill);

static CUtensorMap make_map(PFN_encodeTiled enc, const void* ptr, int inner, int outer, int box_inner, int box_outer,
                            CUtensorMapSwizzle swz = CU_TENSOR_MAP_SWIZZLE_128B) {
    CUtensorMap m;
    cuuint64_t dims[2] = {(cuuint64_t)inner, (cuuint64_t)outer};
    cuuint64_t strides[1] = {(cuuint64_t)inner * 2};
    cuuint32_t box[2] = {(cuuint32_t)box_inner, (cuuint32_t)box_outer};
    cuuint32_t es[2] = {1, 1};
    enc(&m, CU_TENSOR_MAP_DATA_TYPE_BFLOAT16, 2, const_cast<void*>(ptr), dims, strides, box, es, CU_TENSOR_MAP_INTERLEAVE_NONE,
        swz, CU_TENSOR_MAP_L2_PROMOTION_L2_256B, CU_TENSOR_MAP_FLOAT_OOB_FILL_NONE);
    return m;
}

extern "C" void kernel_launch(void* const* d_in, const int* in_sizes, int n_in, void* d_out, int out_size) {
    const bf16* A_q = (const bf16*)d_in[0];
    const bf16* A_k = (const bf16*)d_in[1];
    const bf16* A_v = (const bf16*)d_in[2];
    const bf16* A_shk = (const bf16*)d_in[3];
    const bf16* A_ssk = (const bf16*)d_in[4];
    const bf16* A_ssD = (const bf16*)d_in[5];
    const bf16* w1 = (const bf16*)d_in[7];
    const bf16* w2 = (const bf16*)d_in[8];
    const bf16* w3 = (const bf16*)d_in[9];
    const bf16* w4 = (const bf16*)d_in[10];
    bf16* out = (bf16*)d_out;

    static PFN_encodeTiled enc = nullptr;
    static bool attr_done = false;
    if (!enc) {
        void* fn = nullptr;
        cudaDriverEntryPointQueryResult qr;
        cudaGetDriverEntryPoint("cuTensorMapEncodeTiled", &fn, cudaEnableDefault, &qr);
        enc = (PFN_encodeTiled)fn;
    }
    if (!attr_done) {
        cudaFuncSetAttribute(mega_kernel, cudaFuncAttributeMaxDynamicSharedMemorySize, MEGA_SMEM);
        attr_done = true;
    }
    void* p_act;
    cudaGetSymbolAddress(&p_act, g_act);
    bf16* act = (bf16*)(((uintptr_t)p_act + 0x1fffff) & ~(uintptr_t)0x1fffff);

    MegaMaps tm;
    tm.q = make_map(enc, A_q, D_, S_, 64, 128);
    tm.act = make_map(enc, act, D_, R_END, 64, 128);
    tm.w1 = make_map(enc, w1, D_, D_, 64, 64);
    tm.w2 = make_map(enc, w2, D_, D_, 64, 64);
    tm.w3 = make_map(enc, w3, F_, D_, 64, 64);
    tm.w4 = make_map(enc, w4, D_, F_, 64, 64);
    {
        cuuint64_t dims[4] = {64, 16, 256, 8}, strides[3] = {128, D_ * 2, (cuuint64_t)2048 * D_ * 2};
        cuuint32_t box[4] = {64, 4, 1, 8}, es[4] = {1, 1, 1, 1};
        enc(&tm.y, CU_TENSOR_MAP_DATA_TYPE_BFLOAT16, 4, act + (size_t)R_Y * D_, dims, strides, box, es, CU_TENSOR_MAP_INTERLEAVE_NONE,
            CU_TENSOR_MAP_SWIZZLE_128B, CU_TENSOR_MAP_L2_PROMOTION_NONE, CU_TENSOR_MAP_FLOAT_OOB_FILL_NONE);
    }
    for (int i = 0; i < 2; i++) {
        cuuint64_t dims[4] = {D_, 4, 8, S_ / 32}, strides[3] = {8 * D_ * 2, D_ * 2, 32 * D_ * 2};
        cuuint32_t box[4] = {16, 4, 8, 4}, es[4] = {1, 1, 1, 1};
        enc(i ? &tm.v : &tm.k, CU_TENSOR_MAP_DATA_TYPE_BFLOAT16, 4, (void*)(i ? A_v : A_k), dims, strides, box, es, CU_TENSOR_MAP_INTERLEAVE_NONE,
            CU_TENSOR_MAP_SWIZZLE_32B, CU_TENSOR_MAP_L2_PROMOTION_NONE, CU_TENSOR_MAP_FLOAT_OOB_FILL_NONE);
    }
    mega_kernel<<<2 * NCL, 384, MEGA_SMEM, cudaStreamPerThread>>>(tm, out, act, w1, w2, w3, A_q, A_k, A_v, A_shk, A_ssk, A_ssD);
}
```

```cpp
#include <cuda_runtime.h>
#include <cuda_bf16.h>
#include <cuda.h>
#include <stdint.h>

typedef __nv_bfloat16 bf16;

constexpr int S_ = 2048;
constexpr int D_ = 1024;
constexpr int F_ = 3584;

constexpr int R_XA = 0, R_X1 = 256, R_H2 = 512, R_Y = 1536, R_H = 16384 + 8, R_HP = S_ + 8, R_END = R_H + 2 * R_HP;
__device__ __align__(1024) bf16 g_act[(size_t)(R_END + 1024) * D_];
__device__ __align__(16) float g_cpart[16 * (F_ + D_)];
__device__ __align__(128) float2 g_stats[3 * S_ * 8];

__device__ __forceinline__ float bfr(float x) { return __bfloat162float(__float2bfloat16_rn(x)); }
__device__ __forceinline__ uint32_t pack2(float lo, float hi) {
    __nv_bfloat162 v = __floats2bfloat162_rn(lo, hi);
    return *reinterpret_cast<uint32_t*>(&v);
}
__device__ __forceinline__ float lo2f(uint32_t v) { return __uint_as_float(v << 16); }
__device__ __forceinline__ float hi2f(uint32_t v) { return __uint_as_float(v & 0xffff0000u); }
__device__ __forceinline__ float frcp(float x) { float r; asm("rcp.approx.f32 %0, %1;" : "=f"(r) : "f"(x)); return r; }
__device__ __forceinline__ float fsqrt(float x) { float r; asm("sqrt.approx.f32 %0, %1;" : "=f"(r) : "f"(x)); return r; }
__device__ __forceinline__ uint32_t smem_u32(const void* p) { return (uint32_t)__cvta_generic_to_shared(p); }

__device__ __forceinline__ void mbar_init(uint32_t bar, uint32_t cnt) {
    asm volatile("mbarrier.init.shared::cta.b64 [%0], %1;" ::"r"(bar), "r"(cnt));
}
__device__ __forceinline__ void mbar_expect_tx(uint32_t bar, uint32_t bytes) {
    asm volatile("mbarrier.arrive.expect_tx.shared::cta.b64 _, [%0], %1;" ::"r"(bar), "r"(bytes) : "memory");
}
__device__ __forceinline__ void mbar_arrive(uint32_t bar) {
    asm volatile("mbarrier.arrive.shared::cta.b64 _, [%0];" ::"r"(bar) : "memory");
}
__device__ __forceinline__ void mbar_wait(uint32_t bar, uint32_t parity) {
    asm volatile(
        "{\n.reg .pred p;\n.reg .u32 n;\n"
        "mbarrier.try_wait.parity.shared::cta.b64 p, [%0], %1;\n"
        "@p bra LD;\n"
        "mov.u32 n, 0;\n"
        "LW:\n"
        "mbarrier.try_wait.parity.shared::cta.b64 p, [%0], %1;\n"
        "@p bra LD;\n"
        "add.u32 n, n, 1;\n"
        "setp.lt.u32 p, n, 0x400000;\n"
        "@p bra LW;\n"
        "LD:\n}\n"
        ::"r"(bar), "r"(parity) : "memory");
}
__device__ __forceinline__ void tma_load_2d(uint32_t dst, const CUtensorMap* tm, uint32_t bar, int c0, int c1) {
    asm volatile(
        "cp.async.bulk.tensor.2d.shared::cluster.global.mbarrier::complete_tx::bytes [%0], [%1, {%3, %4}], [%2];"
        ::"r"(dst), "l"((uint64_t)tm), "r"(bar), "r"(c0), "r"(c1) : "memory");
}
__device__ __forceinline__ void tma_load_2d_mc(uint32_t dst, const CUtensorMap* tm, uint32_t bar, int c0, int c1) {
    asm volatile(
        "cp.async.bulk.tensor.2d.shared::cluster.global.mbarrier::complete_tx::bytes.multicast::cluster [%0], [%1, {%3, %4}], [%2], %5;"
        ::"r"(dst), "l"((uint64_t)tm), "r"(bar), "r"(c0), "r"(c1), "h"((uint16_t)3) : "memory");
}
__device__ __forceinline__ void tma_prefetch_2d(const CUtensorMap* tm, int c0, int c1) {
    asm volatile("cp.async.bulk.prefetch.tensor.2d.L2.global.tile [%0, {%1, %2}];" ::"l"((uint64_t)tm), "r"(c0), "r"(c1) : "memory");
}
__device__ __forceinline__ void tma_store_2d(const CUtensorMap* tm, uint32_t src, int c0, int c1) {
    asm volatile("cp.async.bulk.tensor.2d.global.shared::cta.bulk_group [%0, {%2, %3}], [%1];"
                 ::"l"((uint64_t)tm), "r"(src), "r"(c0), "r"(c1) : "memory");
}
__device__ __forceinline__ void wgmma_fence() { asm volatile("wgmma.fence.sync.aligned;" ::: "memory"); }
__device__ __forceinline__ void wgmma_commit() { asm volatile("wgmma.commit_group.sync.aligned;" ::: "memory"); }
template <int N> __device__ __forceinline__ void wgmma_wait() { asm volatile("wgmma.wait_group.sync.aligned %0;" ::"n"(N) : "memory"); }
__device__ __forceinline__ void named_bar_arrive(int id, int n) { asm volatile("bar.arrive %0, %1;" ::"r"(id), "r"(n) : "memory"); }
__device__ __forceinline__ void named_bar_sync(int id, int n) { asm volatile("bar.sync %0, %1;" ::"r"(id), "r"(n) : "memory"); }

__device__ __forceinline__ uint32_t desc_a(uint32_t addr) { return ((addr & 0x3FFFF) >> 4) | (1u << 16); }
__device__ __forceinline__ uint32_t desc_b(uint32_t addr) { return ((addr & 0x3FFFF) >> 4) | (512u << 16); }

__device__ __forceinline__ void wgmma_m64n192k16(float (&d)[96], uint32_t descA, uint32_t descB) {
  asm volatile("{\n.reg .pred p;\n.reg .b64 da, db;\nsetp.eq.b32 p, 0, 0;\nmov.b64 da, {%96, %98};\nmov.b64 db, {%97, %98};\n"
    "wgmma.mma_async.sync.aligned.m64n192k16.f32.bf16.bf16 "
    "{%0, %1, %2, %3, %4, %5, %6, %7, %8, %9, %10, %11, %12, %13, %14, %15, %16, %17, %18, %19, %20, %21, %22, %23, %24, %25, %26, %27, %28, %29, %30, %31, %32, %33, %34, %35, %36, %37, %38, %39, %40, %41, %42, %43, %44, %45, %46, %47, %48, %49, %50, %51, %52, %53, %54, %55, %56, %57, %58, %59, %60, %61, %62, %63, %64, %65, %66, %67, %68, %69, %70, %71, %72, %73, %74, %75, %76, %77, %78, %79, %80, %81, %82, %83, %84, %85, %86, %87, %88, %89, %90, %91, %92, %93, %94, %95}, "
    "da, db, p, 1, 1, 0, 1;\n}\n"
    : "+f"(d[0]), "+f"(d[1]), "+f"(d[2]), "+f"(d[3]), "+f"(d[4]), "+f"(d[5]), "+f"(d[6]), "+f"(d[7]), "+f"(d[8]), "+f"(d[9]), "+f"(d[10]), "+f"(d[11]), "+f"(d[12]), "+f"(d[13]), "+f"(d[14]), "+f"(d[15]), "+f"(d[16]), "+f"(d[17]), "+f"(d[18]), "+f"(d[19]), "+f"(d[20]), "+f"(d[21]), "+f"(d[22]), "+f"(d[23]), "+f"(d[24]), "+f"(d[25]), "+f"(d[26]), "+f"(d[27]), "+f"(d[28]), "+f"(d[29]), "+f"(d[30]), "+f"(d[31]), "+f"(d[32]), "+f"(d[33]), "+f"(d[34]), "+f"(d[35]), "+f"(d[36]), "+f"(d[37]), "+f"(d[38]), "+f"(d[39]), "+f"(d[40]), "+f"(d[41]), "+f"(d[42]), "+f"(d[43]), "+f"(d[44]), "+f"(d[45]), "+f"(d[46]), "+f"(d[47]), "+f"(d[48]), "+f"(d[49]), "+f"(d[50]), "+f"(d[51]), "+f"(d[52]), "+f"(d[53]), "+f"(d[54]), "+f"(d[55]), "+f"(d[56]), "+f"(d[57]), "+f"(d[58]), "+f"(d[59]), "+f"(d[60]), "+f"(d[61]), "+f"(d[62]), "+f"(d[63]), "+f"(d[64]), "+f"(d[65]), "+f"(d[66]), "+f"(d[67]), "+f"(d[68]), "+f"(d[69]), "+f"(d[70]), "+f"(d[71]), "+f"(d[72]), "+f"(d[73]), "+f"(d[74]), "+f"(d[75]), "+f"(d[76]), "+f"(d[77]), "+f"(d[78]), "+f"(d[79]), "+f"(d[80]), "+f"(d[81]), "+f"(d[82]), "+f"(d[83]), "+f"(d[84]), "+f"(d[85]), "+f"(d[86]), "+f"(d[87]), "+f"(d[88]), "+f"(d[89]), "+f"(d[90]), "+f"(d[91]), "+f"(d[92]), "+f"(d[93]), "+f"(d[94]), "+f"(d[95])
    : "r"(descA), "r"(descB), "r"(0x40000040u));
}

__device__ __forceinline__ void wgmma_m64n256k16(float (&d)[128], uint32_t descA, uint32_t descB) {
  asm volatile("{\n.reg .pred p;\n.reg .b64 da, db;\nsetp.eq.b32 p, 0, 0;\nmov.b64 da, {%128, %130};\nmov.b64 db, {%129, %130};\n"
    "wgmma.mma_async.sync.aligned.m64n256k16.f32.bf16.bf16 "
    "{%0, %1, %2, %3, %4, %5, %6, %7, %8, %9, %10, %11, %12, %13, %14, %15, %16, %17, %18, %19, %20, %21, %22, %23, %24, %25, %26, %27, %28, %29, %30, %31, %32, %33, %34, %35, %36, %37, %38, %39, %40, %41, %42, %43, %44, %45, %46, %47, %48, %49, %50, %51, %52, %53, %54, %55, %56, %57, %58, %59, %60, %61, %62, %63, %64, %65, %66, %67, %68, %69, %70, %71, %72, %73, %74, %75, %76, %77, %78, %79, %80, %81, %82, %83, %84, %85, %86, %87, %88, %89, %90, %91, %92, %93, %94, %95, %96, %97, %98, %99, %100, %101, %102, %103, %104, %105, %106, %107, %108, %109, %110, %111, %112, %113, %114, %115, %116, %117, %118, %119, %120, %121, %122, %123, %124, %125, %126, %127}, "
    "da, db, p, 1, 1, 0, 1;\n}\n"
    : "+f"(d[0]), "+f"(d[1]), "+f"(d[2]), "+f"(d[3]), "+f"(d[4]), "+f"(d[5]), "+f"(d[6]), "+f"(d[7]), "+f"(d[8]), "+f"(d[9]), "+f"(d[10]), "+f"(d[11]), "+f"(d[12]), "+f"(d[13]), "+f"(d[14]), "+f"(d[15]), "+f"(d[16]), "+f"(d[17]), "+f"(d[18]), "+f"(d[19]), "+f"(d[20]), "+f"(d[21]), "+f"(d[22]), "+f"(d[23]), "+f"(d[24]), "+f"(d[25]), "+f"(d[26]), "+f"(d[27]), "+f"(d[28]), "+f"(d[29]), "+f"(d[30]), "+f"(d[31]), "+f"(d[32]), "+f"(d[33]), "+f"(d[34]), "+f"(d[35]), "+f"(d[36]), "+f"(d[37]), "+f"(d[38]), "+f"(d[39]), "+f"(d[40]), "+f"(d[41]), "+f"(d[42]), "+f"(d[43]), "+f"(d[44]), "+f"(d[45]), "+f"(d[46]), "+f"(d[47]), "+f"(d[48]), "+f"(d[49]), "+f"(d[50]), "+f"(d[51]), "+f"(d[52]), "+f"(d[53]), "+f"(d[54]), "+f"(d[55]), "+f"(d[56]), "+f"(d[57]), "+f"(d[58]), "+f"(d[59]), "+f"(d[60]), "+f"(d[61]), "+f"(d[62]), "+f"(d[63]), "+f"(d[64]), "+f"(d[65]), "+f"(d[66]), "+f"(d[67]), "+f"(d[68]), "+f"(d[69]), "+f"(d[70]), "+f"(d[71]), "+f"(d[72]), "+f"(d[73]), "+f"(d[74]), "+f"(d[75]), "+f"(d[76]), "+f"(d[77]), "+f"(d[78]), "+f"(d[79]), "+f"(d[80]), "+f"(d[81]), "+f"(d[82]), "+f"(d[83]), "+f"(d[84]), "+f"(d[85]), "+f"(d[86]), "+f"(d[87]), "+f"(d[88]), "+f"(d[89]), "+f"(d[90]), "+f"(d[91]), "+f"(d[92]), "+f"(d[93]), "+f"(d[94]), "+f"(d[95]), "+f"(d[96]), "+f"(d[97]), "+f"(d[98]), "+f"(d[99]), "+f"(d[100]), "+f"(d[101]), "+f"(d[102]), "+f"(d[103]), "+f"(d[104]), "+f"(d[105]), "+f"(d[106]), "+f"(d[107]), "+f"(d[108]), "+f"(d[109]), "+f"(d[110]), "+f"(d[111]), "+f"(d[112]), "+f"(d[113]), "+f"(d[114]), "+f"(d[115]), "+f"(d[116]), "+f"(d[117]), "+f"(d[118]), "+f"(d[119]), "+f"(d[120]), "+f"(d[121]), "+f"(d[122]), "+f"(d[123]), "+f"(d[124]), "+f"(d[125]), "+f"(d[126]), "+f"(d[127])
    : "r"(descA), "r"(descB), "r"(0x40000040u));
}

__device__ __forceinline__ void wgmma_m64n128k16(float (&d)[64], uint32_t descA, uint32_t descB) {
  asm volatile("{\n.reg .pred p;\n.reg .b64 da, db;\nsetp.eq.b32 p, 0, 0;\nmov.b64 da, {%64, %66};\nmov.b64 db, {%65, %66};\n"
    "wgmma.mma_async.sync.aligned.m64n128k16.f32.bf16.bf16 "
    "{%0, %1, %2, %3, %4, %5, %6, %7, %8, %9, %10, %11, %12, %13, %14, %15, %16, %17, %18, %19, %20, %21, %22, %23, %24, %25, %26, %27, %28, %29, %30, %31, %32, %33, %34, %35, %36, %37, %38, %39, %40, %41, %42, %43, %44, %45, %46, %47, %48, %49, %50, %51, %52, %53, %54, %55, %56, %57, %58, %59, %60, %61, %62, %63}, "
    "da, db, p, 1, 1, 0, 1;\n}\n"
    : "+f"(d[0]), "+f"(d[1]), "+f"(d[2]), "+f"(d[3]), "+f"(d[4]), "+f"(d[5]), "+f"(d[6]), "+f"(d[7]), "+f"(d[8]), "+f"(d[9]), "+f"(d[10]), "+f"(d[11]), "+f"(d[12]), "+f"(d[13]), "+f"(d[14]), "+f"(d[15]), "+f"(d[16]), "+f"(d[17]), "+f"(d[18]), "+f"(d[19]), "+f"(d[20]), "+f"(d[21]), "+f"(d[22]), "+f"(d[23]), "+f"(d[24]), "+f"(d[25]), "+f"(d[26]), "+f"(d[27]), "+f"(d[28]), "+f"(d[29]), "+f"(d[30]), "+f"(d[31]), "+f"(d[32]), "+f"(d[33]), "+f"(d[34]), "+f"(d[35]), "+f"(d[36]), "+f"(d[37]), "+f"(d[38]), "+f"(d[39]), "+f"(d[40]), "+f"(d[41]), "+f"(d[42]), "+f"(d[43]), "+f"(d[44]), "+f"(d[45]), "+f"(d[46]), "+f"(d[47]), "+f"(d[48]), "+f"(d[49]), "+f"(d[50]), "+f"(d[51]), "+f"(d[52]), "+f"(d[53]), "+f"(d[54]), "+f"(d[55]), "+f"(d[56]), "+f"(d[57]), "+f"(d[58]), "+f"(d[59]), "+f"(d[60]), "+f"(d[61]), "+f"(d[62]), "+f"(d[63])
    : "r"(descA), "r"(descB), "r"(0x40000040u));
}

template <int BN> struct WG;
template <> struct WG<128> { static __device__ __forceinline__ void mma(float (&d)[64], uint32_t a, uint32_t b) { wgmma_m64n128k16(d, a, b); } };
template <> struct WG<256> { static __device__ __forceinline__ void mma(float (&d)[128], uint32_t a, uint32_t b) { wgmma_m64n256k16(d, a, b); } };
template <> struct WG<192> { static __device__ __forceinline__ void mma(float (&d)[96], uint32_t a, uint32_t b) { wgmma_m64n192k16(d, a, b); } };

#define DBG_T(i)
__device__ __forceinline__ void fence_async_smem() { asm volatile("fence.proxy.async.shared::cta;" ::: "memory"); }
__device__ __forceinline__ void prefetch_tmap(const CUtensorMap* tm) { asm volatile("prefetch.tensormap [%0];" ::"l"((uint64_t)tm) : "memory"); }
__device__ __forceinline__ uint32_t mapa_u32(uint32_t addr, uint32_t cta) {
    uint32_t r;
    asm volatile("mapa.shared::cluster.u32 %0, %1, %2;" : "=r"(r) : "r"(addr), "r"(cta));
    return r;
}
__device__ __forceinline__ void mbar_arrive_cluster(uint32_t cluster_addr) {
    asm volatile("mbarrier.arrive.shared::cluster.b64 _, [%0];" ::"r"(cluster_addr) : "memory");
}
__device__ __forceinline__ bool elect_one() {
    uint32_t p;
    asm volatile("{\n.reg .pred P;\nelect.sync _|P, 0xffffffff;\nselp.u32 %0, 1, 0, P;\n}\n" : "=r"(p));
    return p != 0;
}
__device__ __forceinline__ void cluster_arrive_relaxed() { asm volatile("barrier.cluster.arrive.relaxed.aligned;" ::: "memory"); }
__device__ __forceinline__ void cluster_wait() { asm volatile("barrier.cluster.wait.acquire.aligned;" ::: "memory"); }

__device__ __forceinline__ uint32_t bsub2(uint32_t a, uint32_t b) {
    __nv_bfloat162 r = __hsub2(*reinterpret_cast<__nv_bfloat162*>(&a), *reinterpret_cast<__nv_bfloat162*>(&b));
    return *reinterpret_cast<uint32_t*>(&r);
}
__device__ __forceinline__ uint32_t bmul2(uint32_t a, uint32_t b) {
    __nv_bfloat162 r = __hmul2(*reinterpret_cast<__nv_bfloat162*>(&a), *reinterpret_cast<__nv_bfloat162*>(&b));
    return *reinterpret_cast<uint32_t*>(&r);
}
__device__ __forceinline__ uint32_t badd2(uint32_t a, uint32_t b) {
    __nv_bfloat162 r = __hadd2(*reinterpret_cast<__nv_bfloat162*>(&a), *reinterpret_cast<__nv_bfloat162*>(&b));
    return *reinterpret_cast<uint32_t*>(&r);
}
constexpr int BM = 128, BK = 64;
constexpr int R5_STAGE = 32768, R5_N = 5;
constexpr int R4_STAGE = 49152, R4_N = 4;
constexpr int R4B_STAGE = 40960;
constexpr int OFF_STG5 = 0, OFF_R = 32768;
constexpr int OFF_EPI = 196608;
constexpr int OFF_BAR = OFF_EPI + 32768;
constexpr int OFF_RS = OFF_BAR + 256;
constexpr int OFF_CS = OFF_RS + 1024;
constexpr int MEGA_SMEM = OFF_CS + 1792;
enum { FL_XA = 0, FL_H = 2, FL_X1 = 4, FL_H2 = 6, FL_CS = 10, FL_KINDS = 11 };
constexpr int FL_PITCH = 64;
constexpr int FL_WORDS = 2 * FL_KINDS * 16 * FL_PITCH;
__device__ unsigned int g_flag[FL_WORDS];
__device__ __align__(8) unsigned int g_ticket[18 * FL_PITCH];
constexpr int NCL = 66;
__device__ __forceinline__ unsigned int* flag_ptr(int layer, int kind, int i) { return g_flag + ((layer * FL_KINDS + kind) * 16 + i) * FL_PITCH; }

__device__ __forceinline__ void wait_flag(const unsigned int* p, unsigned int target) {
    long long t0 = clock64();
    while (true) {
        unsigned int v;
        asm volatile("ld.relaxed.gpu.global.u32 %0, [%1];" : "=r"(v) : "l"(p) : "memory");
        if ((int)(v - target) >= 0) break;
        if (clock64() - t0 > 2000000000LL) break;
    }
    asm volatile("fence.acquire.gpu;" ::: "memory");
}
__device__ __forceinline__ void fence_proxy_async() {
    asm volatile("fence.proxy.async.global;" ::: "memory");
    asm volatile("fence.proxy.async.shared::cta;" ::: "memory");
}
__device__ __forceinline__ void stsm4(uint32_t addr, uint32_t r0, uint32_t r1, uint32_t r2, uint32_t r3) {
    asm volatile("stmatrix.sync.aligned.m8n8.x4.shared.b16 [%0], {%1,%2,%3,%4};" ::"r"(addr), "r"(r0), "r"(r1), "r"(r2), "r"(r3));
}
__device__ __forceinline__ uint4 lds128(uint32_t a) {
    uint4 v;
    asm volatile("ld.shared.v4.b32 {%0,%1,%2,%3}, [%4];" : "=r"(v.x), "=r"(v.y), "=r"(v.z), "=r"(v.w) : "r"(a) : "memory");
    return v;
}
__device__ __forceinline__ void stg128(void* p, uint4 v) {
    asm volatile("st.global.v4.b32 [%0], {%1,%2,%3,%4};" ::"l"(p), "r"(v.x), "r"(v.y), "r"(v.z), "r"(v.w) : "memory");
}
__device__ __forceinline__ float gelu_tanh_h(float hx) {
    float z = hx * fmaf(hx * hx, 8.0f * 0.035677408136300125f, 2.0f * 0.7978845608028654f);
    float t;
    asm("tanh.approx.f32 %0, %1;" : "=f"(t) : "f"(z));
    return fmaf(hx, t, hx);
}
__device__ __forceinline__ uint32_t gelu2h(uint32_t hx) {
    uint32_t r;
    asm("{\n.reg .b32 z;\nmul.rn.bf16x2 z, %1, %1;\nfma.rn.bf16x2 z, z, %2, %3;\nmul.rn.bf16x2 z, z, %1;\ntanh.approx.bf16x2 z, z;\nfma.rn.bf16x2 %0, %1, z, %1;\n}"
        : "=r"(r) : "r"(hx), "r"(0x3e923e92u), "r"(0x3fcc3fccu));
    return r;
}
__device__ __forceinline__ uint4 gelu8h(uint4 v) { return make_uint4(gelu2h(v.x), gelu2h(v.y), gelu2h(v.z), gelu2h(v.w)); }

__device__ __forceinline__ void row_stats(const float2* p, uint32_t tag, float& mean, float& var) {
    float2 v[8];
#pragma unroll 1
    for (int n = 0; n < (1 << 20); n++) {
#pragma unroll
        for (int i = 0; i < 8; i++)
            asm volatile("{\n.reg .b64 t;\nld.relaxed.gpu.global.b64 t, [%2];\nmov.b64 {%0, %1}, t;\n}" : "=f"(v[i].x), "=f"(v[i].y) : "l"(p + 128 * i) : "memory");
        uint32_t old = 0;
#pragma unroll
        for (int i = 0; i < 8; i++) old |= __float_as_uint(v[i].y) ^ tag;
        if ((int)old >= 0) break;
    }
    mean = (((v[0].x + v[1].x) + (v[2].x + v[3].x)) + ((v[4].x + v[5].x) + (v[6].x + v[7].x))) * 0.125f;
    float m2 = 0.f, d2 = 0.f;
#pragma unroll
    for (int i = 0; i < 8; i++) { m2 += fabsf(v[i].y); d2 = fmaf(v[i].x - mean, v[i].x - mean, d2); }
    var = fmaf(128.0f, d2, m2) * (1.0f / D_);
}
struct RingState { uint32_t st, ph; };

#define DT(i)
#define DP(i)
#define GT(i)
#define TM(i)

template <int BN, int NST>
__device__ __forceinline__ void kblock(float (&acc)[BN / 2], uint32_t da, uint32_t db, uint32_t bfull, RingState& rs) {
    mbar_wait(bfull + 8 * rs.st, rs.ph);
    wgmma_fence();
#pragma unroll
    for (int k = 0; k < 4; k++) WG<BN>::mma(acc, da + k * 2, db + k * 128);
    wgmma_commit();
    if (++rs.st == NST) { rs.st = 0; rs.ph ^= 1; }
}
template <int BN, int NST, int STAGE>
__device__ __forceinline__ void mainloop(float (&acc)[BN / 2], int KB, uint32_t da0, uint32_t db0, uint32_t bfull, uint32_t rel, bool rel_on,
                                         RingState& rs, int dbg) {
    uint32_t prev = rs.st ? rs.st - 1 : NST - 1;
#pragma unroll 1
    for (int kk = 0; kk < KB; kk++) {
        const uint32_t cur = rs.st;
        kblock<BN, NST>(acc, da0 + cur * (STAGE / 16), db0 + cur * (STAGE / 16), bfull, rs);
        wgmma_wait<1>();
        if (rel_on) mbar_arrive_cluster(rel + 8 * prev);
        prev = cur;
    }
    wgmma_wait<0>();
#pragma unroll
    for (int i = 0; i < BN / 2; i++) asm volatile("" : "+f"(acc[i])::"memory");
    if (rel_on) mbar_arrive_cluster(rel + 8 * prev);
}
template <int N> __device__ __forceinline__ void zero_acc(float (&acc)[N]) {
#pragma unroll
    for (int i = 0; i < N; i++) acc[i] = 0.f;
}
__device__ __forceinline__ void ldsm4(uint32_t& r0, uint32_t& r1, uint32_t& r2, uint32_t& r3, uint32_t addr) {
    asm volatile("ldmatrix.sync.aligned.m8n8.x4.shared.b16 {%0,%1,%2,%3}, [%4];" : "=r"(r0), "=r"(r1), "=r"(r2), "=r"(r3) : "r"(addr));
}

__device__ __forceinline__ void ldsm4t(uint32_t& r0, uint32_t& r1, uint32_t& r2, uint32_t& r3, uint32_t addr) {
    asm volatile("ldmatrix.sync.aligned.m8n8.x4.trans.shared.b16 {%0,%1,%2,%3}, [%4];" : "=r"(r0), "=r"(r1), "=r"(r2), "=r"(r3) : "r"(addr));
}

#define DBG_S(i)
#define DBG_OUT(r, o)
#define DBG_F(i)
#define DBG_W(i)
constexpr int CV_CH = 8;
constexpr int CV_SL = 16384;
constexpr int CV_QG = 128 * 8 + 16;
constexpr int CV_HPL = 2048 + 192;
constexpr int CV_0 = 32768, CV_H = 9 * CV_SL, CV_BAR = OFF_RS - CV_0;

template <int K> __device__ __forceinline__ void cv_mma(float (&d)[64], const uint32_t (&a)[4], uint32_t db, int acc);
template <> __device__ __forceinline__ void cv_mma<0>(float (&d)[64], const uint32_t (&a)[4], uint32_t db, int acc) {
    asm volatile("{\n.reg .pred p;\n.reg .b64 b;\nsetp.ne.b32 p, %70, 0;\nmov.b64 b, {%68, %69};\n"
        "wgmma.mma_async.sync.aligned.m64n128k16.f32.bf16.bf16 {%0,%1,%2,%3,%4,%5,%6,%7,%8,%9,%10,%11,%12,%13,%14,%15,%16,%17,%18,%19,%20,%21,%22,%23,%24,%25,%26,%27,%28,%29,%30,%31,%32,%33,%34,%35,%36,%37,%38,%39,%40,%41,%42,%43,%44,%45,%46,%47,%48,%49,%50,%51,%52,%53,%54,%55,%56,%57,%58,%59,%60,%61,%62,%63}, {%64,%65,%66,%67}, b, p, 1, 1, 0;\n}\n"
        : "+f"(d[0]), "+f"(d[1]), "+f"(d[2]), "+f"(d[3]), "+f"(d[4]), "+f"(d[5]), "+f"(d[6]), "+f"(d[7]), "+f"(d[8]), "+f"(d[9]), "+f"(d[10]), "+f"(d[11]), "+f"(d[12]), "+f"(d[13]), "+f"(d[14]), "+f"(d[15]), "+f"(d[16]), "+f"(d[17]), "+f"(d[18]), "+f"(d[19]), "+f"(d[20]), "+f"(d[21]), "+f"(d[22]), "+f"(d[23]), "+f"(d[24]), "+f"(d[25]), "+f"(d[26]), "+f"(d[27]), "+f"(d[28]), "+f"(d[29]), "+f"(d[30]), "+f"(d[31]), "+f"(d[32]), "+f"(d[33]), "+f"(d[34]), "+f"(d[35]), "+f"(d[36]), "+f"(d[37]), "+f"(d[38]), "+f"(d[39]), "+f"(d[40]), "+f"(d[41]), "+f"(d[42]), "+f"(d[43]), "+f"(d[44]), "+f"(d[45]), "+f"(d[46]), "+f"(d[47]), "+f"(d[48]), "+f"(d[49]), "+f"(d[50]), "+f"(d[51]), "+f"(d[52]), "+f"(d[53]), "+f"(d[54]), "+f"(d[55]), "+f"(d[56]), "+f"(d[57]), "+f"(d[58]), "+f"(d[59]), "+f"(d[60]), "+f"(d[61]), "+f"(d[62]), "+f"(d[63])
        : "r"(a[0]), "r"(a[1]), "r"(a[2]), "r"(a[3]), "r"(db), "r"(8u), "r"(acc));
}
template <> __device__ __forceinline__ void cv_mma<1>(float (&d)[64], const uint32_t (&a)[4], uint32_t db, int acc) {
    asm volatile("{\n.reg .pred p;\n.reg .b64 b;\nsetp.ne.b32 p, %62, 0;\nmov.b64 b, {%60, %61};\n"
        "wgmma.mma_async.sync.aligned.m64n112k16.f32.bf16.bf16 {%0,%1,%2,%3,%4,%5,%6,%7,%8,%9,%10,%11,%12,%13,%14,%15,%16,%17,%18,%19,%20,%21,%22,%23,%24,%25,%26,%27,%28,%29,%30,%31,%32,%33,%34,%35,%36,%37,%38,%39,%40,%41,%42,%43,%44,%45,%46,%47,%48,%49,%50,%51,%52,%53,%54,%55}, {%56,%57,%58,%59}, b, p, 1, 1, 0;\n}\n"
        : "+f"(d[0]), "+f"(d[1]), "+f"(d[2]), "+f"(d[3]), "+f"(d[4]), "+f"(d[5]), "+f"(d[6]), "+f"(d[7]), "+f"(d[8]), "+f"(d[9]), "+f"(d[10]), "+f"(d[11]), "+f"(d[12]), "+f"(d[13]), "+f"(d[14]), "+f"(d[15]), "+f"(d[16]), "+f"(d[17]), "+f"(d[18]), "+f"(d[19]), "+f"(d[20]), "+f"(d[21]), "+f"(d[22]), "+f"(d[23]), "+f"(d[24]), "+f"(d[25]), "+f"(d[26]), "+f"(d[27]), "+f"(d[28]), "+f"(d[29]), "+f"(d[30]), "+f"(d[31]), "+f"(d[32]), "+f"(d[33]), "+f"(d[34]), "+f"(d[35]), "+f"(d[36]), "+f"(d[37]), "+f"(d[38]), "+f"(d[39]), "+f"(d[40]), "+f"(d[41]), "+f"(d[42]), "+f"(d[43]), "+f"(d[44]), "+f"(d[45]), "+f"(d[46]), "+f"(d[47]), "+f"(d[48]), "+f"(d[49]), "+f"(d[50]), "+f"(d[51]), "+f"(d[52]), "+f"(d[53]), "+f"(d[54]), "+f"(d[55])
        : "r"(a[0]), "r"(a[1]), "r"(a[2]), "r"(a[3]), "r"(db), "r"(8u), "r"(acc));
}
template <> __device__ __forceinline__ void cv_mma<2>(float (&d)[64], const uint32_t (&a)[4], uint32_t db, int acc) {
    asm volatile("{\n.reg .pred p;\n.reg .b64 b;\nsetp.ne.b32 p, %54, 0;\nmov.b64 b, {%52, %53};\n"
        "wgmma.mma_async.sync.aligned.m64n96k16.f32.bf16.bf16 {%0,%1,%2,%3,%4,%5,%6,%7,%8,%9,%10,%11,%12,%13,%14,%15,%16,%17,%18,%19,%20,%21,%22,%23,%24,%25,%26,%27,%28,%29,%30,%31,%32,%33,%34,%35,%36,%37,%38,%39,%40,%41,%42,%43,%44,%45,%46,%47}, {%48,%49,%50,%51}, b, p, 1, 1, 0;\n}\n"
        : "+f"(d[0]), "+f"(d[1]), "+f"(d[2]), "+f"(d[3]), "+f"(d[4]), "+f"(d[5]), "+f"(d[6]), "+f"(d[7]), "+f"(d[8]), "+f"(d[9]), "+f"(d[10]), "+f"(d[11]), "+f"(d[12]), "+f"(d[13]), "+f"(d[14]), "+f"(d[15]), "+f"(d[16]), "+f"(d[17]), "+f"(d[18]), "+f"(d[19]), "+f"(d[20]), "+f"(d[21]), "+f"(d[22]), "+f"(d[23]), "+f"(d[24]), "+f"(d[25]), "+f"(d[26]), "+f"(d[27]), "+f"(d[28]), "+f"(d[29]), "+f"(d[30]), "+f"(d[31]), "+f"(d[32]), "+f"(d[33]), "+f"(d[34]), "+f"(d[35]), "+f"(d[36]), "+f"(d[37]), "+f"(d[38]), "+f"(d[39]), "+f"(d[40]), "+f"(d[41]), "+f"(d[42]), "+f"(d[43]), "+f"(d[44]), "+f"(d[45]), "+f"(d[46]), "+f"(d[47])
        : "r"(a[0]), "r"(a[1]), "r"(a[2]), "r"(a[3]), "r"(db), "r"(8u), "r"(acc));
}
template <> __device__ __forceinline__ void cv_mma<3>(float (&d)[64], const uint32_t (&a)[4], uint32_t db, int acc) {
    asm volatile("{\n.reg .pred p;\n.reg .b64 b;\nsetp.ne.b32 p, %46, 0;\nmov.b64 b, {%44, %45};\n"
        "wgmma.mma_async.sync.aligned.m64n80k16.f32.bf16.bf16 {%0,%1,%2,%3,%4,%5,%6,%7,%8,%9,%10,%11,%12,%13,%14,%15,%16,%17,%18,%19,%20,%21,%22,%23,%24,%25,%26,%27,%28,%29,%30,%31,%32,%33,%34,%35,%36,%37,%38,%39}, {%40,%41,%42,%43}, b, p, 1, 1, 0;\n}\n"
        : "+f"(d[0]), "+f"(d[1]), "+f"(d[2]), "+f"(d[3]), "+f"(d[4]), "+f"(d[5]), "+f"(d[6]), "+f"(d[7]), "+f"(d[8]), "+f"(d[9]), "+f"(d[10]), "+f"(d[11]), "+f"(d[12]), "+f"(d[13]), "+f"(d[14]), "+f"(d[15]), "+f"(d[16]), "+f"(d[17]), "+f"(d[18]), "+f"(d[19]), "+f"(d[20]), "+f"(d[21]), "+f"(d[22]), "+f"(d[23]), "+f"(d[24]), "+f"(d[25]), "+f"(d[26]), "+f"(d[27]), "+f"(d[28]), "+f"(d[29]), "+f"(d[30]), "+f"(d[31]), "+f"(d[32]), "+f"(d[33]), "+f"(d[34]), "+f"(d[35]), "+f"(d[36]), "+f"(d[37]), "+f"(d[38]), "+f"(d[39])
        : "r"(a[0]), "r"(a[1]), "r"(a[2]), "r"(a[3]), "r"(db), "r"(8u), "r"(acc));
}
template <> __device__ __forceinline__ void cv_mma<4>(float (&d)[64], const uint32_t (&a)[4], uint32_t db, int acc) {
    asm volatile("{\n.reg .pred p;\n.reg .b64 b;\nsetp.ne.b32 p, %38, 0;\nmov.b64 b, {%36, %37};\n"
        "wgmma.mma_async.sync.aligned.m64n64k16.f32.bf16.bf16 {%0,%1,%2,%3,%4,%5,%6,%7,%8,%9,%10,%11,%12,%13,%14,%15,%16,%17,%18,%19,%20,%21,%22,%23,%24,%25,%26,%27,%28,%29,%30,%31}, {%32,%33,%34,%35}, b, p, 1, 1, 0;\n}\n"
        : "+f"(d[0]), "+f"(d[1]), "+f"(d[2]), "+f"(d[3]), "+f"(d[4]), "+f"(d[5]), "+f"(d[6]), "+f"(d[7]), "+f"(d[8]), "+f"(d[9]), "+f"(d[10]), "+f"(d[11]), "+f"(d[12]), "+f"(d[13]), "+f"(d[14]), "+f"(d[15]), "+f"(d[16]), "+f"(d[17]), "+f"(d[18]), "+f"(d[19]), "+f"(d[20]), "+f"(d[21]), "+f"(d[22]), "+f"(d[23]), "+f"(d[24]), "+f"(d[25]), "+f"(d[26]), "+f"(d[27]), "+f"(d[28]), "+f"(d[29]), "+f"(d[30]), "+f"(d[31])
        : "r"(a[0]), "r"(a[1]), "r"(a[2]), "r"(a[3]), "r"(db), "r"(8u), "r"(acc));
}
template <> __device__ __forceinline__ void cv_mma<5>(float (&d)[64], const uint32_t (&a)[4], uint32_t db, int acc) {
    asm volatile("{\n.reg .pred p;\n.reg .b64 b;\nsetp.ne.b32 p, %30, 0;\nmov.b64 b, {%28, %29};\n"
        "wgmma.mma_async.sync.aligned.m64n48k16.f32.bf16.bf16 {%0,%1,%2,%3,%4,%5,%6,%7,%8,%9,%10,%11,%12,%13,%14,%15,%16,%17,%18,%19,%20,%21,%22,%23}, {%24,%25,%26,%27}, b, p, 1, 1, 0;\n}\n"
        : "+f"(d[0]), "+f"(d[1]), "+f"(d[2]), "+f"(d[3]), "+f"(d[4]), "+f"(d[5]), "+f"(d[6]), "+f"(d[7]), "+f"(d[8]), "+f"(d[9]), "+f"(d[10]), "+f"(d[11]), "+f"(d[12]), "+f"(d[13]), "+f"(d[14]), "+f"(d[15]), "+f"(d[16]), "+f"(d[17]), "+f"(d[18]), "+f"(d[19]), "+f"(d[20]), "+f"(d[21]), "+f"(d[22]), "+f"(d[23])
        : "r"(a[0]), "r"(a[1]), "r"(a[2]), "r"(a[3]), "r"(db), "r"(8u), "r"(acc));
}
template <> __device__ __forceinline__ void cv_mma<6>(float (&d)[64], const uint32_t (&a)[4], uint32_t db, int acc) {
    asm volatile("{\n.reg .pred p;\n.reg .b64 b;\nsetp.ne.b32 p, %22, 0;\nmov.b64 b, {%20, %21};\n"
        "wgmma.mma_async.sync.aligned.m64n32k16.f32.bf16.bf16 {%0,%1,%2,%3,%4,%5,%6,%7,%8,%9,%10,%11,%12,%13,%14,%15}, {%16,%17,%18,%19}, b, p, 1, 1, 0;\n}\n"
        : "+f"(d[0]), "+f"(d[1]), "+f"(d[2]), "+f"(d[3]), "+f"(d[4]), "+f"(d[5]), "+f"(d[6]), "+f"(d[7]), "+f"(d[8]), "+f"(d[9]), "+f"(d[10]), "+f"(d[11]), "+f"(d[12]), "+f"(d[13]), "+f"(d[14]), "+f"(d[15])
        : "r"(a[0]), "r"(a[1]), "r"(a[2]), "r"(a[3]), "r"(db), "r"(8u), "r"(acc));
}
template <> __device__ __forceinline__ void cv_mma<7>(float (&d)[64], const uint32_t (&a)[4], uint32_t db, int acc) {
    asm volatile("{\n.reg .pred p;\n.reg .b64 b;\nsetp.ne.b32 p, %14, 0;\nmov.b64 b, {%12, %13};\n"
        "wgmma.mma_async.sync.aligned.m64n16k16.f32.bf16.bf16 {%0,%1,%2,%3,%4,%5,%6,%7}, {%8,%9,%10,%11}, b, p, 1, 1, 0;\n}\n"
        : "+f"(d[0]), "+f"(d[1]), "+f"(d[2]), "+f"(d[3]), "+f"(d[4]), "+f"(d[5]), "+f"(d[6]), "+f"(d[7])
        : "r"(a[0]), "r"(a[1]), "r"(a[2]), "r"(a[3]), "r"(db), "r"(8u), "r"(acc));
}
__device__ __forceinline__ void stsm4t(uint32_t addr, uint32_t r0, uint32_t r1, uint32_t r2, uint32_t r3) {
    asm volatile("stmatrix.sync.aligned.m8n8.x4.trans.shared.b16 [%0], {%1,%2,%3,%4};" ::"r"(addr), "r"(r0), "r"(r1), "r"(r2), "r"(r3) : "memory");
}
__device__ __forceinline__ void cp16(uint32_t dst, const void* src, int n = 16) {
    asm volatile("cp.async.cg.shared.global.L2::128B [%0], [%1], 16, %2;" ::"r"(dst), "l"(src), "r"(n) : "memory");
}
__device__ __forceinline__ void cp_arrive(uint32_t bar) { asm volatile("cp.async.mbarrier.arrive.noinc.shared::cta.b64 [%0];" ::"r"(bar) : "memory"); }
__device__ __forceinline__ void lds64(uint32_t& x, uint32_t& y, uint32_t a) { asm volatile("ld.shared.v2.b32 {%0,%1}, [%2];" : "=r"(x), "=r"(y) : "r"(a) : "memory"); }
__device__ __forceinline__ void sts128(uint32_t a, uint32_t x, uint32_t y, uint32_t z, uint32_t w) {
    asm volatile("st.shared.v4.b32 [%0], {%1,%2,%3,%4};" ::"r"(a), "r"(x), "r"(y), "r"(z), "r"(w) : "memory");
}
__device__ __forceinline__ uint32_t bfma2(uint32_t a, uint32_t b, uint32_t c) {
    uint32_t r;
    asm("fma.rn.bf16x2 %0, %1, %2, %3;" : "=r"(r) : "r"(a), "r"(b), "r"(c));
    return r;
}
#define CV_NS 4
#define CV_W 1
constexpr int CV_GC = 8 / CV_NS, CV_NA = (CV_W + 2) * CV_NS;
struct CvAddr { uint32_t pa[2], p0[4], db, rdy, xw, xr, bar; bool wrap, neg[2]; };
template <int G> __device__ __forceinline__ void cv_load(uint32_t (&a)[CV_NA][4], const CvAddr& p) {
    if constexpr (G % CV_GC == 0) mbar_wait(p.rdy + 8 * (G / CV_GC), 0);
#pragma unroll
    for (int i = G * CV_NS; i < (G + 1) * CV_NS; i++) {
        const int of = (i / 2 % 2) * CV_QG + (i / 8) * CV_SL + 256 * (i % 2 + (i / 2 & 2));
        if ((i & 5) == 0) {
#pragma unroll
            for (int e = 0; e < 4; e++) asm volatile("ld.shared.b32 %0, [%1];" : "=r"(a[i % CV_NA][e]) : "r"(p.p0[e] + of) : "memory");
            if (i < 8) { if (p.neg[0]) a[i % CV_NA][0] = 0; if (p.neg[1]) a[i % CV_NA][2] = 0; }
        } else {
            lds64(a[i % CV_NA][0], a[i % CV_NA][1], p.pa[0] + of - 256);
            lds64(a[i % CV_NA][2], a[i % CV_NA][3], p.pa[1] + of - 256);
        }
    }
}
__device__ __forceinline__ float vadd(float a, float b) {
    float r;
    asm volatile("add.f32 %0, %1, %2;" : "=f"(r) : "f"(a), "f"(b));
    return r;
}
template <int K> __device__ __forceinline__ uint32_t cv_tail(float (&d)[64], bool wrap) {
    float* z = d + 56 - 8 * K;
    z[4] = vadd(z[4], K > 0 ? z[10] : 0.f);
    if constexpr (K > 0) z[5] = vadd(z[5], z[11]);
    z[0] = vadd(z[0], z[6]);
    z[1] = vadd(z[1], z[7]);
    return pack2(wrap ? (K > 0 ? z[8] : 0.f) : z[4], wrap ? z[4] : z[0]);
}
template <int K> __device__ __forceinline__ uint32_t cv_fin(const float (&d)[64], uint32_t x) { return pack2(d[61 - 8 * K] + lo2f(x), d[57 - 8 * K] + hi2f(x)); }
template <int G>
__device__ __forceinline__ void cv_steps(float (&d)[2][64], uint32_t (&a)[CV_NA][4], uint32_t (&tv)[2][8], const CvAddr& p) {
    constexpr int K = G / CV_GC, GN = 8 * CV_GC;
    constexpr int T = G - CV_W - CV_GC, F = T - 1, TK = T / CV_GC, FK = F / CV_GC;
    if constexpr (G == 0) cv_load<0>(a, p);
    if constexpr (G < GN) {
        wgmma_fence();
#pragma unroll
        for (int i = G * CV_NS; i < (G + 1) * CV_NS; i++)
            cv_mma<K>(d[i / 2 % 2], a[i % CV_NA], p.db + (i / 2 % 2) * (CV_HPL / 8) + 16 * K + 2 * (i % 2 + (i / 2 & 2)), i & ~2 ? 1 : p.bar >> 8);
        wgmma_commit();
    }
    if constexpr (G < GN - 1) cv_load<G + 1>(a, p);
    if constexpr (T >= 0 && T % CV_GC == 0) {
        tv[0][TK] = cv_tail<TK>(d[0], p.wrap);
        tv[1][TK] = cv_tail<TK>(d[1], p.wrap);
        if constexpr (TK & 1) sts128(p.xw + TK / 2 * 512, tv[0][TK - 1], tv[0][TK], tv[1][TK - 1], tv[1][TK]);
    }
    if constexpr (F >= 0 && F % (2 * CV_GC) == CV_GC) {
        const uint4 x = lds128(p.xr + FK / 2 * 512);
        tv[0][FK - 1] = cv_fin<FK - 1>(d[0], x.x); tv[0][FK] = cv_fin<FK>(d[0], x.y);
        tv[1][FK - 1] = cv_fin<FK - 1>(d[1], x.z); tv[1][FK] = cv_fin<FK>(d[1], x.w);
    }
    if constexpr (G < GN - 1) wgmma_wait<CV_W>();
    if constexpr (G == GN - 1) wgmma_wait<0>();
    if constexpr (T >= 0 && T % (2 * CV_GC) == CV_GC) named_bar_sync(p.bar, 128);
    if constexpr (F < GN - CV_GC) cv_steps<G + 1>(d, a, tv, p);
}

#define CV_PF 7
#define Y_FIRST 0
#define W3_AT 1
struct MegaMaps {
    CUtensorMap q, act;
    CUtensorMap w1, w2, w3, w4;
    CUtensorMap k, v, y;
};

__global__ void __cluster_dims__(2, 1, 1) __launch_bounds__(384, 1)
mega_kernel(const __grid_constant__ MegaMaps tm, bf16* __restrict__ outp, bf16* act, const bf16* __restrict__ w1p, const bf16* __restrict__ w2p,
            const bf16* __restrict__ w3p, const bf16* __restrict__ xq, const bf16* __restrict__ kp, const bf16* __restrict__ vp,
            const bf16* __restrict__ shk, const bf16* __restrict__ ssk, const bf16* __restrict__ ssD) {
    extern __shared__ __align__(1024) uint8_t sgen[];
    const uint32_t sbase = smem_u32(sgen);
    const int warp = __shfl_sync(0xffffffffu, threadIdx.x >> 5, 0), lane = threadIdx.x & 31;
    const int rank = blockIdx.x & 1;
    const uint32_t s_bar = sbase + OFF_BAR;
    const uint32_t f5 = s_bar, e5 = s_bar + 64, f4 = s_bar + 144, e4 = s_bar + 104;
    const uint32_t b_rfull = s_bar + 176, b_role = s_bar + 184, b_stg = s_bar + 136, b_h2 = s_bar + 32;
    const uint32_t s_epi = sbase + OFF_EPI, s_stg = sbase + OFF_STG5, s_r = sbase + OFF_R;
    uint8_t* sm = sgen + CV_0;
    const uint32_t sb = sbase + CV_0;
    const int tid = threadIdx.x, wg = warp >> 2, w = warp & 3;
    const int d0 = blockIdx.x * CV_CH;
    const bool cv = blockIdx.x < D_ / CV_CH;
    const uint32_t b_full = sb + CV_BAR, b_rdy = b_full + 64, b_h = b_full + 128;
    GT(0);
    if (tid == 0) TM(0);
    auto row_at = [&](int r) { return sb + CV_SL + (r < 0 ? -8192 : 0) + ((r & 127) >> 5) * 1024 + (r & 7) * 128 + ((r >> 3) & 3) * 32 + ((r ^ rank) & 1) * 16; };
    auto load_kv = [&](int c) {
#pragma unroll
        for (int i = 0; i < 2; i++)
            asm volatile("cp.async.bulk.tensor.4d.shared::cluster.global.mbarrier::complete_tx::bytes.multicast::cluster [%0], [%1, {%3, %4, %4, %5}], [%2], %6;"
                         ::"r"(sb + (c + 1) * CV_SL + rank * 8192 + i * 4096), "l"((uint64_t)(i ? &tm.v : &tm.k)), "r"(b_full + 8 * c), "r"(d0 & ~15), "r"(0),
                         "r"(8 * c + 4 * rank), "h"((uint16_t)3) : "memory");
    };
    auto bulk = [&](uint32_t dst, const void* src, uint32_t n, uint32_t bar) {
        asm volatile("cp.async.bulk.shared::cluster.global.mbarrier::complete_tx::bytes [%0], [%1], %2, [%3];" ::"r"(dst), "l"(src), "r"(n), "r"(bar) : "memory");
    };
    auto put_h = [&](int ch) {
        const uint32_t dk = (tid & 127) ? 0 : *reinterpret_cast<const volatile uint32_t*>(sm + CV_BAR + 160 + 16 * wg + 2 * ch);
        uint4 v[4];
#pragma unroll
        for (int i = 0; i < 4; i++) v[i] = lds128(sbase + ch * 4096 + i * 2048 + (tid & 127) * 16);
        v[0].x = pack2(lo2f(v[0].x) + lo2f(dk), hi2f(v[0].x));
        v[2].x = pack2(lo2f(v[2].x) + hi2f(dk), hi2f(v[2].x));
#pragma unroll
        for (int i = 0; i < 4; i++)
            sts128(sb + CV_H + (2 * ch + (i & 2) + (tid & 1)) * CV_HPL + (127 - ((tid & 127) >> 1)) * 16 - (i & 1) * 1024, v[i].x, v[i].y, v[i].z, v[i].w);
    };
    int bi, bj, m0, tb;
    uint32_t ep;
    auto get_role = [&]() {
        mbar_wait(b_role, 0);
        int role;
        asm volatile("ld.shared.v2.b32 {%0,%1}, [%2];" : "=r"(role), "=r"(ep) : "r"(s_bar + 192) : "memory");
        bi = (role >> 3) * 2 + rank; bj = role & 7; m0 = bi * BM; tb = (role >> 3) * 2048 + rank * 128;
        return role < 64;
    };

    if (warp >= 8) {
        asm volatile("setmaxnreg.dec.sync.aligned.u32 88;");
        cluster_arrive_relaxed();
        if (!cv) cluster_wait(); else {
            const int bt = tid - 256, g = lane >> 2, t = lane & 3;
            if (bt < 16) sts128(row_at((bt & 7) - 8) + (bt >> 3) * 4096, 0, 0, 0, 0);
#pragma unroll
            for (int i = 0; i < 4; i++)
                cp16(row_at(bt) + i * 4096, (i & 1 ? vp : kp) + (size_t)(bt + (i >> 1) * 128) * D_ + d0);
            DBG_S(16 + (3));
            uint2 wa;
            asm volatile("ld.global.nc.v2.b32 {%0,%1}, [%2];" : "=r"(wa.x), "=r"(wa.y) : "l"(shk + (d0 + g) * 4));
            const int mi = lane >> 3, r0 = 32 * w + 8 * ((lane >> 1) & 3) - (lane & 1);
            const uint32_t ka0 = row_at(r0 + 2 * mi - 3), ka1 = row_at(r0 + 2 * (mi & 1) + 5) + (mi >> 1) * 8192;
            const uint32_t va0 = row_at(r0 + 2 * mi + 1) + 4096, va1 = row_at(r0 - 1) + 4096 + (mi & 1) * 8192;
            const uint32_t qd = sb + g * CV_QG + (32 * w + 8 * t) * 8, qd0 = qd + (t & 2) * 16, qd1 = qd + (~t & 2) * 16;
            const uint32_t w0 = __byte_perm(wa.x, 0, 0x1010), w1 = __byte_perm(wa.x, 0, 0x3232), w2 = __byte_perm(wa.y, 0, 0x1010), w3 = __byte_perm(wa.y, 0, 0x3232);
            cluster_wait();
            DBG_S(16 + (5));
            asm volatile("cp.async.wait_all;" ::: "memory");
            named_bar_sync(7, 128);
            DBG_S(16 + (1));
            struct KV { uint32_t k[2][6], v[2][5]; };
            auto get = [&](KV& x, uint32_t so) {
                ldsm4t(x.k[0][0], x.k[0][1], x.k[0][2], x.k[0][3], ka0 + so);
                ldsm4t(x.k[0][4], x.k[0][5], x.k[1][4], x.k[1][5], ka1 + so);
                ldsm4t(x.k[1][0], x.k[1][1], x.k[1][2], x.k[1][3], ka0 + so + 8192);
                asm volatile("ldmatrix.sync.aligned.m8n8.x2.trans.shared.b16 {%0,%1}, [%2];" : "=r"(x.v[0][0]), "=r"(x.v[1][0]) : "r"(va1 + so));
                ldsm4t(x.v[0][1], x.v[0][2], x.v[0][3], x.v[0][4], va0 + so);
                ldsm4t(x.v[1][1], x.v[1][2], x.v[1][3], x.v[1][4], va0 + so + 8192);
            };
            auto build = [&](int c, const KV& x, KV& nx) {
                const uint32_t so = c * CV_SL;
                DBG_F(1);
                uint32_t early;
                asm volatile("{\n.reg .pred p;\nmbarrier.test_wait.parity.shared::cta.b64 p, [%1], 0;\nvote.sync.all.pred p, p, -1;\nselp.u32 %0, 1, 0, p;\n}"
                             : "=r"(early) : "r"(b_full + 8 * (c < 7 ? c + 1 : c)) : "memory");
                if (early) get(nx, so + CV_SL);
                DBG_F(2);
                uint32_t p[8][2];
#pragma unroll
                for (int sg = 0; sg < 2; sg++) {
                    uint32_t u[5], ke[6];
#pragma unroll
                    for (int i = 0; i < 6; i++) ke[i] = __byte_perm(x.k[sg][i], x.k[sg][i ? i - 1 : 0], 0x5432);
#pragma unroll
                    for (int i = 0; i < 5; i++) {
                        u[i] = bmul2(bfma2(x.k[sg][i + 1], w0, bfma2(ke[i + 1], w1, bfma2(x.k[sg][i], w2, bmul2(ke[i], w3)))), x.v[sg][i]);
                        if (i) { p[2 * i - 1][sg] = u[i]; p[2 * i - 2][sg] = __byte_perm(u[i], u[i - 1], 0x5432); }
                    }
                }
                DBG_F(3);
#pragma unroll
                for (int j = 0; j < 4; j++) sts128((j & 2 ? qd1 : qd0) + so + 16 * (j & 1), p[2 * j][0], p[2 * j][1], p[2 * j + 1][0], p[2 * j + 1][1]);
                __syncwarp();
                DBG_F(4);
                if (lane == 0) {
                    mbar_arrive(b_rdy + 8 * c);
                    if (c == w) {
                        if (c < 3) load_kv(c + 5);
                        else { bulk(sbase + 16384, ssk + (size_t)(d0 + 4) * S_, 16384, b_h + 16); bulk(b_full + 192, ssD + d0, 16, b_h + 16); }
                    }
                    if (c == w + 4 && (CV_PF >> w & 1)) {
                        const uint32_t n = w == 0 ? 32768 : w == 3 ? 57344 : 16384;
                        const char* src = reinterpret_cast<const char*>(w == 0 ? xq : w == 1 ? w1p : w == 2 ? w2p : w3p) + (size_t)blockIdx.x * n;
                        asm volatile("cp.async.bulk.prefetch.L2.global [%0], %1;" ::"l"(src), "r"(n) : "memory");
                    }
                }
                DBG_F(5);
                named_bar_sync(7, 128);
                DBG_F(6);
                DBG_S(16 + (c == 0 ? 4 : 5 + c));
                if (!early) { mbar_wait(b_full + 8 * c + 8, 0); get(nx, so + CV_SL); }
                DBG_F(7);
            };
            KV x0, x1;
            get(x0, 0);
#pragma unroll 1
            for (int c = 0; c < 8; c += 2) { build(c, x0, x1); build(c + 1, x1, x0); }
            mbar_wait(b_h + 16, 0);
            put_h(4); put_h(6);
            fence_async_smem();
            __syncwarp();
            if (lane == 0) mbar_arrive(b_full);
            named_bar_sync(7, 128);
            DBG_S(16 + (13));
        }
    } else {
        if (elect_one()) {
            mbar_init(b_full + 8 * warp, warp ? 1 : 4);
            mbar_init(b_rdy + 8 * warp, 4);
            if (warp) mbar_expect_tx(b_full + 8 * warp, 16384);
            if (w == 0 && cv) {
                mbar_init(b_h + 8 * wg, 1);
                mbar_expect_tx(b_h + 8 * wg, 8192 + 16);
                fence_async_smem();
                bulk(sbase + wg * 8192, ssk + (size_t)(d0 + 2 * wg) * S_, 8192, b_h + 8 * wg);
                bulk(b_full + 160 + 16 * wg, ssD + d0, 16, b_h + 8 * wg);
            }
            mbar_init(s_bar + 8 * warp, 1);
            mbar_init(s_bar + 64 + 8 * warp, 4);
            mbar_init(s_bar + 128 + 8 * warp, warp < 2 ? 4 << warp : warp == 6 ? 2 : 1);
            if (warp == 0) mbar_arrive(f5);
            if (warp == 7) mbar_expect_tx(b_role, 8);
            if (warp == 1) { mbar_init(b_h + 16, 1); mbar_expect_tx(b_h + 16, 16384 + 16); }
            if (w == 2) sts128(s_bar + 224 + 16 * wg, 0, 0, 0, 0);
            asm volatile("fence.mbarrier_init.release.cluster;" ::: "memory");
            if (warp == 2) { prefetch_tmap(&tm.k); prefetch_tmap(&tm.v); }
        }
        __syncwarp();
        DBG_W(1);
        cluster_arrive_relaxed();
        asm volatile("setmaxnreg.inc.sync.aligned.u32 208;");
        DBG_W(2);
        const int zi = (tid & 127) - 32;
        if (zi >= 0 && zi < 48) sts128(sb + CV_H + (4 * wg + (zi / 6 & 3) + (zi / 24) * 8) * CV_HPL + 2048 + (zi % 6) * 16, 0, 0, 0, 0);
        DBG_W(3);
        cluster_wait();
        DBG_W(5);
        if (cv) {
            if (tid == 32) {
#pragma unroll 1
                for (int c = 1; c < 5; c++) load_kv(c);
                prefetch_tmap(&tm.y);
            }
            __syncwarp();
            DBG_W(6);
            const int g = lane >> 2, t = lane & 3;
            const int x0 = 32 + 8 * w + g - 2 * t;
            CvAddr p;
            p.rdy = b_rdy;
            p.bar = 1 + wg;
            p.xr = sbase + (warp ^ 2) * 2048 + lane * 16;
            p.xw = sbase + warp * 2048 + (g * 4 + ((t - (w >> 1)) & 3)) * 16;
            p.wrap = t == 0 && w >= 2;
            mbar_wait(b_h + 8 * wg, 0);
            DBG_W(4);
            put_h(2 * wg);
            fence_async_smem();
            named_bar_sync(1 + wg, 128);
            float acc[2][64];
            zero_acc(acc[0]); zero_acc(acc[1]);
#pragma unroll 1
            for (int round = 0; round < 2; round++) {
                const int ch = round * 4 + 2 * wg;
                uint32_t a[CV_NA][4], tv[2][8];
#pragma unroll
                for (int e = 0; e < 2; e++) {
                    const int x = x0 - 8 * e;
                    p.neg[e] = x < 32;
                    p.pa[e] = sb + ch * CV_QG + 8 * (x ^ (x >> 2 & 4));
                    p.p0[2 * e] = p.pa[e] + (x < 32 ? 768 + 4 - CV_SL : -256);
                    p.p0[2 * e + 1] = p.pa[e] + (x < 32 ? 768 : -256 + 4);
                }
                p.db = (((sb + CV_H + ch * 2 * CV_HPL) & 0x3FFFF) >> 4) | ((CV_HPL / 16) << 16);
                if (round) mbar_wait(b_full, 0);
                DBG_S(7 + 3 * round);
                cv_steps<0>(acc, a, tv, p);
                DBG_S(8 + 3 * round);
                const int r128 = 4 * (lane >> 3) + 2 * (lane & 1) + ((~lane >> 2) & 1);
#pragma unroll
                for (int i = 0; i < 2; i++) {
                    const uint32_t ta = sb + ((ch + i + 1) & 7) * CV_SL + 12288 + r128 * 128 + ((((~lane & 2) * 2 + w) ^ (r128 & 7)) << 4);
                    stsm4t(ta, tv[i][0], tv[i][1], tv[i][2], tv[i][3]);
                    stsm4t(ta + 2048, tv[i][4], tv[i][5], tv[i][6], tv[i][7]);
                }
                fence_async_smem();
                named_bar_sync(1 + wg, 128);
                if ((tid & 127) < 2) {
                    const int d = d0 + ch + (tid & 1);
                    asm volatile("cp.async.bulk.tensor.4d.global.shared::cta.bulk_group [%0, {%2, %3, %4, %2}], [%1];"
                                 ::"l"((uint64_t)&tm.y), "r"(sb + ((ch + (tid & 1) + 1) & 7) * CV_SL + 12288), "r"(0), "r"(4 * (d >> 8)), "r"(d & 255) : "memory");
                    asm volatile("cp.async.bulk.commit_group;" ::: "memory");
                }
                __syncwarp();
                DBG_S(9 + 3 * round);
            }
            GT(1);
        }
    }
    int warp2 = warp;
    asm volatile("" : "+r"(warp2));
    if (warp2 >= 8) {
        asm volatile("setmaxnreg.dec.sync.aligned.u32 72;");
        if (warp == 8) { if (elect_one()) {
            if (rank == 0) {
                uint32_t smid;
                asm volatile("mov.u32 %0, %%smid;" : "=r"(smid));
                const int t = smid >> 1;
                int team = t < 32 ? t & 7 : t < 60 ? 1 + (t - 32) % 7 : t < 62 ? t - 54 : 0;
                const unsigned long long arr = atomicAdd(reinterpret_cast<unsigned long long*>(g_ticket + 16 * FL_PITCH), 1ull);
                const uint32_t e1 = (uint32_t)(arr / NCL) + 1;
                unsigned int* tk = g_ticket + (e1 & 1) * 8 * FL_PITCH;
                int slot = atomicAdd(tk + team * FL_PITCH, 1u);
                atomicAdd(g_ticket + 17 * FL_PITCH, 1u);
                if (blockIdx.x < 16) g_ticket[((~e1 & 1) * 8 + (blockIdx.x >> 1)) * FL_PITCH] = 0;
                if (slot >= 8) {
                    const long long t0 = clock64();
                    while ((int)(*(volatile unsigned int*)(g_ticket + 17 * FL_PITCH) - e1 * NCL) < 0 && clock64() - t0 < 100000) {}
                    for (team = 0; team < 8; team++)
                        if ((slot = atomicAdd(tk + team * FL_PITCH, 1u)) < 8) break;
                }
#pragma unroll
                for (int i = 0; i < 2; i++)
                    asm volatile("st.async.weak.shared::cluster.mbarrier::complete_tx::bytes.v2.b32 [%0], {%1, %2}, [%3];"
                                 ::"r"(mapa_u32(s_bar + 192, i)), "r"(team * 8 + slot), "r"(e1), "r"(mapa_u32(b_role, i)) : "memory");
            }
            if (get_role()) {
            TM(2);
            mbar_expect_tx(b_rfull, 32768);
            tma_load_2d(sbase + 16384, &tm.q, b_rfull, bj * 128, m0);
            tma_load_2d(sb + 8 * CV_SL, &tm.q, b_rfull, bj * 128 + 64, m0);
            int s5 = 0, s4 = 0;
            uint32_t p5 = 0, p4 = 1;
            auto putB = [&](const CUtensorMap* tB, int kc, uint32_t bytes) {
                const uint32_t full = f5 + 8 * s5;
                mbar_wait(full + 64, (p5 >> s5) & 1);
                mbar_expect_tx(full, bytes);
                tma_load_2d_mc(s_r + 16384 + rank * 8192 + s5 * R5_STAGE, tB, full, bj * 128 + rank * 64, kc);
                p5 ^= 1u << s5;
            };
            auto putA = [&](int c, int r) {
                tma_load_2d(s_r + s5 * R5_STAGE, &tm.act, f5 + 8 * s5, c, r);
                if (++s5 == R5_N) s5 = 0;
            };
            prefetch_tmap(&tm.act); prefetch_tmap(&tm.w1); prefetch_tmap(&tm.w2); prefetch_tmap(&tm.w3); prefetch_tmap(&tm.w4);
            auto own_first = [&](int it) {
                const int hf = it >= 9, c = it - 2 - 7 * hf;
                return (it < 2 ? 2 * bj + it : 2 * (c + (c >= bj)) + hf) * BK;
            };
            const unsigned int n8 = 8 * ep, nh = (bi == 0 || bi == 15) ? 2 * n8 : 3 * n8;
#pragma unroll 1
            for (int layer = 0; layer < 2; layer++) {
                s5 = 2;
#pragma unroll 1
                for (int kk = -(layer | Y_FIRST); kk < 5 - (layer | Y_FIRST); kk++) {
                    if (kk & 4) {
                        if (layer == 0) { TM(1); wait_flag(flag_ptr(0, FL_CS, 8 + bj), 8 * n8); TM(4); fence_proxy_async(); }
                        mbar_wait(e5 + 8, (p5 >> 1) & 1);
                        mbar_expect_tx(f5 + 8, 32768);
                        tma_load_2d(s_r + R5_STAGE, &tm.act, f5 + 8, (bj >> 1) * 256 + rank * 128, R_Y + (tb & ~255) + (bj & 1) * 128);
                        tma_load_2d(s_r + R5_STAGE + 16384, &tm.act, f5 + 8, (bj >> 1) * 256 + rank * 128 + 64, R_Y + (tb & ~255) + (bj & 1) * 128);
                        p5 ^= 2;
                        if (layer == 0) TM(5);
                    } else {
                        putB(&tm.w1, own_first(kk), kk < 2 ? 16384 : R5_STAGE);
                        if (++s5 == R5_N) s5 = 0;
                    }
                }
                s5 = 4;
#pragma unroll 1
                for (int kk = 2; kk < 16; kk++) {
                    const int kc = own_first(kk);
                    if (kk >= 4) putB(&tm.w1, kc, R5_STAGE);
                    if (kk == 2 || kk == 9) {
                        wait_flag(flag_ptr(layer, FL_XA + (kk & 1), bi), n8);
                        if (layer == 0 && kk == 2) TM(14);
                        DP(8 * (FL_XA + (kk & 1)) + 3);
                        fence_proxy_async();
                        DP(8 * (FL_XA + (kk & 1)) + 4);
                    }
                    putA(kc, R_XA + tb);
                }
                mbar_wait(e5 + 24, (p5 >> 3) & 1);
                mbar_arrive(f5 + 24);
                p5 ^= 8;
                s5 = 4;
#pragma unroll 1
                for (int kk = 0; kk < 5; kk++) { putB(&tm.w2, kk * 2 * BK, R5_STAGE); if (++s5 == R5_N) s5 = 0; }
#pragma unroll 1
                for (int kk = 0; kk < 16; kk++) {
                    const int kc = ((kk & 7) * 2 + (kk >> 3)) * BK;
                    if (kk >= 5) putB(&tm.w2, kc, R5_STAGE);
                    if ((kk & 7) == 0) {
                        wait_flag(flag_ptr(layer, FL_H + (kk >> 3), bi), nh);
                        DP(8 * (FL_H + (kk >> 3)) + 3);
                        fence_proxy_async();
                        DP(8 * (FL_H + (kk >> 3)) + 4);
                    }
                    putA(kc, R_H + layer * R_HP + m0 + (int)((0x4031u >> ((kk & 6) << 1)) & 7) - 2);
                }
#pragma unroll 1
                for (int it = 0; it < 32; it++) {
                    const int kc = it >= 16 ? (it - 16) * BK : own_first(it);
                    const int nb = it < 16 ? 4 : 3, n0 = bj * 448 + (it < 16 ? 0 : 256);
                    if (it > 0 && it < 4) {
                        const int i = (it - 1) * 3 >> 1;
                        mbar_wait(e5 + 8 * i, (p5 >> i) & 1);
                        mbar_wait(e5 + 8 * i + 8, (p5 >> (i + 1)) & 1);
                    }
                    mbar_wait(e4 + 8 * s4, p4);
                    if (it >= 16 && it < 19) mbar_wait(e4 + 8 * s4 + 8, p4);
                    uint32_t sa = s_r + s4 * (it < 16 ? R4_STAGE : R4B_STAGE), full = f4 + 8 * s4;
                    mbar_expect_tx(full, (it < 2 ? 0 : 16384) + nb * 8192);
#pragma unroll 1
                    for (int j = (it ^ rank) & 1; j < nb; j += 2) tma_load_2d_mc(sa + (it < 16 ? -32768 : 16384) + j * 8192, &tm.w3, full, n0 + j * 64, kc);
                    if (it == 3 || it == 9) {
                        wait_flag(flag_ptr(layer, FL_X1 + (it >> 3), bi), n8);
                        DP(8 * (FL_X1 + (it >> 3)) + 3);
                        fence_proxy_async();
                        DP(8 * (FL_X1 + (it >> 3)) + 4);
                        if (it == 3) tma_load_2d(s_r + 2 * R4_STAGE, &tm.act, f4 + 16, own_first(2), R_X1 + tb);
                    }
                    if (it >= 3) tma_load_2d(sa, &tm.act, full, kc, R_X1 + tb);
                    if (++s4 == R4_N) { s4 = 0; p4 ^= 1; }
                }
                wait_flag(flag_ptr(layer, FL_H2, bi), n8);
                fence_proxy_async();
                s5 = 0;
#pragma unroll 1
                for (int j = 0; j < 7; j++) {
                    if (j > 0 && (j & 1) == 0) {
                        mbar_wait(b_h2 + 4 * j, layer);
                        fence_proxy_async();
                    }
                    const int ra = R_H2 + (j >> 1) * 256 + tb;
#pragma unroll 1
                    for (int b = 0; b < 8; b++) {
                        if (j == 0 && b < R4_N) mbar_wait(e4 + 8 * b, p4);
                        putB(&tm.w4, (7 * b + j) * BK, R5_STAGE);
                        putA(((j & 1) * 8 + b) * BK, ra);
                    }
                }
            }
        } } } else {
            auto colsum = [&](bool is1, int bi, int bj) {
                const int pitch = is1 ? D_ : F_, c = is1 ? bj * 128 + (lane & 15) * 8 : bj * 448 + min((warp & 2) * 128 + lane * 8, 440);
                const bf16* p = (is1 ? w1p : w3p) + ((bi * 64 + (is1 ? (lane >> 4) * 32 : 0)) * pitch + c);
                float a[8];
#pragma unroll
                for (int i = 0; i < 8; i++) a[i] = 0.f;
#pragma unroll 1
                for (int r0 = is1 ? 32 : 0; r0 < 64; r0 += 8) {
                    uint4 v[8];
#pragma unroll
                    for (int r = 0; r < 8; r++, p += pitch) v[r] = __ldg(reinterpret_cast<const uint4*>(p));
#pragma unroll
                    for (int r = 0; r < 8; r++) {
                        a[0] += lo2f(v[r].x); a[1] += hi2f(v[r].x); a[2] += lo2f(v[r].y); a[3] += hi2f(v[r].y);
                        a[4] += lo2f(v[r].z); a[5] += hi2f(v[r].z); a[6] += lo2f(v[r].w); a[7] += hi2f(v[r].w);
                    }
                }
                if (is1) {
#pragma unroll
                    for (int i = 0; i < 8; i++) a[i] += __shfl_xor_sync(0xffffffffu, a[i], 16);
                }
                float4* dst = reinterpret_cast<float4*>(g_cpart + bi * (F_ + D_) + (is1 ? F_ : 0) + c);
                dst[0] = make_float4(a[0], a[1], a[2], a[3]);
                dst[1] = make_float4(a[4], a[5], a[6], a[7]);
                asm volatile("fence.release.gpu;" ::: "memory");
                __syncwarp();
                if (lane == 0) asm volatile("red.relaxed.gpu.global.add.u32 [%0], 1;" ::"l"(flag_ptr(!is1, FL_CS, bj)) : "memory");
            };
            if (cv && warp == 10) colsum(true, blockIdx.x >> 3, blockIdx.x & 7);
            float4 keep[2];
            const bool on = get_role();
            if (on && warp == 11) {
                uint4* ps = reinterpret_cast<uint4*>(g_stats + (bi * 8 + bj) * 128) + lane;
                ps[0] = ps[32] = make_uint4(0, 0, 0, 0);
                asm volatile("fence.acq_rel.gpu;" ::: "memory");
                __syncwarp();
                if (lane == 0) mbar_arrive(b_rfull);
            }
#pragma unroll 1
            for (int layer = on ? 0 : 2; layer < 2; layer++) {
                if (warp == 10) {
#pragma unroll 1
                    for (int kind = 0; kind < 6; kind += 2) {
                        const uint32_t src = kind == FL_H ? s_stg : s_epi;
                        const int r = kind == FL_H ? R_H + layer * R_HP + m0 : (kind == FL_XA ? R_XA : R_X1) + tb;
#pragma unroll 1
                        for (int hf = 0; hf < 2; hf++) {
                            named_bar_sync(5 + hf, 288);
                            if (lane == 0) {
                                DP(8 * (kind + hf));
                                tma_store_2d(&tm.act, src + hf * 16384, bj * 128 + hf * 64, r);
                                asm volatile("cp.async.bulk.commit_group;" ::: "memory");
                                asm volatile("cp.async.bulk.wait_group 0;" ::: "memory");
                                DP(8 * (kind + hf) + 1);
                                DP(8 * (kind + hf) + 2);
                                unsigned int* fp = flag_ptr(layer, kind + hf, bi);
                                asm volatile("red.relaxed.gpu.global.add.u32 [%0], 1;" ::"l"(fp) : "memory");
                                if (kind == FL_H) {
                                    if (bi > 0) asm volatile("red.relaxed.gpu.global.add.u32 [%0], 1;" ::"l"(fp - FL_PITCH) : "memory");
                                    if (bi < 15) asm volatile("red.relaxed.gpu.global.add.u32 [%0], 1;" ::"l"(fp + FL_PITCH) : "memory");
                                }
                            }
                            __syncwarp();
                        }
                    }
                } else {
                    uint32_t* rs = reinterpret_cast<uint32_t*>(sgen + OFF_RS);
                    float* cs = reinterpret_cast<float*>(sgen + OFF_CS);
#pragma unroll 1
                    for (int which = 0; which < 2; which++) {
                        if (layer < which) {
                            if (warp == 11 && lane == 0) {
                                wait_flag(flag_ptr(0, FL_XA + W3_AT, bi), 8 * ep);
                                asm volatile("cp.async.bulk.prefetch.L2.global [%0], %1;" ::"l"(w3p + (bi * 8 + bj) * 28672), "r"(57344) : "memory");
                            }
                            __syncwarp();
                            colsum(false, bi, bj);
                        }
                        if (warp == 11) continue;
                        if (layer == 0) {
                            if (lane == 0) wait_flag(flag_ptr(which, FL_CS, bj), (16 << which) * ep);
                            __syncwarp();
#pragma unroll 1
                            for (int c = (which ? 384 : 768) + lane * 4; c < 896; c += 128) {
                                const float* cp = g_cpart + (which ? bj * 448 + min(c & 511, 444) : F_ + bj * 128 + lane * 4);
                                float4 a = make_float4(0.f, 0.f, 0.f, 0.f);
#pragma unroll
                                for (int r0 = 0; r0 < 16; r0 += 8) {
                                    float4 v[8];
#pragma unroll
                                    for (int r = 0; r < 8; r++) v[r] = __ldcg(reinterpret_cast<const float4*>(cp + (r0 + r) * (F_ + D_)));
#pragma unroll
                                    for (int r = 0; r < 8; r++) { a.x += v[r].x; a.y += v[r].y; a.z += v[r].z; a.w += v[r].w; }
                                }
                                if (c < 768) *reinterpret_cast<float4*>(cs + min(c & 511, 444)) = a;
                                keep[0] = a;
                            }
                        }
                        if (lane == 0 && (layer | which)) wait_flag(flag_ptr(layer, which == 0 ? FL_XA : FL_X1, bi), 8 * ep);
                        __syncwarp();
                        *reinterpret_cast<float4*>(cs + 256 + lane * 4) = keep[0];
                        { const float4 k0 = keep[0]; keep[0] = keep[1]; keep[1] = k0; }
#pragma unroll 1
                        for (int i = 0; i < 4; i++) {
                            const int r = i * 32 + lane;
                            float mean, var;
                            row_stats(g_stats + (1 + which) * S_ * 8 + bi * 1024 + r, ~layer << 31, mean, var);
                            const uint32_t c0 = pack2(mean, fsqrt(bfr(bfr(var) + 1e-5f)));
                            if (lane < 19 && (layer | which | i) == 0) asm volatile("mbarrier.inval.shared::cta.b64 [%0];" ::"r"(b_full + 8 * lane) : "memory");
                            __syncwarp();
                            rs[r] = c0;
                            const float rd = frcp(hi2f(c0));
                            rs[128 + r] = pack2((mean - lo2f(c0)) * rd, fsqrt(bfr(bfr(var * rd * rd) + 1e-5f)));
                        }
                        __syncwarp();
                        named_bar_arrive(3, 288);
                    }
                }
                const uint32_t s_cnt = s_bar + 224;
                auto ticket = [&](uint32_t a) {
                    uint32_t v = 0;
                    if (lane == 0) asm volatile("atom.acq_rel.cta.shared.add.u32 %0, [%1], 1;" : "=r"(v) : "r"(a) : "memory");
                    return v;
                };
                mbar_wait(b_stg, 0);
                int u = __shfl_sync(0xffffffffu, ticket(s_cnt + 16 + 4 * layer), 0), step = 0;
#pragma unroll 1
                while (true) {
#pragma unroll 1
                    for (; step < 5 && u >= (int)((0x3830201810ull >> (8 * step)) & 255); step++) {
                        if (step == 1) { named_bar_arrive(4, 352); continue; }
                        const int part = step ? step - 1 : 0;
                        __syncwarp();
                        if (ticket(s_cnt + 4 * part) == 3 * layer + 2) {
                            asm volatile("fence.release.gpu;" ::: "memory");
                            unsigned int* fp = flag_ptr(layer, FL_H2 + part, bi);
                            asm volatile("red.relaxed.gpu.global.add.u32 [%0], 1;" ::"l"(fp) : "memory");
                            if (part > 0) { wait_flag(fp, 8 * ep); mbar_arrive(b_h2 + 8 * part); }
                        }
                        __syncwarp();
                        if (step == 2) mbar_wait(b_stg, 1);
                    }
                    if (u >= 56) break;
                    const uint32_t un = ticket(s_cnt + 16 + 4 * layer);
                    const int job = u >> 3, r = (u & 7) * 16 + (lane >> 3);
                    const uint32_t sp = sbase + ((job & 2) ? OFF_STG5 : OFF_EPI) + r * 256 + (job & 1) * 128;
                    bf16* gp = act + (size_t)(R_H2 + (job >> 1) * 256 + tb + r) * D_ + ((job & 1) * 8 + bj) * 64 + (lane & 7) * 8;
                    uint4 v[4];
#pragma unroll
                    for (int e = 0; e < 4; e++) v[e] = lds128(sp + e * 1024 + (((lane & 7) ^ ((r + 4 * e) & 7)) << 4));
#pragma unroll
                    for (int e = 0; e < 4; e++) stg128(gp + 4 * e * D_, gelu8h(v[e]));
                    u = __shfl_sync(0xffffffffu, un, 0);
                }
                if (layer == 0 && warp == 11) {
                    const char* ps = reinterpret_cast<const char*>(g_stats + bi * 1024) + lane * 128;
                    const char* py = reinterpret_cast<const char*>(act + (size_t)(R_Y + (tb & ~255) + (bj & 1) * 128 + (lane >> 1)) * D_ + (bj >> 1) * 256 + rank * 128) + (lane & 1) * 128;
#pragma unroll 1
                    for (int i = 0; i < 8; i++) {
                        asm volatile("prefetch.global.L2 [%0];" ::"l"(py + (size_t)i * 16 * D_ * 2) : "memory");
                        if (i >= 6) asm volatile("prefetch.global.L2 [%0];" ::"l"(ps + (i & 1) * 4096) : "memory");
                        __nanosleep(400);
                    }
                }
            }
        }
        __syncwarp();
        asm volatile("barrier.cluster.arrive.relaxed.aligned;\nbarrier.cluster.wait.acquire.aligned; // helpers" ::: "memory");
    } else {
        DT(0);
        GT(2);
        if (tid == 0) TM(10);
        auto put_y = [&]() {
            if ((tid & 127) < 2 && cv) {
                if (tid == 0) TM(6);
                asm volatile("cp.async.bulk.wait_group 0;" ::: "memory");
                asm volatile("red.relaxed.gpu.global.add.u32 [%0], 1;" ::"l"(flag_ptr(0, FL_CS, 8 + (blockIdx.x >> 4))) : "memory");
                if (tid == 0) TM(7);
                if (tid == 128) TM(8);
            }
            __syncwarp();
        };
        put_y();
        asm volatile("setmaxnreg.inc.sync.aligned.u32 216;");
        if (get_role()) {
        const bool rel_on = (tid & 95) == 0;
        const uint32_t rel5 = mapa_u32(e5, (warp & 1) ^ rank), rel4 = rel5 + (e4 - e5);
        const uint32_t da0 = desc_a(s_r + wg * 8192), db0 = desc_b(s_r + BM * BK * 2), dae = da0 + (OFF_EPI - OFF_R) / 16, db4 = db0 - 49152 / 16;
        auto skip5 = [&](RingState& rs) {
            if (rel_on) mbar_arrive_cluster(rel5 + 8 * rs.st);
            rs.st++;
        };
        const int t = lane & 3;
        const int row = warp * 16 + (lane >> 2);
        const uint32_t st_w = (uint32_t)((warp * 16 + ((lane >> 3) & 1) * 8 + (lane & 7)) * 256 + (((lane >> 4) ^ (lane & 7)) << 4));
        const uint32_t fr = (uint32_t)((warp * 16 + ((lane >> 3) & 1) * 8 + (lane & 7)) * 128 + (((lane >> 4) ^ (lane & 7)) << 4));
        auto copy_out = [&](bf16* dst, uint32_t src) {
            const int r = warp * 16 + (lane >> 4);
            bf16* ox = dst + (size_t)(m0 + r) * D_ + bj * 128 + (lane & 15) * 8;
            const uint32_t ra = src + ((lane & 15) >> 3) * 16384 + r * 128;
            uint4 v[8];
#pragma unroll
            for (int it = 0; it < 8; it++) v[it] = lds128(ra + it * 256 + (((lane & 7) ^ ((2 * it + (lane >> 4)) & 7)) << 4));
#pragma unroll
            for (int it = 0; it < 8; it++) *reinterpret_cast<uint4*>(ox + (size_t)it * 2 * D_) = v[it];
        };
        auto put_stats = [&](const uint32_t (&w)[32], int which, int layer) {
            float sm[2] = {0.f, 0.f}, sq[2] = {0.f, 0.f};
#pragma unroll
            for (int e = 0; e < 32; e++) {
                const float e0 = lo2f(w[e]), e1 = hi2f(w[e]);
                sm[e & 1] += e0 + e1; sq[e & 1] = fmaf(e0, e0, fmaf(e1, e1, sq[e & 1]));
            }
#pragma unroll
            for (int of = 1; of < 4; of <<= 1)
#pragma unroll
                for (int e = 0; e < 2; e++) { sm[e] += __shfl_xor_sync(0xffffffffu, sm[e], of); sq[e] += __shfl_xor_sync(0xffffffffu, sq[e], of); }
            if (t < 2) {
                const float s1 = t ? sm[1] : sm[0], q1 = t ? sq[1] : sq[0], mu = s1 * (1.0f / 128);
                asm volatile("{\n.reg .b64 t;\nmov.b64 t, {%1, %2};\nst.relaxed.gpu.global.b64 [%0], t;\n}"
                             ::"l"(g_stats + which * S_ * 8 + (bi * 8 + bj) * 128 + row + 8 * t), "f"(mu), "r"(__float_as_uint(fmaxf(q1 - s1 * mu, 0.f)) | ~layer << 31) : "memory");
            }
        };
        const float* csp = reinterpret_cast<const float*>(sgen + OFF_CS) + 2 * t;
        float mrow[2], rrow[2];
        const uint32_t* rsp = reinterpret_cast<const uint32_t*>(sgen + OFF_RS) + row;
        auto row_consts = [&](bool twice) {
#pragma unroll
            for (int e = 0; e < 2; e++) {
                const uint32_t q0 = rsp[8 * e], q1 = rsp[128 + 8 * e];
                mrow[e] = twice ? fmaf(lo2f(q1), hi2f(q0), lo2f(q0)) : lo2f(q0);
                rrow[e] = 0.5f * frcp(twice ? hi2f(q0) * hi2f(q1) : hi2f(q0));
            }
        };
        auto stage = [&](const float* acc, uint32_t dst, int j0, float2 (&cs)[8], const float* cnext) {
            float2 cn[8];
#pragma unroll
            for (int e = 0; e < 8; e++) cn[e] = *reinterpret_cast<const float2*>(cnext + 8 * e);
#pragma unroll
            for (int j = 0; j < 8; j += 2) {
                uint32_t w[4];
#pragma unroll
                for (int e = 0; e < 2; e++) {
                    const float* a = acc + 4 * (j + e);
                    w[2 * e] = pack2(fmaf(-mrow[0], cs[j + e].x, a[0]) * rrow[0], fmaf(-mrow[0], cs[j + e].y, a[1]) * rrow[0]);
                    w[2 * e + 1] = pack2(fmaf(-mrow[1], cs[j + e].x, a[2]) * rrow[1], fmaf(-mrow[1], cs[j + e].y, a[3]) * rrow[1]);
                }
                stsm4((dst + st_w) ^ (((j0 + j) & 15) << 4), w[0], w[1], w[2], w[3]);
            }
#pragma unroll
            for (int e = 0; e < 8; e++) cs[e] = cn[e];
        };
        RingState r5{1, 0}, r4{0, 0};
        DT(1);
        uint32_t x[32];
        mbar_wait(b_rfull, 0);
#pragma unroll
        for (int jp = 0; jp < 8; jp++) ldsm4(x[4 * jp], x[4 * jp + 1], x[4 * jp + 2], x[4 * jp + 3], sbase + 16384 + (fr ^ ((jp & 3) << 5)) + (jp >> 2) * (16384 + 8 * CV_SL));
#pragma unroll
        for (int e = 0; e < 32; e++) asm volatile("" : "+r"(x[e]));
        named_bar_sync(9 + wg, 128);
        if ((tid & 95) < R5_N) mbar_arrive_cluster(rel5 + 8 * lane);
#pragma unroll 1
        for (int layer = 0; layer < 2; layer++) {
            {
                DT(2 + 24 * layer);
                if (layer == 0 && tid == 0) TM(12);
                put_stats(x, 0, layer);
                DT(20 + 24 * layer);
                DT(22 + 24 * layer);
                uint32_t mb[2];
                float rd[2];
                {
                    float mean, var;
                    row_stats(g_stats + bi * 1024 + warp * 16 + (lane & 15), ~layer << 31, mean, var);
                    __syncwarp();
                    const float r1 = frcp(bfr(fsqrt(bfr(bfr(var) + 1e-5f))));
                    const uint32_t m1 = pack2(mean, mean);
#pragma unroll
                    for (int e = 0; e < 2; e++) { mb[e] = __shfl_sync(0xffffffffu, m1, (lane >> 2) + 8 * e); rd[e] = __shfl_sync(0xffffffffu, r1, (lane >> 2) + 8 * e); }
                }
                DT(21 + 24 * layer);
                if (layer == 0 && tid == 0) TM(11);
                mbar_wait(f5 + 8, r5.ph);
                if (layer == 0) GT(3);
                if (layer == 0 && tid == 0) TM(9);
                const uint32_t ya = s_r + R5_STAGE + wg * 16384 + ((lane >> 4) * 8 + (lane & 7)) * 128 + ((((warp & 3) * 2 + ((lane >> 3) & 1)) ^ (lane & 7)) << 4);
                uint32_t y[16];
#pragma unroll
                for (int e = 0; e < 32; e++) {
                    if ((e & 15) == 0) {
#pragma unroll
                        for (int jp = 0; jp < 4; jp++) ldsm4t(y[4 * jp], y[4 * jp + 1], y[4 * jp + 2], y[4 * jp + 3], ya + jp * 2048 + e * 512);
                    }
                    const uint32_t d = bsub2(x[e], mb[e & 1]);
                    x[e] = badd2(x[e], bmul2(pack2(lo2f(d) * rd[e & 1], hi2f(d) * rd[e & 1]), y[e & 15]));
                    if ((e & 3) == 3) stsm4(s_epi + (fr ^ (((e >> 2) & 3) << 5)) + (e >> 4) * 16384, x[e - 3], x[e - 2], x[e - 1], x[e]);
                    if ((e & 15) == 15) { fence_async_smem(); named_bar_arrive(5 + (e >> 4), 288); }
                }
                DT(19 + 24 * layer);
                named_bar_sync(9 + wg, 128);
                skip5(r5);
                DT(3 + 24 * layer);
                if (layer == 0 && tid == 0) TM(13);
            }
            {
                float acc[64];
                zero_acc(acc);
                kblock<128, R5_N>(acc, dae, db0 + 2 * (R5_STAGE / 16), f5, r5);
                kblock<128, R5_N>(acc, dae + 1024, db0 + 3 * (R5_STAGE / 16), f5, r5);
                put_stats(x, 1, layer);
                wgmma_wait<1>();
                if (rel_on) mbar_arrive_cluster(rel5 + 16);
                mainloop<128, R5_N, R5_STAGE>(acc, 14, da0, db0, f5, rel5, rel_on, r5, 15 + 24 * layer);
                DT(4 + 24 * layer);
                if (layer == 0 && tid == 0) TM(15);
                named_bar_sync(3, 288);
                row_consts(true);
                float2 cs[8];
#pragma unroll
                for (int j = 0; j < 16; j += 2) {
                    if ((j & 7) == 0) {
#pragma unroll
                        for (int e = 0; e < 8; e++) cs[e] = *reinterpret_cast<const float2*>(csp + 256 + 8 * (j + e));
                    }
                    uint32_t w[4];
#pragma unroll
                    for (int e = 0; e < 4; e++) {
                        const float* a = acc + 4 * j + 2 * e;
                        const float2 c = cs[(j & 7) + (e >> 1)];
                        w[e] = pack2(gelu_tanh_h(fmaf(-mrow[e & 1], c.x, a[0]) * rrow[e & 1]), gelu_tanh_h(fmaf(-mrow[e & 1], c.y, a[1]) * rrow[e & 1]));
                    }
                    stsm4(s_stg + (fr ^ ((j & 7) << 4)) + (j >> 3) * 16384, w[0], w[1], w[2], w[3]);
                    if ((j & 7) == 6) { fence_async_smem(); named_bar_arrive(5 + (j >> 3), 288); }
                }
                DT(5 + 24 * layer);
            }
            {
                float acc[64];
                zero_acc(acc);
                uint32_t u[32];
                {
                    uint32_t mb[2];
                    float rd[2];
#pragma unroll
                    for (int e = 0; e < 2; e++) { const uint32_t q0 = rsp[8 * e]; mb[e] = (q0 & 0xffffu) * 0x10001u; rd[e] = frcp(hi2f(q0)); }
#pragma unroll
                    for (int e = 0; e < 32; e++) {
                        const uint32_t d = bsub2(x[e], mb[e & 1]);
                        u[e] = pack2(lo2f(d) * rd[e & 1], hi2f(d) * rd[e & 1]);
                        asm volatile("" : "+r"(u[e]));
                    }
                }
                mbar_wait(f5 + 24, r5.ph);
                skip5(r5);
                kblock<128, R5_N>(acc, da0 + 4 * (R5_STAGE / 16), db0 + 4 * (R5_STAGE / 16), f5, r5);
                DT(16 + 24 * layer);
                mainloop<128, R5_N, R5_STAGE>(acc, 15, da0, db0, f5, rel5, rel_on, r5, -1);
                DT(6 + 24 * layer);
#pragma unroll
                for (int j = 0; j < 16; j += 2) {
#pragma unroll
                    for (int e = 0; e < 4; e++) u[2 * j + e] = badd2(u[2 * j + e], pack2(acc[4 * j + 2 * e], acc[4 * j + 2 * e + 1]));
                    stsm4(s_epi + (fr ^ ((j & 7) << 4)) + (j >> 3) * 16384, u[2 * j], u[2 * j + 1], u[2 * j + 2], u[2 * j + 3]);
                    if ((j & 7) == 6) { fence_async_smem(); named_bar_arrive(5 + (j >> 3), 288); }
                }
#pragma unroll
                for (int e = 0; e < 32; e++) x[e] = badd2(x[e], u[e]);
                named_bar_sync(9 + wg, 128);
                DT(7 + 24 * layer);
                if (layer == 0) GT(7);
            }
            {
                float2 cs[8];
                {
                    float acc[128];
                    zero_acc(acc);
                    kblock<256, R4_N>(acc, dae, db4, f4, r4);
                    kblock<256, R4_N>(acc, dae + 1024, db4 + R4_STAGE / 16, f4, r4);
                    {
                        uint32_t w[32];
#pragma unroll
                        for (int jp = 0; jp < 8; jp++) ldsm4(w[4 * jp], w[4 * jp + 1], w[4 * jp + 2], w[4 * jp + 3], s_epi + (fr ^ ((jp & 3) << 5)) + (jp >> 2) * 16384);
                        put_stats(w, 2, layer);
                    }
                    wgmma_wait<1>();
                    if (rel_on) mbar_arrive_cluster(rel4);
                    mainloop<256, R4_N, R4_STAGE>(acc, 14, da0, db4, f4, rel4, rel_on, r4, 17 + 24 * layer);
                    DT(8 + 24 * layer);
                    named_bar_sync(3, 288);
                    row_consts(false);
#pragma unroll
                    for (int e = 0; e < 8; e++) cs[e] = *reinterpret_cast<const float2*>(csp + 8 * e);
#pragma unroll
                    for (int j = 0; j < 32; j += 8) stage(acc + 4 * j, j < 16 ? s_epi : s_stg, j, cs, csp + 8 * (j + 8));
                    __syncwarp();
                if (lane == 0) mbar_arrive(b_stg);
                }
                DT(9 + 24 * layer);
                float acc[96];
                zero_acc(acc);
                kblock<192, R4_N>(acc, da0, db0, f4, r4);
                mainloop<192, R4_N, R4B_STAGE>(acc, 15, da0, db0, f4, rel4, rel_on, r4, -1);
                DT(10 + 24 * layer);
                named_bar_sync(4, 352);
#pragma unroll
                for (int j = 0; j < 24; j += 8) stage(acc + 4 * j, j < 16 ? s_epi : s_stg, j, cs, csp + 256 + 8 * (j < 16 ? j + 8 : 0));
                __syncwarp();
                if (lane == 0) mbar_arrive(b_stg);
                DT(11 + 24 * layer);
            }
            {
                float acc[64];
#pragma unroll
                for (int i = 0; i < 32; i++) asm volatile("shl.b32 %0, %2, 16;\nand.b32 %1, %2, 0xffff0000;" : "=f"(acc[2 * i]), "=f"(acc[2 * i + 1]) : "r"(x[i]));
                kblock<128, R5_N>(acc, da0, db0, f5, r5);
                DT(18 + 24 * layer);
                mainloop<128, R5_N, R5_STAGE>(acc, 55, da0, db0, f5, rel5, rel_on, r5, 62 - 40 * (layer ^ 1));
                DT(12 + 24 * layer);
#pragma unroll
                for (int i = 0; i < 32; i++) x[i] = pack2(acc[2 * i], acc[2 * i + 1]);
                DT(13 + 24 * layer);
                if (layer == 0) GT(6);
                DT(14 + 24 * layer);
            }
        }
#pragma unroll
        for (int jp = 0; jp < 8; jp++) stsm4(s_epi + (fr ^ ((jp & 3) << 5)) + (jp >> 2) * 16384, x[4 * jp], x[4 * jp + 1], x[4 * jp + 2], x[4 * jp + 3]);
        __syncwarp();
        copy_out(outp, s_epi);
        DT(38);
        GT(4);
        }
        cluster_arrive_relaxed();
        cluster_wait();
    }
}

typedef CUresult (*PFN_encodeTiled)(CUtensorMap*, CUtensorMapDataType, cuuint32_t, void*, const cuuint64_t*, const cuuint64_t*,
                                    const cuuint32_t*, const cuuint32_t*, CUtensorMapInterleave, CUtensorMapSwizzle,
                                    CUtensorMapL2promotion, CUtensorMapFloatOOBfill);

static CUtensorMap make_map(PFN_encodeTiled enc, const void* ptr, int inner, int outer, int box_inner, int box_outer,
                            CUtensorMapSwizzle swz = CU_TENSOR_MAP_SWIZZLE_128B) {
    CUtensorMap m;
    cuuint64_t dims[2] = {(cuuint64_t)inner, (cuuint64_t)outer};
    cuuint64_t strides[1] = {(cuuint64_t)inner * 2};
    cuuint32_t box[2] = {(cuuint32_t)box_inner, (cuuint32_t)box_outer};
    cuuint32_t es[2] = {1, 1};
    enc(&m, CU_TENSOR_MAP_DATA_TYPE_BFLOAT16, 2, const_cast<void*>(ptr), dims, strides, box, es, CU_TENSOR_MAP_INTERLEAVE_NONE,
        swz, CU_TENSOR_MAP_L2_PROMOTION_L2_256B, CU_TENSOR_MAP_FLOAT_OOB_FILL_NONE);
    return m;
}

extern "C" void kernel_launch(void* const* d_in, const int* in_sizes, int n_in, void* d_out, int out_size) {
    const bf16* A_q = (const bf16*)d_in[0];
    const bf16* A_k = (const bf16*)d_in[1];
    const bf16* A_v = (const bf16*)d_in[2];
    const bf16* A_shk = (const bf16*)d_in[3];
    const bf16* A_ssk = (const bf16*)d_in[4];
    const bf16* A_ssD = (const bf16*)d_in[5];
    const bf16* w1 = (const bf16*)d_in[7];
    const bf16* w2 = (const bf16*)d_in[8];
    const bf16* w3 = (const bf16*)d_in[9];
    const bf16* w4 = (const bf16*)d_in[10];
    bf16* out = (bf16*)d_out;

    static PFN_encodeTiled enc = nullptr;
    static bool attr_done = false;
    if (!enc) {
        void* fn = nullptr;
        cudaDriverEntryPointQueryResult qr;
        cudaGetDriverEntryPoint("cuTensorMapEncodeTiled", &fn, cudaEnableDefault, &qr);
        enc = (PFN_encodeTiled)fn;
    }
    if (!attr_done) {
        cudaFuncSetAttribute(mega_kernel, cudaFuncAttributeMaxDynamicSharedMemorySize, MEGA_SMEM);
        attr_done = true;
    }
    void* p_act;
    cudaGetSymbolAddress(&p_act, g_act);
    bf16* act = (bf16*)(((uintptr_t)p_act + 0x1fffff) & ~(uintptr_t)0x1fffff);

    MegaMaps tm;
    tm.q = make_map(enc, A_q, D_, S_, 64, 128);
    tm.act = make_map(enc, act, D_, R_END, 64, 128);
    tm.w1 = make_map(enc, w1, D_, D_, 64, 64);
    tm.w2 = make_map(enc, w2, D_, D_, 64, 64);
    tm.w3 = make_map(enc, w3, F_, D_, 64, 64);
    tm.w4 = make_map(enc, w4, D_, F_, 64, 64);
    {
        cuuint64_t dims[4] = {64, 16, 256, 8}, strides[3] = {128, D_ * 2, (cuuint64_t)2048 * D_ * 2};
        cuuint32_t box[4] = {64, 4, 1, 8}, es[4] = {1, 1, 1, 1};
        enc(&tm.y, CU_TENSOR_MAP_DATA_TYPE_BFLOAT16, 4, act + (size_t)R_Y * D_, dims, strides, box, es, CU_TENSOR_MAP_INTERLEAVE_NONE,
            CU_TENSOR_MAP_SWIZZLE_128B, CU_TENSOR_MAP_L2_PROMOTION_NONE, CU_TENSOR_MAP_FLOAT_OOB_FILL_NONE);
    }
    for (int i = 0; i < 2; i++) {
        cuuint64_t dims[4] = {D_, 4, 8, S_ / 32}, strides[3] = {8 * D_ * 2, D_ * 2, 32 * D_ * 2};
        cuuint32_t box[4] = {16, 4, 8, 4}, es[4] = {1, 1, 1, 1};
        enc(i ? &tm.v : &tm.k, CU_TENSOR_MAP_DATA_TYPE_BFLOAT16, 4, (void*)(i ? A_v : A_k), dims, strides, box, es, CU_TENSOR_MAP_INTERLEAVE_NONE,
            CU_TENSOR_MAP_SWIZZLE_32B, CU_TENSOR_MAP_L2_PROMOTION_NONE, CU_TENSOR_MAP_FLOAT_OOB_FILL_NONE);
    }
    mega_kernel<<<2 * NCL, 384, MEGA_SMEM, cudaStreamPerThread>>>(tm, out, act, w1, w2, w3, A_q, A_k, A_v, A_shk, A_ssk, A_ssD);
}
```

```cpp
#include <cuda_runtime.h>
#include <cuda_bf16.h>
#include <cuda.h>
#include <stdint.h>

typedef __nv_bfloat16 bf16;

constexpr int S_ = 2048;
constexpr int D_ = 1024;
constexpr int F_ = 3584;

constexpr int R_XA = 0, R_X1 = 256, R_H2 = 512, R_Y = 1536, R_H = 16384 + 8, R_HP = S_ + 8, R_END = R_H + 2 * R_HP;
__device__ __align__(1024) bf16 g_act[(size_t)(R_END + 1024) * D_];
__device__ __align__(16) float g_cpart[16 * (F_ + D_)];
__device__ __align__(128) float2 g_stats[3 * S_ * 8];

__device__ __forceinline__ float bfr(float x) { return __bfloat162float(__float2bfloat16_rn(x)); }
__device__ __forceinline__ uint32_t pack2(float lo, float hi) {
    __nv_bfloat162 v = __floats2bfloat162_rn(lo, hi);
    return *reinterpret_cast<uint32_t*>(&v);
}
__device__ __forceinline__ float lo2f(uint32_t v) { return __uint_as_float(v << 16); }
__device__ __forceinline__ float hi2f(uint32_t v) { return __uint_as_float(v & 0xffff0000u); }
__device__ __forceinline__ float frcp(float x) { float r; asm("rcp.approx.f32 %0, %1;" : "=f"(r) : "f"(x)); return r; }
__device__ __forceinline__ float fsqrt(float x) { float r; asm("sqrt.approx.f32 %0, %1;" : "=f"(r) : "f"(x)); return r; }
__device__ __forceinline__ uint32_t smem_u32(const void* p) { return (uint32_t)__cvta_generic_to_shared(p); }

__device__ __forceinline__ void mbar_init(uint32_t bar, uint32_t cnt) {
    asm volatile("mbarrier.init.shared::cta.b64 [%0], %1;" ::"r"(bar), "r"(cnt));
}
__device__ __forceinline__ void mbar_expect_tx(uint32_t bar, uint32_t bytes) {
    asm volatile("mbarrier.arrive.expect_tx.shared::cta.b64 _, [%0], %1;" ::"r"(bar), "r"(bytes) : "memory");
}
__device__ __forceinline__ void mbar_arrive(uint32_t bar) {
    asm volatile("mbarrier.arrive.shared::cta.b64 _, [%0];" ::"r"(bar) : "memory");
}
__device__ __forceinline__ void mbar_wait(uint32_t bar, uint32_t parity) {
    asm volatile(
        "{\n.reg .pred p;\n.reg .u32 n;\n"
        "mbarrier.try_wait.parity.shared::cta.b64 p, [%0], %1;\n"
        "@p bra LD;\n"
        "mov.u32 n, 0;\n"
        "LW:\n"
        "mbarrier.try_wait.parity.shared::cta.b64 p, [%0], %1;\n"
        "@p bra LD;\n"
        "add.u32 n, n, 1;\n"
        "setp.lt.u32 p, n, 0x400000;\n"
        "@p bra LW;\n"
        "LD:\n}\n"
        ::"r"(bar), "r"(parity) : "memory");
}
__device__ __forceinline__ void tma_load_2d(uint32_t dst, const CUtensorMap* tm, uint32_t bar, int c0, int c1) {
    asm volatile(
        "cp.async.bulk.tensor.2d.shared::cluster.global.mbarrier::complete_tx::bytes [%0], [%1, {%3, %4}], [%2];"
        ::"r"(dst), "l"((uint64_t)tm), "r"(bar), "r"(c0), "r"(c1) : "memory");
}
__device__ __forceinline__ void tma_load_2d_mc(uint32_t dst, const CUtensorMap* tm, uint32_t bar, int c0, int c1) {
    asm volatile(
        "cp.async.bulk.tensor.2d.shared::cluster.global.mbarrier::complete_tx::bytes.multicast::cluster [%0], [%1, {%3, %4}], [%2], %5;"
        ::"r"(dst), "l"((uint64_t)tm), "r"(bar), "r"(c0), "r"(c1), "h"((uint16_t)3) : "memory");
}
__device__ __forceinline__ void tma_prefetch_2d(const CUtensorMap* tm, int c0, int c1) {
    asm volatile("cp.async.bulk.prefetch.tensor.2d.L2.global.tile [%0, {%1, %2}];" ::"l"((uint64_t)tm), "r"(c0), "r"(c1) : "memory");
}
__device__ __forceinline__ void tma_store_2d(const CUtensorMap* tm, uint32_t src, int c0, int c1) {
    asm volatile("cp.async.bulk.tensor.2d.global.shared::cta.bulk_group [%0, {%2, %3}], [%1];"
                 ::"l"((uint64_t)tm), "r"(src), "r"(c0), "r"(c1) : "memory");
}
__device__ __forceinline__ void wgmma_fence() { asm volatile("wgmma.fence.sync.aligned;" ::: "memory"); }
__device__ __forceinline__ void wgmma_commit() { asm volatile("wgmma.commit_group.sync.aligned;" ::: "memory"); }
template <int N> __device__ __forceinline__ void wgmma_wait() { asm volatile("wgmma.wait_group.sync.aligned %0;" ::"n"(N) : "memory"); }
__device__ __forceinline__ void named_bar_arrive(int id, int n) { asm volatile("bar.arrive %0, %1;" ::"r"(id), "r"(n) : "memory"); }
__device__ __forceinline__ void named_bar_sync(int id, int n) { asm volatile("bar.sync %0, %1;" ::"r"(id), "r"(n) : "memory"); }

__device__ __forceinline__ uint32_t desc_a(uint32_t addr) { return ((addr & 0x3FFFF) >> 4) | (1u << 16); }
__device__ __forceinline__ uint32_t desc_b(uint32_t addr) { return ((addr & 0x3FFFF) >> 4) | (512u << 16); }

__device__ __forceinline__ void wgmma_m64n192k16(float (&d)[96], uint32_t descA, uint32_t descB) {
  asm volatile("{\n.reg .pred p;\n.reg .b64 da, db;\nsetp.eq.b32 p, 0, 0;\nmov.b64 da, {%96, %98};\nmov.b64 db, {%97, %98};\n"
    "wgmma.mma_async.sync.aligned.m64n192k16.f32.bf16.bf16 "
    "{%0, %1, %2, %3, %4, %5, %6, %7, %8, %9, %10, %11, %12, %13, %14, %15, %16, %17, %18, %19, %20, %21, %22, %23, %24, %25, %26, %27, %28, %29, %30, %31, %32, %33, %34, %35, %36, %37, %38, %39, %40, %41, %42, %43, %44, %45, %46, %47, %48, %49, %50, %51, %52, %53, %54, %55, %56, %57, %58, %59, %60, %61, %62, %63, %64, %65, %66, %67, %68, %69, %70, %71, %72, %73, %74, %75, %76, %77, %78, %79, %80, %81, %82, %83, %84, %85, %86, %87, %88, %89, %90, %91, %92, %93, %94, %95}, "
    "da, db, p, 1, 1, 0, 1;\n}\n"
    : "+f"(d[0]), "+f"(d[1]), "+f"(d[2]), "+f"(d[3]), "+f"(d[4]), "+f"(d[5]), "+f"(d[6]), "+f"(d[7]), "+f"(d[8]), "+f"(d[9]), "+f"(d[10]), "+f"(d[11]), "+f"(d[12]), "+f"(d[13]), "+f"(d[14]), "+f"(d[15]), "+f"(d[16]), "+f"(d[17]), "+f"(d[18]), "+f"(d[19]), "+f"(d[20]), "+f"(d[21]), "+f"(d[22]), "+f"(d[23]), "+f"(d[24]), "+f"(d[25]), "+f"(d[26]), "+f"(d[27]), "+f"(d[28]), "+f"(d[29]), "+f"(d[30]), "+f"(d[31]), "+f"(d[32]), "+f"(d[33]), "+f"(d[34]), "+f"(d[35]), "+f"(d[36]), "+f"(d[37]), "+f"(d[38]), "+f"(d[39]), "+f"(d[40]), "+f"(d[41]), "+f"(d[42]), "+f"(d[43]), "+f"(d[44]), "+f"(d[45]), "+f"(d[46]), "+f"(d[47]), "+f"(d[48]), "+f"(d[49]), "+f"(d[50]), "+f"(d[51]), "+f"(d[52]), "+f"(d[53]), "+f"(d[54]), "+f"(d[55]), "+f"(d[56]), "+f"(d[57]), "+f"(d[58]), "+f"(d[59]), "+f"(d[60]), "+f"(d[61]), "+f"(d[62]), "+f"(d[63]), "+f"(d[64]), "+f"(d[65]), "+f"(d[66]), "+f"(d[67]), "+f"(d[68]), "+f"(d[69]), "+f"(d[70]), "+f"(d[71]), "+f"(d[72]), "+f"(d[73]), "+f"(d[74]), "+f"(d[75]), "+f"(d[76]), "+f"(d[77]), "+f"(d[78]), "+f"(d[79]), "+f"(d[80]), "+f"(d[81]), "+f"(d[82]), "+f"(d[83]), "+f"(d[84]), "+f"(d[85]), "+f"(d[86]), "+f"(d[87]), "+f"(d[88]), "+f"(d[89]), "+f"(d[90]), "+f"(d[91]), "+f"(d[92]), "+f"(d[93]), "+f"(d[94]), "+f"(d[95])
    : "r"(descA), "r"(descB), "r"(0x40000040u));
}

__device__ __forceinline__ void wgmma_m64n256k16(float (&d)[128], uint32_t descA, uint32_t descB) {
  asm volatile("{\n.reg .pred p;\n.reg .b64 da, db;\nsetp.eq.b32 p, 0, 0;\nmov.b64 da, {%128, %130};\nmov.b64 db, {%129, %130};\n"
    "wgmma.mma_async.sync.aligned.m64n256k16.f32.bf16.bf16 "
    "{%0, %1, %2, %3, %4, %5, %6, %7, %8, %9, %10, %11, %12, %13, %14, %15, %16, %17, %18, %19, %20, %21, %22, %23, %24, %25, %26, %27, %28, %29, %30, %31, %32, %33, %34, %35, %36, %37, %38, %39, %40, %41, %42, %43, %44, %45, %46, %47, %48, %49, %50, %51, %52, %53, %54, %55, %56, %57, %58, %59, %60, %61, %62, %63, %64, %65, %66, %67, %68, %69, %70, %71, %72, %73, %74, %75, %76, %77, %78, %79, %80, %81, %82, %83, %84, %85, %86, %87, %88, %89, %90, %91, %92, %93, %94, %95, %96, %97, %98, %99, %100, %101, %102, %103, %104, %105, %106, %107, %108, %109, %110, %111, %112, %113, %114, %115, %116, %117, %118, %119, %120, %121, %122, %123, %124, %125, %126, %127}, "
    "da, db, p, 1, 1, 0, 1;\n}\n"
    : "+f"(d[0]), "+f"(d[1]), "+f"(d[2]), "+f"(d[3]), "+f"(d[4]), "+f"(d[5]), "+f"(d[6]), "+f"(d[7]), "+f"(d[8]), "+f"(d[9]), "+f"(d[10]), "+f"(d[11]), "+f"(d[12]), "+f"(d[13]), "+f"(d[14]), "+f"(d[15]), "+f"(d[16]), "+f"(d[17]), "+f"(d[18]), "+f"(d[19]), "+f"(d[20]), "+f"(d[21]), "+f"(d[22]), "+f"(d[23]), "+f"(d[24]), "+f"(d[25]), "+f"(d[26]), "+f"(d[27]), "+f"(d[28]), "+f"(d[29]), "+f"(d[30]), "+f"(d[31]), "+f"(d[32]), "+f"(d[33]), "+f"(d[34]), "+f"(d[35]), "+f"(d[36]), "+f"(d[37]), "+f"(d[38]), "+f"(d[39]), "+f"(d[40]), "+f"(d[41]), "+f"(d[42]), "+f"(d[43]), "+f"(d[44]), "+f"(d[45]), "+f"(d[46]), "+f"(d[47]), "+f"(d[48]), "+f"(d[49]), "+f"(d[50]), "+f"(d[51]), "+f"(d[52]), "+f"(d[53]), "+f"(d[54]), "+f"(d[55]), "+f"(d[56]), "+f"(d[57]), "+f"(d[58]), "+f"(d[59]), "+f"(d[60]), "+f"(d[61]), "+f"(d[62]), "+f"(d[63]), "+f"(d[64]), "+f"(d[65]), "+f"(d[66]), "+f"(d[67]), "+f"(d[68]), "+f"(d[69]), "+f"(d[70]), "+f"(d[71]), "+f"(d[72]), "+f"(d[73]), "+f"(d[74]), "+f"(d[75]), "+f"(d[76]), "+f"(d[77]), "+f"(d[78]), "+f"(d[79]), "+f"(d[80]), "+f"(d[81]), "+f"(d[82]), "+f"(d[83]), "+f"(d[84]), "+f"(d[85]), "+f"(d[86]), "+f"(d[87]), "+f"(d[88]), "+f"(d[89]), "+f"(d[90]), "+f"(d[91]), "+f"(d[92]), "+f"(d[93]), "+f"(d[94]), "+f"(d[95]), "+f"(d[96]), "+f"(d[97]), "+f"(d[98]), "+f"(d[99]), "+f"(d[100]), "+f"(d[101]), "+f"(d[102]), "+f"(d[103]), "+f"(d[104]), "+f"(d[105]), "+f"(d[106]), "+f"(d[107]), "+f"(d[108]), "+f"(d[109]), "+f"(d[110]), "+f"(d[111]), "+f"(d[112]), "+f"(d[113]), "+f"(d[114]), "+f"(d[115]), "+f"(d[116]), "+f"(d[117]), "+f"(d[118]), "+f"(d[119]), "+f"(d[120]), "+f"(d[121]), "+f"(d[122]), "+f"(d[123]), "+f"(d[124]), "+f"(d[125]), "+f"(d[126]), "+f"(d[127])
    : "r"(descA), "r"(descB), "r"(0x40000040u));
}

__device__ __forceinline__ void wgmma_m64n128k16(float (&d)[64], uint32_t descA, uint32_t descB) {
  asm volatile("{\n.reg .pred p;\n.reg .b64 da, db;\nsetp.eq.b32 p, 0, 0;\nmov.b64 da, {%64, %66};\nmov.b64 db, {%65, %66};\n"
    "wgmma.mma_async.sync.aligned.m64n128k16.f32.bf16.bf16 "
    "{%0, %1, %2, %3, %4, %5, %6, %7, %8, %9, %10, %11, %12, %13, %14, %15, %16, %17, %18, %19, %20, %21, %22, %23, %24, %25, %26, %27, %28, %29, %30, %31, %32, %33, %34, %35, %36, %37, %38, %39, %40, %41, %42, %43, %44, %45, %46, %47, %48, %49, %50, %51, %52, %53, %54, %55, %56, %57, %58, %59, %60, %61, %62, %63}, "
    "da, db, p, 1, 1, 0, 1;\n}\n"
    : "+f"(d[0]), "+f"(d[1]), "+f"(d[2]), "+f"(d[3]), "+f"(d[4]), "+f"(d[5]), "+f"(d[6]), "+f"(d[7]), "+f"(d[8]), "+f"(d[9]), "+f"(d[10]), "+f"(d[11]), "+f"(d[12]), "+f"(d[13]), "+f"(d[14]), "+f"(d[15]), "+f"(d[16]), "+f"(d[17]), "+f"(d[18]), "+f"(d[19]), "+f"(d[20]), "+f"(d[21]), "+f"(d[22]), "+f"(d[23]), "+f"(d[24]), "+f"(d[25]), "+f"(d[26]), "+f"(d[27]), "+f"(d[28]), "+f"(d[29]), "+f"(d[30]), "+f"(d[31]), "+f"(d[32]), "+f"(d[33]), "+f"(d[34]), "+f"(d[35]), "+f"(d[36]), "+f"(d[37]), "+f"(d[38]), "+f"(d[39]), "+f"(d[40]), "+f"(d[41]), "+f"(d[42]), "+f"(d[43]), "+f"(d[44]), "+f"(d[45]), "+f"(d[46]), "+f"(d[47]), "+f"(d[48]), "+f"(d[49]), "+f"(d[50]), "+f"(d[51]), "+f"(d[52]), "+f"(d[53]), "+f"(d[54]), "+f"(d[55]), "+f"(d[56]), "+f"(d[57]), "+f"(d[58]), "+f"(d[59]), "+f"(d[60]), "+f"(d[61]), "+f"(d[62]), "+f"(d[63])
    : "r"(descA), "r"(descB), "r"(0x40000040u));
}

template <int BN> struct WG;
template <> struct WG<128> { static __device__ __forceinline__ void mma(float (&d)[64], uint32_t a, uint32_t b) { wgmma_m64n128k16(d, a, b); } };
template <> struct WG<256> { static __device__ __forceinline__ void mma(float (&d)[128], uint32_t a, uint32_t b) { wgmma_m64n256k16(d, a, b); } };
template <> struct WG<192> { static __device__ __forceinline__ void mma(float (&d)[96], uint32_t a, uint32_t b) { wgmma_m64n192k16(d, a, b); } };

#define DBG_T(i)
__device__ __forceinline__ void fence_async_smem() { asm volatile("fence.proxy.async.shared::cta;" ::: "memory"); }
__device__ __forceinline__ void prefetch_tmap(const CUtensorMap* tm) { asm volatile("prefetch.tensormap [%0];" ::"l"((uint64_t)tm) : "memory"); }
__device__ __forceinline__ uint32_t mapa_u32(uint32_t addr, uint32_t cta) {
    uint32_t r;
    asm volatile("mapa.shared::cluster.u32 %0, %1, %2;" : "=r"(r) : "r"(addr), "r"(cta));
    return r;
}
__device__ __forceinline__ void mbar_arrive_cluster(uint32_t cluster_addr) {
    asm volatile("mbarrier.arrive.shared::cluster.b64 _, [%0];" ::"r"(cluster_addr) : "memory");
}
__device__ __forceinline__ bool elect_one() {
    uint32_t p;
    asm volatile("{\n.reg .pred P;\nelect.sync _|P, 0xffffffff;\nselp.u32 %0, 1, 0, P;\n}\n" : "=r"(p));
    return p != 0;
}
__device__ __forceinline__ void cluster_arrive_relaxed() { asm volatile("barrier.cluster.arrive.relaxed.aligned;" ::: "memory"); }
__device__ __forceinline__ void cluster_wait() { asm volatile("barrier.cluster.wait.acquire.aligned;" ::: "memory"); }

__device__ __forceinline__ uint32_t bsub2(uint32_t a, uint32_t b) {
    __nv_bfloat162 r = __hsub2(*reinterpret_cast<__nv_bfloat162*>(&a), *reinterpret_cast<__nv_bfloat162*>(&b));
    return *reinterpret_cast<uint32_t*>(&r);
}
__device__ __forceinline__ uint32_t bmul2(uint32_t a, uint32_t b) {
    __nv_bfloat162 r = __hmul2(*reinterpret_cast<__nv_bfloat162*>(&a), *reinterpret_cast<__nv_bfloat162*>(&b));
    return *reinterpret_cast<uint32_t*>(&r);
}
__device__ __forceinline__ uint32_t badd2(uint32_t a, uint32_t b) {
    __nv_bfloat162 r = __hadd2(*reinterpret_cast<__nv_bfloat162*>(&a), *reinterpret_cast<__nv_bfloat162*>(&b));
    return *reinterpret_cast<uint32_t*>(&r);
}
constexpr int BM = 128, BK = 64;
constexpr int R5_STAGE = 32768, R5_N = 5;
constexpr int R4_STAGE = 49152, R4_N = 4;
constexpr int R4B_STAGE = 40960;
constexpr int OFF_STG5 = 0, OFF_R = 32768;
constexpr int OFF_EPI = 196608;
constexpr int OFF_BAR = OFF_EPI + 32768;
constexpr int OFF_RS = OFF_BAR + 256;
constexpr int OFF_CS = OFF_RS + 1024;
constexpr int MEGA_SMEM = OFF_CS + 1792;
enum { FL_XA = 0, FL_H = 2, FL_X1 = 4, FL_H2 = 6, FL_CS = 10, FL_KINDS = 11 };
constexpr int FL_PITCH = 64;
constexpr int FL_WORDS = 2 * FL_KINDS * 16 * FL_PITCH;
__device__ unsigned int g_flag[FL_WORDS];
__device__ __align__(8) unsigned int g_ticket[18 * FL_PITCH];
constexpr int NCL = 66;
__device__ __forceinline__ unsigned int* flag_ptr(int layer, int kind, int i) { return g_flag + ((layer * FL_KINDS + kind) * 16 + i) * FL_PITCH; }

__device__ __forceinline__ void wait_flag(const unsigned int* p, unsigned int target) {
    long long t0 = clock64();
    while (true) {
        unsigned int v;
        asm volatile("ld.relaxed.gpu.global.u32 %0, [%1];" : "=r"(v) : "l"(p) : "memory");
        if ((int)(v - target) >= 0) break;
        if (clock64() - t0 > 2000000000LL) break;
    }
    asm volatile("fence.acquire.gpu;" ::: "memory");
}
__device__ __forceinline__ void fence_proxy_async() {
    asm volatile("fence.proxy.async.global;" ::: "memory");
    asm volatile("fence.proxy.async.shared::cta;" ::: "memory");
}
__device__ __forceinline__ void stsm4(uint32_t addr, uint32_t r0, uint32_t r1, uint32_t r2, uint32_t r3) {
    asm volatile("stmatrix.sync.aligned.m8n8.x4.shared.b16 [%0], {%1,%2,%3,%4};" ::"r"(addr), "r"(r0), "r"(r1), "r"(r2), "r"(r3));
}
__device__ __forceinline__ uint4 lds128(uint32_t a) {
    uint4 v;
    asm volatile("ld.shared.v4.b32 {%0,%1,%2,%3}, [%4];" : "=r"(v.x), "=r"(v.y), "=r"(v.z), "=r"(v.w) : "r"(a) : "memory");
    return v;
}
__device__ __forceinline__ void stg128(void* p, uint4 v) {
    asm volatile("st.global.v4.b32 [%0], {%1,%2,%3,%4};" ::"l"(p), "r"(v.x), "r"(v.y), "r"(v.z), "r"(v.w) : "memory");
}
__device__ __forceinline__ float gelu_tanh_h(float hx) {
    float z = hx * fmaf(hx * hx, 8.0f * 0.035677408136300125f, 2.0f * 0.7978845608028654f);
    float t;
    asm("tanh.approx.f32 %0, %1;" : "=f"(t) : "f"(z));
    return fmaf(hx, t, hx);
}
__device__ __forceinline__ uint32_t gelu2h(uint32_t hx) {
    uint32_t r;
    asm("{\n.reg .b32 z;\nmul.rn.bf16x2 z, %1, %1;\nfma.rn.bf16x2 z, z, %2, %3;\nmul.rn.bf16x2 z, z, %1;\ntanh.approx.bf16x2 z, z;\nfma.rn.bf16x2 %0, %1, z, %1;\n}"
        : "=r"(r) : "r"(hx), "r"(0x3e923e92u), "r"(0x3fcc3fccu));
    return r;
}
__device__ __forceinline__ uint4 gelu8h(uint4 v) { return make_uint4(gelu2h(v.x), gelu2h(v.y), gelu2h(v.z), gelu2h(v.w)); }

__device__ __forceinline__ void row_stats(const float2* p, uint32_t tag, float& mean, float& var) {
    float2 v[8];
#pragma unroll 1
    for (int n = 0; n < (1 << 20); n++) {
#pragma unroll
        for (int i = 0; i < 8; i++)
            asm volatile("{\n.reg .b64 t;\nld.relaxed.gpu.global.b64 t, [%2];\nmov.b64 {%0, %1}, t;\n}" : "=f"(v[i].x), "=f"(v[i].y) : "l"(p + 128 * i) : "memory");
        uint32_t old = 0;
#pragma unroll
        for (int i = 0; i < 8; i++) old |= __float_as_uint(v[i].y) ^ tag;
        if ((int)old >= 0) break;
    }
    mean = (((v[0].x + v[1].x) + (v[2].x + v[3].x)) + ((v[4].x + v[5].x) + (v[6].x + v[7].x))) * 0.125f;
    float m2 = 0.f, d2 = 0.f;
#pragma unroll
    for (int i = 0; i < 8; i++) { m2 += fabsf(v[i].y); d2 = fmaf(v[i].x - mean, v[i].x - mean, d2); }
    var = fmaf(128.0f, d2, m2) * (1.0f / D_);
}
struct RingState { uint32_t st, ph; };

#define DT(i)
#define DP(i)
#define GT(i)
#define TM(i)

template <int BN, int NST>
__device__ __forceinline__ void kblock(float (&acc)[BN / 2], uint32_t da, uint32_t db, uint32_t bfull, RingState& rs) {
    mbar_wait(bfull + 8 * rs.st, rs.ph);
    wgmma_fence();
#pragma unroll
    for (int k = 0; k < 4; k++) WG<BN>::mma(acc, da + k * 2, db + k * 128);
    wgmma_commit();
    if (++rs.st == NST) { rs.st = 0; rs.ph ^= 1; }
}
template <int BN, int NST, int STAGE>
__device__ __forceinline__ void mainloop(float (&acc)[BN / 2], int KB, uint32_t da0, uint32_t db0, uint32_t bfull, uint32_t rel, bool rel_on,
                                         RingState& rs, int dbg) {
    uint32_t prev = rs.st ? rs.st - 1 : NST - 1;
#pragma unroll 1
    for (int kk = 0; kk < KB; kk++) {
        const uint32_t cur = rs.st;
        kblock<BN, NST>(acc, da0 + cur * (STAGE / 16), db0 + cur * (STAGE / 16), bfull, rs);
        wgmma_wait<1>();
        if (rel_on) mbar_arrive_cluster(rel + 8 * prev);
        prev = cur;
    }
    wgmma_wait<0>();
#pragma unroll
    for (int i = 0; i < BN / 2; i++) asm volatile("" : "+f"(acc[i])::"memory");
    if (rel_on) mbar_arrive_cluster(rel + 8 * prev);
}
template <int N> __device__ __forceinline__ void zero_acc(float (&acc)[N]) {
#pragma unroll
    for (int i = 0; i < N; i++) acc[i] = 0.f;
}
__device__ __forceinline__ void ldsm4(uint32_t& r0, uint32_t& r1, uint32_t& r2, uint32_t& r3, uint32_t addr) {
    asm volatile("ldmatrix.sync.aligned.m8n8.x4.shared.b16 {%0,%1,%2,%3}, [%4];" : "=r"(r0), "=r"(r1), "=r"(r2), "=r"(r3) : "r"(addr));
}

__device__ __forceinline__ void ldsm4t(uint32_t& r0, uint32_t& r1, uint32_t& r2, uint32_t& r3, uint32_t addr) {
    asm volatile("ldmatrix.sync.aligned.m8n8.x4.trans.shared.b16 {%0,%1,%2,%3}, [%4];" : "=r"(r0), "=r"(r1), "=r"(r2), "=r"(r3) : "r"(addr));
}

#define DBG_S(i)
#define DBG_OUT(r, o)
#define DBG_F(i)
#define DBG_W(i)
constexpr int CV_CH = 8;
constexpr int CV_SL = 16384;
constexpr int CV_QG = 128 * 8 + 16;
constexpr int CV_HPL = 2048 + 192;
constexpr int CV_0 = 32768, CV_H = 9 * CV_SL, CV_BAR = OFF_RS - CV_0;

template <int K> __device__ __forceinline__ void cv_mma(float (&d)[64], const uint32_t (&a)[4], uint32_t db, int acc);
template <> __device__ __forceinline__ void cv_mma<0>(float (&d)[64], const uint32_t (&a)[4], uint32_t db, int acc) {
    asm volatile("{\n.reg .pred p;\n.reg .b64 b;\nsetp.ne.b32 p, %70, 0;\nmov.b64 b, {%68, %69};\n"
        "wgmma.mma_async.sync.aligned.m64n128k16.f32.bf16.bf16 {%0,%1,%2,%3,%4,%5,%6,%7,%8,%9,%10,%11,%12,%13,%14,%15,%16,%17,%18,%19,%20,%21,%22,%23,%24,%25,%26,%27,%28,%29,%30,%31,%32,%33,%34,%35,%36,%37,%38,%39,%40,%41,%42,%43,%44,%45,%46,%47,%48,%49,%50,%51,%52,%53,%54,%55,%56,%57,%58,%59,%60,%61,%62,%63}, {%64,%65,%66,%67}, b, p, 1, 1, 0;\n}\n"
        : "+f"(d[0]), "+f"(d[1]), "+f"(d[2]), "+f"(d[3]), "+f"(d[4]), "+f"(d[5]), "+f"(d[6]), "+f"(d[7]), "+f"(d[8]), "+f"(d[9]), "+f"(d[10]), "+f"(d[11]), "+f"(d[12]), "+f"(d[13]), "+f"(d[14]), "+f"(d[15]), "+f"(d[16]), "+f"(d[17]), "+f"(d[18]), "+f"(d[19]), "+f"(d[20]), "+f"(d[21]), "+f"(d[22]), "+f"(d[23]), "+f"(d[24]), "+f"(d[25]), "+f"(d[26]), "+f"(d[27]), "+f"(d[28]), "+f"(d[29]), "+f"(d[30]), "+f"(d[31]), "+f"(d[32]), "+f"(d[33]), "+f"(d[34]), "+f"(d[35]), "+f"(d[36]), "+f"(d[37]), "+f"(d[38]), "+f"(d[39]), "+f"(d[40]), "+f"(d[41]), "+f"(d[42]), "+f"(d[43]), "+f"(d[44]), "+f"(d[45]), "+f"(d[46]), "+f"(d[47]), "+f"(d[48]), "+f"(d[49]), "+f"(d[50]), "+f"(d[51]), "+f"(d[52]), "+f"(d[53]), "+f"(d[54]), "+f"(d[55]), "+f"(d[56]), "+f"(d[57]), "+f"(d[58]), "+f"(d[59]), "+f"(d[60]), "+f"(d[61]), "+f"(d[62]), "+f"(d[63])
        : "r"(a[0]), "r"(a[1]), "r"(a[2]), "r"(a[3]), "r"(db), "r"(8u), "r"(acc));
}
template <> __device__ __forceinline__ void cv_mma<1>(float (&d)[64], const uint32_t (&a)[4], uint32_t db, int acc) {
    asm volatile("{\n.reg .pred p;\n.reg .b64 b;\nsetp.ne.b32 p, %62, 0;\nmov.b64 b, {%60, %61};\n"
        "wgmma.mma_async.sync.aligned.m64n112k16.f32.bf16.bf16 {%0,%1,%2,%3,%4,%5,%6,%7,%8,%9,%10,%11,%12,%13,%14,%15,%16,%17,%18,%19,%20,%21,%22,%23,%24,%25,%26,%27,%28,%29,%30,%31,%32,%33,%34,%35,%36,%37,%38,%39,%40,%41,%42,%43,%44,%45,%46,%47,%48,%49,%50,%51,%52,%53,%54,%55}, {%56,%57,%58,%59}, b, p, 1, 1, 0;\n}\n"
        : "+f"(d[0]), "+f"(d[1]), "+f"(d[2]), "+f"(d[3]), "+f"(d[4]), "+f"(d[5]), "+f"(d[6]), "+f"(d[7]), "+f"(d[8]), "+f"(d[9]), "+f"(d[10]), "+f"(d[11]), "+f"(d[12]), "+f"(d[13]), "+f"(d[14]), "+f"(d[15]), "+f"(d[16]), "+f"(d[17]), "+f"(d[18]), "+f"(d[19]), "+f"(d[20]), "+f"(d[21]), "+f"(d[22]), "+f"(d[23]), "+f"(d[24]), "+f"(d[25]), "+f"(d[26]), "+f"(d[27]), "+f"(d[28]), "+f"(d[29]), "+f"(d[30]), "+f"(d[31]), "+f"(d[32]), "+f"(d[33]), "+f"(d[34]), "+f"(d[35]), "+f"(d[36]), "+f"(d[37]), "+f"(d[38]), "+f"(d[39]), "+f"(d[40]), "+f"(d[41]), "+f"(d[42]), "+f"(d[43]), "+f"(d[44]), "+f"(d[45]), "+f"(d[46]), "+f"(d[47]), "+f"(d[48]), "+f"(d[49]), "+f"(d[50]), "+f"(d[51]), "+f"(d[52]), "+f"(d[53]), "+f"(d[54]), "+f"(d[55])
        : "r"(a[0]), "r"(a[1]), "r"(a[2]), "r"(a[3]), "r"(db), "r"(8u), "r"(acc));
}
template <> __device__ __forceinline__ void cv_mma<2>(float (&d)[64], const uint32_t (&a)[4], uint32_t db, int acc) {
    asm volatile("{\n.reg .pred p;\n.reg .b64 b;\nsetp.ne.b32 p, %54, 0;\nmov.b64 b, {%52, %53};\n"
        "wgmma.mma_async.sync.aligned.m64n96k16.f32.bf16.bf16 {%0,%1,%2,%3,%4,%5,%6,%7,%8,%9,%10,%11,%12,%13,%14,%15,%16,%17,%18,%19,%20,%21,%22,%23,%24,%25,%26,%27,%28,%29,%30,%31,%32,%33,%34,%35,%36,%37,%38,%39,%40,%41,%42,%43,%44,%45,%46,%47}, {%48,%49,%50,%51}, b, p, 1, 1, 0;\n}\n"
        : "+f"(d[0]), "+f"(d[1]), "+f"(d[2]), "+f"(d[3]), "+f"(d[4]), "+f"(d[5]), "+f"(d[6]), "+f"(d[7]), "+f"(d[8]), "+f"(d[9]), "+f"(d[10]), "+f"(d[11]), "+f"(d[12]), "+f"(d[13]), "+f"(d[14]), "+f"(d[15]), "+f"(d[16]), "+f"(d[17]), "+f"(d[18]), "+f"(d[19]), "+f"(d[20]), "+f"(d[21]), "+f"(d[22]), "+f"(d[23]), "+f"(d[24]), "+f"(d[25]), "+f"(d[26]), "+f"(d[27]), "+f"(d[28]), "+f"(d[29]), "+f"(d[30]), "+f"(d[31]), "+f"(d[32]), "+f"(d[33]), "+f"(d[34]), "+f"(d[35]), "+f"(d[36]), "+f"(d[37]), "+f"(d[38]), "+f"(d[39]), "+f"(d[40]), "+f"(d[41]), "+f"(d[42]), "+f"(d[43]), "+f"(d[44]), "+f"(d[45]), "+f"(d[46]), "+f"(d[47])
        : "r"(a[0]), "r"(a[1]), "r"(a[2]), "r"(a[3]), "r"(db), "r"(8u), "r"(acc));
}
template <> __device__ __forceinline__ void cv_mma<3>(float (&d)[64], const uint32_t (&a)[4], uint32_t db, int acc) {
    asm volatile("{\n.reg .pred p;\n.reg .b64 b;\nsetp.ne.b32 p, %46, 0;\nmov.b64 b, {%44, %45};\n"
        "wgmma.mma_async.sync.aligned.m64n80k16.f32.bf16.bf16 {%0,%1,%2,%3,%4,%5,%6,%7,%8,%9,%10,%11,%12,%13,%14,%15,%16,%17,%18,%19,%20,%21,%22,%23,%24,%25,%26,%27,%28,%29,%30,%31,%32,%33,%34,%35,%36,%37,%38,%39}, {%40,%41,%42,%43}, b, p, 1, 1, 0;\n}\n"
        : "+f"(d[0]), "+f"(d[1]), "+f"(d[2]), "+f"(d[3]), "+f"(d[4]), "+f"(d[5]), "+f"(d[6]), "+f"(d[7]), "+f"(d[8]), "+f"(d[9]), "+f"(d[10]), "+f"(d[11]), "+f"(d[12]), "+f"(d[13]), "+f"(d[14]), "+f"(d[15]), "+f"(d[16]), "+f"(d[17]), "+f"(d[18]), "+f"(d[19]), "+f"(d[20]), "+f"(d[21]), "+f"(d[22]), "+f"(d[23]), "+f"(d[24]), "+f"(d[25]), "+f"(d[26]), "+f"(d[27]), "+f"(d[28]), "+f"(d[29]), "+f"(d[30]), "+f"(d[31]), "+f"(d[32]), "+f"(d[33]), "+f"(d[34]), "+f"(d[35]), "+f"(d[36]), "+f"(d[37]), "+f"(d[38]), "+f"(d[39])
        : "r"(a[0]), "r"(a[1]), "r"(a[2]), "r"(a[3]), "r"(db), "r"(8u), "r"(acc));
}
template <> __device__ __forceinline__ void cv_mma<4>(float (&d)[64], const uint32_t (&a)[4], uint32_t db, int acc) {
    asm volatile("{\n.reg .pred p;\n.reg .b64 b;\nsetp.ne.b32 p, %38, 0;\nmov.b64 b, {%36, %37};\n"
        "wgmma.mma_async.sync.aligned.m64n64k16.f32.bf16.bf16 {%0,%1,%2,%3,%4,%5,%6,%7,%8,%9,%10,%11,%12,%13,%14,%15,%16,%17,%18,%19,%20,%21,%22,%23,%24,%25,%26,%27,%28,%29,%30,%31}, {%32,%33,%34,%35}, b, p, 1, 1, 0;\n}\n"
        : "+f"(d[0]), "+f"(d[1]), "+f"(d[2]), "+f"(d[3]), "+f"(d[4]), "+f"(d[5]), "+f"(d[6]), "+f"(d[7]), "+f"(d[8]), "+f"(d[9]), "+f"(d[10]), "+f"(d[11]), "+f"(d[12]), "+f"(d[13]), "+f"(d[14]), "+f"(d[15]), "+f"(d[16]), "+f"(d[17]), "+f"(d[18]), "+f"(d[19]), "+f"(d[20]), "+f"(d[21]), "+f"(d[22]), "+f"(d[23]), "+f"(d[24]), "+f"(d[25]), "+f"(d[26]), "+f"(d[27]), "+f"(d[28]), "+f"(d[29]), "+f"(d[30]), "+f"(d[31])
        : "r"(a[0]), "r"(a[1]), "r"(a[2]), "r"(a[3]), "r"(db), "r"(8u), "r"(acc));
}
template <> __device__ __forceinline__ void cv_mma<5>(float (&d)[64], const uint32_t (&a)[4], uint32_t db, int acc) {
    asm volatile("{\n.reg .pred p;\n.reg .b64 b;\nsetp.ne.b32 p, %30, 0;\nmov.b64 b, {%28, %29};\n"
        "wgmma.mma_async.sync.aligned.m64n48k16.f32.bf16.bf16 {%0,%1,%2,%3,%4,%5,%6,%7,%8,%9,%10,%11,%12,%13,%14,%15,%16,%17,%18,%19,%20,%21,%22,%23}, {%24,%25,%26,%27}, b, p, 1, 1, 0;\n}\n"
        : "+f"(d[0]), "+f"(d[1]), "+f"(d[2]), "+f"(d[3]), "+f"(d[4]), "+f"(d[5]), "+f"(d[6]), "+f"(d[7]), "+f"(d[8]), "+f"(d[9]), "+f"(d[10]), "+f"(d[11]), "+f"(d[12]), "+f"(d[13]), "+f"(d[14]), "+f"(d[15]), "+f"(d[16]), "+f"(d[17]), "+f"(d[18]), "+f"(d[19]), "+f"(d[20]), "+f"(d[21]), "+f"(d[22]), "+f"(d[23])
        : "r"(a[0]), "r"(a[1]), "r"(a[2]), "r"(a[3]), "r"(db), "r"(8u), "r"(acc));
}
template <> __device__ __forceinline__ void cv_mma<6>(float (&d)[64], const uint32_t (&a)[4], uint32_t db, int acc) {
    asm volatile("{\n.reg .pred p;\n.reg .b64 b;\nsetp.ne.b32 p, %22, 0;\nmov.b64 b, {%20, %21};\n"
        "wgmma.mma_async.sync.aligned.m64n32k16.f32.bf16.bf16 {%0,%1,%2,%3,%4,%5,%6,%7,%8,%9,%10,%11,%12,%13,%14,%15}, {%16,%17,%18,%19}, b, p, 1, 1, 0;\n}\n"
        : "+f"(d[0]), "+f"(d[1]), "+f"(d[2]), "+f"(d[3]), "+f"(d[4]), "+f"(d[5]), "+f"(d[6]), "+f"(d[7]), "+f"(d[8]), "+f"(d[9]), "+f"(d[10]), "+f"(d[11]), "+f"(d[12]), "+f"(d[13]), "+f"(d[14]), "+f"(d[15])
        : "r"(a[0]), "r"(a[1]), "r"(a[2]), "r"(a[3]), "r"(db), "r"(8u), "r"(acc));
}
template <> __device__ __forceinline__ void cv_mma<7>(float (&d)[64], const uint32_t (&a)[4], uint32_t db, int acc) {
    asm volatile("{\n.reg .pred p;\n.reg .b64 b;\nsetp.ne.b32 p, %14, 0;\nmov.b64 b, {%12, %13};\n"
        "wgmma.mma_async.sync.aligned.m64n16k16.f32.bf16.bf16 {%0,%1,%2,%3,%4,%5,%6,%7}, {%8,%9,%10,%11}, b, p, 1, 1, 0;\n}\n"
        : "+f"(d[0]), "+f"(d[1]), "+f"(d[2]), "+f"(d[3]), "+f"(d[4]), "+f"(d[5]), "+f"(d[6]), "+f"(d[7])
        : "r"(a[0]), "r"(a[1]), "r"(a[2]), "r"(a[3]), "r"(db), "r"(8u), "r"(acc));
}
__device__ __forceinline__ void stsm4t(uint32_t addr, uint32_t r0, uint32_t r1, uint32_t r2, uint32_t r3) {
    asm volatile("stmatrix.sync.aligned.m8n8.x4.trans.shared.b16 [%0], {%1,%2,%3,%4};" ::"r"(addr), "r"(r0), "r"(r1), "r"(r2), "r"(r3) : "memory");
}
__device__ __forceinline__ void cp16(uint32_t dst, const void* src, int n = 16) {
    asm volatile("cp.async.cg.shared.global.L2::128B [%0], [%1], 16, %2;" ::"r"(dst), "l"(src), "r"(n) : "memory");
}
__device__ __forceinline__ void cp_arrive(uint32_t bar) { asm volatile("cp.async.mbarrier.arrive.noinc.shared::cta.b64 [%0];" ::"r"(bar) : "memory"); }
__device__ __forceinline__ void lds64(uint32_t& x, uint32_t& y, uint32_t a) { asm volatile("ld.shared.v2.b32 {%0,%1}, [%2];" : "=r"(x), "=r"(y) : "r"(a) : "memory"); }
__device__ __forceinline__ void sts128(uint32_t a, uint32_t x, uint32_t y, uint32_t z, uint32_t w) {
    asm volatile("st.shared.v4.b32 [%0], {%1,%2,%3,%4};" ::"r"(a), "r"(x), "r"(y), "r"(z), "r"(w) : "memory");
}
__device__ __forceinline__ uint32_t bfma2(uint32_t a, uint32_t b, uint32_t c) {
    uint32_t r;
    asm("fma.rn.bf16x2 %0, %1, %2, %3;" : "=r"(r) : "r"(a), "r"(b), "r"(c));
    return r;
}
#define CV_NS 4
#define CV_W 1
constexpr int CV_GC = 8 / CV_NS, CV_NA = (CV_W + 2) * CV_NS;
struct CvAddr { uint32_t pa[2], p0[4], db, rdy, xw, xr, bar; bool wrap, neg[2]; };
template <int G> __device__ __forceinline__ void cv_load(uint32_t (&a)[CV_NA][4], const CvAddr& p) {
    if constexpr (G % CV_GC == 0) mbar_wait(p.rdy + 8 * (G / CV_GC), 0);
#pragma unroll
    for (int i = G * CV_NS; i < (G + 1) * CV_NS; i++) {
        const int of = (i / 2 % 2) * CV_QG + (i / 8) * CV_SL + 256 * (i % 2 + (i / 2 & 2));
        if ((i & 5) == 0) {
#pragma unroll
            for (int e = 0; e < 4; e++) asm volatile("ld.shared.b32 %0, [%1];" : "=r"(a[i % CV_NA][e]) : "r"(p.p0[e] + of) : "memory");
            if (i < 8) { if (p.neg[0]) a[i % CV_NA][0] = 0; if (p.neg[1]) a[i % CV_NA][2] = 0; }
        } else {
            lds64(a[i % CV_NA][0], a[i % CV_NA][1], p.pa[0] + of - 256);
            lds64(a[i % CV_NA][2], a[i % CV_NA][3], p.pa[1] + of - 256);
        }
    }
}
__device__ __forceinline__ float vadd(float a, float b) {
    float r;
    asm volatile("add.f32 %0, %1, %2;" : "=f"(r) : "f"(a), "f"(b));
    return r;
}
template <int K> __device__ __forceinline__ uint32_t cv_tail(float (&d)[64], bool wrap) {
    float* z = d + 56 - 8 * K;
    z[4] = vadd(z[4], K > 0 ? z[10] : 0.f);
    if constexpr (K > 0) z[5] = vadd(z[5], z[11]);
    z[0] = vadd(z[0], z[6]);
    z[1] = vadd(z[1], z[7]);
    return pack2(wrap ? (K > 0 ? z[8] : 0.f) : z[4], wrap ? z[4] : z[0]);
}
template <int K> __device__ __forceinline__ uint32_t cv_fin(const float (&d)[64], uint32_t x) { return pack2(d[61 - 8 * K] + lo2f(x), d[57 - 8 * K] + hi2f(x)); }
template <int G>
__device__ __forceinline__ void cv_steps(float (&d)[2][64], uint32_t (&a)[CV_NA][4], uint32_t (&tv)[2][8], const CvAddr& p) {
    constexpr int K = G / CV_GC, GN = 8 * CV_GC;
    constexpr int T = G - CV_W - CV_GC, F = T - 1, TK = T / CV_GC, FK = F / CV_GC;
    if constexpr (G == 0) cv_load<0>(a, p);
    if constexpr (G < GN) {
        wgmma_fence();
#pragma unroll
        for (int i = G * CV_NS; i < (G + 1) * CV_NS; i++)
            cv_mma<K>(d[i / 2 % 2], a[i % CV_NA], p.db + (i / 2 % 2) * (CV_HPL / 8) + 16 * K + 2 * (i % 2 + (i / 2 & 2)), i & ~2 ? 1 : p.bar >> 8);
        wgmma_commit();
    }
    if constexpr (G < GN - 1) cv_load<G + 1>(a, p);
    if constexpr (T >= 0 && T % CV_GC == 0) {
        tv[0][TK] = cv_tail<TK>(d[0], p.wrap);
        tv[1][TK] = cv_tail<TK>(d[1], p.wrap);
        if constexpr (TK & 1) sts128(p.xw + TK / 2 * 512, tv[0][TK - 1], tv[0][TK], tv[1][TK - 1], tv[1][TK]);
    }
    if constexpr (F >= 0 && F % (2 * CV_GC) == CV_GC) {
        const uint4 x = lds128(p.xr + FK / 2 * 512);
        tv[0][FK - 1] = cv_fin<FK - 1>(d[0], x.x); tv[0][FK] = cv_fin<FK>(d[0], x.y);
        tv[1][FK - 1] = cv_fin<FK - 1>(d[1], x.z); tv[1][FK] = cv_fin<FK>(d[1], x.w);
    }
    if constexpr (G < GN - 1) wgmma_wait<CV_W>();
    if constexpr (G == GN - 1) wgmma_wait<0>();
    if constexpr (T >= 0 && T % (2 * CV_GC) == CV_GC) named_bar_sync(p.bar, 128);
    if constexpr (F < GN - CV_GC) cv_steps<G + 1>(d, a, tv, p);
}

#define CV_PF 7
#define Y_FIRST 1
#define Y_HOLD 0
#define W3_AT 1
struct MegaMaps {
    CUtensorMap q, act;
    CUtensorMap w1, w2, w3, w4;
    CUtensorMap k, v, y;
};

__global__ void __cluster_dims__(2, 1, 1) __launch_bounds__(384, 1)
mega_kernel(const __grid_constant__ MegaMaps tm, bf16* __restrict__ outp, bf16* act, const bf16* __restrict__ w1p, const bf16* __restrict__ w2p,
            const bf16* __restrict__ w3p, const bf16* __restrict__ xq, const bf16* __restrict__ kp, const bf16* __restrict__ vp,
            const bf16* __restrict__ shk, const bf16* __restrict__ ssk, const bf16* __restrict__ ssD) {
    extern __shared__ __align__(1024) uint8_t sgen[];
    const uint32_t sbase = smem_u32(sgen);
    const int warp = __shfl_sync(0xffffffffu, threadIdx.x >> 5, 0), lane = threadIdx.x & 31;
    const int rank = blockIdx.x & 1;
    const uint32_t s_bar = sbase + OFF_BAR;
    const uint32_t f5 = s_bar, e5 = s_bar + 64, f4 = s_bar + 144, e4 = s_bar + 104;
    const uint32_t b_rfull = s_bar + 176, b_role = s_bar + 184, b_stg = s_bar + 136, b_h2 = s_bar + 32;
    const uint32_t s_epi = sbase + OFF_EPI, s_stg = sbase + OFF_STG5, s_r = sbase + OFF_R;
    uint8_t* sm = sgen + CV_0;
    const uint32_t sb = sbase + CV_0;
    const int tid = threadIdx.x, wg = warp >> 2, w = warp & 3;
    const int d0 = blockIdx.x * CV_CH;
    const bool cv = blockIdx.x < D_ / CV_CH;
    const uint32_t b_full = sb + CV_BAR, b_rdy = b_full + 64, b_h = b_full + 128;
    GT(0);
    if (tid == 0) TM(0);
    auto row_at = [&](int r) { return sb + CV_SL + (r < 0 ? -8192 : 0) + ((r & 127) >> 5) * 1024 + (r & 7) * 128 + ((r >> 3) & 3) * 32 + ((r ^ rank) & 1) * 16; };
    auto load_kv = [&](int c) {
#pragma unroll
        for (int i = 0; i < 2; i++)
            asm volatile("cp.async.bulk.tensor.4d.shared::cluster.global.mbarrier::complete_tx::bytes.multicast::cluster [%0], [%1, {%3, %4, %4, %5}], [%2], %6;"
                         ::"r"(sb + (c + 1) * CV_SL + rank * 8192 + i * 4096), "l"((uint64_t)(i ? &tm.v : &tm.k)), "r"(b_full + 8 * c), "r"(d0 & ~15), "r"(0),
                         "r"(8 * c + 4 * rank), "h"((uint16_t)3) : "memory");
    };
    auto bulk = [&](uint32_t dst, const void* src, uint32_t n, uint32_t bar) {
        asm volatile("cp.async.bulk.shared::cluster.global.mbarrier::complete_tx::bytes [%0], [%1], %2, [%3];" ::"r"(dst), "l"(src), "r"(n), "r"(bar) : "memory");
    };
    auto put_h = [&](int ch) {
        const uint32_t dk = (tid & 127) ? 0 : *reinterpret_cast<const volatile uint32_t*>(sm + CV_BAR + 160 + 16 * wg + 2 * ch);
        uint4 v[4];
#pragma unroll
        for (int i = 0; i < 4; i++) v[i] = lds128(sbase + ch * 4096 + i * 2048 + (tid & 127) * 16);
        v[0].x = pack2(lo2f(v[0].x) + lo2f(dk), hi2f(v[0].x));
        v[2].x = pack2(lo2f(v[2].x) + hi2f(dk), hi2f(v[2].x));
#pragma unroll
        for (int i = 0; i < 4; i++)
            sts128(sb + CV_H + (2 * ch + (i & 2) + (tid & 1)) * CV_HPL + (127 - ((tid & 127) >> 1)) * 16 - (i & 1) * 1024, v[i].x, v[i].y, v[i].z, v[i].w);
    };
    int bi, bj, m0, tb;
    uint32_t ep;
    auto get_role = [&]() {
        mbar_wait(b_role, 0);
        int role;
        asm volatile("ld.shared.v2.b32 {%0,%1}, [%2];" : "=r"(role), "=r"(ep) : "r"(s_bar + 192) : "memory");
        bi = (role >> 3) * 2 + rank; bj = role & 7; m0 = bi * BM; tb = (role >> 3) * 2048 + rank * 128;
        return role < 64;
    };

    if (warp >= 8) {
        asm volatile("setmaxnreg.dec.sync.aligned.u32 88;");
        cluster_arrive_relaxed();
        if (!cv) cluster_wait(); else {
            const int bt = tid - 256, g = lane >> 2, t = lane & 3;
            if (bt < 16) sts128(row_at((bt & 7) - 8) + (bt >> 3) * 4096, 0, 0, 0, 0);
#pragma unroll
            for (int i = 0; i < 4; i++)
                cp16(row_at(bt) + i * 4096, (i & 1 ? vp : kp) + (size_t)(bt + (i >> 1) * 128) * D_ + d0);
            DBG_S(16 + (3));
            uint2 wa;
            asm volatile("ld.global.nc.v2.b32 {%0,%1}, [%2];" : "=r"(wa.x), "=r"(wa.y) : "l"(shk + (d0 + g) * 4));
            const int mi = lane >> 3, r0 = 32 * w + 8 * ((lane >> 1) & 3) - (lane & 1);
            const uint32_t ka0 = row_at(r0 + 2 * mi - 3), ka1 = row_at(r0 + 2 * (mi & 1) + 5) + (mi >> 1) * 8192;
            const uint32_t va0 = row_at(r0 + 2 * mi + 1) + 4096, va1 = row_at(r0 - 1) + 4096 + (mi & 1) * 8192;
            const uint32_t qd = sb + g * CV_QG + (32 * w + 8 * t) * 8, qd0 = qd + (t & 2) * 16, qd1 = qd + (~t & 2) * 16;
            const uint32_t w0 = __byte_perm(wa.x, 0, 0x1010), w1 = __byte_perm(wa.x, 0, 0x3232), w2 = __byte_perm(wa.y, 0, 0x1010), w3 = __byte_perm(wa.y, 0, 0x3232);
            cluster_wait();
            DBG_S(16 + (5));
            asm volatile("cp.async.wait_all;" ::: "memory");
            named_bar_sync(7, 128);
            DBG_S(16 + (1));
            struct KV { uint32_t k[2][6], v[2][5]; };
            auto get = [&](KV& x, uint32_t so) {
                ldsm4t(x.k[0][0], x.k[0][1], x.k[0][2], x.k[0][3], ka0 + so);
                ldsm4t(x.k[0][4], x.k[0][5], x.k[1][4], x.k[1][5], ka1 + so);
                ldsm4t(x.k[1][0], x.k[1][1], x.k[1][2], x.k[1][3], ka0 + so + 8192);
                asm volatile("ldmatrix.sync.aligned.m8n8.x2.trans.shared.b16 {%0,%1}, [%2];" : "=r"(x.v[0][0]), "=r"(x.v[1][0]) : "r"(va1 + so));
                ldsm4t(x.v[0][1], x.v[0][2], x.v[0][3], x.v[0][4], va0 + so);
                ldsm4t(x.v[1][1], x.v[1][2], x.v[1][3], x.v[1][4], va0 + so + 8192);
            };
            auto build = [&](int c, const KV& x, KV& nx) {
                const uint32_t so = c * CV_SL;
                DBG_F(1);
                uint32_t early;
                asm volatile("{\n.reg .pred p;\nmbarrier.test_wait.parity.shared::cta.b64 p, [%1], 0;\nvote.sync.all.pred p, p, -1;\nselp.u32 %0, 1, 0, p;\n}"
                             : "=r"(early) : "r"(b_full + 8 * (c < 7 ? c + 1 : c)) : "memory");
                if (early) get(nx, so + CV_SL);
                DBG_F(2);
                uint32_t p[8][2];
#pragma unroll
                for (int sg = 0; sg < 2; sg++) {
                    uint32_t u[5], ke[6];
#pragma unroll
                    for (int i = 0; i < 6; i++) ke[i] = __byte_perm(x.k[sg][i], x.k[sg][i ? i - 1 : 0], 0x5432);
#pragma unroll
                    for (int i = 0; i < 5; i++) {
                        u[i] = bmul2(bfma2(x.k[sg][i + 1], w0, bfma2(ke[i + 1], w1, bfma2(x.k[sg][i], w2, bmul2(ke[i], w3)))), x.v[sg][i]);
                        if (i) { p[2 * i - 1][sg] = u[i]; p[2 * i - 2][sg] = __byte_perm(u[i], u[i - 1], 0x5432); }
                    }
                }
                DBG_F(3);
#pragma unroll
                for (int j = 0; j < 4; j++) sts128((j & 2 ? qd1 : qd0) + so + 16 * (j & 1), p[2 * j][0], p[2 * j][1], p[2 * j + 1][0], p[2 * j + 1][1]);
                __syncwarp();
                DBG_F(4);
                if (lane == 0) {
                    mbar_arrive(b_rdy + 8 * c);
                    if (c == w) {
                        if (c < 3) load_kv(c + 5);
                        else { bulk(sbase + 16384, ssk + (size_t)(d0 + 4) * S_, 16384, b_h + 16); bulk(b_full + 192, ssD + d0, 16, b_h + 16); }
                    }
                    if (c == w + 4 && (CV_PF >> w & 1)) {
                        const uint32_t n = w == 0 ? 32768 : w == 3 ? 57344 : 16384;
                        const char* src = reinterpret_cast<const char*>(w == 0 ? xq : w == 1 ? w1p : w == 2 ? w2p : w3p) + (size_t)blockIdx.x * n;
                        asm volatile("cp.async.bulk.prefetch.L2.global [%0], %1;" ::"l"(src), "r"(n) : "memory");
                    }
                }
                DBG_F(5);
                named_bar_sync(7, 128);
                DBG_F(6);
                DBG_S(16 + (c == 0 ? 4 : 5 + c));
                if (!early) { mbar_wait(b_full + 8 * c + 8, 0); get(nx, so + CV_SL); }
                DBG_F(7);
            };
            KV x0, x1;
            get(x0, 0);
#pragma unroll 1
            for (int c = 0; c < 8; c += 2) { build(c, x0, x1); build(c + 1, x1, x0); }
            mbar_wait(b_h + 16, 0);
            put_h(4); put_h(6);
            fence_async_smem();
            __syncwarp();
            if (lane == 0) mbar_arrive(b_full);
            named_bar_sync(7, 128);
            DBG_S(16 + (13));
        }
    } else {
        if (elect_one()) {
            mbar_init(b_full + 8 * warp, warp ? 1 : 4);
            mbar_init(b_rdy + 8 * warp, 4);
            if (warp) mbar_expect_tx(b_full + 8 * warp, 16384);
            if (w == 0 && cv) {
                mbar_init(b_h + 8 * wg, 1);
                mbar_expect_tx(b_h + 8 * wg, 8192 + 16);
                fence_async_smem();
                bulk(sbase + wg * 8192, ssk + (size_t)(d0 + 2 * wg) * S_, 8192, b_h + 8 * wg);
                bulk(b_full + 160 + 16 * wg, ssD + d0, 16, b_h + 8 * wg);
            }
            mbar_init(s_bar + 8 * warp, 1);
            mbar_init(s_bar + 64 + 8 * warp, 4);
            mbar_init(s_bar + 128 + 8 * warp, warp < 2 ? 4 << warp : warp == 6 ? 2 : 1);
            if (warp == 0) mbar_arrive(f5);
            if (warp == 7) mbar_expect_tx(b_role, 8);
            if (warp == 1) { mbar_init(b_h + 16, 1); mbar_expect_tx(b_h + 16, 16384 + 16); }
            if (w == 2) sts128(s_bar + 224 + 16 * wg, 0, 0, 0, 0);
            asm volatile("fence.mbarrier_init.release.cluster;" ::: "memory");
            if (warp == 2) { prefetch_tmap(&tm.k); prefetch_tmap(&tm.v); }
        }
        __syncwarp();
        DBG_W(1);
        cluster_arrive_relaxed();
        asm volatile("setmaxnreg.inc.sync.aligned.u32 208;");
        DBG_W(2);
        const int zi = (tid & 127) - 32;
        if (zi >= 0 && zi < 48) sts128(sb + CV_H + (4 * wg + (zi / 6 & 3) + (zi / 24) * 8) * CV_HPL + 2048 + (zi % 6) * 16, 0, 0, 0, 0);
        DBG_W(3);
        cluster_wait();
        DBG_W(5);
        if (cv) {
            if (tid == 32) {
#pragma unroll 1
                for (int c = 1; c < 5; c++) load_kv(c);
                prefetch_tmap(&tm.y);
            }
            __syncwarp();
            DBG_W(6);
            const int g = lane >> 2, t = lane & 3;
            const int x0 = 32 + 8 * w + g - 2 * t;
            CvAddr p;
            p.rdy = b_rdy;
            p.bar = 1 + wg;
            p.xr = sbase + (warp ^ 2) * 2048 + lane * 16;
            p.xw = sbase + warp * 2048 + (g * 4 + ((t - (w >> 1)) & 3)) * 16;
            p.wrap = t == 0 && w >= 2;
            mbar_wait(b_h + 8 * wg, 0);
            DBG_W(4);
            put_h(2 * wg);
            fence_async_smem();
            named_bar_sync(1 + wg, 128);
            float acc[2][64];
            zero_acc(acc[0]); zero_acc(acc[1]);
#pragma unroll 1
            for (int round = 0; round < 2; round++) {
                const int ch = round * 4 + 2 * wg;
                uint32_t a[CV_NA][4], tv[2][8];
#pragma unroll
                for (int e = 0; e < 2; e++) {
                    const int x = x0 - 8 * e;
                    p.neg[e] = x < 32;
                    p.pa[e] = sb + ch * CV_QG + 8 * (x ^ (x >> 2 & 4));
                    p.p0[2 * e] = p.pa[e] + (x < 32 ? 768 + 4 - CV_SL : -256);
                    p.p0[2 * e + 1] = p.pa[e] + (x < 32 ? 768 : -256 + 4);
                }
                p.db = (((sb + CV_H + ch * 2 * CV_HPL) & 0x3FFFF) >> 4) | ((CV_HPL / 16) << 16);
                if (round) mbar_wait(b_full, 0);
                DBG_S(7 + 3 * round);
                cv_steps<0>(acc, a, tv, p);
                DBG_S(8 + 3 * round);
                const int r128 = 4 * (lane >> 3) + 2 * (lane & 1) + ((~lane >> 2) & 1);
#pragma unroll
                for (int i = 0; i < 2; i++) {
                    const uint32_t ta = sb + ((ch + i + 1) & 7) * CV_SL + 12288 + r128 * 128 + ((((~lane & 2) * 2 + w) ^ (r128 & 7)) << 4);
                    stsm4t(ta, tv[i][0], tv[i][1], tv[i][2], tv[i][3]);
                    stsm4t(ta + 2048, tv[i][4], tv[i][5], tv[i][6], tv[i][7]);
                }
                fence_async_smem();
                named_bar_sync(1 + wg, 128);
                if ((tid & 127) < 2) {
                    const int d = d0 + ch + (tid & 1);
                    asm volatile("cp.async.bulk.tensor.4d.global.shared::cta.bulk_group [%0, {%2, %3, %4, %2}], [%1];"
                                 ::"l"((uint64_t)&tm.y), "r"(sb + ((ch + (tid & 1) + 1) & 7) * CV_SL + 12288), "r"(0), "r"(4 * (d >> 8)), "r"(d & 255) : "memory");
                    asm volatile("cp.async.bulk.commit_group;" ::: "memory");
                }
                __syncwarp();
                DBG_S(9 + 3 * round);
            }
            GT(1);
        }
    }
    int warp2 = warp;
    asm volatile("" : "+r"(warp2));
    if (warp2 >= 8) {
        asm volatile("setmaxnreg.dec.sync.aligned.u32 72;");
        if (warp == 8) { if (elect_one()) {
            if (rank == 0) {
                uint32_t smid;
                asm volatile("mov.u32 %0, %%smid;" : "=r"(smid));
                const int t = smid >> 1;
                int team = t < 32 ? t & 7 : t < 60 ? 1 + (t - 32) % 7 : t < 62 ? t - 54 : 0;
                const unsigned long long arr = atomicAdd(reinterpret_cast<unsigned long long*>(g_ticket + 16 * FL_PITCH), 1ull);
                const uint32_t e1 = (uint32_t)(arr / NCL) + 1;
                unsigned int* tk = g_ticket + (e1 & 1) * 8 * FL_PITCH;
                int slot = atomicAdd(tk + team * FL_PITCH, 1u);
                atomicAdd(g_ticket + 17 * FL_PITCH, 1u);
                if (blockIdx.x < 16) g_ticket[((~e1 & 1) * 8 + (blockIdx.x >> 1)) * FL_PITCH] = 0;
                if (slot >= 8) {
                    const long long t0 = clock64();
                    while ((int)(*(volatile unsigned int*)(g_ticket + 17 * FL_PITCH) - e1 * NCL) < 0 && clock64() - t0 < 100000) {}
                    for (team = 0; team < 8; team++)
                        if ((slot = atomicAdd(tk + team * FL_PITCH, 1u)) < 8) break;
                }
#pragma unroll
                for (int i = 0; i < 2; i++)
                    asm volatile("st.async.weak.shared::cluster.mbarrier::complete_tx::bytes.v2.b32 [%0], {%1, %2}, [%3];"
                                 ::"r"(mapa_u32(s_bar + 192, i)), "r"(team * 8 + slot), "r"(e1), "r"(mapa_u32(b_role, i)) : "memory");
            }
            if (get_role()) {
            TM(2);
            mbar_expect_tx(b_rfull, 32768);
            tma_load_2d(sbase + 16384, &tm.q, b_rfull, bj * 128, m0);
            tma_load_2d(sb + 8 * CV_SL, &tm.q, b_rfull, bj * 128 + 64, m0);
            int s5 = 0, s4 = 0;
            uint32_t p5 = 0, p4 = 1;
            auto putB = [&](const CUtensorMap* tB, int kc, uint32_t bytes) {
                const uint32_t full = f5 + 8 * s5;
                mbar_wait(full + 64, (p5 >> s5) & 1);
                mbar_expect_tx(full, bytes);
                tma_load_2d_mc(s_r + 16384 + rank * 8192 + s5 * R5_STAGE, tB, full, bj * 128 + rank * 64, kc);
                p5 ^= 1u << s5;
            };
            auto putA = [&](int c, int r) {
                tma_load_2d(s_r + s5 * R5_STAGE, &tm.act, f5 + 8 * s5, c, r);
                if (++s5 == R5_N) s5 = 0;
            };
            prefetch_tmap(&tm.act); prefetch_tmap(&tm.w1); prefetch_tmap(&tm.w2); prefetch_tmap(&tm.w3); prefetch_tmap(&tm.w4);
            auto own_first = [&](int it) {
                const int hf = it >= 9, c = it - 2 - 7 * hf;
                return (it < 2 ? 2 * bj + it : 2 * (c + (c >= bj)) + hf) * BK;
            };
            const unsigned int n8 = 8 * ep, nh = (bi == 0 || bi == 15) ? 2 * n8 : 3 * n8;
#pragma unroll 1
            for (int layer = 0; layer < 2; layer++) {
                s5 = 2;
#pragma unroll 1
                for (int kk = -(layer | Y_FIRST); kk < 5 - (layer | Y_FIRST); kk++) {
                    if (kk & 4) {
                        if (layer == 0) { TM(1); wait_flag(flag_ptr(0, FL_CS, 8 + bj), 8 * n8); TM(4); fence_proxy_async(); }
                        mbar_wait(e5 + 8, (p5 >> 1) & 1);
                        mbar_expect_tx(f5 + 8, 32768);
                        tma_load_2d(s_r + R5_STAGE, &tm.act, f5 + 8, (bj >> 1) * 256 + rank * 128, R_Y + (tb & ~255) + (bj & 1) * 128);
                        tma_load_2d(s_r + R5_STAGE + 16384, &tm.act, f5 + 8, (bj >> 1) * 256 + rank * 128 + 64, R_Y + (tb & ~255) + (bj & 1) * 128);
                        p5 ^= 2;
                        if (layer == 0) TM(5);
                    } else {
                        if (kk == Y_HOLD && layer == 0) mbar_wait(f5 + 8, 0);
                        putB(&tm.w1, own_first(kk), kk < 2 ? 16384 : R5_STAGE);
                        if (++s5 == R5_N) s5 = 0;
                    }
                }
                s5 = 4;
#pragma unroll 1
                for (int kk = 2; kk < 16; kk++) {
                    const int kc = own_first(kk);
                    if (kk >= 4) putB(&tm.w1, kc, R5_STAGE);
                    if (kk == 2 || kk == 9) {
                        wait_flag(flag_ptr(layer, FL_XA + (kk & 1), bi), n8);
                        if (layer == 0 && kk == 2) TM(14);
                        DP(8 * (FL_XA + (kk & 1)) + 3);
                        fence_proxy_async();
                        DP(8 * (FL_XA + (kk & 1)) + 4);
                    }
                    putA(kc, R_XA + tb);
                }
                mbar_wait(e5 + 24, (p5 >> 3) & 1);
                mbar_arrive(f5 + 24);
                p5 ^= 8;
                s5 = 4;
#pragma unroll 1
                for (int kk = 0; kk < 5; kk++) { putB(&tm.w2, kk * 2 * BK, R5_STAGE); if (++s5 == R5_N) s5 = 0; }
#pragma unroll 1
                for (int kk = 0; kk < 16; kk++) {
                    const int kc = ((kk & 7) * 2 + (kk >> 3)) * BK;
                    if (kk >= 5) putB(&tm.w2, kc, R5_STAGE);
                    if ((kk & 7) == 0) {
                        wait_flag(flag_ptr(layer, FL_H + (kk >> 3), bi), nh);
                        DP(8 * (FL_H + (kk >> 3)) + 3);
                        fence_proxy_async();
                        DP(8 * (FL_H + (kk >> 3)) + 4);
                    }
                    putA(kc, R_H + layer * R_HP + m0 + (int)((0x4031u >> ((kk & 6) << 1)) & 7) - 2);
                }
#pragma unroll 1
                for (int it = 0; it < 32; it++) {
                    const int kc = it >= 16 ? (it - 16) * BK : own_first(it);
                    const int nb = it < 16 ? 4 : 3, n0 = bj * 448 + (it < 16 ? 0 : 256);
                    if (it > 0 && it < 4) {
                        const int i = (it - 1) * 3 >> 1;
                        mbar_wait(e5 + 8 * i, (p5 >> i) & 1);
                        mbar_wait(e5 + 8 * i + 8, (p5 >> (i + 1)) & 1);
                    }
                    mbar_wait(e4 + 8 * s4, p4);
                    if (it >= 16 && it < 19) mbar_wait(e4 + 8 * s4 + 8, p4);
                    uint32_t sa = s_r + s4 * (it < 16 ? R4_STAGE : R4B_STAGE), full = f4 + 8 * s4;
                    mbar_expect_tx(full, (it < 2 ? 0 : 16384) + nb * 8192);
#pragma unroll 1
                    for (int j = (it ^ rank) & 1; j < nb; j += 2) tma_load_2d_mc(sa + (it < 16 ? -32768 : 16384) + j * 8192, &tm.w3, full, n0 + j * 64, kc);
                    if (it == 3 || it == 9) {
                        wait_flag(flag_ptr(layer, FL_X1 + (it >> 3), bi), n8);
                        DP(8 * (FL_X1 + (it >> 3)) + 3);
                        fence_proxy_async();
                        DP(8 * (FL_X1 + (it >> 3)) + 4);
                        if (it == 3) tma_load_2d(s_r + 2 * R4_STAGE, &tm.act, f4 + 16, own_first(2), R_X1 + tb);
                    }
                    if (it >= 3) tma_load_2d(sa, &tm.act, full, kc, R_X1 + tb);
                    if (++s4 == R4_N) { s4 = 0; p4 ^= 1; }
                }
                wait_flag(flag_ptr(layer, FL_H2, bi), n8);
                fence_proxy_async();
                s5 = 0;
#pragma unroll 1
                for (int j = 0; j < 7; j++) {
                    if (j > 0 && (j & 1) == 0) {
                        mbar_wait(b_h2 + 4 * j, layer);
                        fence_proxy_async();
                    }
                    const int ra = R_H2 + (j >> 1) * 256 + tb;
#pragma unroll 1
                    for (int b = 0; b < 8; b++) {
                        if (j == 0 && b < R4_N) mbar_wait(e4 + 8 * b, p4);
                        putB(&tm.w4, (7 * b + j) * BK, R5_STAGE);
                        putA(((j & 1) * 8 + b) * BK, ra);
                    }
                }
            }
        } } } else {
            auto colsum = [&](bool is1, int bi, int bj) {
                const int pitch = is1 ? D_ : F_, c = is1 ? bj * 128 + (lane & 15) * 8 : bj * 448 + min((warp & 2) * 128 + lane * 8, 440);
                const bf16* p = (is1 ? w1p : w3p) + ((bi * 64 + (is1 ? (lane >> 4) * 32 : 0)) * pitch + c);
                float a[8];
#pragma unroll
                for (int i = 0; i < 8; i++) a[i] = 0.f;
#pragma unroll 1
                for (int r0 = is1 ? 32 : 0; r0 < 64; r0 += 8) {
                    uint4 v[8];
#pragma unroll
                    for (int r = 0; r < 8; r++, p += pitch) v[r] = __ldg(reinterpret_cast<const uint4*>(p));
#pragma unroll
                    for (int r = 0; r < 8; r++) {
                        a[0] += lo2f(v[r].x); a[1] += hi2f(v[r].x); a[2] += lo2f(v[r].y); a[3] += hi2f(v[r].y);
                        a[4] += lo2f(v[r].z); a[5] += hi2f(v[r].z); a[6] += lo2f(v[r].w); a[7] += hi2f(v[r].w);
                    }
                }
                if (is1) {
#pragma unroll
                    for (int i = 0; i < 8; i++) a[i] += __shfl_xor_sync(0xffffffffu, a[i], 16);
                }
                float4* dst = reinterpret_cast<float4*>(g_cpart + bi * (F_ + D_) + (is1 ? F_ : 0) + c);
                dst[0] = make_float4(a[0], a[1], a[2], a[3]);
                dst[1] = make_float4(a[4], a[5], a[6], a[7]);
                asm volatile("fence.release.gpu;" ::: "memory");
                __syncwarp();
                if (lane == 0) asm volatile("red.relaxed.gpu.global.add.u32 [%0], 1;" ::"l"(flag_ptr(!is1, FL_CS, bj)) : "memory");
            };
            if (cv && warp == 10) colsum(true, blockIdx.x >> 3, blockIdx.x & 7);
            float4 keep[2];
            const bool on = get_role();
            if (on && warp == 11) {
                uint4* ps = reinterpret_cast<uint4*>(g_stats + (bi * 8 + bj) * 128) + lane;
                ps[0] = ps[32] = make_uint4(0, 0, 0, 0);
                asm volatile("fence.acq_rel.gpu;" ::: "memory");
                __syncwarp();
                if (lane == 0) mbar_arrive(b_rfull);
            }
#pragma unroll 1
            for (int layer = on ? 0 : 2; layer < 2; layer++) {
                if (warp == 10) {
#pragma unroll 1
                    for (int kind = 0; kind < 6; kind += 2) {
                        const uint32_t src = kind == FL_H ? s_stg : s_epi;
                        const int r = kind == FL_H ? R_H + layer * R_HP + m0 : (kind == FL_XA ? R_XA : R_X1) + tb;
#pragma unroll 1
                        for (int hf = 0; hf < 2; hf++) {
                            named_bar_sync(5 + hf, 288);
                            if (lane == 0) {
                                DP(8 * (kind + hf));
                                tma_store_2d(&tm.act, src + hf * 16384, bj * 128 + hf * 64, r);
                                asm volatile("cp.async.bulk.commit_group;" ::: "memory");
                                asm volatile("cp.async.bulk.wait_group 0;" ::: "memory");
                                DP(8 * (kind + hf) + 1);
                                DP(8 * (kind + hf) + 2);
                                unsigned int* fp = flag_ptr(layer, kind + hf, bi);
                                asm volatile("red.relaxed.gpu.global.add.u32 [%0], 1;" ::"l"(fp) : "memory");
                                if (kind == FL_H) {
                                    if (bi > 0) asm volatile("red.relaxed.gpu.global.add.u32 [%0], 1;" ::"l"(fp - FL_PITCH) : "memory");
                                    if (bi < 15) asm volatile("red.relaxed.gpu.global.add.u32 [%0], 1;" ::"l"(fp + FL_PITCH) : "memory");
                                }
                            }
                            __syncwarp();
                        }
                    }
                } else {
                    uint32_t* rs = reinterpret_cast<uint32_t*>(sgen + OFF_RS);
                    float* cs = reinterpret_cast<float*>(sgen + OFF_CS);
#pragma unroll 1
                    for (int which = 0; which < 2; which++) {
                        if (layer < which) {
                            if (warp == 11 && lane == 0) {
                                wait_flag(flag_ptr(0, FL_XA + W3_AT, bi), 8 * ep);
                                asm volatile("cp.async.bulk.prefetch.L2.global [%0], %1;" ::"l"(w3p + (bi * 8 + bj) * 28672), "r"(57344) : "memory");
                            }
                            __syncwarp();
                            colsum(false, bi, bj);
                        }
                        if (warp == 11) continue;
                        if (layer == 0) {
                            if (lane == 0) wait_flag(flag_ptr(which, FL_CS, bj), (16 << which) * ep);
                            __syncwarp();
#pragma unroll 1
                            for (int c = (which ? 384 : 768) + lane * 4; c < 896; c += 128) {
                                const float* cp = g_cpart + (which ? bj * 448 + min(c & 511, 444) : F_ + bj * 128 + lane * 4);
                                float4 a = make_float4(0.f, 0.f, 0.f, 0.f);
#pragma unroll
                                for (int r0 = 0; r0 < 16; r0 += 8) {
                                    float4 v[8];
#pragma unroll
                                    for (int r = 0; r < 8; r++) v[r] = __ldcg(reinterpret_cast<const float4*>(cp + (r0 + r) * (F_ + D_)));
#pragma unroll
                                    for (int r = 0; r < 8; r++) { a.x += v[r].x; a.y += v[r].y; a.z += v[r].z; a.w += v[r].w; }
                                }
                                if (c < 768) *reinterpret_cast<float4*>(cs + min(c & 511, 444)) = a;
                                keep[0] = a;
                            }
                        }
                        if (lane == 0 && (layer | which)) wait_flag(flag_ptr(layer, which == 0 ? FL_XA : FL_X1, bi), 8 * ep);
                        __syncwarp();
                        *reinterpret_cast<float4*>(cs + 256 + lane * 4) = keep[0];
                        { const float4 k0 = keep[0]; keep[0] = keep[1]; keep[1] = k0; }
#pragma unroll 1
                        for (int i = 0; i < 4; i++) {
                            const int r = i * 32 + lane;
                            float mean, var;
                            row_stats(g_stats + (1 + which) * S_ * 8 + bi * 1024 + r, ~layer << 31, mean, var);
                            const uint32_t c0 = pack2(mean, fsqrt(bfr(bfr(var) + 1e-5f)));
                            if (lane < 19 && (layer | which | i) == 0) asm volatile("mbarrier.inval.shared::cta.b64 [%0];" ::"r"(b_full + 8 * lane) : "memory");
                            __syncwarp();
                            rs[r] = c0;
                            const float rd = frcp(hi2f(c0));
                            rs[128 + r] = pack2((mean - lo2f(c0)) * rd, fsqrt(bfr(bfr(var * rd * rd) + 1e-5f)));
                        }
                        __syncwarp();
                        named_bar_arrive(3, 288);
                    }
                }
                const uint32_t s_cnt = s_bar + 224;
                auto ticket = [&](uint32_t a) {
                    uint32_t v = 0;
                    if (lane == 0) asm volatile("atom.acq_rel.cta.shared.add.u32 %0, [%1], 1;" : "=r"(v) : "r"(a) : "memory");
                    return v;
                };
                mbar_wait(b_stg, 0);
                int u = __shfl_sync(0xffffffffu, ticket(s_cnt + 16 + 4 * layer), 0), step = 0;
#pragma unroll 1
                while (true) {
#pragma unroll 1
                    for (; step < 5 && u >= (int)((0x3830201810ull >> (8 * step)) & 255); step++) {
                        if (step == 1) { named_bar_arrive(4, 352); continue; }
                        const int part = step ? step - 1 : 0;
                        __syncwarp();
                        if (ticket(s_cnt + 4 * part) == 3 * layer + 2) {
                            asm volatile("fence.release.gpu;" ::: "memory");
                            unsigned int* fp = flag_ptr(layer, FL_H2 + part, bi);
                            asm volatile("red.relaxed.gpu.global.add.u32 [%0], 1;" ::"l"(fp) : "memory");
                            if (part > 0) { wait_flag(fp, 8 * ep); mbar_arrive(b_h2 + 8 * part); }
                        }
                        __syncwarp();
                        if (step == 2) mbar_wait(b_stg, 1);
                    }
                    if (u >= 56) break;
                    const uint32_t un = ticket(s_cnt + 16 + 4 * layer);
                    const int job = u >> 3, r = (u & 7) * 16 + (lane >> 3);
                    const uint32_t sp = sbase + ((job & 2) ? OFF_STG5 : OFF_EPI) + r * 256 + (job & 1) * 128;
                    bf16* gp = act + (size_t)(R_H2 + (job >> 1) * 256 + tb + r) * D_ + ((job & 1) * 8 + bj) * 64 + (lane & 7) * 8;
                    uint4 v[4];
#pragma unroll
                    for (int e = 0; e < 4; e++) v[e] = lds128(sp + e * 1024 + (((lane & 7) ^ ((r + 4 * e) & 7)) << 4));
#pragma unroll
                    for (int e = 0; e < 4; e++) stg128(gp + 4 * e * D_, gelu8h(v[e]));
                    u = __shfl_sync(0xffffffffu, un, 0);
                }
                if (layer == 0 && warp == 11) {
                    const char* ps = reinterpret_cast<const char*>(g_stats + bi * 1024) + lane * 128;
                    const char* py = reinterpret_cast<const char*>(act + (size_t)(R_Y + (tb & ~255) + (bj & 1) * 128 + (lane >> 1)) * D_ + (bj >> 1) * 256 + rank * 128) + (lane & 1) * 128;
#pragma unroll 1
                    for (int i = 0; i < 8; i++) {
                        asm volatile("prefetch.global.L2 [%0];" ::"l"(py + (size_t)i * 16 * D_ * 2) : "memory");
                        if (i >= 6) asm volatile("prefetch.global.L2 [%0];" ::"l"(ps + (i & 1) * 4096) : "memory");
                        __nanosleep(400);
                    }
                }
            }
        }
        __syncwarp();
        asm volatile("barrier.cluster.arrive.relaxed.aligned;\nbarrier.cluster.wait.acquire.aligned; // helpers" ::: "memory");
    } else {
        DT(0);
        GT(2);
        if (tid == 0) TM(10);
        auto put_y = [&]() {
            if ((tid & 127) < 2 && cv) {
                if (tid == 0) TM(6);
                asm volatile("cp.async.bulk.wait_group 0;" ::: "memory");
                asm volatile("red.relaxed.gpu.global.add.u32 [%0], 1;" ::"l"(flag_ptr(0, FL_CS, 8 + (blockIdx.x >> 4))) : "memory");
                if (tid == 0) TM(7);
                if (tid == 128) TM(8);
            }
            __syncwarp();
        };
        put_y();
        asm volatile("setmaxnreg.inc.sync.aligned.u32 216;");
        if (get_role()) {
        const bool rel_on = (tid & 95) == 0;
        const uint32_t rel5 = mapa_u32(e5, (warp & 1) ^ rank), rel4 = rel5 + (e4 - e5);
        const uint32_t da0 = desc_a(s_r + wg * 8192), db0 = desc_b(s_r + BM * BK * 2), dae = da0 + (OFF_EPI - OFF_R) / 16, db4 = db0 - 49152 / 16;
        auto skip5 = [&](RingState& rs) {
            if (rel_on) mbar_arrive_cluster(rel5 + 8 * rs.st);
            rs.st++;
        };
        const int t = lane & 3;
        const int row = warp * 16 + (lane >> 2);
        const uint32_t st_w = (uint32_t)((warp * 16 + ((lane >> 3) & 1) * 8 + (lane & 7)) * 256 + (((lane >> 4) ^ (lane & 7)) << 4));
        const uint32_t fr = (uint32_t)((warp * 16 + ((lane >> 3) & 1) * 8 + (lane & 7)) * 128 + (((lane >> 4) ^ (lane & 7)) << 4));
        auto copy_out = [&](bf16* dst, uint32_t src) {
            const int r = warp * 16 + (lane >> 4);
            bf16* ox = dst + (size_t)(m0 + r) * D_ + bj * 128 + (lane & 15) * 8;
            const uint32_t ra = src + ((lane & 15) >> 3) * 16384 + r * 128;
            uint4 v[8];
#pragma unroll
            for (int it = 0; it < 8; it++) v[it] = lds128(ra + it * 256 + (((lane & 7) ^ ((2 * it + (lane >> 4)) & 7)) << 4));
#pragma unroll
            for (int it = 0; it < 8; it++) *reinterpret_cast<uint4*>(ox + (size_t)it * 2 * D_) = v[it];
        };
        auto put_stats = [&](const uint32_t (&w)[32], int which, int layer) {
            float sm[2] = {0.f, 0.f}, sq[2] = {0.f, 0.f};
#pragma unroll
            for (int e = 0; e < 32; e++) {
                const float e0 = lo2f(w[e]), e1 = hi2f(w[e]);
                sm[e & 1] += e0 + e1; sq[e & 1] = fmaf(e0, e0, fmaf(e1, e1, sq[e & 1]));
            }
#pragma unroll
            for (int of = 1; of < 4; of <<= 1)
#pragma unroll
                for (int e = 0; e < 2; e++) { sm[e] += __shfl_xor_sync(0xffffffffu, sm[e], of); sq[e] += __shfl_xor_sync(0xffffffffu, sq[e], of); }
            if (t < 2) {
                const float s1 = t ? sm[1] : sm[0], q1 = t ? sq[1] : sq[0], mu = s1 * (1.0f / 128);
                asm volatile("{\n.reg .b64 t;\nmov.b64 t, {%1, %2};\nst.relaxed.gpu.global.b64 [%0], t;\n}"
                             ::"l"(g_stats + which * S_ * 8 + (bi * 8 + bj) * 128 + row + 8 * t), "f"(mu), "r"(__float_as_uint(fmaxf(q1 - s1 * mu, 0.f)) | ~layer << 31) : "memory");
            }
        };
        const float* csp = reinterpret_cast<const float*>(sgen + OFF_CS) + 2 * t;
        float mrow[2], rrow[2];
        const uint32_t* rsp = reinterpret_cast<const uint32_t*>(sgen + OFF_RS) + row;
        auto row_consts = [&](bool twice) {
#pragma unroll
            for (int e = 0; e < 2; e++) {
                const uint32_t q0 = rsp[8 * e], q1 = rsp[128 + 8 * e];
                mrow[e] = twice ? fmaf(lo2f(q1), hi2f(q0), lo2f(q0)) : lo2f(q0);
                rrow[e] = 0.5f * frcp(twice ? hi2f(q0) * hi2f(q1) : hi2f(q0));
            }
        };
        auto stage = [&](const float* acc, uint32_t dst, int j0, float2 (&cs)[8], const float* cnext) {
            float2 cn[8];
#pragma unroll
            for (int e = 0; e < 8; e++) cn[e] = *reinterpret_cast<const float2*>(cnext + 8 * e);
#pragma unroll
            for (int j = 0; j < 8; j += 2) {
                uint32_t w[4];
#pragma unroll
                for (int e = 0; e < 2; e++) {
                    const float* a = acc + 4 * (j + e);
                    w[2 * e] = pack2(fmaf(-mrow[0], cs[j + e].x, a[0]) * rrow[0], fmaf(-mrow[0], cs[j + e].y, a[1]) * rrow[0]);
                    w[2 * e + 1] = pack2(fmaf(-mrow[1], cs[j + e].x, a[2]) * rrow[1], fmaf(-mrow[1], cs[j + e].y, a[3]) * rrow[1]);
                }
                stsm4((dst + st_w) ^ (((j0 + j) & 15) << 4), w[0], w[1], w[2], w[3]);
            }
#pragma unroll
            for (int e = 0; e < 8; e++) cs[e] = cn[e];
        };
        RingState r5{1, 0}, r4{0, 0};
        DT(1);
        uint32_t x[32];
        mbar_wait(b_rfull, 0);
#pragma unroll
        for (int jp = 0; jp < 8; jp++) ldsm4(x[4 * jp], x[4 * jp + 1], x[4 * jp + 2], x[4 * jp + 3], sbase + 16384 + (fr ^ ((jp & 3) << 5)) + (jp >> 2) * (16384 + 8 * CV_SL));
#pragma unroll
        for (int e = 0; e < 32; e++) asm volatile("" : "+r"(x[e]));
        named_bar_sync(9 + wg, 128);
        if ((tid & 95) < R5_N) mbar_arrive_cluster(rel5 + 8 * lane);
#pragma unroll 1
        for (int layer = 0; layer < 2; layer++) {
            {
                DT(2 + 24 * layer);
                if (layer == 0 && tid == 0) TM(12);
                put_stats(x, 0, layer);
                DT(20 + 24 * layer);
                DT(22 + 24 * layer);
                uint32_t mb[2];
                float rd[2];
                {
                    float mean, var;
                    row_stats(g_stats + bi * 1024 + warp * 16 + (lane & 15), ~layer << 31, mean, var);
                    __syncwarp();
                    const float r1 = frcp(bfr(fsqrt(bfr(bfr(var) + 1e-5f))));
                    const uint32_t m1 = pack2(mean, mean);
#pragma unroll
                    for (int e = 0; e < 2; e++) { mb[e] = __shfl_sync(0xffffffffu, m1, (lane >> 2) + 8 * e); rd[e] = __shfl_sync(0xffffffffu, r1, (lane >> 2) + 8 * e); }
                }
                DT(21 + 24 * layer);
                if (layer == 0 && tid == 0) TM(11);
                mbar_wait(f5 + 8, r5.ph);
                if (layer == 0) GT(3);
                if (layer == 0 && tid == 0) TM(9);
                const uint32_t ya = s_r + R5_STAGE + wg * 16384 + ((lane >> 4) * 8 + (lane & 7)) * 128 + ((((warp & 3) * 2 + ((lane >> 3) & 1)) ^ (lane & 7)) << 4);
                uint32_t y[16];
#pragma unroll
                for (int e = 0; e < 32; e++) {
                    if ((e & 15) == 0) {
#pragma unroll
                        for (int jp = 0; jp < 4; jp++) ldsm4t(y[4 * jp], y[4 * jp + 1], y[4 * jp + 2], y[4 * jp + 3], ya + jp * 2048 + e * 512);
                    }
                    const uint32_t d = bsub2(x[e], mb[e & 1]);
                    x[e] = badd2(x[e], bmul2(pack2(lo2f(d) * rd[e & 1], hi2f(d) * rd[e & 1]), y[e & 15]));
                    if ((e & 3) == 3) stsm4(s_epi + (fr ^ (((e >> 2) & 3) << 5)) + (e >> 4) * 16384, x[e - 3], x[e - 2], x[e - 1], x[e]);
                    if ((e & 15) == 15) { fence_async_smem(); named_bar_arrive(5 + (e >> 4), 288); }
                }
                DT(19 + 24 * layer);
                named_bar_sync(9 + wg, 128);
                skip5(r5);
                DT(3 + 24 * layer);
                if (layer == 0 && tid == 0) TM(13);
            }
            {
                float acc[64];
                zero_acc(acc);
                kblock<128, R5_N>(acc, dae, db0 + 2 * (R5_STAGE / 16), f5, r5);
                kblock<128, R5_N>(acc, dae + 1024, db0 + 3 * (R5_STAGE / 16), f5, r5);
                put_stats(x, 1, layer);
                wgmma_wait<1>();
                if (rel_on) mbar_arrive_cluster(rel5 + 16);
                mainloop<128, R5_N, R5_STAGE>(acc, 14, da0, db0, f5, rel5, rel_on, r5, 15 + 24 * layer);
                DT(4 + 24 * layer);
                if (layer == 0 && tid == 0) TM(15);
                named_bar_sync(3, 288);
                row_consts(true);
                float2 cs[8];
#pragma unroll
                for (int j = 0; j < 16; j += 2) {
                    if ((j & 7) == 0) {
#pragma unroll
                        for (int e = 0; e < 8; e++) cs[e] = *reinterpret_cast<const float2*>(csp + 256 + 8 * (j + e));
                    }
                    uint32_t w[4];
#pragma unroll
                    for (int e = 0; e < 4; e++) {
                        const float* a = acc + 4 * j + 2 * e;
                        const float2 c = cs[(j & 7) + (e >> 1)];
                        w[e] = gelu2h(pack2(fmaf(-mrow[e & 1], c.x, a[0]) * rrow[e & 1], fmaf(-mrow[e & 1], c.y, a[1]) * rrow[e & 1]));
                    }
                    stsm4(s_stg + (fr ^ ((j & 7) << 4)) + (j >> 3) * 16384, w[0], w[1], w[2], w[3]);
                    if ((j & 7) == 6) { fence_async_smem(); named_bar_arrive(5 + (j >> 3), 288); }
                }
                DT(5 + 24 * layer);
            }
            {
                float acc[64];
                zero_acc(acc);
                uint32_t u[32];
                {
                    uint32_t mb[2];
                    float rd[2];
#pragma unroll
                    for (int e = 0; e < 2; e++) { const uint32_t q0 = rsp[8 * e]; mb[e] = (q0 & 0xffffu) * 0x10001u; rd[e] = frcp(hi2f(q0)); }
#pragma unroll
                    for (int e = 0; e < 32; e++) {
                        const uint32_t d = bsub2(x[e], mb[e & 1]);
                        u[e] = pack2(lo2f(d) * rd[e & 1], hi2f(d) * rd[e & 1]);
                        asm volatile("" : "+r"(u[e]));
                    }
                }
                mbar_wait(f5 + 24, r5.ph);
                skip5(r5);
                kblock<128, R5_N>(acc, da0 + 4 * (R5_STAGE / 16), db0 + 4 * (R5_STAGE / 16), f5, r5);
                DT(16 + 24 * layer);
                mainloop<128, R5_N, R5_STAGE>(acc, 15, da0, db0, f5, rel5, rel_on, r5, -1);
                DT(6 + 24 * layer);
#pragma unroll
                for (int j = 0; j < 16; j += 2) {
#pragma unroll
                    for (int e = 0; e < 4; e++) u[2 * j + e] = badd2(u[2 * j + e], pack2(acc[4 * j + 2 * e], acc[4 * j + 2 * e + 1]));
                    stsm4(s_epi + (fr ^ ((j & 7) << 4)) + (j >> 3) * 16384, u[2 * j], u[2 * j + 1], u[2 * j + 2], u[2 * j + 3]);
                    if ((j & 7) == 6) { fence_async_smem(); named_bar_arrive(5 + (j >> 3), 288); }
                }
#pragma unroll
                for (int e = 0; e < 32; e++) x[e] = badd2(x[e], u[e]);
                named_bar_sync(9 + wg, 128);
                DT(7 + 24 * layer);
                if (layer == 0) GT(7);
            }
            {
                float2 cs[8];
                {
                    float acc[128];
                    zero_acc(acc);
                    kblock<256, R4_N>(acc, dae, db4, f4, r4);
                    kblock<256, R4_N>(acc, dae + 1024, db4 + R4_STAGE / 16, f4, r4);
                    {
                        uint32_t w[32];
#pragma unroll
                        for (int jp = 0; jp < 8; jp++) ldsm4(w[4 * jp], w[4 * jp + 1], w[4 * jp + 2], w[4 * jp + 3], s_epi + (fr ^ ((jp & 3) << 5)) + (jp >> 2) * 16384);
                        put_stats(w, 2, layer);
                    }
                    wgmma_wait<1>();
                    if (rel_on) mbar_arrive_cluster(rel4);
                    mainloop<256, R4_N, R4_STAGE>(acc, 14, da0, db4, f4, rel4, rel_on, r4, 17 + 24 * layer);
                    DT(8 + 24 * layer);
                    named_bar_sync(3, 288);
                    row_consts(false);
#pragma unroll
                    for (int e = 0; e < 8; e++) cs[e] = *reinterpret_cast<const float2*>(csp + 8 * e);
#pragma unroll
                    for (int j = 0; j < 32; j += 8) stage(acc + 4 * j, j < 16 ? s_epi : s_stg, j, cs, csp + 8 * (j + 8));
                    __syncwarp();
                if (lane == 0) mbar_arrive(b_stg);
                }
                DT(9 + 24 * layer);
                float acc[96];
                zero_acc(acc);
                kblock<192, R4_N>(acc, da0, db0, f4, r4);
                mainloop<192, R4_N, R4B_STAGE>(acc, 15, da0, db0, f4, rel4, rel_on, r4, -1);
                DT(10 + 24 * layer);
                named_bar_sync(4, 352);
#pragma unroll
                for (int j = 0; j < 24; j += 8) stage(acc + 4 * j, j < 16 ? s_epi : s_stg, j, cs, csp + 256 + 8 * (j < 16 ? j + 8 : 0));
                __syncwarp();
                if (lane == 0) mbar_arrive(b_stg);
                DT(11 + 24 * layer);
            }
            {
                float acc[64];
#pragma unroll
                for (int i = 0; i < 32; i++) asm volatile("shl.b32 %0, %2, 16;\nand.b32 %1, %2, 0xffff0000;" : "=f"(acc[2 * i]), "=f"(acc[2 * i + 1]) : "r"(x[i]));
                kblock<128, R5_N>(acc, da0, db0, f5, r5);
                DT(18 + 24 * layer);
                mainloop<128, R5_N, R5_STAGE>(acc, 55, da0, db0, f5, rel5, rel_on, r5, 62 - 40 * (layer ^ 1));
                DT(12 + 24 * layer);
#pragma unroll
                for (int i = 0; i < 32; i++) x[i] = pack2(acc[2 * i], acc[2 * i + 1]);
                DT(13 + 24 * layer);
                if (layer == 0) GT(6);
                DT(14 + 24 * layer);
            }
        }
#pragma unroll
        for (int jp = 0; jp < 8; jp++) stsm4(s_epi + (fr ^ ((jp & 3) << 5)) + (jp >> 2) * 16384, x[4 * jp], x[4 * jp + 1], x[4 * jp + 2], x[4 * jp + 3]);
        __syncwarp();
        copy_out(outp, s_epi);
        DT(38);
        GT(4);
        }
        cluster_arrive_relaxed();
        cluster_wait();
    }
}

typedef CUresult (*PFN_encodeTiled)(CUtensorMap*, CUtensorMapDataType, cuuint32_t, void*, const cuuint64_t*, const cuuint64_t*,
                                    const cuuint32_t*, const cuuint32_t*, CUtensorMapInterleave, CUtensorMapSwizzle,
                                    CUtensorMapL2promotion, CUtensorMapFloatOOBfill);

static CUtensorMap make_map(PFN_encodeTiled enc, const void* ptr, int inner, int outer, int box_inner, int box_outer,
                            CUtensorMapSwizzle swz = CU_TENSOR_MAP_SWIZZLE_128B) {
    CUtensorMap m;
    cuuint64_t dims[2] = {(cuuint64_t)inner, (cuuint64_t)outer};
    cuuint64_t strides[1] = {(cuuint64_t)inner * 2};
    cuuint32_t box[2] = {(cuuint32_t)box_inner, (cuuint32_t)box_outer};
    cuuint32_t es[2] = {1, 1};
    enc(&m, CU_TENSOR_MAP_DATA_TYPE_BFLOAT16, 2, const_cast<void*>(ptr), dims, strides, box, es, CU_TENSOR_MAP_INTERLEAVE_NONE,
        swz, CU_TENSOR_MAP_L2_PROMOTION_L2_256B, CU_TENSOR_MAP_FLOAT_OOB_FILL_NONE);
    return m;
}

extern "C" void kernel_launch(void* const* d_in, const int* in_sizes, int n_in, void* d_out, int out_size) {
    const bf16* A_q = (const bf16*)d_in[0];
    const bf16* A_k = (const bf16*)d_in[1];
    const bf16* A_v = (const bf16*)d_in[2];
    const bf16* A_shk = (const bf16*)d_in[3];
    const bf16* A_ssk = (const bf16*)d_in[4];
    const bf16* A_ssD = (const bf16*)d_in[5];
    const bf16* w1 = (const bf16*)d_in[7];
    const bf16* w2 = (const bf16*)d_in[8];
    const bf16* w3 = (const bf16*)d_in[9];
    const bf16* w4 = (const bf16*)d_in[10];
    bf16* out = (bf16*)d_out;

    static PFN_encodeTiled enc = nullptr;
    static bool attr_done = false;
    if (!enc) {
        void* fn = nullptr;
        cudaDriverEntryPointQueryResult qr;
        cudaGetDriverEntryPoint("cuTensorMapEncodeTiled", &fn, cudaEnableDefault, &qr);
        enc = (PFN_encodeTiled)fn;
    }
    if (!attr_done) {
        cudaFuncSetAttribute(mega_kernel, cudaFuncAttributeMaxDynamicSharedMemorySize, MEGA_SMEM);
        attr_done = true;
    }
    void* p_act;
    cudaGetSymbolAddress(&p_act, g_act);
    bf16* act = (bf16*)(((uintptr_t)p_act + 0x1fffff) & ~(uintptr_t)0x1fffff);

    MegaMaps tm;
    tm.q = make_map(enc, A_q, D_, S_, 64, 128);
    tm.act = make_map(enc, act, D_, R_END, 64, 128);
    tm.w1 = make_map(enc, w1, D_, D_, 64, 64);
    tm.w2 = make_map(enc, w2, D_, D_, 64, 64);
    tm.w3 = make_map(enc, w3, F_, D_, 64, 64);
    tm.w4 = make_map(enc, w4, D_, F_, 64, 64);
    {
        cuuint64_t dims[4] = {64, 16, 256, 8}, strides[3] = {128, D_ * 2, (cuuint64_t)2048 * D_ * 2};
        cuuint32_t box[4] = {64, 4, 1, 8}, es[4] = {1, 1, 1, 1};
        enc(&tm.y, CU_TENSOR_MAP_DATA_TYPE_BFLOAT16, 4, act + (size_t)R_Y * D_, dims, strides, box, es, CU_TENSOR_MAP_INTERLEAVE_NONE,
            CU_TENSOR_MAP_SWIZZLE_128B, CU_TENSOR_MAP_L2_PROMOTION_NONE, CU_TENSOR_MAP_FLOAT_OOB_FILL_NONE);
    }
    for (int i = 0; i < 2; i++) {
        cuuint64_t dims[4] = {D_, 4, 8, S_ / 32}, strides[3] = {8 * D_ * 2, D_ * 2, 32 * D_ * 2};
        cuuint32_t box[4] = {16, 4, 8, 4}, es[4] = {1, 1, 1, 1};
        enc(i ? &tm.v : &tm.k, CU_TENSOR_MAP_DATA_TYPE_BFLOAT16, 4, (void*)(i ? A_v : A_k), dims, strides, box, es, CU_TENSOR_MAP_INTERLEAVE_NONE,
            CU_TENSOR_MAP_SWIZZLE_32B, CU_TENSOR_MAP_L2_PROMOTION_NONE, CU_TENSOR_MAP_FLOAT_OOB_FILL_NONE);
    }
    mega_kernel<<<2 * NCL, 384, MEGA_SMEM, cudaStreamPerThread>>>(tm, out, act, w1, w2, w3, A_q, A_k, A_v, A_shk, A_ssk, A_ssD);
}
```

```cpp
#include <cuda_runtime.h>
#include <cuda_bf16.h>
#include <cuda.h>
#include <stdint.h>

typedef __nv_bfloat16 bf16;

constexpr int S_ = 2048;
constexpr int D_ = 1024;
constexpr int F_ = 3584;

constexpr int R_XA = 0, R_X1 = 256, R_H2 = 512, R_Y = 1536, R_H = 16384 + 8, R_HP = S_ + 8, R_END = R_H + 2 * R_HP;
__device__ __align__(1024) bf16 g_act[(size_t)(R_END + 1024) * D_];
__device__ __align__(16) float g_cpart[16 * (F_ + D_)];
__device__ __align__(128) float2 g_stats[3 * S_ * 8];

__device__ __forceinline__ float bfr(float x) { return __bfloat162float(__float2bfloat16_rn(x)); }
__device__ __forceinline__ uint32_t pack2(float lo, float hi) {
    __nv_bfloat162 v = __floats2bfloat162_rn(lo, hi);
    return *reinterpret_cast<uint32_t*>(&v);
}
__device__ __forceinline__ float lo2f(uint32_t v) { return __uint_as_float(v << 16); }
__device__ __forceinline__ float hi2f(uint32_t v) { return __uint_as_float(v & 0xffff0000u); }
__device__ __forceinline__ float frcp(float x) { float r; asm("rcp.approx.f32 %0, %1;" : "=f"(r) : "f"(x)); return r; }
__device__ __forceinline__ float fsqrt(float x) { float r; asm("sqrt.approx.f32 %0, %1;" : "=f"(r) : "f"(x)); return r; }
__device__ __forceinline__ uint32_t smem_u32(const void* p) { return (uint32_t)__cvta_generic_to_shared(p); }

__device__ __forceinline__ void mbar_init(uint32_t bar, uint32_t cnt) {
    asm volatile("mbarrier.init.shared::cta.b64 [%0], %1;" ::"r"(bar), "r"(cnt));
}
__device__ __forceinline__ void mbar_expect_tx(uint32_t bar, uint32_t bytes) {
    asm volatile("mbarrier.arrive.expect_tx.shared::cta.b64 _, [%0], %1;" ::"r"(bar), "r"(bytes) : "memory");
}
__device__ __forceinline__ void mbar_arrive(uint32_t bar) {
    asm volatile("mbarrier.arrive.shared::cta.b64 _, [%0];" ::"r"(bar) : "memory");
}
__device__ __forceinline__ void mbar_wait(uint32_t bar, uint32_t parity) {
    asm volatile(
        "{\n.reg .pred p;\n.reg .u32 n;\n"
        "mbarrier.try_wait.parity.shared::cta.b64 p, [%0], %1;\n"
        "@p bra LD;\n"
        "mov.u32 n, 0;\n"
        "LW:\n"
        "mbarrier.try_wait.parity.shared::cta.b64 p, [%0], %1;\n"
        "@p bra LD;\n"
        "add.u32 n, n, 1;\n"
        "setp.lt.u32 p, n, 0x400000;\n"
        "@p bra LW;\n"
        "LD:\n}\n"
        ::"r"(bar), "r"(parity) : "memory");
}
__device__ __forceinline__ void tma_load_2d(uint32_t dst, const CUtensorMap* tm, uint32_t bar, int c0, int c1) {
    asm volatile(
        "cp.async.bulk.tensor.2d.shared::cluster.global.mbarrier::complete_tx::bytes [%0], [%1, {%3, %4}], [%2];"
        ::"r"(dst), "l"((uint64_t)tm), "r"(bar), "r"(c0), "r"(c1) : "memory");
}
__device__ __forceinline__ void tma_load_2d_mc(uint32_t dst, const CUtensorMap* tm, uint32_t bar, int c0, int c1) {
    asm volatile(
        "cp.async.bulk.tensor.2d.shared::cluster.global.mbarrier::complete_tx::bytes.multicast::cluster [%0], [%1, {%3, %4}], [%2], %5;"
        ::"r"(dst), "l"((uint64_t)tm), "r"(bar), "r"(c0), "r"(c1), "h"((uint16_t)3) : "memory");
}
__device__ __forceinline__ void tma_prefetch_2d(const CUtensorMap* tm, int c0, int c1) {
    asm volatile("cp.async.bulk.prefetch.tensor.2d.L2.global.tile [%0, {%1, %2}];" ::"l"((uint64_t)tm), "r"(c0), "r"(c1) : "memory");
}
__device__ __forceinline__ void tma_store_2d(const CUtensorMap* tm, uint32_t src, int c0, int c1) {
    asm volatile("cp.async.bulk.tensor.2d.global.shared::cta.bulk_group [%0, {%2, %3}], [%1];"
                 ::"l"((uint64_t)tm), "r"(src), "r"(c0), "r"(c1) : "memory");
}
__device__ __forceinline__ void wgmma_fence() { asm volatile("wgmma.fence.sync.aligned;" ::: "memory"); }
__device__ __forceinline__ void wgmma_commit() { asm volatile("wgmma.commit_group.sync.aligned;" ::: "memory"); }
template <int N> __device__ __forceinline__ void wgmma_wait() { asm volatile("wgmma.wait_group.sync.aligned %0;" ::"n"(N) : "memory"); }
__device__ __forceinline__ void named_bar_arrive(int id, int n) { asm volatile("bar.arrive %0, %1;" ::"r"(id), "r"(n) : "memory"); }
__device__ __forceinline__ void named_bar_sync(int id, int n) { asm volatile("bar.sync %0, %1;" ::"r"(id), "r"(n) : "memory"); }

__device__ __forceinline__ uint32_t desc_a(uint32_t addr) { return ((addr & 0x3FFFF) >> 4) | (1u << 16); }
__device__ __forceinline__ uint32_t desc_b(uint32_t addr) { return ((addr & 0x3FFFF) >> 4) | (512u << 16); }

template <int ACC> __device__ __forceinline__ void wgmma_m64n192k16(float (&d)[96], uint32_t descA, uint32_t descB) {
  asm volatile("{\n.reg .pred p;\n.reg .b64 da, db;\nsetp.ne.b32 p, %99, 0;\nmov.b64 da, {%96, %98};\nmov.b64 db, {%97, %98};\n"
    "wgmma.mma_async.sync.aligned.m64n192k16.f32.bf16.bf16 "
    "{%0, %1, %2, %3, %4, %5, %6, %7, %8, %9, %10, %11, %12, %13, %14, %15, %16, %17, %18, %19, %20, %21, %22, %23, %24, %25, %26, %27, %28, %29, %30, %31, %32, %33, %34, %35, %36, %37, %38, %39, %40, %41, %42, %43, %44, %45, %46, %47, %48, %49, %50, %51, %52, %53, %54, %55, %56, %57, %58, %59, %60, %61, %62, %63, %64, %65, %66, %67, %68, %69, %70, %71, %72, %73, %74, %75, %76, %77, %78, %79, %80, %81, %82, %83, %84, %85, %86, %87, %88, %89, %90, %91, %92, %93, %94, %95}, "
    "da, db, p, 1, 1, 0, 1;\n}\n"
    : "+f"(d[0]), "+f"(d[1]), "+f"(d[2]), "+f"(d[3]), "+f"(d[4]), "+f"(d[5]), "+f"(d[6]), "+f"(d[7]), "+f"(d[8]), "+f"(d[9]), "+f"(d[10]), "+f"(d[11]), "+f"(d[12]), "+f"(d[13]), "+f"(d[14]), "+f"(d[15]), "+f"(d[16]), "+f"(d[17]), "+f"(d[18]), "+f"(d[19]), "+f"(d[20]), "+f"(d[21]), "+f"(d[22]), "+f"(d[23]), "+f"(d[24]), "+f"(d[25]), "+f"(d[26]), "+f"(d[27]), "+f"(d[28]), "+f"(d[29]), "+f"(d[30]), "+f"(d[31]), "+f"(d[32]), "+f"(d[33]), "+f"(d[34]), "+f"(d[35]), "+f"(d[36]), "+f"(d[37]), "+f"(d[38]), "+f"(d[39]), "+f"(d[40]), "+f"(d[41]), "+f"(d[42]), "+f"(d[43]), "+f"(d[44]), "+f"(d[45]), "+f"(d[46]), "+f"(d[47]), "+f"(d[48]), "+f"(d[49]), "+f"(d[50]), "+f"(d[51]), "+f"(d[52]), "+f"(d[53]), "+f"(d[54]), "+f"(d[55]), "+f"(d[56]), "+f"(d[57]), "+f"(d[58]), "+f"(d[59]), "+f"(d[60]), "+f"(d[61]), "+f"(d[62]), "+f"(d[63]), "+f"(d[64]), "+f"(d[65]), "+f"(d[66]), "+f"(d[67]), "+f"(d[68]), "+f"(d[69]), "+f"(d[70]), "+f"(d[71]), "+f"(d[72]), "+f"(d[73]), "+f"(d[74]), "+f"(d[75]), "+f"(d[76]), "+f"(d[77]), "+f"(d[78]), "+f"(d[79]), "+f"(d[80]), "+f"(d[81]), "+f"(d[82]), "+f"(d[83]), "+f"(d[84]), "+f"(d[85]), "+f"(d[86]), "+f"(d[87]), "+f"(d[88]), "+f"(d[89]), "+f"(d[90]), "+f"(d[91]), "+f"(d[92]), "+f"(d[93]), "+f"(d[94]), "+f"(d[95])
    : "r"(descA), "r"(descB), "r"(0x40000040u), "n"(ACC));
}

template <int ACC> __device__ __forceinline__ void wgmma_m64n256k16(float (&d)[128], uint32_t descA, uint32_t descB) {
  asm volatile("{\n.reg .pred p;\n.reg .b64 da, db;\nsetp.ne.b32 p, %131, 0;\nmov.b64 da, {%128, %130};\nmov.b64 db, {%129, %130};\n"
    "wgmma.mma_async.sync.aligned.m64n256k16.f32.bf16.bf16 "
    "{%0, %1, %2, %3, %4, %5, %6, %7, %8, %9, %10, %11, %12, %13, %14, %15, %16, %17, %18, %19, %20, %21, %22, %23, %24, %25, %26, %27, %28, %29, %30, %31, %32, %33, %34, %35, %36, %37, %38, %39, %40, %41, %42, %43, %44, %45, %46, %47, %48, %49, %50, %51, %52, %53, %54, %55, %56, %57, %58, %59, %60, %61, %62, %63, %64, %65, %66, %67, %68, %69, %70, %71, %72, %73, %74, %75, %76, %77, %78, %79, %80, %81, %82, %83, %84, %85, %86, %87, %88, %89, %90, %91, %92, %93, %94, %95, %96, %97, %98, %99, %100, %101, %102, %103, %104, %105, %106, %107, %108, %109, %110, %111, %112, %113, %114, %115, %116, %117, %118, %119, %120, %121, %122, %123, %124, %125, %126, %127}, "
    "da, db, p, 1, 1, 0, 1;\n}\n"
    : "+f"(d[0]), "+f"(d[1]), "+f"(d[2]), "+f"(d[3]), "+f"(d[4]), "+f"(d[5]), "+f"(d[6]), "+f"(d[7]), "+f"(d[8]), "+f"(d[9]), "+f"(d[10]), "+f"(d[11]), "+f"(d[12]), "+f"(d[13]), "+f"(d[14]), "+f"(d[15]), "+f"(d[16]), "+f"(d[17]), "+f"(d[18]), "+f"(d[19]), "+f"(d[20]), "+f"(d[21]), "+f"(d[22]), "+f"(d[23]), "+f"(d[24]), "+f"(d[25]), "+f"(d[26]), "+f"(d[27]), "+f"(d[28]), "+f"(d[29]), "+f"(d[30]), "+f"(d[31]), "+f"(d[32]), "+f"(d[33]), "+f"(d[34]), "+f"(d[35]), "+f"(d[36]), "+f"(d[37]), "+f"(d[38]), "+f"(d[39]), "+f"(d[40]), "+f"(d[41]), "+f"(d[42]), "+f"(d[43]), "+f"(d[44]), "+f"(d[45]), "+f"(d[46]), "+f"(d[47]), "+f"(d[48]), "+f"(d[49]), "+f"(d[50]), "+f"(d[51]), "+f"(d[52]), "+f"(d[53]), "+f"(d[54]), "+f"(d[55]), "+f"(d[56]), "+f"(d[57]), "+f"(d[58]), "+f"(d[59]), "+f"(d[60]), "+f"(d[61]), "+f"(d[62]), "+f"(d[63]), "+f"(d[64]), "+f"(d[65]), "+f"(d[66]), "+f"(d[67]), "+f"(d[68]), "+f"(d[69]), "+f"(d[70]), "+f"(d[71]), "+f"(d[72]), "+f"(d[73]), "+f"(d[74]), "+f"(d[75]), "+f"(d[76]), "+f"(d[77]), "+f"(d[78]), "+f"(d[79]), "+f"(d[80]), "+f"(d[81]), "+f"(d[82]), "+f"(d[83]), "+f"(d[84]), "+f"(d[85]), "+f"(d[86]), "+f"(d[87]), "+f"(d[88]), "+f"(d[89]), "+f"(d[90]), "+f"(d[91]), "+f"(d[92]), "+f"(d[93]), "+f"(d[94]), "+f"(d[95]), "+f"(d[96]), "+f"(d[97]), "+f"(d[98]), "+f"(d[99]), "+f"(d[100]), "+f"(d[101]), "+f"(d[102]), "+f"(d[103]), "+f"(d[104]), "+f"(d[105]), "+f"(d[106]), "+f"(d[107]), "+f"(d[108]), "+f"(d[109]), "+f"(d[110]), "+f"(d[111]), "+f"(d[112]), "+f"(d[113]), "+f"(d[114]), "+f"(d[115]), "+f"(d[116]), "+f"(d[117]), "+f"(d[118]), "+f"(d[119]), "+f"(d[120]), "+f"(d[121]), "+f"(d[122]), "+f"(d[123]), "+f"(d[124]), "+f"(d[125]), "+f"(d[126]), "+f"(d[127])
    : "r"(descA), "r"(descB), "r"(0x40000040u), "n"(ACC));
}

template <int ACC> __device__ __forceinline__ void wgmma_m64n128k16(float (&d)[64], uint32_t descA, uint32_t descB) {
  asm volatile("{\n.reg .pred p;\n.reg .b64 da, db;\nsetp.ne.b32 p, %67, 0;\nmov.b64 da, {%64, %66};\nmov.b64 db, {%65, %66};\n"
    "wgmma.mma_async.sync.aligned.m64n128k16.f32.bf16.bf16 "
    "{%0, %1, %2, %3, %4, %5, %6, %7, %8, %9, %10, %11, %12, %13, %14, %15, %16, %17, %18, %19, %20, %21, %22, %23, %24, %25, %26, %27, %28, %29, %30, %31, %32, %33, %34, %35, %36, %37, %38, %39, %40, %41, %42, %43, %44, %45, %46, %47, %48, %49, %50, %51, %52, %53, %54, %55, %56, %57, %58, %59, %60, %61, %62, %63}, "
    "da, db, p, 1, 1, 0, 1;\n}\n"
    : "+f"(d[0]), "+f"(d[1]), "+f"(d[2]), "+f"(d[3]), "+f"(d[4]), "+f"(d[5]), "+f"(d[6]), "+f"(d[7]), "+f"(d[8]), "+f"(d[9]), "+f"(d[10]), "+f"(d[11]), "+f"(d[12]), "+f"(d[13]), "+f"(d[14]), "+f"(d[15]), "+f"(d[16]), "+f"(d[17]), "+f"(d[18]), "+f"(d[19]), "+f"(d[20]), "+f"(d[21]), "+f"(d[22]), "+f"(d[23]), "+f"(d[24]), "+f"(d[25]), "+f"(d[26]), "+f"(d[27]), "+f"(d[28]), "+f"(d[29]), "+f"(d[30]), "+f"(d[31]), "+f"(d[32]), "+f"(d[33]), "+f"(d[34]), "+f"(d[35]), "+f"(d[36]), "+f"(d[37]), "+f"(d[38]), "+f"(d[39]), "+f"(d[40]), "+f"(d[41]), "+f"(d[42]), "+f"(d[43]), "+f"(d[44]), "+f"(d[45]), "+f"(d[46]), "+f"(d[47]), "+f"(d[48]), "+f"(d[49]), "+f"(d[50]), "+f"(d[51]), "+f"(d[52]), "+f"(d[53]), "+f"(d[54]), "+f"(d[55]), "+f"(d[56]), "+f"(d[57]), "+f"(d[58]), "+f"(d[59]), "+f"(d[60]), "+f"(d[61]), "+f"(d[62]), "+f"(d[63])
    : "r"(descA), "r"(descB), "r"(0x40000040u), "n"(ACC));
}

template <int BN> struct WG;
template <> struct WG<128> { template <int ACC> static __device__ __forceinline__ void mma(float (&d)[64], uint32_t a, uint32_t b) { wgmma_m64n128k16<ACC>(d, a, b); } };
template <> struct WG<256> { template <int ACC> static __device__ __forceinline__ void mma(float (&d)[128], uint32_t a, uint32_t b) { wgmma_m64n256k16<ACC>(d, a, b); } };
template <> struct WG<192> { template <int ACC> static __device__ __forceinline__ void mma(float (&d)[96], uint32_t a, uint32_t b) { wgmma_m64n192k16<ACC>(d, a, b); } };

#define DBG_T(i)
__device__ __forceinline__ void fence_async_smem() { asm volatile("fence.proxy.async.shared::cta;" ::: "memory"); }
__device__ __forceinline__ void prefetch_tmap(const CUtensorMap* tm) { asm volatile("prefetch.tensormap [%0];" ::"l"((uint64_t)tm) : "memory"); }
__device__ __forceinline__ uint32_t mapa_u32(uint32_t addr, uint32_t cta) {
    uint32_t r;
    asm volatile("mapa.shared::cluster.u32 %0, %1, %2;" : "=r"(r) : "r"(addr), "r"(cta));
    return r;
}
__device__ __forceinline__ void mbar_arrive_cluster(uint32_t cluster_addr) {
    asm volatile("mbarrier.arrive.shared::cluster.b64 _, [%0];" ::"r"(cluster_addr) : "memory");
}
__device__ __forceinline__ bool elect_one() {
    uint32_t p;
    asm volatile("{\n.reg .pred P;\nelect.sync _|P, 0xffffffff;\nselp.u32 %0, 1, 0, P;\n}\n" : "=r"(p));
    return p != 0;
}
__device__ __forceinline__ void cluster_arrive_relaxed() { asm volatile("barrier.cluster.arrive.relaxed.aligned;" ::: "memory"); }
__device__ __forceinline__ void cluster_wait() { asm volatile("barrier.cluster.wait.acquire.aligned;" ::: "memory"); }

__device__ __forceinline__ uint32_t bsub2(uint32_t a, uint32_t b) {
    __nv_bfloat162 r = __hsub2(*reinterpret_cast<__nv_bfloat162*>(&a), *reinterpret_cast<__nv_bfloat162*>(&b));
    return *reinterpret_cast<uint32_t*>(&r);
}
__device__ __forceinline__ uint32_t bmul2(uint32_t a, uint32_t b) {
    __nv_bfloat162 r = __hmul2(*reinterpret_cast<__nv_bfloat162*>(&a), *reinterpret_cast<__nv_bfloat162*>(&b));
    return *reinterpret_cast<uint32_t*>(&r);
}
__device__ __forceinline__ uint32_t badd2(uint32_t a, uint32_t b) {
    __nv_bfloat162 r = __hadd2(*reinterpret_cast<__nv_bfloat162*>(&a), *reinterpret_cast<__nv_bfloat162*>(&b));
    return *reinterpret_cast<uint32_t*>(&r);
}
constexpr int BM = 128, BK = 64;
constexpr int R5_STAGE = 32768, R5_N = 5;
constexpr int R4_STAGE = 49152, R4_N = 4;
constexpr int R4B_STAGE = 40960;
constexpr int OFF_STG5 = 0, OFF_R = 32768;
constexpr int OFF_EPI = 196608;
constexpr int OFF_BAR = OFF_EPI + 32768;
constexpr int OFF_RS = OFF_BAR + 256;
constexpr int OFF_CS = OFF_RS + 1024;
constexpr int MEGA_SMEM = OFF_CS + 1792;
enum { FL_XA = 0, FL_H = 2, FL_X1 = 4, FL_H2 = 6, FL_CS = 10, FL_KINDS = 11 };
constexpr int FL_PITCH = 64;
constexpr int FL_WORDS = 2 * FL_KINDS * 16 * FL_PITCH;
__device__ unsigned int g_flag[FL_WORDS];
__device__ __align__(8) unsigned int g_ticket[18 * FL_PITCH];
constexpr int NCL = 66;
__device__ __forceinline__ unsigned int* flag_ptr(int layer, int kind, int i) { return g_flag + ((layer * FL_KINDS + kind) * 16 + i) * FL_PITCH; }

__device__ __forceinline__ void wait_flag(const unsigned int* p, unsigned int target) {
    long long t0 = clock64();
    while (true) {
        unsigned int v;
        asm volatile("ld.relaxed.gpu.global.u32 %0, [%1];" : "=r"(v) : "l"(p) : "memory");
        if ((int)(v - target) >= 0) break;
        if (clock64() - t0 > 2000000000LL) break;
    }
    asm volatile("fence.acquire.gpu;" ::: "memory");
}
__device__ __forceinline__ void fence_proxy_async() {
    asm volatile("fence.proxy.async.global;" ::: "memory");
    asm volatile("fence.proxy.async.shared::cta;" ::: "memory");
}
__device__ __forceinline__ void stsm4(uint32_t addr, uint32_t r0, uint32_t r1, uint32_t r2, uint32_t r3) {
    asm volatile("stmatrix.sync.aligned.m8n8.x4.shared.b16 [%0], {%1,%2,%3,%4};" ::"r"(addr), "r"(r0), "r"(r1), "r"(r2), "r"(r3));
}
__device__ __forceinline__ uint4 lds128(uint32_t a) {
    uint4 v;
    asm volatile("ld.shared.v4.b32 {%0,%1,%2,%3}, [%4];" : "=r"(v.x), "=r"(v.y), "=r"(v.z), "=r"(v.w) : "r"(a) : "memory");
    return v;
}
__device__ __forceinline__ void stg128(void* p, uint4 v) {
    asm volatile("st.global.v4.b32 [%0], {%1,%2,%3,%4};" ::"l"(p), "r"(v.x), "r"(v.y), "r"(v.z), "r"(v.w) : "memory");
}
__device__ __forceinline__ float gelu_tanh_h(float hx) {
    float z = hx * fmaf(hx * hx, 8.0f * 0.035677408136300125f, 2.0f * 0.7978845608028654f);
    float t;
    asm("tanh.approx.f32 %0, %1;" : "=f"(t) : "f"(z));
    return fmaf(hx, t, hx);
}
__device__ __forceinline__ uint32_t gelu2h(uint32_t hx) {
    uint32_t r;
    asm("{\n.reg .b32 z;\nmul.rn.bf16x2 z, %1, %1;\nfma.rn.bf16x2 z, z, %2, %3;\nmul.rn.bf16x2 z, z, %1;\ntanh.approx.bf16x2 z, z;\nfma.rn.bf16x2 %0, %1, z, %1;\n}"
        : "=r"(r) : "r"(hx), "r"(0x3e923e92u), "r"(0x3fcc3fccu));
    return r;
}
__device__ __forceinline__ uint4 gelu8h(uint4 v) { return make_uint4(gelu2h(v.x), gelu2h(v.y), gelu2h(v.z), gelu2h(v.w)); }

__device__ __forceinline__ void row_stats(const float2* p, uint32_t tag, float& mean, float& var) {
    float2 v[8];
#pragma unroll 1
    for (int n = 0; n < (1 << 20); n++) {
#pragma unroll
        for (int i = 0; i < 8; i++)
            asm volatile("{\n.reg .b64 t;\nld.relaxed.gpu.global.b64 t, [%2];\nmov.b64 {%0, %1}, t;\n}" : "=f"(v[i].x), "=f"(v[i].y) : "l"(p + 128 * i) : "memory");
        uint32_t old = 0;
#pragma unroll
        for (int i = 0; i < 8; i++) old |= __float_as_uint(v[i].y) ^ tag;
        if ((int)old >= 0) break;
    }
    mean = (((v[0].x + v[1].x) + (v[2].x + v[3].x)) + ((v[4].x + v[5].x) + (v[6].x + v[7].x))) * 0.125f;
    float m2 = 0.f, d2 = 0.f;
#pragma unroll
    for (int i = 0; i < 8; i++) { m2 += fabsf(v[i].y); d2 = fmaf(v[i].x - mean, v[i].x - mean, d2); }
    var = fmaf(128.0f, d2, m2) * (1.0f / D_);
}
struct RingState { uint32_t st, ph; };

#define DT(i)
#define DP(i)
#define GT(i)
#define TM(i)

template <int BN, int NST, int ACC = 1>
__device__ __forceinline__ void kblock(float (&acc)[BN / 2], uint32_t da, uint32_t db, uint32_t bfull, RingState& rs) {
    mbar_wait(bfull + 8 * rs.st, rs.ph);
    wgmma_fence();
    WG<BN>::template mma<ACC>(acc, da, db);
#pragma unroll
    for (int k = 1; k < 4; k++) WG<BN>::template mma<1>(acc, da + k * 2, db + k * 128);
    wgmma_commit();
    if (++rs.st == NST) { rs.st = 0; rs.ph ^= 1; }
}
template <int BN, int NST, int STAGE, class F>
__device__ __forceinline__ void mainloop(float (&acc)[BN / 2], int KB, uint32_t da0, uint32_t db0, uint32_t bfull, uint32_t rel, bool rel_on,
                                         RingState& rs, int dbg, F pre) {
    uint32_t prev = rs.st ? rs.st - 1 : NST - 1;
#pragma unroll 1
    for (int kk = 0; kk < KB; kk++) {
        const uint32_t cur = rs.st;
        kblock<BN, NST>(acc, da0 + cur * (STAGE / 16), db0 + cur * (STAGE / 16), bfull, rs);
        wgmma_wait<1>();
        if (rel_on) mbar_arrive_cluster(rel + 8 * prev);
        prev = cur;
    }
    pre();
    wgmma_wait<0>();
#pragma unroll
    for (int i = 0; i < BN / 2; i++) asm volatile("" : "+f"(acc[i])::"memory");
    if (rel_on) mbar_arrive_cluster(rel + 8 * prev);
}
__device__ __forceinline__ void hmma(float (&c)[4], uint32_t a0, uint32_t a1, uint32_t a2, uint32_t a3, uint32_t b0, uint32_t b1, bool first) {
    if (first) asm("{\n.reg .f32 z;\nmov.f32 z, 0f00000000;\nmma.sync.aligned.m16n8k16.row.col.f32.bf16.bf16.f32 {%0,%1,%2,%3}, {%4,%5,%6,%7}, {%8,%9}, {z,z,z,z};\n}"
        : "=f"(c[0]), "=f"(c[1]), "=f"(c[2]), "=f"(c[3]) : "r"(a0), "r"(a1), "r"(a2), "r"(a3), "r"(b0), "r"(b1));
    else
    asm("mma.sync.aligned.m16n8k16.row.col.f32.bf16.bf16.f32 {%0,%1,%2,%3}, {%4,%5,%6,%7}, {%8,%9}, {%0,%1,%2,%3};"
        : "+f"(c[0]), "+f"(c[1]), "+f"(c[2]), "+f"(c[3]) : "r"(a0), "r"(a1), "r"(a2), "r"(a3), "r"(b0), "r"(b1));
}
__device__ __forceinline__ void hmma8(float (&c)[4], uint32_t a0, uint32_t a1, uint32_t b0, bool first) {
    if (first) asm("{\n.reg .f32 z;\nmov.f32 z, 0f00000000;\nmma.sync.aligned.m16n8k8.row.col.f32.bf16.bf16.f32 {%0,%1,%2,%3}, {%4,%5}, {%6}, {z,z,z,z};\n}"
        : "=f"(c[0]), "=f"(c[1]), "=f"(c[2]), "=f"(c[3]) : "r"(a0), "r"(a1), "r"(b0));
    else
    asm("mma.sync.aligned.m16n8k8.row.col.f32.bf16.bf16.f32 {%0,%1,%2,%3}, {%4,%5}, {%6}, {%0,%1,%2,%3};"
        : "+f"(c[0]), "+f"(c[1]), "+f"(c[2]), "+f"(c[3]) : "r"(a0), "r"(a1), "r"(b0));
}
template <int N> __device__ __forceinline__ void zero_acc(float (&acc)[N]) {
#pragma unroll
    for (int i = 0; i < N; i++) acc[i] = 0.f;
}
__device__ __forceinline__ void ldsm4(uint32_t& r0, uint32_t& r1, uint32_t& r2, uint32_t& r3, uint32_t addr) {
    asm volatile("ldmatrix.sync.aligned.m8n8.x4.shared.b16 {%0,%1,%2,%3}, [%4];" : "=r"(r0), "=r"(r1), "=r"(r2), "=r"(r3) : "r"(addr));
}

__device__ __forceinline__ void ldsm4t(uint32_t& r0, uint32_t& r1, uint32_t& r2, uint32_t& r3, uint32_t addr) {
    asm volatile("ldmatrix.sync.aligned.m8n8.x4.trans.shared.b16 {%0,%1,%2,%3}, [%4];" : "=r"(r0), "=r"(r1), "=r"(r2), "=r"(r3) : "r"(addr));
}

#define DBG_S(i)
#define DBG_OUT(r, o)
#define DBG_F(i)
#define DBG_W(i)
constexpr int CV_CH = 8;
constexpr int CV_SL = 16384;
constexpr int CV_QG = 128 * 8 + 16;
constexpr int CV_HPL = 2048 + 192;
constexpr int CV_0 = 32768, CV_H = 9 * CV_SL, CV_BAR = OFF_RS - CV_0;

template <int K> __device__ __forceinline__ void cv_mma(float (&d)[64], const uint32_t (&a)[4], uint32_t db, int acc);
template <> __device__ __forceinline__ void cv_mma<0>(float (&d)[64], const uint32_t (&a)[4], uint32_t db, int acc) {
    asm volatile("{\n.reg .pred p;\n.reg .b64 b;\nsetp.ne.b32 p, %70, 0;\nmov.b64 b, {%68, %69};\n"
        "wgmma.mma_async.sync.aligned.m64n128k16.f32.bf16.bf16 {%0,%1,%2,%3,%4,%5,%6,%7,%8,%9,%10,%11,%12,%13,%14,%15,%16,%17,%18,%19,%20,%21,%22,%23,%24,%25,%26,%27,%28,%29,%30,%31,%32,%33,%34,%35,%36,%37,%38,%39,%40,%41,%42,%43,%44,%45,%46,%47,%48,%49,%50,%51,%52,%53,%54,%55,%56,%57,%58,%59,%60,%61,%62,%63}, {%64,%65,%66,%67}, b, p, 1, 1, 0;\n}\n"
        : "+f"(d[0]), "+f"(d[1]), "+f"(d[2]), "+f"(d[3]), "+f"(d[4]), "+f"(d[5]), "+f"(d[6]), "+f"(d[7]), "+f"(d[8]), "+f"(d[9]), "+f"(d[10]), "+f"(d[11]), "+f"(d[12]), "+f"(d[13]), "+f"(d[14]), "+f"(d[15]), "+f"(d[16]), "+f"(d[17]), "+f"(d[18]), "+f"(d[19]), "+f"(d[20]), "+f"(d[21]), "+f"(d[22]), "+f"(d[23]), "+f"(d[24]), "+f"(d[25]), "+f"(d[26]), "+f"(d[27]), "+f"(d[28]), "+f"(d[29]), "+f"(d[30]), "+f"(d[31]), "+f"(d[32]), "+f"(d[33]), "+f"(d[34]), "+f"(d[35]), "+f"(d[36]), "+f"(d[37]), "+f"(d[38]), "+f"(d[39]), "+f"(d[40]), "+f"(d[41]), "+f"(d[42]), "+f"(d[43]), "+f"(d[44]), "+f"(d[45]), "+f"(d[46]), "+f"(d[47]), "+f"(d[48]), "+f"(d[49]), "+f"(d[50]), "+f"(d[51]), "+f"(d[52]), "+f"(d[53]), "+f"(d[54]), "+f"(d[55]), "+f"(d[56]), "+f"(d[57]), "+f"(d[58]), "+f"(d[59]), "+f"(d[60]), "+f"(d[61]), "+f"(d[62]), "+f"(d[63])
        : "r"(a[0]), "r"(a[1]), "r"(a[2]), "r"(a[3]), "r"(db), "r"(8u), "r"(acc));
}
template <> __device__ __forceinline__ void cv_mma<1>(float (&d)[64], const uint32_t (&a)[4], uint32_t db, int acc) {
    asm volatile("{\n.reg .pred p;\n.reg .b64 b;\nsetp.ne.b32 p, %62, 0;\nmov.b64 b, {%60, %61};\n"
        "wgmma.mma_async.sync.aligned.m64n112k16.f32.bf16.bf16 {%0,%1,%2,%3,%4,%5,%6,%7,%8,%9,%10,%11,%12,%13,%14,%15,%16,%17,%18,%19,%20,%21,%22,%23,%24,%25,%26,%27,%28,%29,%30,%31,%32,%33,%34,%35,%36,%37,%38,%39,%40,%41,%42,%43,%44,%45,%46,%47,%48,%49,%50,%51,%52,%53,%54,%55}, {%56,%57,%58,%59}, b, p, 1, 1, 0;\n}\n"
        : "+f"(d[0]), "+f"(d[1]), "+f"(d[2]), "+f"(d[3]), "+f"(d[4]), "+f"(d[5]), "+f"(d[6]), "+f"(d[7]), "+f"(d[8]), "+f"(d[9]), "+f"(d[10]), "+f"(d[11]), "+f"(d[12]), "+f"(d[13]), "+f"(d[14]), "+f"(d[15]), "+f"(d[16]), "+f"(d[17]), "+f"(d[18]), "+f"(d[19]), "+f"(d[20]), "+f"(d[21]), "+f"(d[22]), "+f"(d[23]), "+f"(d[24]), "+f"(d[25]), "+f"(d[26]), "+f"(d[27]), "+f"(d[28]), "+f"(d[29]), "+f"(d[30]), "+f"(d[31]), "+f"(d[32]), "+f"(d[33]), "+f"(d[34]), "+f"(d[35]), "+f"(d[36]), "+f"(d[37]), "+f"(d[38]), "+f"(d[39]), "+f"(d[40]), "+f"(d[41]), "+f"(d[42]), "+f"(d[43]), "+f"(d[44]), "+f"(d[45]), "+f"(d[46]), "+f"(d[47]), "+f"(d[48]), "+f"(d[49]), "+f"(d[50]), "+f"(d[51]), "+f"(d[52]), "+f"(d[53]), "+f"(d[54]), "+f"(d[55])
        : "r"(a[0]), "r"(a[1]), "r"(a[2]), "r"(a[3]), "r"(db), "r"(8u), "r"(acc));
}
template <> __device__ __forceinline__ void cv_mma<2>(float (&d)[64], const uint32_t (&a)[4], uint32_t db, int acc) {
    asm volatile("{\n.reg .pred p;\n.reg .b64 b;\nsetp.ne.b32 p, %54, 0;\nmov.b64 b, {%52, %53};\n"
        "wgmma.mma_async.sync.aligned.m64n96k16.f32.bf16.bf16 {%0,%1,%2,%3,%4,%5,%6,%7,%8,%9,%10,%11,%12,%13,%14,%15,%16,%17,%18,%19,%20,%21,%22,%23,%24,%25,%26,%27,%28,%29,%30,%31,%32,%33,%34,%35,%36,%37,%38,%39,%40,%41,%42,%43,%44,%45,%46,%47}, {%48,%49,%50,%51}, b, p, 1, 1, 0;\n}\n"
        : "+f"(d[0]), "+f"(d[1]), "+f"(d[2]), "+f"(d[3]), "+f"(d[4]), "+f"(d[5]), "+f"(d[6]), "+f"(d[7]), "+f"(d[8]), "+f"(d[9]), "+f"(d[10]), "+f"(d[11]), "+f"(d[12]), "+f"(d[13]), "+f"(d[14]), "+f"(d[15]), "+f"(d[16]), "+f"(d[17]), "+f"(d[18]), "+f"(d[19]), "+f"(d[20]), "+f"(d[21]), "+f"(d[22]), "+f"(d[23]), "+f"(d[24]), "+f"(d[25]), "+f"(d[26]), "+f"(d[27]), "+f"(d[28]), "+f"(d[29]), "+f"(d[30]), "+f"(d[31]), "+f"(d[32]), "+f"(d[33]), "+f"(d[34]), "+f"(d[35]), "+f"(d[36]), "+f"(d[37]), "+f"(d[38]), "+f"(d[39]), "+f"(d[40]), "+f"(d[41]), "+f"(d[42]), "+f"(d[43]), "+f"(d[44]), "+f"(d[45]), "+f"(d[46]), "+f"(d[47])
        : "r"(a[0]), "r"(a[1]), "r"(a[2]), "r"(a[3]), "r"(db), "r"(8u), "r"(acc));
}
template <> __device__ __forceinline__ void cv_mma<3>(float (&d)[64], const uint32_t (&a)[4], uint32_t db, int acc) {
    asm volatile("{\n.reg .pred p;\n.reg .b64 b;\nsetp.ne.b32 p, %46, 0;\nmov.b64 b, {%44, %45};\n"
        "wgmma.mma_async.sync.aligned.m64n80k16.f32.bf16.bf16 {%0,%1,%2,%3,%4,%5,%6,%7,%8,%9,%10,%11,%12,%13,%14,%15,%16,%17,%18,%19,%20,%21,%22,%23,%24,%25,%26,%27,%28,%29,%30,%31,%32,%33,%34,%35,%36,%37,%38,%39}, {%40,%41,%42,%43}, b, p, 1, 1, 0;\n}\n"
        : "+f"(d[0]), "+f"(d[1]), "+f"(d[2]), "+f"(d[3]), "+f"(d[4]), "+f"(d[5]), "+f"(d[6]), "+f"(d[7]), "+f"(d[8]), "+f"(d[9]), "+f"(d[10]), "+f"(d[11]), "+f"(d[12]), "+f"(d[13]), "+f"(d[14]), "+f"(d[15]), "+f"(d[16]), "+f"(d[17]), "+f"(d[18]), "+f"(d[19]), "+f"(d[20]), "+f"(d[21]), "+f"(d[22]), "+f"(d[23]), "+f"(d[24]), "+f"(d[25]), "+f"(d[26]), "+f"(d[27]), "+f"(d[28]), "+f"(d[29]), "+f"(d[30]), "+f"(d[31]), "+f"(d[32]), "+f"(d[33]), "+f"(d[34]), "+f"(d[35]), "+f"(d[36]), "+f"(d[37]), "+f"(d[38]), "+f"(d[39])
        : "r"(a[0]), "r"(a[1]), "r"(a[2]), "r"(a[3]), "r"(db), "r"(8u), "r"(acc));
}
template <> __device__ __forceinline__ void cv_mma<4>(float (&d)[64], const uint32_t (&a)[4], uint32_t db, int acc) {
    asm volatile("{\n.reg .pred p;\n.reg .b64 b;\nsetp.ne.b32 p, %38, 0;\nmov.b64 b, {%36, %37};\n"
        "wgmma.mma_async.sync.aligned.m64n64k16.f32.bf16.bf16 {%0,%1,%2,%3,%4,%5,%6,%7,%8,%9,%10,%11,%12,%13,%14,%15,%16,%17,%18,%19,%20,%21,%22,%23,%24,%25,%26,%27,%28,%29,%30,%31}, {%32,%33,%34,%35}, b, p, 1, 1, 0;\n}\n"
        : "+f"(d[0]), "+f"(d[1]), "+f"(d[2]), "+f"(d[3]), "+f"(d[4]), "+f"(d[5]), "+f"(d[6]), "+f"(d[7]), "+f"(d[8]), "+f"(d[9]), "+f"(d[10]), "+f"(d[11]), "+f"(d[12]), "+f"(d[13]), "+f"(d[14]), "+f"(d[15]), "+f"(d[16]), "+f"(d[17]), "+f"(d[18]), "+f"(d[19]), "+f"(d[20]), "+f"(d[21]), "+f"(d[22]), "+f"(d[23]), "+f"(d[24]), "+f"(d[25]), "+f"(d[26]), "+f"(d[27]), "+f"(d[28]), "+f"(d[29]), "+f"(d[30]), "+f"(d[31])
        : "r"(a[0]), "r"(a[1]), "r"(a[2]), "r"(a[3]), "r"(db), "r"(8u), "r"(acc));
}
template <> __device__ __forceinline__ void cv_mma<5>(float (&d)[64], const uint32_t (&a)[4], uint32_t db, int acc) {
    asm volatile("{\n.reg .pred p;\n.reg .b64 b;\nsetp.ne.b32 p, %30, 0;\nmov.b64 b, {%28, %29};\n"
        "wgmma.mma_async.sync.aligned.m64n48k16.f32.bf16.bf16 {%0,%1,%2,%3,%4,%5,%6,%7,%8,%9,%10,%11,%12,%13,%14,%15,%16,%17,%18,%19,%20,%21,%22,%23}, {%24,%25,%26,%27}, b, p, 1, 1, 0;\n}\n"
        : "+f"(d[0]), "+f"(d[1]), "+f"(d[2]), "+f"(d[3]), "+f"(d[4]), "+f"(d[5]), "+f"(d[6]), "+f"(d[7]), "+f"(d[8]), "+f"(d[9]), "+f"(d[10]), "+f"(d[11]), "+f"(d[12]), "+f"(d[13]), "+f"(d[14]), "+f"(d[15]), "+f"(d[16]), "+f"(d[17]), "+f"(d[18]), "+f"(d[19]), "+f"(d[20]), "+f"(d[21]), "+f"(d[22]), "+f"(d[23])
        : "r"(a[0]), "r"(a[1]), "r"(a[2]), "r"(a[3]), "r"(db), "r"(8u), "r"(acc));
}
template <> __device__ __forceinline__ void cv_mma<6>(float (&d)[64], const uint32_t (&a)[4], uint32_t db, int acc) {
    asm volatile("{\n.reg .pred p;\n.reg .b64 b;\nsetp.ne.b32 p, %22, 0;\nmov.b64 b, {%20, %21};\n"
        "wgmma.mma_async.sync.aligned.m64n32k16.f32.bf16.bf16 {%0,%1,%2,%3,%4,%5,%6,%7,%8,%9,%10,%11,%12,%13,%14,%15}, {%16,%17,%18,%19}, b, p, 1, 1, 0;\n}\n"
        : "+f"(d[0]), "+f"(d[1]), "+f"(d[2]), "+f"(d[3]), "+f"(d[4]), "+f"(d[5]), "+f"(d[6]), "+f"(d[7]), "+f"(d[8]), "+f"(d[9]), "+f"(d[10]), "+f"(d[11]), "+f"(d[12]), "+f"(d[13]), "+f"(d[14]), "+f"(d[15])
        : "r"(a[0]), "r"(a[1]), "r"(a[2]), "r"(a[3]), "r"(db), "r"(8u), "r"(acc));
}
template <> __device__ __forceinline__ void cv_mma<7>(float (&d)[64], const uint32_t (&a)[4], uint32_t db, int acc) {
    asm volatile("{\n.reg .pred p;\n.reg .b64 b;\nsetp.ne.b32 p, %14, 0;\nmov.b64 b, {%12, %13};\n"
        "wgmma.mma_async.sync.aligned.m64n16k16.f32.bf16.bf16 {%0,%1,%2,%3,%4,%5,%6,%7}, {%8,%9,%10,%11}, b, p, 1, 1, 0;\n}\n"
        : "+f"(d[0]), "+f"(d[1]), "+f"(d[2]), "+f"(d[3]), "+f"(d[4]), "+f"(d[5]), "+f"(d[6]), "+f"(d[7])
        : "r"(a[0]), "r"(a[1]), "r"(a[2]), "r"(a[3]), "r"(db), "r"(8u), "r"(acc));
}
__device__ __forceinline__ void stsm4t(uint32_t addr, uint32_t r0, uint32_t r1, uint32_t r2, uint32_t r3) {
    asm volatile("stmatrix.sync.aligned.m8n8.x4.trans.shared.b16 [%0], {%1,%2,%3,%4};" ::"r"(addr), "r"(r0), "r"(r1), "r"(r2), "r"(r3) : "memory");
}
__device__ __forceinline__ void cp16(uint32_t dst, const void* src, int n = 16) {
    asm volatile("cp.async.cg.shared.global.L2::128B [%0], [%1], 16, %2;" ::"r"(dst), "l"(src), "r"(n) : "memory");
}
__device__ __forceinline__ void cp_arrive(uint32_t bar) { asm volatile("cp.async.mbarrier.arrive.noinc.shared::cta.b64 [%0];" ::"r"(bar) : "memory"); }
__device__ __forceinline__ void lds64(uint32_t& x, uint32_t& y, uint32_t a) { asm volatile("ld.shared.v2.b32 {%0,%1}, [%2];" : "=r"(x), "=r"(y) : "r"(a) : "memory"); }
__device__ __forceinline__ void sts128(uint32_t a, uint32_t x, uint32_t y, uint32_t z, uint32_t w) {
    asm volatile("st.shared.v4.b32 [%0], {%1,%2,%3,%4};" ::"r"(a), "r"(x), "r"(y), "r"(z), "r"(w) : "memory");
}
__device__ __forceinline__ uint32_t bfma2(uint32_t a, uint32_t b, uint32_t c) {
    uint32_t r;
    asm("fma.rn.bf16x2 %0, %1, %2, %3;" : "=r"(r) : "r"(a), "r"(b), "r"(c));
    return r;
}
#define CV_NS 4
#define CV_W 1
constexpr int CV_GC = 8 / CV_NS, CV_NA = (CV_W + 2) * CV_NS;
struct CvAddr { uint32_t pa[2], p0[4], db, rdy, xw, xr, bar; bool wrap, neg[2]; };
template <int G> __device__ __forceinline__ void cv_load(uint32_t (&a)[CV_NA][4], const CvAddr& p) {
    if constexpr (G % CV_GC == 0) mbar_wait(p.rdy + 8 * (G / CV_GC), 0);
#pragma unroll
    for (int i = G * CV_NS; i < (G + 1) * CV_NS; i++) {
        const int of = (i / 2 % 2) * CV_QG + (i / 8) * CV_SL + 256 * (i % 2 + (i / 2 & 2));
        if ((i & 5) == 0) {
#pragma unroll
            for (int e = 0; e < 4; e++) asm volatile("ld.shared.b32 %0, [%1];" : "=r"(a[i % CV_NA][e]) : "r"(p.p0[e] + of) : "memory");
            if (i < 8) { if (p.neg[0]) a[i % CV_NA][0] = 0; if (p.neg[1]) a[i % CV_NA][2] = 0; }
        } else {
            lds64(a[i % CV_NA][0], a[i % CV_NA][1], p.pa[0] + of - 256);
            lds64(a[i % CV_NA][2], a[i % CV_NA][3], p.pa[1] + of - 256);
        }
    }
}
__device__ __forceinline__ float vadd(float a, float b) {
    float r;
    asm volatile("add.f32 %0, %1, %2;" : "=f"(r) : "f"(a), "f"(b));
    return r;
}
template <int K> __device__ __forceinline__ uint32_t cv_tail(float (&d)[64], bool wrap) {
    float* z = d + 56 - 8 * K;
    z[4] = vadd(z[4], K > 0 ? z[10] : 0.f);
    if constexpr (K > 0) z[5] = vadd(z[5], z[11]);
    z[0] = vadd(z[0], z[6]);
    z[1] = vadd(z[1], z[7]);
    return pack2(wrap ? (K > 0 ? z[8] : 0.f) : z[4], wrap ? z[4] : z[0]);
}
template <int K> __device__ __forceinline__ uint32_t cv_fin(const float (&d)[64], uint32_t x) { return pack2(d[61 - 8 * K] + lo2f(x), d[57 - 8 * K] + hi2f(x)); }
template <int G>
__device__ __forceinline__ void cv_steps(float (&d)[2][64], uint32_t (&a)[CV_NA][4], uint32_t (&tv)[2][8], const CvAddr& p) {
    constexpr int K = G / CV_GC, GN = 8 * CV_GC;
    constexpr int T = G - CV_W - CV_GC, F = T - 1, TK = T / CV_GC, FK = F / CV_GC;
    if constexpr (G == 0) cv_load<0>(a, p);
    if constexpr (G < GN) {
        wgmma_fence();
#pragma unroll
        for (int i = G * CV_NS; i < (G + 1) * CV_NS; i++)
            cv_mma<K>(d[i / 2 % 2], a[i % CV_NA], p.db + (i / 2 % 2) * (CV_HPL / 8) + 16 * K + 2 * (i % 2 + (i / 2 & 2)), i & ~2 ? 1 : p.bar >> 8);
        wgmma_commit();
    }
    if constexpr (G < GN - 1) cv_load<G + 1>(a, p);
    if constexpr (T >= 0 && T % CV_GC == 0) {
        tv[0][TK] = cv_tail<TK>(d[0], p.wrap);
        tv[1][TK] = cv_tail<TK>(d[1], p.wrap);
        if constexpr (TK & 1) sts128(p.xw + TK / 2 * 512, tv[0][TK - 1], tv[0][TK], tv[1][TK - 1], tv[1][TK]);
    }
    if constexpr (F >= 0 && F % (2 * CV_GC) == CV_GC) {
        const uint4 x = lds128(p.xr + FK / 2 * 512);
        tv[0][FK - 1] = cv_fin<FK - 1>(d[0], x.x); tv[0][FK] = cv_fin<FK>(d[0], x.y);
        tv[1][FK - 1] = cv_fin<FK - 1>(d[1], x.z); tv[1][FK] = cv_fin<FK>(d[1], x.w);
    }
    if constexpr (G < GN - 1) wgmma_wait<CV_W>();
    if constexpr (G == GN - 1) wgmma_wait<0>();
    if constexpr (T >= 0 && T % (2 * CV_GC) == CV_GC) named_bar_sync(p.bar, 128);
    if constexpr (F < GN - CV_GC) cv_steps<G + 1>(d, a, tv, p);
}

#define CV_PF 7
#define Y_FIRST 1
#define Y_HOLD 0
#define PS2_EARLY 1
#define W3_AT 1
struct MegaMaps {
    CUtensorMap q, act;
    CUtensorMap w1, w2, w3, w4;
    CUtensorMap k, v, y;
};

__global__ void __cluster_dims__(2, 1, 1) __launch_bounds__(384, 1)
mega_kernel(const __grid_constant__ MegaMaps tm, bf16* __restrict__ outp, bf16* act, const bf16* __restrict__ w1p, const bf16* __restrict__ w2p,
            const bf16* __restrict__ w3p, const bf16* __restrict__ xq, const bf16* __restrict__ kp, const bf16* __restrict__ vp,
            const bf16* __restrict__ shk, const bf16* __restrict__ ssk, const bf16* __restrict__ ssD) {
    extern __shared__ __align__(1024) uint8_t sgen[];
    const uint32_t sbase = smem_u32(sgen);
    const int warp = __shfl_sync(0xffffffffu, threadIdx.x >> 5, 0), lane = threadIdx.x & 31;
    const int rank = blockIdx.x & 1;
    const uint32_t s_bar = sbase + OFF_BAR;
    const uint32_t f5 = s_bar, e5 = s_bar + 64, f4 = s_bar + 144, e4 = s_bar + 104;
    const uint32_t b_rfull = s_bar + 176, b_role = s_bar + 184, b_stg = s_bar + 136, b_h2 = s_bar + 32;
    const uint32_t s_epi = sbase + OFF_EPI, s_stg = sbase + OFF_STG5, s_r = sbase + OFF_R;
    uint8_t* sm = sgen + CV_0;
    const uint32_t sb = sbase + CV_0;
    const int tid = threadIdx.x, wg = warp >> 2, w = warp & 3;
    const int d0 = blockIdx.x * CV_CH;
    const bool cv = blockIdx.x < D_ / CV_CH;
    const uint32_t b_full = sb + CV_BAR, b_rdy = b_full + 64, b_h = b_full + 128;
    GT(0);
    if (tid == 0) TM(0);
    auto row_at = [&](int r) { return sb + CV_SL + (r < 0 ? -8192 : 0) + ((r & 127) >> 5) * 1024 + (r & 7) * 128 + ((r >> 3) & 3) * 32 + ((r ^ rank) & 1) * 16; };
    auto load_kv = [&](int c) {
#pragma unroll
        for (int i = 0; i < 2; i++)
            asm volatile("cp.async.bulk.tensor.4d.shared::cluster.global.mbarrier::complete_tx::bytes.multicast::cluster [%0], [%1, {%3, %4, %4, %5}], [%2], %6;"
                         ::"r"(sb + (c + 1) * CV_SL + rank * 8192 + i * 4096), "l"((uint64_t)(i ? &tm.v : &tm.k)), "r"(b_full + 8 * c), "r"(d0 & ~15), "r"(0),
                         "r"(8 * c + 4 * rank), "h"((uint16_t)3) : "memory");
    };
    auto bulk = [&](uint32_t dst, const void* src, uint32_t n, uint32_t bar) {
        asm volatile("cp.async.bulk.shared::cluster.global.mbarrier::complete_tx::bytes [%0], [%1], %2, [%3];" ::"r"(dst), "l"(src), "r"(n), "r"(bar) : "memory");
    };
    auto put_h = [&](int ch) {
        const uint32_t dk = (tid & 127) ? 0 : *reinterpret_cast<const volatile uint32_t*>(sm + CV_BAR + 160 + 16 * wg + 2 * ch);
        uint4 v[4];
#pragma unroll
        for (int i = 0; i < 4; i++) v[i] = lds128(sbase + ch * 4096 + i * 2048 + (tid & 127) * 16);
        v[0].x = pack2(lo2f(v[0].x) + lo2f(dk), hi2f(v[0].x));
        v[2].x = pack2(lo2f(v[2].x) + hi2f(dk), hi2f(v[2].x));
#pragma unroll
        for (int i = 0; i < 4; i++)
            sts128(sb + CV_H + (2 * ch + (i & 2) + (tid & 1)) * CV_HPL + (127 - ((tid & 127) >> 1)) * 16 - (i & 1) * 1024, v[i].x, v[i].y, v[i].z, v[i].w);
    };
    int bi, bj, m0, tb;
    uint32_t ep;
    auto get_role = [&]() {
        mbar_wait(b_role, 0);
        int role;
        asm volatile("ld.shared.v2.b32 {%0,%1}, [%2];" : "=r"(role), "=r"(ep) : "r"(s_bar + 192) : "memory");
        bi = (role >> 3) * 2 + rank; bj = role & 7; m0 = bi * BM; tb = (role >> 3) * 2048 + rank * 128;
        return role < 64;
    };

    if (warp >= 8) {
        asm volatile("setmaxnreg.dec.sync.aligned.u32 88;");
        cluster_arrive_relaxed();
        if (!cv) cluster_wait(); else {
            const int bt = tid - 256, g = lane >> 2, t = lane & 3;
            if (bt < 16) sts128(row_at((bt & 7) - 8) + (bt >> 3) * 4096, 0, 0, 0, 0);
#pragma unroll
            for (int i = 0; i < 4; i++)
                cp16(row_at(bt) + i * 4096, (i & 1 ? vp : kp) + (size_t)(bt + (i >> 1) * 128) * D_ + d0);
            DBG_S(16 + (3));
            uint2 wa;
            asm volatile("ld.global.nc.v2.b32 {%0,%1}, [%2];" : "=r"(wa.x), "=r"(wa.y) : "l"(shk + (d0 + g) * 4));
            const int mi = lane >> 3, r0 = 32 * w + 8 * ((lane >> 1) & 3) - (lane & 1);
            const uint32_t ka0 = row_at(r0 + 2 * mi - 3), ka1 = row_at(r0 + 2 * (mi & 1) + 5) + (mi >> 1) * 8192;
            const uint32_t va0 = row_at(r0 + 2 * mi + 1) + 4096, va1 = row_at(r0 - 1) + 4096 + (mi & 1) * 8192;
            const uint32_t qd = sb + g * CV_QG + (32 * w + 8 * t) * 8, qd0 = qd + (t & 2) * 16, qd1 = qd + (~t & 2) * 16;
            const uint32_t w0 = __byte_perm(wa.x, 0, 0x1010), w1 = __byte_perm(wa.x, 0, 0x3232), w2 = __byte_perm(wa.y, 0, 0x1010), w3 = __byte_perm(wa.y, 0, 0x3232);
            cluster_wait();
            DBG_S(16 + (5));
            asm volatile("cp.async.wait_all;" ::: "memory");
            named_bar_sync(7, 128);
            DBG_S(16 + (1));
            struct KV { uint32_t k[2][6], v[2][5]; };
            auto get = [&](KV& x, uint32_t so) {
                ldsm4t(x.k[0][0], x.k[0][1], x.k[0][2], x.k[0][3], ka0 + so);
                ldsm4t(x.k[0][4], x.k[0][5], x.k[1][4], x.k[1][5], ka1 + so);
                ldsm4t(x.k[1][0], x.k[1][1], x.k[1][2], x.k[1][3], ka0 + so + 8192);
                asm volatile("ldmatrix.sync.aligned.m8n8.x2.trans.shared.b16 {%0,%1}, [%2];" : "=r"(x.v[0][0]), "=r"(x.v[1][0]) : "r"(va1 + so));
                ldsm4t(x.v[0][1], x.v[0][2], x.v[0][3], x.v[0][4], va0 + so);
                ldsm4t(x.v[1][1], x.v[1][2], x.v[1][3], x.v[1][4], va0 + so + 8192);
            };
            auto build = [&](int c, const KV& x, KV& nx) {
                const uint32_t so = c * CV_SL;
                DBG_F(1);
                uint32_t early;
                asm volatile("{\n.reg .pred p;\nmbarrier.test_wait.parity.shared::cta.b64 p, [%1], 0;\nvote.sync.all.pred p, p, -1;\nselp.u32 %0, 1, 0, p;\n}"
                             : "=r"(early) : "r"(b_full + 8 * (c < 7 ? c + 1 : c)) : "memory");
                if (early) get(nx, so + CV_SL);
                DBG_F(2);
                uint32_t p[8][2];
#pragma unroll
                for (int sg = 0; sg < 2; sg++) {
                    uint32_t u[5], ke[6];
#pragma unroll
                    for (int i = 0; i < 6; i++) ke[i] = __byte_perm(x.k[sg][i], x.k[sg][i ? i - 1 : 0], 0x5432);
#pragma unroll
                    for (int i = 0; i < 5; i++) {
                        u[i] = bmul2(bfma2(x.k[sg][i + 1], w0, bfma2(ke[i + 1], w1, bfma2(x.k[sg][i], w2, bmul2(ke[i], w3)))), x.v[sg][i]);
                        if (i) { p[2 * i - 1][sg] = u[i]; p[2 * i - 2][sg] = __byte_perm(u[i], u[i - 1], 0x5432); }
                    }
                }
                DBG_F(3);
#pragma unroll
                for (int j = 0; j < 4; j++) sts128((j & 2 ? qd1 : qd0) + so + 16 * (j & 1), p[2 * j][0], p[2 * j][1], p[2 * j + 1][0], p[2 * j + 1][1]);
                __syncwarp();
                DBG_F(4);
                if (lane == 0) {
                    mbar_arrive(b_rdy + 8 * c);
                    if (c == w) {
                        if (c < 3) load_kv(c + 5);
                        else { bulk(sbase + 16384, ssk + (size_t)(d0 + 4) * S_, 16384, b_h + 16); bulk(b_full + 192, ssD + d0, 16, b_h + 16); }
                    }
                    if (c == w + 4 && (CV_PF >> w & 1)) {
                        const uint32_t n = w == 0 ? 32768 : w == 3 ? 57344 : 16384;
                        const char* src = reinterpret_cast<const char*>(w == 0 ? xq : w == 1 ? w1p : w == 2 ? w2p : w3p) + (size_t)blockIdx.x * n;
                        asm volatile("cp.async.bulk.prefetch.L2.global [%0], %1;" ::"l"(src), "r"(n) : "memory");
                    }
                }
                DBG_F(5);
                named_bar_sync(7, 128);
                DBG_F(6);
                DBG_S(16 + (c == 0 ? 4 : 5 + c));
                if (!early) { mbar_wait(b_full + 8 * c + 8, 0); get(nx, so + CV_SL); }
                DBG_F(7);
            };
            KV x0, x1;
            get(x0, 0);
#pragma unroll 1
            for (int c = 0; c < 8; c += 2) { build(c, x0, x1); build(c + 1, x1, x0); }
            mbar_wait(b_h + 16, 0);
            put_h(4); put_h(6);
            fence_async_smem();
            __syncwarp();
            if (lane == 0) mbar_arrive(b_full);
            named_bar_sync(7, 128);
            DBG_S(16 + (13));
        }
    } else {
        if (elect_one()) {
            mbar_init(b_full + 8 * warp, warp ? 1 : 4);
            mbar_init(b_rdy + 8 * warp, 4);
            if (warp) mbar_expect_tx(b_full + 8 * warp, 16384);
            if (w == 0 && cv) {
                mbar_init(b_h + 8 * wg, 1);
                mbar_expect_tx(b_h + 8 * wg, 8192 + 16);
                fence_async_smem();
                bulk(sbase + wg * 8192, ssk + (size_t)(d0 + 2 * wg) * S_, 8192, b_h + 8 * wg);
                bulk(b_full + 160 + 16 * wg, ssD + d0, 16, b_h + 8 * wg);
            }
            mbar_init(s_bar + 8 * warp, 1);
            mbar_init(s_bar + 64 + 8 * warp, 4);
            mbar_init(s_bar + 128 + 8 * warp, warp < 2 ? 4 << warp : warp == 6 ? 2 : 1);
            if (warp == 0) mbar_arrive(f5);
            if (warp == 7) mbar_expect_tx(b_role, 8);
            if (warp == 1) { mbar_init(b_h + 16, 1); mbar_expect_tx(b_h + 16, 16384 + 16); }
            if (w == 2) sts128(s_bar + 224 + 16 * wg, 0, 0, 0, 0);
            asm volatile("fence.mbarrier_init.release.cluster;" ::: "memory");
            if (warp == 2) { prefetch_tmap(&tm.k); prefetch_tmap(&tm.v); }
        }
        __syncwarp();
        DBG_W(1);
        cluster_arrive_relaxed();
        asm volatile("setmaxnreg.inc.sync.aligned.u32 208;");
        DBG_W(2);
        const int zi = (tid & 127) - 32;
        if (zi >= 0 && zi < 48) sts128(sb + CV_H + (4 * wg + (zi / 6 & 3) + (zi / 24) * 8) * CV_HPL + 2048 + (zi % 6) * 16, 0, 0, 0, 0);
        DBG_W(3);
        cluster_wait();
        DBG_W(5);
        if (cv) {
            if (tid == 32) {
#pragma unroll 1
                for (int c = 1; c < 5; c++) load_kv(c);
                prefetch_tmap(&tm.y);
            }
            __syncwarp();
            DBG_W(6);
            const int g = lane >> 2, t = lane & 3;
            const int x0 = 32 + 8 * w + g - 2 * t;
            CvAddr p;
            p.rdy = b_rdy;
            p.bar = 1 + wg;
            p.xr = sbase + (warp ^ 2) * 2048 + lane * 16;
            p.xw = sbase + warp * 2048 + (g * 4 + ((t - (w >> 1)) & 3)) * 16;
            p.wrap = t == 0 && w >= 2;
            mbar_wait(b_h + 8 * wg, 0);
            DBG_W(4);
            put_h(2 * wg);
            fence_async_smem();
            named_bar_sync(1 + wg, 128);
            float acc[2][64];
            zero_acc(acc[0]); zero_acc(acc[1]);
#pragma unroll 1
            for (int round = 0; round < 2; round++) {
                const int ch = round * 4 + 2 * wg;
                uint32_t a[CV_NA][4], tv[2][8];
#pragma unroll
                for (int e = 0; e < 2; e++) {
                    const int x = x0 - 8 * e;
                    p.neg[e] = x < 32;
                    p.pa[e] = sb + ch * CV_QG + 8 * (x ^ (x >> 2 & 4));
                    p.p0[2 * e] = p.pa[e] + (x < 32 ? 768 + 4 - CV_SL : -256);
                    p.p0[2 * e + 1] = p.pa[e] + (x < 32 ? 768 : -256 + 4);
                }
                p.db = (((sb + CV_H + ch * 2 * CV_HPL) & 0x3FFFF) >> 4) | ((CV_HPL / 16) << 16);
                if (round) mbar_wait(b_full, 0);
                DBG_S(7 + 3 * round);
                cv_steps<0>(acc, a, tv, p);
                DBG_S(8 + 3 * round);
                const int r128 = 4 * (lane >> 3) + 2 * (lane & 1) + ((~lane >> 2) & 1);
#pragma unroll
                for (int i = 0; i < 2; i++) {
                    const uint32_t ta = sb + ((ch + i + 1) & 7) * CV_SL + 12288 + r128 * 128 + ((((~lane & 2) * 2 + w) ^ (r128 & 7)) << 4);
                    stsm4t(ta, tv[i][0], tv[i][1], tv[i][2], tv[i][3]);
                    stsm4t(ta + 2048, tv[i][4], tv[i][5], tv[i][6], tv[i][7]);
                }
                fence_async_smem();
                named_bar_sync(1 + wg, 128);
                if ((tid & 127) < 2) {
                    const int d = d0 + ch + (tid & 1);
                    asm volatile("cp.async.bulk.tensor.4d.global.shared::cta.bulk_group [%0, {%2, %3, %4, %2}], [%1];"
                                 ::"l"((uint64_t)&tm.y), "r"(sb + ((ch + (tid & 1) + 1) & 7) * CV_SL + 12288), "r"(0), "r"(4 * (d >> 8)), "r"(d & 255) : "memory");
                    asm volatile("cp.async.bulk.commit_group;" ::: "memory");
                }
                __syncwarp();
                DBG_S(9 + 3 * round);
            }
            GT(1);
        }
    }
    int warp2 = warp;
    asm volatile("" : "+r"(warp2));
    if (warp2 >= 8) {
        asm volatile("setmaxnreg.dec.sync.aligned.u32 72;");
        if (warp == 8) { if (elect_one()) {
            if (rank == 0) {
                uint32_t smid;
                asm volatile("mov.u32 %0, %%smid;" : "=r"(smid));
                const int t = smid >> 1;
                int team = t < 32 ? t & 7 : t < 60 ? 1 + (t - 32) % 7 : t < 62 ? t - 54 : 0;
                const unsigned long long arr = atomicAdd(reinterpret_cast<unsigned long long*>(g_ticket + 16 * FL_PITCH), 1ull);
                const uint32_t e1 = (uint32_t)(arr / NCL) + 1;
                unsigned int* tk = g_ticket + (e1 & 1) * 8 * FL_PITCH;
                int slot = atomicAdd(tk + team * FL_PITCH, 1u);
                atomicAdd(g_ticket + 17 * FL_PITCH, 1u);
                if (blockIdx.x < 16) g_ticket[((~e1 & 1) * 8 + (blockIdx.x >> 1)) * FL_PITCH] = 0;
                if (slot >= 8) {
                    const long long t0 = clock64();
                    while ((int)(*(volatile unsigned int*)(g_ticket + 17 * FL_PITCH) - e1 * NCL) < 0 && clock64() - t0 < 100000) {}
                    for (team = 0; team < 8; team++)
                        if ((slot = atomicAdd(tk + team * FL_PITCH, 1u)) < 8) break;
                }
#pragma unroll
                for (int i = 0; i < 2; i++)
                    asm volatile("st.async.weak.shared::cluster.mbarrier::complete_tx::bytes.v2.b32 [%0], {%1, %2}, [%3];"
                                 ::"r"(mapa_u32(s_bar + 192, i)), "r"(team * 8 + slot), "r"(e1), "r"(mapa_u32(b_role, i)) : "memory");
            }
            if (get_role()) {
            TM(2);
            mbar_expect_tx(b_rfull, 32768);
            tma_load_2d(sbase + 16384, &tm.q, b_rfull, bj * 128, m0);
            tma_load_2d(sb + 8 * CV_SL, &tm.q, b_rfull, bj * 128 + 64, m0);
            int s5 = 0, s4 = 0;
            uint32_t p5 = 0, p4 = 1;
            auto putB = [&](const CUtensorMap* tB, int kc, uint32_t bytes) {
                const uint32_t full = f5 + 8 * s5;
                mbar_wait(full + 64, (p5 >> s5) & 1);
                mbar_expect_tx(full, bytes);
                tma_load_2d_mc(s_r + 16384 + rank * 8192 + s5 * R5_STAGE, tB, full, bj * 128 + rank * 64, kc);
                p5 ^= 1u << s5;
            };
            auto putA = [&](int c, int r) {
                tma_load_2d(s_r + s5 * R5_STAGE, &tm.act, f5 + 8 * s5, c, r);
                if (++s5 == R5_N) s5 = 0;
            };
            prefetch_tmap(&tm.act); prefetch_tmap(&tm.w1); prefetch_tmap(&tm.w2); prefetch_tmap(&tm.w3); prefetch_tmap(&tm.w4);
            auto own_first = [&](int it) {
                const int hf = it >= 9, c = it - 2 - 7 * hf;
                return (it < 2 ? 2 * bj + it : 2 * (c + (c >= bj)) + hf) * BK;
            };
            const unsigned int n8 = 8 * ep, nh = (bi == 0 || bi == 15) ? 2 * n8 : 3 * n8;
#pragma unroll 1
            for (int layer = 0; layer < 2; layer++) {
                s5 = 2;
#pragma unroll 1
                for (int kk = -(layer | Y_FIRST); kk < 5 - (layer | Y_FIRST); kk++) {
                    if (kk & 4) {
                        if (layer == 0) { TM(1); wait_flag(flag_ptr(0, FL_CS, 8 + bj), 8 * n8); TM(4); fence_proxy_async(); }
                        mbar_wait(e5 + 8, (p5 >> 1) & 1);
                        mbar_expect_tx(f5 + 8, 32768);
                        tma_load_2d(s_r + R5_STAGE, &tm.act, f5 + 8, (bj >> 1) * 256 + rank * 128, R_Y + (tb & ~255) + (bj & 1) * 128);
                        tma_load_2d(s_r + R5_STAGE + 16384, &tm.act, f5 + 8, (bj >> 1) * 256 + rank * 128 + 64, R_Y + (tb & ~255) + (bj & 1) * 128);
                        p5 ^= 2;
                        if (layer == 0) TM(5);
                    } else {
                        if (kk == Y_HOLD && layer == 0) mbar_wait(f5 + 8, 0);
                        putB(&tm.w1, own_first(kk), kk < 2 ? 16384 : R5_STAGE);
                        if (++s5 == R5_N) s5 = 0;
                    }
                }
                s5 = 4;
#pragma unroll 1
                for (int kk = 2; kk < 16; kk++) {
                    const int kc = own_first(kk);
                    if (kk >= 4) putB(&tm.w1, kc, R5_STAGE);
                    if (kk == 2 || kk == 9) {
                        wait_flag(flag_ptr(layer, FL_XA + (kk & 1), bi), n8);
                        if (layer == 0 && kk == 2) TM(14);
                        DP(8 * (FL_XA + (kk & 1)) + 3);
                        fence_proxy_async();
                        DP(8 * (FL_XA + (kk & 1)) + 4);
                    }
                    putA(kc, R_XA + tb);
                }
                mbar_wait(e5 + 24, (p5 >> 3) & 1);
                mbar_arrive(f5 + 24);
                p5 ^= 8;
                s5 = 4;
#pragma unroll 1
                for (int kk = 0; kk < 5; kk++) { putB(&tm.w2, kk * 2 * BK, R5_STAGE); if (++s5 == R5_N) s5 = 0; }
#pragma unroll 1
                for (int kk = 0; kk < 16; kk++) {
                    const int kc = ((kk & 7) * 2 + (kk >> 3)) * BK;
                    if (kk >= 5) putB(&tm.w2, kc, R5_STAGE);
                    if ((kk & 7) == 0) {
                        wait_flag(flag_ptr(layer, FL_H + (kk >> 3), bi), nh);
                        DP(8 * (FL_H + (kk >> 3)) + 3);
                        fence_proxy_async();
                        DP(8 * (FL_H + (kk >> 3)) + 4);
                    }
                    putA(kc, R_H + layer * R_HP + m0 + (int)((0x4031u >> ((kk & 6) << 1)) & 7) - 2);
                }
#pragma unroll 1
                for (int it = 0; it < 32; it++) {
                    const int kc = it >= 16 ? (it - 16) * BK : own_first(it);
                    const int nb = it < 16 ? 4 : 3, n0 = bj * 448 + (it < 16 ? 0 : 256);
                    if (it > 0 && it < 4) {
                        const int i = (it - 1) * 3 >> 1;
                        mbar_wait(e5 + 8 * i, (p5 >> i) & 1);
                        mbar_wait(e5 + 8 * i + 8, (p5 >> (i + 1)) & 1);
                    }
                    mbar_wait(e4 + 8 * s4, p4);
                    if (it >= 16 && it < 19) mbar_wait(e4 + 8 * s4 + 8, p4);
                    uint32_t sa = s_r + s4 * (it < 16 ? R4_STAGE : R4B_STAGE), full = f4 + 8 * s4;
                    mbar_expect_tx(full, (it < 2 ? 0 : 16384) + nb * 8192);
#pragma unroll 1
                    for (int j = (it ^ rank) & 1; j < nb; j += 2) tma_load_2d_mc(sa + (it < 16 ? -32768 : 16384) + j * 8192, &tm.w3, full, n0 + j * 64, kc);
                    if (it == 3 || it == 9) {
                        wait_flag(flag_ptr(layer, FL_X1 + (it >> 3), bi), n8);
                        DP(8 * (FL_X1 + (it >> 3)) + 3);
                        fence_proxy_async();
                        DP(8 * (FL_X1 + (it >> 3)) + 4);
                        if (it == 3) tma_load_2d(s_r + 2 * R4_STAGE, &tm.act, f4 + 16, own_first(2), R_X1 + tb);
                    }
                    if (it >= 3) tma_load_2d(sa, &tm.act, full, kc, R_X1 + tb);
                    if (++s4 == R4_N) { s4 = 0; p4 ^= 1; }
                }
                wait_flag(flag_ptr(layer, FL_H2, bi), n8);
                fence_proxy_async();
                s5 = 0;
#pragma unroll 1
                for (int j = 0; j < 7; j++) {
                    if (j > 0 && (j & 1) == 0) {
                        mbar_wait(b_h2 + 4 * j, layer);
                        fence_proxy_async();
                    }
                    const int ra = R_H2 + (j >> 1) * 256 + tb;
#pragma unroll 1
                    for (int b = 0; b < 8; b++) {
                        if (j == 0 && b < R4_N) mbar_wait(e4 + 8 * b, p4);
                        putB(&tm.w4, (7 * b + j) * BK, R5_STAGE);
                        putA(((j & 1) * 8 + b) * BK, ra);
                    }
                }
            }
        } } } else {
            auto colsum = [&](bool is1, int bi, int bj) {
                const int pitch = is1 ? D_ : F_, c = is1 ? bj * 128 + (lane & 15) * 8 : bj * 448 + min((warp & 2) * 128 + lane * 8, 440);
                const bf16* p = (is1 ? w1p : w3p) + ((bi * 64 + (is1 ? (lane >> 4) * 32 : 0)) * pitch + c);
                float a[8];
#pragma unroll
                for (int i = 0; i < 8; i++) a[i] = 0.f;
#pragma unroll 1
                for (int r0 = is1 ? 32 : 0; r0 < 64; r0 += 8) {
                    uint4 v[8];
#pragma unroll
                    for (int r = 0; r < 8; r++, p += pitch) v[r] = __ldg(reinterpret_cast<const uint4*>(p));
#pragma unroll
                    for (int r = 0; r < 8; r++) {
                        a[0] += lo2f(v[r].x); a[1] += hi2f(v[r].x); a[2] += lo2f(v[r].y); a[3] += hi2f(v[r].y);
                        a[4] += lo2f(v[r].z); a[5] += hi2f(v[r].z); a[6] += lo2f(v[r].w); a[7] += hi2f(v[r].w);
                    }
                }
                if (is1) {
#pragma unroll
                    for (int i = 0; i < 8; i++) a[i] += __shfl_xor_sync(0xffffffffu, a[i], 16);
                }
                float4* dst = reinterpret_cast<float4*>(g_cpart + bi * (F_ + D_) + (is1 ? F_ : 0) + c);
                dst[0] = make_float4(a[0], a[1], a[2], a[3]);
                dst[1] = make_float4(a[4], a[5], a[6], a[7]);
                asm volatile("fence.release.gpu;" ::: "memory");
                __syncwarp();
                if (lane == 0) asm volatile("red.relaxed.gpu.global.add.u32 [%0], 1;" ::"l"(flag_ptr(!is1, FL_CS, bj)) : "memory");
            };
            if (cv && warp == 10) colsum(true, blockIdx.x >> 3, blockIdx.x & 7);
            float4 keep[2];
            const bool on = get_role();
            if (on && warp == 11) {
                uint4* ps = reinterpret_cast<uint4*>(g_stats + (bi * 8 + bj) * 128) + lane;
                ps[0] = ps[32] = make_uint4(0, 0, 0, 0);
                asm volatile("fence.acq_rel.gpu;" ::: "memory");
                __syncwarp();
                if (lane == 0) mbar_arrive(b_rfull);
            }
#pragma unroll 1
            for (int layer = on ? 0 : 2; layer < 2; layer++) {
                if (warp == 10) {
#pragma unroll 1
                    for (int kind = 0; kind < 6; kind += 2) {
                        const uint32_t src = kind == FL_H ? s_stg : s_epi;
                        const int r = kind == FL_H ? R_H + layer * R_HP + m0 : (kind == FL_XA ? R_XA : R_X1) + tb;
#pragma unroll 1
                        for (int hf = 0; hf < 2; hf++) {
                            named_bar_sync(5 + hf, 288);
                            if (lane == 0) {
                                DP(8 * (kind + hf));
                                tma_store_2d(&tm.act, src + hf * 16384, bj * 128 + hf * 64, r);
                                asm volatile("cp.async.bulk.commit_group;" ::: "memory");
                                asm volatile("cp.async.bulk.wait_group 0;" ::: "memory");
                                DP(8 * (kind + hf) + 1);
                                DP(8 * (kind + hf) + 2);
                                unsigned int* fp = flag_ptr(layer, kind + hf, bi);
                                asm volatile("red.relaxed.gpu.global.add.u32 [%0], 1;" ::"l"(fp) : "memory");
                                if (kind == FL_H) {
                                    if (bi > 0) asm volatile("red.relaxed.gpu.global.add.u32 [%0], 1;" ::"l"(fp - FL_PITCH) : "memory");
                                    if (bi < 15) asm volatile("red.relaxed.gpu.global.add.u32 [%0], 1;" ::"l"(fp + FL_PITCH) : "memory");
                                }
                            }
                            __syncwarp();
                        }
                    }
                } else {
                    uint32_t* rs = reinterpret_cast<uint32_t*>(sgen + OFF_RS);
                    float* cs = reinterpret_cast<float*>(sgen + OFF_CS);
#pragma unroll 1
                    for (int which = 0; which < 2; which++) {
                        if (layer < which) {
                            if (warp == 11 && lane == 0) {
                                wait_flag(flag_ptr(0, FL_XA + W3_AT, bi), 8 * ep);
                                asm volatile("cp.async.bulk.prefetch.L2.global [%0], %1;" ::"l"(w3p + (bi * 8 + bj) * 28672), "r"(57344) : "memory");
                            }
                            __syncwarp();
                            colsum(false, bi, bj);
                        }
                        if (warp == 11) continue;
                        if (layer == 0) {
                            if (lane == 0) wait_flag(flag_ptr(which, FL_CS, bj), (16 << which) * ep);
                            __syncwarp();
#pragma unroll 1
                            for (int c = (which ? 384 : 768) + lane * 4; c < 896; c += 128) {
                                const float* cp = g_cpart + (which ? bj * 448 + min(c & 511, 444) : F_ + bj * 128 + lane * 4);
                                float4 a = make_float4(0.f, 0.f, 0.f, 0.f);
#pragma unroll
                                for (int r0 = 0; r0 < 16; r0 += 8) {
                                    float4 v[8];
#pragma unroll
                                    for (int r = 0; r < 8; r++) v[r] = __ldcg(reinterpret_cast<const float4*>(cp + (r0 + r) * (F_ + D_)));
#pragma unroll
                                    for (int r = 0; r < 8; r++) { a.x += v[r].x; a.y += v[r].y; a.z += v[r].z; a.w += v[r].w; }
                                }
                                if (c < 768) *reinterpret_cast<float4*>(cs + min(c & 511, 444)) = a;
                                keep[0] = a;
                            }
                        }
                        if (lane == 0 && (layer | which)) wait_flag(flag_ptr(layer, which == 0 ? FL_XA : FL_X1, bi), 8 * ep);
                        __syncwarp();
                        *reinterpret_cast<float4*>(cs + 256 + lane * 4) = keep[0];
                        { const float4 k0 = keep[0]; keep[0] = keep[1]; keep[1] = k0; }
#pragma unroll 1
                        for (int i = 0; i < 4; i++) {
                            const int r = i * 32 + lane;
                            float mean, var;
                            row_stats(g_stats + (1 + which) * S_ * 8 + bi * 1024 + r, ~layer << 31, mean, var);
                            const uint32_t c0 = pack2(mean, fsqrt(bfr(bfr(var) + 1e-5f)));
                            if (lane < 19 && (layer | which | i) == 0) asm volatile("mbarrier.inval.shared::cta.b64 [%0];" ::"r"(b_full + 8 * lane) : "memory");
                            __syncwarp();
                            rs[r] = c0;
                            const float rd = frcp(hi2f(c0));
                            rs[128 + r] = pack2((mean - lo2f(c0)) * rd, fsqrt(bfr(bfr(var * rd * rd) + 1e-5f)));
                        }
                        __syncwarp();
                        named_bar_arrive(3, 160);
                        named_bar_arrive(11, 160);
                    }
                }
                const uint32_t s_cnt = s_bar + 224;
                auto ticket = [&](uint32_t a) {
                    uint32_t v = 0;
                    if (lane == 0) asm volatile("atom.acq_rel.cta.shared.add.u32 %0, [%1], 1;" : "=r"(v) : "r"(a) : "memory");
                    return v;
                };
                mbar_wait(b_stg, 0);
                int u = __shfl_sync(0xffffffffu, ticket(s_cnt + 16 + 4 * layer), 0), step = 0;
#pragma unroll 1
                while (true) {
#pragma unroll 1
                    for (; step < 5 && u >= (int)((0x3830201810ull >> (8 * step)) & 255); step++) {
                        if (step == 1) { named_bar_arrive(4, 224); named_bar_arrive(12, 224); continue; }
                        const int part = step ? step - 1 : 0;
                        __syncwarp();
                        if (ticket(s_cnt + 4 * part) == 3 * layer + 2) {
                            asm volatile("fence.release.gpu;" ::: "memory");
                            unsigned int* fp = flag_ptr(layer, FL_H2 + part, bi);
                            asm volatile("red.relaxed.gpu.global.add.u32 [%0], 1;" ::"l"(fp) : "memory");
                            if (part > 0) { wait_flag(fp, 8 * ep); mbar_arrive(b_h2 + 8 * part); }
                        }
                        __syncwarp();
                        if (step == 2) mbar_wait(b_stg, 1);
                    }
                    if (u >= 56) break;
                    const uint32_t un = ticket(s_cnt + 16 + 4 * layer);
                    const int job = u >> 3, r = (u & 7) * 16 + (lane >> 3);
                    const uint32_t sp = sbase + ((job & 2) ? OFF_STG5 : OFF_EPI) + r * 256 + (job & 1) * 128;
                    bf16* gp = act + (size_t)(R_H2 + (job >> 1) * 256 + tb + r) * D_ + ((job & 1) * 8 + bj) * 64 + (lane & 7) * 8;
                    uint4 v[4];
#pragma unroll
                    for (int e = 0; e < 4; e++) v[e] = lds128(sp + e * 1024 + (((lane & 7) ^ ((r + 4 * e) & 7)) << 4));
#pragma unroll
                    for (int e = 0; e < 4; e++) stg128(gp + 4 * e * D_, gelu8h(v[e]));
                    u = __shfl_sync(0xffffffffu, un, 0);
                }
                if (layer == 0 && warp == 11) {
                    const char* ps = reinterpret_cast<const char*>(g_stats + bi * 1024) + lane * 128;
                    const char* py = reinterpret_cast<const char*>(act + (size_t)(R_Y + (tb & ~255) + (bj & 1) * 128 + (lane >> 1)) * D_ + (bj >> 1) * 256 + rank * 128) + (lane & 1) * 128;
#pragma unroll 1
                    for (int i = 0; i < 8; i++) {
                        asm volatile("prefetch.global.L2 [%0];" ::"l"(py + (size_t)i * 16 * D_ * 2) : "memory");
                        if (i >= 6) asm volatile("prefetch.global.L2 [%0];" ::"l"(ps + (i & 1) * 4096) : "memory");
                        __nanosleep(400);
                    }
                }
            }
        }
        __syncwarp();
        asm volatile("barrier.cluster.arrive.relaxed.aligned;\nbarrier.cluster.wait.acquire.aligned; // helpers" ::: "memory");
    } else {
        DT(0);
        GT(2);
        if (tid == 0) TM(10);
        auto put_y = [&]() {
            if ((tid & 127) < 2 && cv) {
                if (tid == 0) TM(6);
                asm volatile("cp.async.bulk.wait_group 0;" ::: "memory");
                asm volatile("red.relaxed.gpu.global.add.u32 [%0], 1;" ::"l"(flag_ptr(0, FL_CS, 8 + (blockIdx.x >> 4))) : "memory");
                if (tid == 0) TM(7);
                if (tid == 128) TM(8);
            }
            __syncwarp();
        };
        put_y();
        asm volatile("setmaxnreg.inc.sync.aligned.u32 216;");
        if (get_role()) {
        const bool rel_on = (tid & 95) == 0;
        const uint32_t rel5 = mapa_u32(e5, (warp & 1) ^ rank), rel4 = rel5 + (e4 - e5);
        const uint32_t da0 = desc_a(s_r + wg * 8192), db0 = desc_b(s_r + BM * BK * 2), dae = da0 + (OFF_EPI - OFF_R) / 16, db4 = db0 - 49152 / 16;
        auto skip5 = [&](RingState& rs) {
            if (rel_on) mbar_arrive_cluster(rel5 + 8 * rs.st);
            rs.st++;
        };
        const int t = lane & 3;
        const int row = warp * 16 + (lane >> 2);
        const uint32_t st_w = (uint32_t)((warp * 16 + ((lane >> 3) & 1) * 8 + (lane & 7)) * 256 + (((lane >> 4) ^ (lane & 7)) << 4));
        const uint32_t fr = (uint32_t)((warp * 16 + ((lane >> 3) & 1) * 8 + (lane & 7)) * 128 + (((lane >> 4) ^ (lane & 7)) << 4));
        auto copy_out = [&](bf16* dst, uint32_t src) {
            const int r = warp * 16 + (lane >> 4);
            bf16* ox = dst + (size_t)(m0 + r) * D_ + bj * 128 + (lane & 15) * 8;
            const uint32_t ra = src + ((lane & 15) >> 3) * 16384 + r * 128;
            uint4 v[8];
#pragma unroll
            for (int it = 0; it < 8; it++) v[it] = lds128(ra + it * 256 + (((lane & 7) ^ ((2 * it + (lane >> 4)) & 7)) << 4));
#pragma unroll
            for (int it = 0; it < 8; it++) *reinterpret_cast<uint4*>(ox + (size_t)it * 2 * D_) = v[it];
        };
        auto put_stats = [&](const uint32_t (&w)[32], int which, int layer) {
            float c[6][4];
#pragma unroll
            for (int e = 0; e < 32; e++) {
                hmma8(c[e & 3], w[e & ~1], w[e | 1], w[e], e < 4);
                if ((e & 3) == 0) hmma(c[4 + (e >> 2 & 1)], w[e], w[e + 1], w[e + 2], w[e + 3], 0x3f803f80u, 0x3f803f80u, e < 8);
            }
            if (t == lane >> 3) {
#pragma unroll
                for (int e = 0; e < 2; e++) {
                    const float q1 = lane & 4 ? c[e][2 * e + 1] + c[e + 2][2 * e + 1] : c[e][2 * e] + c[e + 2][2 * e], s1 = c[4][2 * e] + c[5][2 * e], mu = s1 * (1.0f / 128);
                    asm volatile("{\n.reg .b64 t;\nmov.b64 t, {%1, %2};\nst.relaxed.gpu.global.b64 [%0], t;\n}"
                                 ::"l"(g_stats + which * S_ * 8 + (bi * 8 + bj) * 128 + row + 8 * e), "f"(mu), "r"(__float_as_uint(fmaxf(q1 - s1 * mu, 0.f)) | ~layer << 31) : "memory");
                }
            }
        };
        auto split = [](float r) { const float h = bfr(r); return pack2(h, r - h); };
        auto norm2 = [](uint32_t x, uint32_t m, uint32_t r) {
            const uint32_t d = bsub2(x, m);
            return bfma2(d, __byte_perm(r, 0, 0x1010), bmul2(d, __byte_perm(r, 0, 0x3232)));
        };
        const float* csp = reinterpret_cast<const float*>(sgen + OFF_CS) + 2 * t;
        float mrow[2], rrow[2];
        const uint32_t* rsp = reinterpret_cast<const uint32_t*>(sgen + OFF_RS) + row;
        auto row_consts = [&](bool twice) {
#pragma unroll
            for (int e = 0; e < 2; e++) {
                const uint32_t q0 = rsp[8 * e], q1 = rsp[128 + 8 * e];
                mrow[e] = twice ? fmaf(lo2f(q1), hi2f(q0), lo2f(q0)) : lo2f(q0);
                rrow[e] = 0.5f * frcp(twice ? hi2f(q0) * hi2f(q1) : hi2f(q0));
            }
        };
        auto keep_consts = [&](float2 (&cs)[8]) {
#pragma unroll
            for (int e = 0; e < 8; e++) asm volatile("" : "+f"(cs[e].x), "+f"(cs[e].y));
            asm volatile("" : "+f"(mrow[0]), "+f"(mrow[1]), "+f"(rrow[0]), "+f"(rrow[1]));
        };
        auto stage = [&](const float* acc, uint32_t dst, int j0, float2 (&cs)[8], const float* cnext) {
            float2 cn[8];
#pragma unroll
            for (int e = 0; e < 8; e++) cn[e] = *reinterpret_cast<const float2*>(cnext + 8 * e);
#pragma unroll
            for (int j = 0; j < 8; j += 2) {
                uint32_t w[4];
#pragma unroll
                for (int e = 0; e < 2; e++) {
                    const float* a = acc + 4 * (j + e);
                    w[2 * e] = pack2(fmaf(-mrow[0], cs[j + e].x, a[0]) * rrow[0], fmaf(-mrow[0], cs[j + e].y, a[1]) * rrow[0]);
                    w[2 * e + 1] = pack2(fmaf(-mrow[1], cs[j + e].x, a[2]) * rrow[1], fmaf(-mrow[1], cs[j + e].y, a[3]) * rrow[1]);
                }
                stsm4((dst + st_w) ^ (((j0 + j) & 15) << 4), w[0], w[1], w[2], w[3]);
            }
#pragma unroll
            for (int e = 0; e < 8; e++) cs[e] = cn[e];
        };
        RingState r5{1, 0}, r4{0, 0};
        DT(1);
        uint32_t x[32];
        mbar_wait(b_rfull, 0);
#pragma unroll
        for (int jp = 0; jp < 8; jp++) ldsm4(x[4 * jp], x[4 * jp + 1], x[4 * jp + 2], x[4 * jp + 3], sbase + 16384 + (fr ^ ((jp & 3) << 5)) + (jp >> 2) * (16384 + 8 * CV_SL));
#pragma unroll
        for (int e = 0; e < 32; e++) asm volatile("" : "+r"(x[e]));
        named_bar_sync(9 + wg, 128);
        if ((tid & 95) < R5_N) mbar_arrive_cluster(rel5 + 8 * lane);
#pragma unroll 1
        for (int layer = 0; layer < 2; layer++) {
            {
                DT(2 + 24 * layer);
                if (layer == 0 && tid == 0) TM(12);
                put_stats(x, 0, layer);
                DT(20 + 24 * layer);
                DT(22 + 24 * layer);
                uint32_t mb[2], rd[2];
                {
                    float mean, var;
                    row_stats(g_stats + bi * 1024 + warp * 16 + (lane & 15), ~layer << 31, mean, var);
                    __syncwarp();
                    const uint32_t r1 = split(frcp(bfr(fsqrt(bfr(bfr(var) + 1e-5f)))));
                    const uint32_t m1 = pack2(mean, mean);
#pragma unroll
                    for (int e = 0; e < 2; e++) { mb[e] = __shfl_sync(0xffffffffu, m1, (lane >> 2) + 8 * e); rd[e] = __shfl_sync(0xffffffffu, r1, (lane >> 2) + 8 * e); }
                }
                DT(21 + 24 * layer);
                if (layer == 0 && tid == 0) TM(11);
                mbar_wait(f5 + 8, r5.ph);
                if (layer == 0) GT(3);
                if (layer == 0 && tid == 0) TM(9);
                const uint32_t ya = s_r + R5_STAGE + wg * 16384 + ((lane >> 4) * 8 + (lane & 7)) * 128 + ((((warp & 3) * 2 + ((lane >> 3) & 1)) ^ (lane & 7)) << 4);
                uint32_t y[16];
#pragma unroll
                for (int e = 0; e < 32; e++) {
                    if ((e & 15) == 0) {
#pragma unroll
                        for (int jp = 0; jp < 4; jp++) ldsm4t(y[4 * jp], y[4 * jp + 1], y[4 * jp + 2], y[4 * jp + 3], ya + jp * 2048 + e * 512);
                    }
                    x[e] = bfma2(norm2(x[e], mb[e & 1], rd[e & 1]), y[e & 15], x[e]);
                    if ((e & 3) == 3) stsm4(s_epi + (fr ^ (((e >> 2) & 3) << 5)) + (e >> 4) * 16384, x[e - 3], x[e - 2], x[e - 1], x[e]);
                    if ((e & 15) == 15) { fence_async_smem(); named_bar_arrive(5 + (e >> 4), 288); }
                    if (e == 15) mbar_wait(b_role, 0);
                }
                DT(19 + 24 * layer);
                named_bar_sync(9 + wg, 128);
                skip5(r5);
                DT(3 + 24 * layer);
                if (layer == 0 && tid == 0) TM(13);
            }
            {
                float acc[64];
                kblock<128, R5_N, 0>(acc, dae, db0 + 2 * (R5_STAGE / 16), f5, r5);
                kblock<128, R5_N>(acc, dae + 1024, db0 + 3 * (R5_STAGE / 16), f5, r5);
                put_stats(x, 1, layer);
                wgmma_wait<1>();
                if (rel_on) mbar_arrive_cluster(rel5 + 16);
                float2 cs[8];
                mainloop<128, R5_N, R5_STAGE>(acc, 14, da0, db0, f5, rel5, rel_on, r5, 15 + 24 * layer, [&]() {
                    named_bar_sync(3 + 8 * wg, 160);
                    row_consts(true);
#pragma unroll
                    for (int e = 0; e < 8; e++) cs[e] = *reinterpret_cast<const float2*>(csp + 256 + 8 * e);
                    keep_consts(cs);
                });
                DT(4 + 24 * layer);
                if (layer == 0 && tid == 0) TM(15);
#pragma unroll
                for (int j = 0; j < 16; j += 2) {
                    if (j == 8) {
#pragma unroll
                        for (int e = 0; e < 8; e++) cs[e] = *reinterpret_cast<const float2*>(csp + 256 + 8 * (j + e));
                    }
                    uint32_t w[4];
#pragma unroll
                    for (int e = 0; e < 4; e++) {
                        const float* a = acc + 4 * j + 2 * e;
                        const float2 c = cs[(j & 7) + (e >> 1)];
                        w[e] = gelu2h(pack2(fmaf(-mrow[e & 1], c.x, a[0]) * rrow[e & 1], fmaf(-mrow[e & 1], c.y, a[1]) * rrow[e & 1]));
                    }
                    stsm4(s_stg + (fr ^ ((j & 7) << 4)) + (j >> 3) * 16384, w[0], w[1], w[2], w[3]);
                    if ((j & 7) == 6) { fence_async_smem(); named_bar_arrive(5 + (j >> 3), 288); }
                }
                DT(5 + 24 * layer);
            }
            {
                float acc[64];
                uint32_t u[32];
                {
                    uint32_t mb[2], rd[2];
#pragma unroll
                    for (int e = 0; e < 2; e++) { const uint32_t q0 = rsp[8 * e]; mb[e] = (q0 & 0xffffu) * 0x10001u; rd[e] = split(frcp(hi2f(q0))); }
#pragma unroll
                    for (int e = 0; e < 32; e++) {
                        u[e] = norm2(x[e], mb[e & 1], rd[e & 1]);
                        asm volatile("" : "+r"(u[e]));
                    }
                }
                mbar_wait(f5 + 24, r5.ph);
                skip5(r5);
                kblock<128, R5_N, 0>(acc, da0 + 4 * (R5_STAGE / 16), db0 + 4 * (R5_STAGE / 16), f5, r5);
                DT(16 + 24 * layer);
                mainloop<128, R5_N, R5_STAGE>(acc, 15, da0, db0, f5, rel5, rel_on, r5, -1, []() {});
                DT(6 + 24 * layer);
#pragma unroll
                for (int j = 0; j < 16; j += 2) {
#pragma unroll
                    for (int e = 0; e < 4; e++) u[2 * j + e] = badd2(u[2 * j + e], pack2(acc[4 * j + 2 * e], acc[4 * j + 2 * e + 1]));
                    stsm4(s_epi + (fr ^ ((j & 7) << 4)) + (j >> 3) * 16384, u[2 * j], u[2 * j + 1], u[2 * j + 2], u[2 * j + 3]);
                    if ((j & 7) == 6) { fence_async_smem(); named_bar_arrive(5 + (j >> 3), 288); mbar_wait(b_role, 0); }
                }
#pragma unroll
                for (int e = 0; e < 32; e++) x[e] = badd2(x[e], u[e]);
                put_stats(u, 2, layer);
                named_bar_sync(9 + wg, 128);
                DT(7 + 24 * layer);
                if (layer == 0) GT(7);
            }
            {
                float2 cs[8];
                {
                    float acc[128];
                    kblock<256, R4_N, 0>(acc, dae, db4, f4, r4);
                    kblock<256, R4_N>(acc, dae + 1024, db4 + R4_STAGE / 16, f4, r4);
                    if (!PS2_EARLY) {
                        uint32_t w[32];
#pragma unroll
                        for (int jp = 0; jp < 8; jp++) ldsm4(w[4 * jp], w[4 * jp + 1], w[4 * jp + 2], w[4 * jp + 3], s_epi + (fr ^ ((jp & 3) << 5)) + (jp >> 2) * 16384);
                        put_stats(w, 2, layer);
                    }
                    wgmma_wait<1>();
                    if (rel_on) mbar_arrive_cluster(rel4);
                    mainloop<256, R4_N, R4_STAGE>(acc, 14, da0, db4, f4, rel4, rel_on, r4, 17 + 24 * layer, [&]() {
                        named_bar_sync(3 + 8 * wg, 160);
                        mbar_wait(e4, 1);
                        row_consts(false);
#pragma unroll
                        for (int e = 0; e < 8; e++) cs[e] = *reinterpret_cast<const float2*>(csp + 8 * e);
                        keep_consts(cs);
                    });
                    DT(8 + 24 * layer);
#pragma unroll
                    for (int j = 0; j < 32; j += 8) stage(acc + 4 * j, j < 16 ? s_epi : s_stg, j, cs, csp + 8 * (j + 8));
                    __syncwarp();
                if (lane == 0) mbar_arrive(b_stg);
                }
                DT(9 + 24 * layer);
                float acc[96];
                kblock<192, R4_N, 0>(acc, da0, db0, f4, r4);
                mainloop<192, R4_N, R4B_STAGE>(acc, 15, da0, db0, f4, rel4, rel_on, r4, -1, [&]() {
                    named_bar_sync(4 + 8 * wg, 224);
                });
                DT(10 + 24 * layer);
#pragma unroll
                for (int j = 0; j < 24; j += 8) stage(acc + 4 * j, j < 16 ? s_epi : s_stg, j, cs, csp + 256 + 8 * (j < 16 ? j + 8 : 0));
                __syncwarp();
                if (lane == 0) mbar_arrive(b_stg);
                DT(11 + 24 * layer);
            }
            {
                float acc[64];
#pragma unroll
                for (int i = 0; i < 32; i++) asm volatile("shl.b32 %0, %2, 16;\nand.b32 %1, %2, 0xffff0000;" : "=f"(acc[2 * i]), "=f"(acc[2 * i + 1]) : "r"(x[i]));
                kblock<128, R5_N>(acc, da0, db0, f5, r5);
                DT(18 + 24 * layer);
                mainloop<128, R5_N, R5_STAGE>(acc, 55, da0, db0, f5, rel5, rel_on, r5, 62 - 40 * (layer ^ 1), []() {});
                DT(12 + 24 * layer);
#pragma unroll
                for (int i = 0; i < 32; i++) x[i] = pack2(acc[2 * i], acc[2 * i + 1]);
                DT(13 + 24 * layer);
                if (layer == 0) GT(6);
                DT(14 + 24 * layer);
            }
        }
#pragma unroll
        for (int jp = 0; jp < 8; jp++) stsm4(s_epi + (fr ^ ((jp & 3) << 5)) + (jp >> 2) * 16384, x[4 * jp], x[4 * jp + 1], x[4 * jp + 2], x[4 * jp + 3]);
        __syncwarp();
        copy_out(outp, s_epi);
        DT(38);
        GT(4);
        }
        cluster_arrive_relaxed();
        cluster_wait();
    }
}

typedef CUresult (*PFN_encodeTiled)(CUtensorMap*, CUtensorMapDataType, cuuint32_t, void*, const cuuint64_t*, const cuuint64_t*,
                                    const cuuint32_t*, const cuuint32_t*, CUtensorMapInterleave, CUtensorMapSwizzle,
                                    CUtensorMapL2promotion, CUtensorMapFloatOOBfill);

static CUtensorMap make_map(PFN_encodeTiled enc, const void* ptr, int inner, int outer, int box_inner, int box_outer,
                            CUtensorMapSwizzle swz = CU_TENSOR_MAP_SWIZZLE_128B) {
    CUtensorMap m;
    cuuint64_t dims[2] = {(cuuint64_t)inner, (cuuint64_t)outer};
    cuuint64_t strides[1] = {(cuuint64_t)inner * 2};
    cuuint32_t box[2] = {(cuuint32_t)box_inner, (cuuint32_t)box_outer};
    cuuint32_t es[2] = {1, 1};
    enc(&m, CU_TENSOR_MAP_DATA_TYPE_BFLOAT16, 2, const_cast<void*>(ptr), dims, strides, box, es, CU_TENSOR_MAP_INTERLEAVE_NONE,
        swz, CU_TENSOR_MAP_L2_PROMOTION_L2_256B, CU_TENSOR_MAP_FLOAT_OOB_FILL_NONE);
    return m;
}

extern "C" void kernel_launch(void* const* d_in, const int* in_sizes, int n_in, void* d_out, int out_size) {
    const bf16* A_q = (const bf16*)d_in[0];
    const bf16* A_k = (const bf16*)d_in[1];
    const bf16* A_v = (const bf16*)d_in[2];
    const bf16* A_shk = (const bf16*)d_in[3];
    const bf16* A_ssk = (const bf16*)d_in[4];
    const bf16* A_ssD = (const bf16*)d_in[5];
    const bf16* w1 = (const bf16*)d_in[7];
    const bf16* w2 = (const bf16*)d_in[8];
    const bf16* w3 = (const bf16*)d_in[9];
    const bf16* w4 = (const bf16*)d_in[10];
    bf16* out = (bf16*)d_out;

    static PFN_encodeTiled enc = nullptr;
    static bool attr_done = false;
    if (!enc) {
        void* fn = nullptr;
        cudaDriverEntryPointQueryResult qr;
        cudaGetDriverEntryPoint("cuTensorMapEncodeTiled", &fn, cudaEnableDefault, &qr);
        enc = (PFN_encodeTiled)fn;
    }
    if (!attr_done) {
        cudaFuncSetAttribute(mega_kernel, cudaFuncAttributeMaxDynamicSharedMemorySize, MEGA_SMEM);
        attr_done = true;
    }
    void* p_act;
    cudaGetSymbolAddress(&p_act, g_act);
    bf16* act = (bf16*)(((uintptr_t)p_act + 0x1fffff) & ~(uintptr_t)0x1fffff);

    MegaMaps tm;
    tm.q = make_map(enc, A_q, D_, S_, 64, 128);
    tm.act = make_map(enc, act, D_, R_END, 64, 128);
    tm.w1 = make_map(enc, w1, D_, D_, 64, 64);
    tm.w2 = make_map(enc, w2, D_, D_, 64, 64);
    tm.w3 = make_map(enc, w3, F_, D_, 64, 64);
    tm.w4 = make_map(enc, w4, D_, F_, 64, 64);
    {
        cuuint64_t dims[4] = {64, 16, 256, 8}, strides[3] = {128, D_ * 2, (cuuint64_t)2048 * D_ * 2};
        cuuint32_t box[4] = {64, 4, 1, 8}, es[4] = {1, 1, 1, 1};
        enc(&tm.y, CU_TENSOR_MAP_DATA_TYPE_BFLOAT16, 4, act + (size_t)R_Y * D_, dims, strides, box, es, CU_TENSOR_MAP_INTERLEAVE_NONE,
            CU_TENSOR_MAP_SWIZZLE_128B, CU_TENSOR_MAP_L2_PROMOTION_NONE, CU_TENSOR_MAP_FLOAT_OOB_FILL_NONE);
    }
    for (int i = 0; i < 2; i++) {
        cuuint64_t dims[4] = {D_, 4, 8, S_ / 32}, strides[3] = {8 * D_ * 2, D_ * 2, 32 * D_ * 2};
        cuuint32_t box[4] = {16, 4, 8, 4}, es[4] = {1, 1, 1, 1};
        enc(i ? &tm.v : &tm.k, CU_TENSOR_MAP_DATA_TYPE_BFLOAT16, 4, (void*)(i ? A_v : A_k), dims, strides, box, es, CU_TENSOR_MAP_INTERLEAVE_NONE,
            CU_TENSOR_MAP_SWIZZLE_32B, CU_TENSOR_MAP_L2_PROMOTION_NONE, CU_TENSOR_MAP_FLOAT_OOB_FILL_NONE);
    }
    mega_kernel<<<2 * NCL, 384, MEGA_SMEM, cudaStreamPerThread>>>(tm, out, act, w1, w2, w3, A_q, A_k, A_v, A_shk, A_ssk, A_ssD);
}
```

```cpp
#include <cuda_runtime.h>
#include <cuda_bf16.h>
#include <cuda.h>
#include <stdint.h>

typedef __nv_bfloat16 bf16;

constexpr int S_ = 2048;
constexpr int D_ = 1024;
constexpr int F_ = 3584;

constexpr int R_XA = 0, R_X1 = 256, R_H2 = 512, R_Y = 1536, R_H = 16384 + 8, R_HP = S_ + 8, R_END = R_H + 2 * R_HP;
__device__ __align__(1024) bf16 g_act[(size_t)(R_END + 1024) * D_];
__device__ __align__(16) float g_cpart[16 * (F_ + D_)];
__device__ __align__(128) float2 g_stats[3 * S_ * 8];

__device__ __forceinline__ float bfr(float x) { return __bfloat162float(__float2bfloat16_rn(x)); }
__device__ __forceinline__ uint32_t pack2(float lo, float hi) {
    __nv_bfloat162 v = __floats2bfloat162_rn(lo, hi);
    return *reinterpret_cast<uint32_t*>(&v);
}
__device__ __forceinline__ float lo2f(uint32_t v) { return __uint_as_float(v << 16); }
__device__ __forceinline__ float hi2f(uint32_t v) { return __uint_as_float(v & 0xffff0000u); }
__device__ __forceinline__ float frcp(float x) { float r; asm("rcp.approx.f32 %0, %1;" : "=f"(r) : "f"(x)); return r; }
__device__ __forceinline__ float fsqrt(float x) { float r; asm("sqrt.approx.f32 %0, %1;" : "=f"(r) : "f"(x)); return r; }
__device__ __forceinline__ uint32_t smem_u32(const void* p) { return (uint32_t)__cvta_generic_to_shared(p); }

__device__ __forceinline__ void mbar_init(uint32_t bar, uint32_t cnt) {
    asm volatile("mbarrier.init.shared::cta.b64 [%0], %1;" ::"r"(bar), "r"(cnt));
}
__device__ __forceinline__ void mbar_expect_tx(uint32_t bar, uint32_t bytes) {
    asm volatile("mbarrier.arrive.expect_tx.shared::cta.b64 _, [%0], %1;" ::"r"(bar), "r"(bytes) : "memory");
}
__device__ __forceinline__ void mbar_arrive(uint32_t bar) {
    asm volatile("mbarrier.arrive.shared::cta.b64 _, [%0];" ::"r"(bar) : "memory");
}
__device__ __forceinline__ void mbar_wait(uint32_t bar, uint32_t parity) {
    asm volatile(
        "{\n.reg .pred p;\n.reg .u32 n;\n"
        "mbarrier.try_wait.parity.shared::cta.b64 p, [%0], %1;\n"
        "@p bra LD;\n"
        "mov.u32 n, 0;\n"
        "LW:\n"
        "mbarrier.try_wait.parity.shared::cta.b64 p, [%0], %1;\n"
        "@p bra LD;\n"
        "add.u32 n, n, 1;\n"
        "setp.lt.u32 p, n, 0x400000;\n"
        "@p bra LW;\n"
        "LD:\n}\n"
        ::"r"(bar), "r"(parity) : "memory");
}
__device__ __forceinline__ void tma_load_2d(uint32_t dst, const CUtensorMap* tm, uint32_t bar, int c0, int c1) {
    asm volatile(
        "cp.async.bulk.tensor.2d.shared::cluster.global.mbarrier::complete_tx::bytes [%0], [%1, {%3, %4}], [%2];"
        ::"r"(dst), "l"((uint64_t)tm), "r"(bar), "r"(c0), "r"(c1) : "memory");
}
__device__ __forceinline__ void tma_load_2d_mc(uint32_t dst, const CUtensorMap* tm, uint32_t bar, int c0, int c1) {
    asm volatile(
        "cp.async.bulk.tensor.2d.shared::cluster.global.mbarrier::complete_tx::bytes.multicast::cluster [%0], [%1, {%3, %4}], [%2], %5;"
        ::"r"(dst), "l"((uint64_t)tm), "r"(bar), "r"(c0), "r"(c1), "h"((uint16_t)3) : "memory");
}
__device__ __forceinline__ void tma_prefetch_2d(const CUtensorMap* tm, int c0, int c1) {
    asm volatile("cp.async.bulk.prefetch.tensor.2d.L2.global.tile [%0, {%1, %2}];" ::"l"((uint64_t)tm), "r"(c0), "r"(c1) : "memory");
}
__device__ __forceinline__ void tma_store_2d(const CUtensorMap* tm, uint32_t src, int c0, int c1) {
    asm volatile("cp.async.bulk.tensor.2d.global.shared::cta.bulk_group [%0, {%2, %3}], [%1];"
                 ::"l"((uint64_t)tm), "r"(src), "r"(c0), "r"(c1) : "memory");
}
__device__ __forceinline__ void wgmma_fence() { asm volatile("wgmma.fence.sync.aligned;" ::: "memory"); }
__device__ __forceinline__ void wgmma_commit() { asm volatile("wgmma.commit_group.sync.aligned;" ::: "memory"); }
template <int N> __device__ __forceinline__ void wgmma_wait() { asm volatile("wgmma.wait_group.sync.aligned %0;" ::"n"(N) : "memory"); }
__device__ __forceinline__ void named_bar_arrive(int id, int n) { asm volatile("bar.arrive %0, %1;" ::"r"(id), "r"(n) : "memory"); }
__device__ __forceinline__ void named_bar_sync(int id, int n) { asm volatile("bar.sync %0, %1;" ::"r"(id), "r"(n) : "memory"); }

__device__ __forceinline__ uint32_t desc_a(uint32_t addr) { return ((addr & 0x3FFFF) >> 4) | (1u << 16); }
__device__ __forceinline__ uint32_t desc_b(uint32_t addr) { return ((addr & 0x3FFFF) >> 4) | (512u << 16); }

template <int ACC> __device__ __forceinline__ void wgmma_m64n192k16(float (&d)[96], uint32_t descA, uint32_t descB) {
  asm volatile("{\n.reg .pred p;\n.reg .b64 da, db;\nsetp.ne.b32 p, %99, 0;\nmov.b64 da, {%96, %98};\nmov.b64 db, {%97, %98};\n"
    "wgmma.mma_async.sync.aligned.m64n192k16.f32.bf16.bf16 "
    "{%0, %1, %2, %3, %4, %5, %6, %7, %8, %9, %10, %11, %12, %13, %14, %15, %16, %17, %18, %19, %20, %21, %22, %23, %24, %25, %26, %27, %28, %29, %30, %31, %32, %33, %34, %35, %36, %37, %38, %39, %40, %41, %42, %43, %44, %45, %46, %47, %48, %49, %50, %51, %52, %53, %54, %55, %56, %57, %58, %59, %60, %61, %62, %63, %64, %65, %66, %67, %68, %69, %70, %71, %72, %73, %74, %75, %76, %77, %78, %79, %80, %81, %82, %83, %84, %85, %86, %87, %88, %89, %90, %91, %92, %93, %94, %95}, "
    "da, db, p, 1, 1, 0, 1;\n}\n"
    : "+f"(d[0]), "+f"(d[1]), "+f"(d[2]), "+f"(d[3]), "+f"(d[4]), "+f"(d[5]), "+f"(d[6]), "+f"(d[7]), "+f"(d[8]), "+f"(d[9]), "+f"(d[10]), "+f"(d[11]), "+f"(d[12]), "+f"(d[13]), "+f"(d[14]), "+f"(d[15]), "+f"(d[16]), "+f"(d[17]), "+f"(d[18]), "+f"(d[19]), "+f"(d[20]), "+f"(d[21]), "+f"(d[22]), "+f"(d[23]), "+f"(d[24]), "+f"(d[25]), "+f"(d[26]), "+f"(d[27]), "+f"(d[28]), "+f"(d[29]), "+f"(d[30]), "+f"(d[31]), "+f"(d[32]), "+f"(d[33]), "+f"(d[34]), "+f"(d[35]), "+f"(d[36]), "+f"(d[37]), "+f"(d[38]), "+f"(d[39]), "+f"(d[40]), "+f"(d[41]), "+f"(d[42]), "+f"(d[43]), "+f"(d[44]), "+f"(d[45]), "+f"(d[46]), "+f"(d[47]), "+f"(d[48]), "+f"(d[49]), "+f"(d[50]), "+f"(d[51]), "+f"(d[52]), "+f"(d[53]), "+f"(d[54]), "+f"(d[55]), "+f"(d[56]), "+f"(d[57]), "+f"(d[58]), "+f"(d[59]), "+f"(d[60]), "+f"(d[61]), "+f"(d[62]), "+f"(d[63]), "+f"(d[64]), "+f"(d[65]), "+f"(d[66]), "+f"(d[67]), "+f"(d[68]), "+f"(d[69]), "+f"(d[70]), "+f"(d[71]), "+f"(d[72]), "+f"(d[73]), "+f"(d[74]), "+f"(d[75]), "+f"(d[76]), "+f"(d[77]), "+f"(d[78]), "+f"(d[79]), "+f"(d[80]), "+f"(d[81]), "+f"(d[82]), "+f"(d[83]), "+f"(d[84]), "+f"(d[85]), "+f"(d[86]), "+f"(d[87]), "+f"(d[88]), "+f"(d[89]), "+f"(d[90]), "+f"(d[91]), "+f"(d[92]), "+f"(d[93]), "+f"(d[94]), "+f"(d[95])
    : "r"(descA), "r"(descB), "r"(0x40000040u), "n"(ACC));
}

template <int ACC> __device__ __forceinline__ void wgmma_m64n256k16(float (&d)[128], uint32_t descA, uint32_t descB) {
  asm volatile("{\n.reg .pred p;\n.reg .b64 da, db;\nsetp.ne.b32 p, %131, 0;\nmov.b64 da, {%128, %130};\nmov.b64 db, {%129, %130};\n"
    "wgmma.mma_async.sync.aligned.m64n256k16.f32.bf16.bf16 "
    "{%0, %1, %2, %3, %4, %5, %6, %7, %8, %9, %10, %11, %12, %13, %14, %15, %16, %17, %18, %19, %20, %21, %22, %23, %24, %25, %26, %27, %28, %29, %30, %31, %32, %33, %34, %35, %36, %37, %38, %39, %40, %41, %42, %43, %44, %45, %46, %47, %48, %49, %50, %51, %52, %53, %54, %55, %56, %57, %58, %59, %60, %61, %62, %63, %64, %65, %66, %67, %68, %69, %70, %71, %72, %73, %74, %75, %76, %77, %78, %79, %80, %81, %82, %83, %84, %85, %86, %87, %88, %89, %90, %91, %92, %93, %94, %95, %96, %97, %98, %99, %100, %101, %102, %103, %104, %105, %106, %107, %108, %109, %110, %111, %112, %113, %114, %115, %116, %117, %118, %119, %120, %121, %122, %123, %124, %125, %126, %127}, "
    "da, db, p, 1, 1, 0, 1;\n}\n"
    : "+f"(d[0]), "+f"(d[1]), "+f"(d[2]), "+f"(d[3]), "+f"(d[4]), "+f"(d[5]), "+f"(d[6]), "+f"(d[7]), "+f"(d[8]), "+f"(d[9]), "+f"(d[10]), "+f"(d[11]), "+f"(d[12]), "+f"(d[13]), "+f"(d[14]), "+f"(d[15]), "+f"(d[16]), "+f"(d[17]), "+f"(d[18]), "+f"(d[19]), "+f"(d[20]), "+f"(d[21]), "+f"(d[22]), "+f"(d[23]), "+f"(d[24]), "+f"(d[25]), "+f"(d[26]), "+f"(d[27]), "+f"(d[28]), "+f"(d[29]), "+f"(d[30]), "+f"(d[31]), "+f"(d[32]), "+f"(d[33]), "+f"(d[34]), "+f"(d[35]), "+f"(d[36]), "+f"(d[37]), "+f"(d[38]), "+f"(d[39]), "+f"(d[40]), "+f"(d[41]), "+f"(d[42]), "+f"(d[43]), "+f"(d[44]), "+f"(d[45]), "+f"(d[46]), "+f"(d[47]), "+f"(d[48]), "+f"(d[49]), "+f"(d[50]), "+f"(d[51]), "+f"(d[52]), "+f"(d[53]), "+f"(d[54]), "+f"(d[55]), "+f"(d[56]), "+f"(d[57]), "+f"(d[58]), "+f"(d[59]), "+f"(d[60]), "+f"(d[61]), "+f"(d[62]), "+f"(d[63]), "+f"(d[64]), "+f"(d[65]), "+f"(d[66]), "+f"(d[67]), "+f"(d[68]), "+f"(d[69]), "+f"(d[70]), "+f"(d[71]), "+f"(d[72]), "+f"(d[73]), "+f"(d[74]), "+f"(d[75]), "+f"(d[76]), "+f"(d[77]), "+f"(d[78]), "+f"(d[79]), "+f"(d[80]), "+f"(d[81]), "+f"(d[82]), "+f"(d[83]), "+f"(d[84]), "+f"(d[85]), "+f"(d[86]), "+f"(d[87]), "+f"(d[88]), "+f"(d[89]), "+f"(d[90]), "+f"(d[91]), "+f"(d[92]), "+f"(d[93]), "+f"(d[94]), "+f"(d[95]), "+f"(d[96]), "+f"(d[97]), "+f"(d[98]), "+f"(d[99]), "+f"(d[100]), "+f"(d[101]), "+f"(d[102]), "+f"(d[103]), "+f"(d[104]), "+f"(d[105]), "+f"(d[106]), "+f"(d[107]), "+f"(d[108]), "+f"(d[109]), "+f"(d[110]), "+f"(d[111]), "+f"(d[112]), "+f"(d[113]), "+f"(d[114]), "+f"(d[115]), "+f"(d[116]), "+f"(d[117]), "+f"(d[118]), "+f"(d[119]), "+f"(d[120]), "+f"(d[121]), "+f"(d[122]), "+f"(d[123]), "+f"(d[124]), "+f"(d[125]), "+f"(d[126]), "+f"(d[127])
    : "r"(descA), "r"(descB), "r"(0x40000040u), "n"(ACC));
}

template <int ACC> __device__ __forceinline__ void wgmma_m64n128k16(float (&d)[64], uint32_t descA, uint32_t descB) {
  asm volatile("{\n.reg .pred p;\n.reg .b64 da, db;\nsetp.ne.b32 p, %67, 0;\nmov.b64 da, {%64, %66};\nmov.b64 db, {%65, %66};\n"
    "wgmma.mma_async.sync.aligned.m64n128k16.f32.bf16.bf16 "
    "{%0, %1, %2, %3, %4, %5, %6, %7, %8, %9, %10, %11, %12, %13, %14, %15, %16, %17, %18, %19, %20, %21, %22, %23, %24, %25, %26, %27, %28, %29, %30, %31, %32, %33, %34, %35, %36, %37, %38, %39, %40, %41, %42, %43, %44, %45, %46, %47, %48, %49, %50, %51, %52, %53, %54, %55, %56, %57, %58, %59, %60, %61, %62, %63}, "
    "da, db, p, 1, 1, 0, 1;\n}\n"
    : "+f"(d[0]), "+f"(d[1]), "+f"(d[2]), "+f"(d[3]), "+f"(d[4]), "+f"(d[5]), "+f"(d[6]), "+f"(d[7]), "+f"(d[8]), "+f"(d[9]), "+f"(d[10]), "+f"(d[11]), "+f"(d[12]), "+f"(d[13]), "+f"(d[14]), "+f"(d[15]), "+f"(d[16]), "+f"(d[17]), "+f"(d[18]), "+f"(d[19]), "+f"(d[20]), "+f"(d[21]), "+f"(d[22]), "+f"(d[23]), "+f"(d[24]), "+f"(d[25]), "+f"(d[26]), "+f"(d[27]), "+f"(d[28]), "+f"(d[29]), "+f"(d[30]), "+f"(d[31]), "+f"(d[32]), "+f"(d[33]), "+f"(d[34]), "+f"(d[35]), "+f"(d[36]), "+f"(d[37]), "+f"(d[38]), "+f"(d[39]), "+f"(d[40]), "+f"(d[41]), "+f"(d[42]), "+f"(d[43]), "+f"(d[44]), "+f"(d[45]), "+f"(d[46]), "+f"(d[47]), "+f"(d[48]), "+f"(d[49]), "+f"(d[50]), "+f"(d[51]), "+f"(d[52]), "+f"(d[53]), "+f"(d[54]), "+f"(d[55]), "+f"(d[56]), "+f"(d[57]), "+f"(d[58]), "+f"(d[59]), "+f"(d[60]), "+f"(d[61]), "+f"(d[62]), "+f"(d[63])
    : "r"(descA), "r"(descB), "r"(0x40000040u), "n"(ACC));
}

template <int BN> struct WG;
template <> struct WG<128> { template <int ACC> static __device__ __forceinline__ void mma(float (&d)[64], uint32_t a, uint32_t b) { wgmma_m64n128k16<ACC>(d, a, b); } };
template <> struct WG<256> { template <int ACC> static __device__ __forceinline__ void mma(float (&d)[128], uint32_t a, uint32_t b) { wgmma_m64n256k16<ACC>(d, a, b); } };
template <> struct WG<192> { template <int ACC> static __device__ __forceinline__ void mma(float (&d)[96], uint32_t a, uint32_t b) { wgmma_m64n192k16<ACC>(d, a, b); } };

#define DBG_T(i)
__device__ __forceinline__ void fence_async_smem() { asm volatile("fence.proxy.async.shared::cta;" ::: "memory"); }
__device__ __forceinline__ void prefetch_tmap(const CUtensorMap* tm) { asm volatile("prefetch.tensormap [%0];" ::"l"((uint64_t)tm) : "memory"); }
__device__ __forceinline__ uint32_t mapa_u32(uint32_t addr, uint32_t cta) {
    uint32_t r;
    asm volatile("mapa.shared::cluster.u32 %0, %1, %2;" : "=r"(r) : "r"(addr), "r"(cta));
    return r;
}
__device__ __forceinline__ void mbar_arrive_cluster(uint32_t cluster_addr) {
    asm volatile("mbarrier.arrive.shared::cluster.b64 _, [%0];" ::"r"(cluster_addr) : "memory");
}
__device__ __forceinline__ bool elect_one() {
    uint32_t p;
    asm volatile("{\n.reg .pred P;\nelect.sync _|P, 0xffffffff;\nselp.u32 %0, 1, 0, P;\n}\n" : "=r"(p));
    return p != 0;
}
__device__ __forceinline__ void cluster_arrive_relaxed() { asm volatile("barrier.cluster.arrive.relaxed.aligned;" ::: "memory"); }
__device__ __forceinline__ void cluster_wait() { asm volatile("barrier.cluster.wait.acquire.aligned;" ::: "memory"); }

__device__ __forceinline__ uint32_t bsub2(uint32_t a, uint32_t b) {
    __nv_bfloat162 r = __hsub2(*reinterpret_cast<__nv_bfloat162*>(&a), *reinterpret_cast<__nv_bfloat162*>(&b));
    return *reinterpret_cast<uint32_t*>(&r);
}
__device__ __forceinline__ uint32_t bmul2(uint32_t a, uint32_t b) {
    __nv_bfloat162 r = __hmul2(*reinterpret_cast<__nv_bfloat162*>(&a), *reinterpret_cast<__nv_bfloat162*>(&b));
    return *reinterpret_cast<uint32_t*>(&r);
}
__device__ __forceinline__ uint32_t badd2(uint32_t a, uint32_t b) {
    __nv_bfloat162 r = __hadd2(*reinterpret_cast<__nv_bfloat162*>(&a), *reinterpret_cast<__nv_bfloat162*>(&b));
    return *reinterpret_cast<uint32_t*>(&r);
}
constexpr int BM = 128, BK = 64;
constexpr int R5_STAGE = 32768, R5_N = 5;
constexpr int R4_STAGE = 49152, R4_N = 4;
constexpr int R4B_STAGE = 40960;
constexpr int OFF_STG5 = 0, OFF_R = 32768;
constexpr int OFF_EPI = 196608;
constexpr int OFF_BAR = OFF_EPI + 32768;
constexpr int OFF_RS = OFF_BAR + 256;
constexpr int OFF_CS = OFF_RS + 1024;
constexpr int MEGA_SMEM = OFF_CS + 1792;
enum { FL_XA = 0, FL_H = 2, FL_X1 = 4, FL_H2 = 6, FL_CS = 10, FL_KINDS = 11 };
constexpr int FL_PITCH = 64;
constexpr int FL_WORDS = 2 * FL_KINDS * 16 * FL_PITCH;
__device__ unsigned int g_flag[FL_WORDS];
__device__ __align__(8) unsigned int g_ticket[18 * FL_PITCH];
constexpr int NCL = 66;
__device__ __forceinline__ unsigned int* flag_ptr(int layer, int kind, int i) { return g_flag + ((layer * FL_KINDS + kind) * 16 + i) * FL_PITCH; }

__device__ __forceinline__ void wait_flag(const unsigned int* p, unsigned int target) {
    long long t0 = clock64();
    while (true) {
        unsigned int v;
        asm volatile("ld.relaxed.gpu.global.u32 %0, [%1];" : "=r"(v) : "l"(p) : "memory");
        if ((int)(v - target) >= 0) break;
        if (clock64() - t0 > 2000000000LL) break;
    }
    asm volatile("fence.acquire.gpu;" ::: "memory");
}
__device__ __forceinline__ void fence_proxy_async() {
    asm volatile("fence.proxy.async.global;" ::: "memory");
    asm volatile("fence.proxy.async.shared::cta;" ::: "memory");
}
__device__ __forceinline__ void stsm4(uint32_t addr, uint32_t r0, uint32_t r1, uint32_t r2, uint32_t r3) {
    asm volatile("stmatrix.sync.aligned.m8n8.x4.shared.b16 [%0], {%1,%2,%3,%4};" ::"r"(addr), "r"(r0), "r"(r1), "r"(r2), "r"(r3));
}
__device__ __forceinline__ uint4 lds128(uint32_t a) {
    uint4 v;
    asm volatile("ld.shared.v4.b32 {%0,%1,%2,%3}, [%4];" : "=r"(v.x), "=r"(v.y), "=r"(v.z), "=r"(v.w) : "r"(a) : "memory");
    return v;
}
__device__ __forceinline__ void stg128(void* p, uint4 v) {
    asm volatile("st.global.v4.b32 [%0], {%1,%2,%3,%4};" ::"l"(p), "r"(v.x), "r"(v.y), "r"(v.z), "r"(v.w) : "memory");
}
__device__ __forceinline__ float gelu_tanh_h(float hx) {
    float z = hx * fmaf(hx * hx, 8.0f * 0.035677408136300125f, 2.0f * 0.7978845608028654f);
    float t;
    asm("tanh.approx.f32 %0, %1;" : "=f"(t) : "f"(z));
    return fmaf(hx, t, hx);
}
__device__ __forceinline__ uint32_t gelu2h(uint32_t hx) {
    uint32_t r;
    asm("{\n.reg .b32 z;\nmul.rn.bf16x2 z, %1, %1;\nfma.rn.bf16x2 z, z, %2, %3;\nmul.rn.bf16x2 z, z, %1;\ntanh.approx.bf16x2 z, z;\nfma.rn.bf16x2 %0, %1, z, %1;\n}"
        : "=r"(r) : "r"(hx), "r"(0x3e923e92u), "r"(0x3fcc3fccu));
    return r;
}
__device__ __forceinline__ uint4 gelu8h(uint4 v) { return make_uint4(gelu2h(v.x), gelu2h(v.y), gelu2h(v.z), gelu2h(v.w)); }

__device__ __forceinline__ void row_stats(const float2* p, uint32_t tag, float& mean, float& var) {
    float2 v[8];
#pragma unroll 1
    for (int n = 0; n < (1 << 20); n++) {
#pragma unroll
        for (int i = 0; i < 8; i++)
            asm volatile("{\n.reg .b64 t;\nld.relaxed.gpu.global.b64 t, [%2];\nmov.b64 {%0, %1}, t;\n}" : "=f"(v[i].x), "=f"(v[i].y) : "l"(p + 128 * i) : "memory");
        uint32_t old = 0;
#pragma unroll
        for (int i = 0; i < 8; i++) old |= __float_as_uint(v[i].y) ^ tag;
        if ((int)old >= 0) break;
    }
    mean = (((v[0].x + v[1].x) + (v[2].x + v[3].x)) + ((v[4].x + v[5].x) + (v[6].x + v[7].x))) * 0.125f;
    float m2 = 0.f, d2 = 0.f;
#pragma unroll
    for (int i = 0; i < 8; i++) { m2 += fabsf(v[i].y); d2 = fmaf(v[i].x - mean, v[i].x - mean, d2); }
    var = fmaf(128.0f, d2, m2) * (1.0f / D_);
}
struct RingState { uint32_t st, ph; };

#define DT(i)
#define DT_DECL
#define DT_PAR
#define DT_ARG
#define DT_DUMP
#define DP(i)
#define GT(i)
#define TM(i)

template <int BN, int NST, int ACC = 1>
__device__ __forceinline__ void kblock(float (&acc)[BN / 2], uint32_t da, uint32_t db, uint32_t bfull, RingState& rs) {
    mbar_wait(bfull + 8 * rs.st, rs.ph);
    wgmma_fence();
    WG<BN>::template mma<ACC>(acc, da, db);
#pragma unroll
    for (int k = 1; k < 4; k++) WG<BN>::template mma<1>(acc, da + k * 2, db + k * 128);
    wgmma_commit();
    if (++rs.st == NST) { rs.st = 0; rs.ph ^= 1; }
}
template <int BN, int NST, int STAGE, class F>
__device__ __forceinline__ void mainloop(float (&acc)[BN / 2], int KB, uint32_t da0, uint32_t db0, uint32_t bfull, uint32_t rel, bool rel_on,
                                         RingState& rs, int dbg, F pre DT_PAR) {
    uint32_t prev = rs.st ? rs.st - 1 : NST - 1;
#pragma unroll 1
    for (int kk = 0; kk < KB; kk++) {
        const uint32_t cur = rs.st;
        kblock<BN, NST>(acc, da0 + cur * (STAGE / 16), db0 + cur * (STAGE / 16), bfull, rs);
        wgmma_wait<1>();
        if (rel_on) mbar_arrive_cluster(rel + 8 * prev);
        prev = cur;
    }
    pre();
    wgmma_wait<0>();
#pragma unroll
    for (int i = 0; i < BN / 2; i++) asm volatile("" : "+f"(acc[i])::"memory");
    if (rel_on) mbar_arrive_cluster(rel + 8 * prev);
}
__device__ __forceinline__ void hmma(float (&c)[4], uint32_t a0, uint32_t a1, uint32_t a2, uint32_t a3, uint32_t b0, uint32_t b1, bool first) {
    if (first) asm("{\n.reg .f32 z;\nmov.f32 z, 0f00000000;\nmma.sync.aligned.m16n8k16.row.col.f32.bf16.bf16.f32 {%0,%1,%2,%3}, {%4,%5,%6,%7}, {%8,%9}, {z,z,z,z};\n}"
        : "=f"(c[0]), "=f"(c[1]), "=f"(c[2]), "=f"(c[3]) : "r"(a0), "r"(a1), "r"(a2), "r"(a3), "r"(b0), "r"(b1));
    else
    asm("mma.sync.aligned.m16n8k16.row.col.f32.bf16.bf16.f32 {%0,%1,%2,%3}, {%4,%5,%6,%7}, {%8,%9}, {%0,%1,%2,%3};"
        : "+f"(c[0]), "+f"(c[1]), "+f"(c[2]), "+f"(c[3]) : "r"(a0), "r"(a1), "r"(a2), "r"(a3), "r"(b0), "r"(b1));
}
__device__ __forceinline__ void hmma8(float (&c)[4], uint32_t a0, uint32_t a1, uint32_t b0, bool first) {
    if (first) asm("{\n.reg .f32 z;\nmov.f32 z, 0f00000000;\nmma.sync.aligned.m16n8k8.row.col.f32.bf16.bf16.f32 {%0,%1,%2,%3}, {%4,%5}, {%6}, {z,z,z,z};\n}"
        : "=f"(c[0]), "=f"(c[1]), "=f"(c[2]), "=f"(c[3]) : "r"(a0), "r"(a1), "r"(b0));
    else
    asm("mma.sync.aligned.m16n8k8.row.col.f32.bf16.bf16.f32 {%0,%1,%2,%3}, {%4,%5}, {%6}, {%0,%1,%2,%3};"
        : "+f"(c[0]), "+f"(c[1]), "+f"(c[2]), "+f"(c[3]) : "r"(a0), "r"(a1), "r"(b0));
}
__device__ __forceinline__ void put_stats(const uint32_t (&w)[32], float2* p, uint32_t tag) {
    const int lane = threadIdx.x & 31;
    float c[6][4];
#pragma unroll
    for (int e = 0; e < 32; e++) {
        hmma8(c[e & 3], w[e & ~1], w[e | 1], w[e], e < 4);
        if ((e & 3) == 0) hmma(c[4 + (e >> 2 & 1)], w[e], w[e + 1], w[e + 2], w[e + 3], 0x3f803f80u, 0x3f803f80u, e < 8);
    }
    if ((lane & 3) == lane >> 3) {
#pragma unroll
        for (int e = 0; e < 2; e++) {
            const float q1 = lane & 4 ? c[e][2 * e + 1] + c[e + 2][2 * e + 1] : c[e][2 * e] + c[e + 2][2 * e], s1 = c[4][2 * e] + c[5][2 * e], mu = s1 * (1.0f / 128);
            asm volatile("{\n.reg .b64 t;\nmov.b64 t, {%1, %2};\nst.relaxed.gpu.global.b64 [%0], t;\n}"
                         ::"l"(p + 8 * e), "f"(mu), "r"(__float_as_uint(fmaxf(q1 - s1 * mu, 0.f)) | tag) : "memory");
        }
    }
}
template <int N> __device__ __forceinline__ void zero_acc(float (&acc)[N]) {
#pragma unroll
    for (int i = 0; i < N; i++) acc[i] = 0.f;
}
__device__ __forceinline__ void ldsm4(uint32_t& r0, uint32_t& r1, uint32_t& r2, uint32_t& r3, uint32_t addr) {
    asm volatile("ldmatrix.sync.aligned.m8n8.x4.shared.b16 {%0,%1,%2,%3}, [%4];" : "=r"(r0), "=r"(r1), "=r"(r2), "=r"(r3) : "r"(addr));
}

__device__ __forceinline__ void ldsm4t(uint32_t& r0, uint32_t& r1, uint32_t& r2, uint32_t& r3, uint32_t addr) {
    asm volatile("ldmatrix.sync.aligned.m8n8.x4.trans.shared.b16 {%0,%1,%2,%3}, [%4];" : "=r"(r0), "=r"(r1), "=r"(r2), "=r"(r3) : "r"(addr));
}

#define DBG_S(i)
#define DBG_OUT(r, o)
#define DBG_F(i)
#define DBG_W(i)
constexpr int CV_CH = 8;
constexpr int CV_SL = 16384;
constexpr int CV_QG = 128 * 8 + 16;
constexpr int CV_HPL = 2048 + 192;
constexpr int CV_0 = 32768, CV_H = 9 * CV_SL, CV_BAR = OFF_RS - CV_0;

template <int K> __device__ __forceinline__ void cv_mma(float (&d)[64], const uint32_t (&a)[4], uint32_t db, int acc);
template <> __device__ __forceinline__ void cv_mma<0>(float (&d)[64], const uint32_t (&a)[4], uint32_t db, int acc) {
    asm volatile("{\n.reg .pred p;\n.reg .b64 b;\nsetp.ne.b32 p, %70, 0;\nmov.b64 b, {%68, %69};\n"
        "wgmma.mma_async.sync.aligned.m64n128k16.f32.bf16.bf16 {%0,%1,%2,%3,%4,%5,%6,%7,%8,%9,%10,%11,%12,%13,%14,%15,%16,%17,%18,%19,%20,%21,%22,%23,%24,%25,%26,%27,%28,%29,%30,%31,%32,%33,%34,%35,%36,%37,%38,%39,%40,%41,%42,%43,%44,%45,%46,%47,%48,%49,%50,%51,%52,%53,%54,%55,%56,%57,%58,%59,%60,%61,%62,%63}, {%64,%65,%66,%67}, b, p, 1, 1, 0;\n}\n"
        : "+f"(d[0]), "+f"(d[1]), "+f"(d[2]), "+f"(d[3]), "+f"(d[4]), "+f"(d[5]), "+f"(d[6]), "+f"(d[7]), "+f"(d[8]), "+f"(d[9]), "+f"(d[10]), "+f"(d[11]), "+f"(d[12]), "+f"(d[13]), "+f"(d[14]), "+f"(d[15]), "+f"(d[16]), "+f"(d[17]), "+f"(d[18]), "+f"(d[19]), "+f"(d[20]), "+f"(d[21]), "+f"(d[22]), "+f"(d[23]), "+f"(d[24]), "+f"(d[25]), "+f"(d[26]), "+f"(d[27]), "+f"(d[28]), "+f"(d[29]), "+f"(d[30]), "+f"(d[31]), "+f"(d[32]), "+f"(d[33]), "+f"(d[34]), "+f"(d[35]), "+f"(d[36]), "+f"(d[37]), "+f"(d[38]), "+f"(d[39]), "+f"(d[40]), "+f"(d[41]), "+f"(d[42]), "+f"(d[43]), "+f"(d[44]), "+f"(d[45]), "+f"(d[46]), "+f"(d[47]), "+f"(d[48]), "+f"(d[49]), "+f"(d[50]), "+f"(d[51]), "+f"(d[52]), "+f"(d[53]), "+f"(d[54]), "+f"(d[55]), "+f"(d[56]), "+f"(d[57]), "+f"(d[58]), "+f"(d[59]), "+f"(d[60]), "+f"(d[61]), "+f"(d[62]), "+f"(d[63])
        : "r"(a[0]), "r"(a[1]), "r"(a[2]), "r"(a[3]), "r"(db), "r"(8u), "r"(acc));
}
template <> __device__ __forceinline__ void cv_mma<1>(float (&d)[64], const uint32_t (&a)[4], uint32_t db, int acc) {
    asm volatile("{\n.reg .pred p;\n.reg .b64 b;\nsetp.ne.b32 p, %62, 0;\nmov.b64 b, {%60, %61};\n"
        "wgmma.mma_async.sync.aligned.m64n112k16.f32.bf16.bf16 {%0,%1,%2,%3,%4,%5,%6,%7,%8,%9,%10,%11,%12,%13,%14,%15,%16,%17,%18,%19,%20,%21,%22,%23,%24,%25,%26,%27,%28,%29,%30,%31,%32,%33,%34,%35,%36,%37,%38,%39,%40,%41,%42,%43,%44,%45,%46,%47,%48,%49,%50,%51,%52,%53,%54,%55}, {%56,%57,%58,%59}, b, p, 1, 1, 0;\n}\n"
        : "+f"(d[0]), "+f"(d[1]), "+f"(d[2]), "+f"(d[3]), "+f"(d[4]), "+f"(d[5]), "+f"(d[6]), "+f"(d[7]), "+f"(d[8]), "+f"(d[9]), "+f"(d[10]), "+f"(d[11]), "+f"(d[12]), "+f"(d[13]), "+f"(d[14]), "+f"(d[15]), "+f"(d[16]), "+f"(d[17]), "+f"(d[18]), "+f"(d[19]), "+f"(d[20]), "+f"(d[21]), "+f"(d[22]), "+f"(d[23]), "+f"(d[24]), "+f"(d[25]), "+f"(d[26]), "+f"(d[27]), "+f"(d[28]), "+f"(d[29]), "+f"(d[30]), "+f"(d[31]), "+f"(d[32]), "+f"(d[33]), "+f"(d[34]), "+f"(d[35]), "+f"(d[36]), "+f"(d[37]), "+f"(d[38]), "+f"(d[39]), "+f"(d[40]), "+f"(d[41]), "+f"(d[42]), "+f"(d[43]), "+f"(d[44]), "+f"(d[45]), "+f"(d[46]), "+f"(d[47]), "+f"(d[48]), "+f"(d[49]), "+f"(d[50]), "+f"(d[51]), "+f"(d[52]), "+f"(d[53]), "+f"(d[54]), "+f"(d[55])
        : "r"(a[0]), "r"(a[1]), "r"(a[2]), "r"(a[3]), "r"(db), "r"(8u), "r"(acc));
}
template <> __device__ __forceinline__ void cv_mma<2>(float (&d)[64], const uint32_t (&a)[4], uint32_t db, int acc) {
    asm volatile("{\n.reg .pred p;\n.reg .b64 b;\nsetp.ne.b32 p, %54, 0;\nmov.b64 b, {%52, %53};\n"
        "wgmma.mma_async.sync.aligned.m64n96k16.f32.bf16.bf16 {%0,%1,%2,%3,%4,%5,%6,%7,%8,%9,%10,%11,%12,%13,%14,%15,%16,%17,%18,%19,%20,%21,%22,%23,%24,%25,%26,%27,%28,%29,%30,%31,%32,%33,%34,%35,%36,%37,%38,%39,%40,%41,%42,%43,%44,%45,%46,%47}, {%48,%49,%50,%51}, b, p, 1, 1, 0;\n}\n"
        : "+f"(d[0]), "+f"(d[1]), "+f"(d[2]), "+f"(d[3]), "+f"(d[4]), "+f"(d[5]), "+f"(d[6]), "+f"(d[7]), "+f"(d[8]), "+f"(d[9]), "+f"(d[10]), "+f"(d[11]), "+f"(d[12]), "+f"(d[13]), "+f"(d[14]), "+f"(d[15]), "+f"(d[16]), "+f"(d[17]), "+f"(d[18]), "+f"(d[19]), "+f"(d[20]), "+f"(d[21]), "+f"(d[22]), "+f"(d[23]), "+f"(d[24]), "+f"(d[25]), "+f"(d[26]), "+f"(d[27]), "+f"(d[28]), "+f"(d[29]), "+f"(d[30]), "+f"(d[31]), "+f"(d[32]), "+f"(d[33]), "+f"(d[34]), "+f"(d[35]), "+f"(d[36]), "+f"(d[37]), "+f"(d[38]), "+f"(d[39]), "+f"(d[40]), "+f"(d[41]), "+f"(d[42]), "+f"(d[43]), "+f"(d[44]), "+f"(d[45]), "+f"(d[46]), "+f"(d[47])
        : "r"(a[0]), "r"(a[1]), "r"(a[2]), "r"(a[3]), "r"(db), "r"(8u), "r"(acc));
}
template <> __device__ __forceinline__ void cv_mma<3>(float (&d)[64], const uint32_t (&a)[4], uint32_t db, int acc) {
    asm volatile("{\n.reg .pred p;\n.reg .b64 b;\nsetp.ne.b32 p, %46, 0;\nmov.b64 b, {%44, %45};\n"
        "wgmma.mma_async.sync.aligned.m64n80k16.f32.bf16.bf16 {%0,%1,%2,%3,%4,%5,%6,%7,%8,%9,%10,%11,%12,%13,%14,%15,%16,%17,%18,%19,%20,%21,%22,%23,%24,%25,%26,%27,%28,%29,%30,%31,%32,%33,%34,%35,%36,%37,%38,%39}, {%40,%41,%42,%43}, b, p, 1, 1, 0;\n}\n"
        : "+f"(d[0]), "+f"(d[1]), "+f"(d[2]), "+f"(d[3]), "+f"(d[4]), "+f"(d[5]), "+f"(d[6]), "+f"(d[7]), "+f"(d[8]), "+f"(d[9]), "+f"(d[10]), "+f"(d[11]), "+f"(d[12]), "+f"(d[13]), "+f"(d[14]), "+f"(d[15]), "+f"(d[16]), "+f"(d[17]), "+f"(d[18]), "+f"(d[19]), "+f"(d[20]), "+f"(d[21]), "+f"(d[22]), "+f"(d[23]), "+f"(d[24]), "+f"(d[25]), "+f"(d[26]), "+f"(d[27]), "+f"(d[28]), "+f"(d[29]), "+f"(d[30]), "+f"(d[31]), "+f"(d[32]), "+f"(d[33]), "+f"(d[34]), "+f"(d[35]), "+f"(d[36]), "+f"(d[37]), "+f"(d[38]), "+f"(d[39])
        : "r"(a[0]), "r"(a[1]), "r"(a[2]), "r"(a[3]), "r"(db), "r"(8u), "r"(acc));
}
template <> __device__ __forceinline__ void cv_mma<4>(float (&d)[64], const uint32_t (&a)[4], uint32_t db, int acc) {
    asm volatile("{\n.reg .pred p;\n.reg .b64 b;\nsetp.ne.b32 p, %38, 0;\nmov.b64 b, {%36, %37};\n"
        "wgmma.mma_async.sync.aligned.m64n64k16.f32.bf16.bf16 {%0,%1,%2,%3,%4,%5,%6,%7,%8,%9,%10,%11,%12,%13,%14,%15,%16,%17,%18,%19,%20,%21,%22,%23,%24,%25,%26,%27,%28,%29,%30,%31}, {%32,%33,%34,%35}, b, p, 1, 1, 0;\n}\n"
        : "+f"(d[0]), "+f"(d[1]), "+f"(d[2]), "+f"(d[3]), "+f"(d[4]), "+f"(d[5]), "+f"(d[6]), "+f"(d[7]), "+f"(d[8]), "+f"(d[9]), "+f"(d[10]), "+f"(d[11]), "+f"(d[12]), "+f"(d[13]), "+f"(d[14]), "+f"(d[15]), "+f"(d[16]), "+f"(d[17]), "+f"(d[18]), "+f"(d[19]), "+f"(d[20]), "+f"(d[21]), "+f"(d[22]), "+f"(d[23]), "+f"(d[24]), "+f"(d[25]), "+f"(d[26]), "+f"(d[27]), "+f"(d[28]), "+f"(d[29]), "+f"(d[30]), "+f"(d[31])
        : "r"(a[0]), "r"(a[1]), "r"(a[2]), "r"(a[3]), "r"(db), "r"(8u), "r"(acc));
}
template <> __device__ __forceinline__ void cv_mma<5>(float (&d)[64], const uint32_t (&a)[4], uint32_t db, int acc) {
    asm volatile("{\n.reg .pred p;\n.reg .b64 b;\nsetp.ne.b32 p, %30, 0;\nmov.b64 b, {%28, %29};\n"
        "wgmma.mma_async.sync.aligned.m64n48k16.f32.bf16.bf16 {%0,%1,%2,%3,%4,%5,%6,%7,%8,%9,%10,%11,%12,%13,%14,%15,%16,%17,%18,%19,%20,%21,%22,%23}, {%24,%25,%26,%27}, b, p, 1, 1, 0;\n}\n"
        : "+f"(d[0]), "+f"(d[1]), "+f"(d[2]), "+f"(d[3]), "+f"(d[4]), "+f"(d[5]), "+f"(d[6]), "+f"(d[7]), "+f"(d[8]), "+f"(d[9]), "+f"(d[10]), "+f"(d[11]), "+f"(d[12]), "+f"(d[13]), "+f"(d[14]), "+f"(d[15]), "+f"(d[16]), "+f"(d[17]), "+f"(d[18]), "+f"(d[19]), "+f"(d[20]), "+f"(d[21]), "+f"(d[22]), "+f"(d[23])
        : "r"(a[0]), "r"(a[1]), "r"(a[2]), "r"(a[3]), "r"(db), "r"(8u), "r"(acc));
}
template <> __device__ __forceinline__ void cv_mma<6>(float (&d)[64], const uint32_t (&a)[4], uint32_t db, int acc) {
    asm volatile("{\n.reg .pred p;\n.reg .b64 b;\nsetp.ne.b32 p, %22, 0;\nmov.b64 b, {%20, %21};\n"
        "wgmma.mma_async.sync.aligned.m64n32k16.f32.bf16.bf16 {%0,%1,%2,%3,%4,%5,%6,%7,%8,%9,%10,%11,%12,%13,%14,%15}, {%16,%17,%18,%19}, b, p, 1, 1, 0;\n}\n"
        : "+f"(d[0]), "+f"(d[1]), "+f"(d[2]), "+f"(d[3]), "+f"(d[4]), "+f"(d[5]), "+f"(d[6]), "+f"(d[7]), "+f"(d[8]), "+f"(d[9]), "+f"(d[10]), "+f"(d[11]), "+f"(d[12]), "+f"(d[13]), "+f"(d[14]), "+f"(d[15])
        : "r"(a[0]), "r"(a[1]), "r"(a[2]), "r"(a[3]), "r"(db), "r"(8u), "r"(acc));
}
template <> __device__ __forceinline__ void cv_mma<7>(float (&d)[64], const uint32_t (&a)[4], uint32_t db, int acc) {
    asm volatile("{\n.reg .pred p;\n.reg .b64 b;\nsetp.ne.b32 p, %14, 0;\nmov.b64 b, {%12, %13};\n"
        "wgmma.mma_async.sync.aligned.m64n16k16.f32.bf16.bf16 {%0,%1,%2,%3,%4,%5,%6,%7}, {%8,%9,%10,%11}, b, p, 1, 1, 0;\n}\n"
        : "+f"(d[0]), "+f"(d[1]), "+f"(d[2]), "+f"(d[3]), "+f"(d[4]), "+f"(d[5]), "+f"(d[6]), "+f"(d[7])
        : "r"(a[0]), "r"(a[1]), "r"(a[2]), "r"(a[3]), "r"(db), "r"(8u), "r"(acc));
}
__device__ __forceinline__ void stsm4t(uint32_t addr, uint32_t r0, uint32_t r1, uint32_t r2, uint32_t r3) {
    asm volatile("stmatrix.sync.aligned.m8n8.x4.trans.shared.b16 [%0], {%1,%2,%3,%4};" ::"r"(addr), "r"(r0), "r"(r1), "r"(r2), "r"(r3) : "memory");
}
__device__ __forceinline__ void cp16(uint32_t dst, const void* src, int n = 16) {
    asm volatile("cp.async.cg.shared.global.L2::128B [%0], [%1], 16, %2;" ::"r"(dst), "l"(src), "r"(n) : "memory");
}
__device__ __forceinline__ void cp_arrive(uint32_t bar) { asm volatile("cp.async.mbarrier.arrive.noinc.shared::cta.b64 [%0];" ::"r"(bar) : "memory"); }
__device__ __forceinline__ void lds64(uint32_t& x, uint32_t& y, uint32_t a) { asm volatile("ld.shared.v2.b32 {%0,%1}, [%2];" : "=r"(x), "=r"(y) : "r"(a) : "memory"); }
__device__ __forceinline__ void sts128(uint32_t a, uint32_t x, uint32_t y, uint32_t z, uint32_t w) {
    asm volatile("st.shared.v4.b32 [%0], {%1,%2,%3,%4};" ::"r"(a), "r"(x), "r"(y), "r"(z), "r"(w) : "memory");
}
__device__ __forceinline__ uint32_t bfma2(uint32_t a, uint32_t b, uint32_t c) {
    uint32_t r;
    asm("fma.rn.bf16x2 %0, %1, %2, %3;" : "=r"(r) : "r"(a), "r"(b), "r"(c));
    return r;
}
__device__ __forceinline__ uint32_t split(float r) { const float h = bfr(r); return pack2(h, r - h); }
__device__ __forceinline__ uint32_t norm2(uint32_t x, uint32_t m, uint32_t r) {
    const uint32_t d = bsub2(x, m);
    return bfma2(d, __byte_perm(r, 0, 0x1010), bmul2(d, __byte_perm(r, 0, 0x3232)));
}
#define CV_NS 4
#define CV_W 1
constexpr int CV_GC = 8 / CV_NS, CV_NA = (CV_W + 2) * CV_NS;
struct CvAddr { uint32_t pa[2], p0[4], db, rdy, xw, xr, bar; bool wrap, neg[2]; };
template <int G> __device__ __forceinline__ void cv_load(uint32_t (&a)[CV_NA][4], const CvAddr& p) {
    if constexpr (G % CV_GC == 0) mbar_wait(p.rdy + 8 * (G / CV_GC), 0);
#pragma unroll
    for (int i = G * CV_NS; i < (G + 1) * CV_NS; i++) {
        const int of = (i / 2 % 2) * CV_QG + (i / 8) * CV_SL + 256 * (i % 2 + (i / 2 & 2));
        if ((i & 5) == 0) {
#pragma unroll
            for (int e = 0; e < 4; e++) asm volatile("ld.shared.b32 %0, [%1];" : "=r"(a[i % CV_NA][e]) : "r"(p.p0[e] + of) : "memory");
            if (i < 8) { if (p.neg[0]) a[i % CV_NA][0] = 0; if (p.neg[1]) a[i % CV_NA][2] = 0; }
        } else {
            lds64(a[i % CV_NA][0], a[i % CV_NA][1], p.pa[0] + of - 256);
            lds64(a[i % CV_NA][2], a[i % CV_NA][3], p.pa[1] + of - 256);
        }
    }
}
__device__ __forceinline__ float vadd(float a, float b) {
    float r;
    asm volatile("add.f32 %0, %1, %2;" : "=f"(r) : "f"(a), "f"(b));
    return r;
}
template <int K> __device__ __forceinline__ uint32_t cv_tail(float (&d)[64], bool wrap) {
    float* z = d + 56 - 8 * K;
    z[4] = vadd(z[4], K > 0 ? z[10] : 0.f);
    if constexpr (K > 0) z[5] = vadd(z[5], z[11]);
    z[0] = vadd(z[0], z[6]);
    z[1] = vadd(z[1], z[7]);
    return pack2(wrap ? (K > 0 ? z[8] : 0.f) : z[4], wrap ? z[4] : z[0]);
}
template <int K> __device__ __forceinline__ uint32_t cv_fin(const float (&d)[64], uint32_t x) { return pack2(d[61 - 8 * K] + lo2f(x), d[57 - 8 * K] + hi2f(x)); }
__device__ __forceinline__ void put_y(int first) {
    asm volatile("cp.async.bulk.wait_group 0;" ::: "memory");
    asm volatile("red.relaxed.gpu.global.add.u32 [%0], 1;" ::"l"(flag_ptr(first, FL_CS, 8 + (blockIdx.x >> 4))) : "memory");
}
template <int G>
__device__ __forceinline__ void cv_steps(float (&d)[2][64], uint32_t (&a)[CV_NA][4], uint32_t (&tv)[2][8], const CvAddr& p) {
    constexpr int K = G / CV_GC, GN = 8 * CV_GC;
    constexpr int T = G - CV_W - CV_GC, F = T - 1, TK = T / CV_GC, FK = F / CV_GC;
    if constexpr (G == 0) cv_load<0>(a, p);
    if constexpr (G < GN) {
        wgmma_fence();
#pragma unroll
        for (int i = G * CV_NS; i < (G + 1) * CV_NS; i++)
            cv_mma<K>(d[i / 2 % 2], a[i % CV_NA], p.db + (i / 2 % 2) * (CV_HPL / 8) + 16 * K + 2 * (i % 2 + (i / 2 & 2)), i & ~2 ? 1 : p.bar >> 8);
        wgmma_commit();
    }
    if constexpr (G < GN - 1) cv_load<G + 1>(a, p);
    if constexpr (T >= 0 && T % CV_GC == 0) {
        tv[0][TK] = cv_tail<TK>(d[0], p.wrap);
        tv[1][TK] = cv_tail<TK>(d[1], p.wrap);
        if constexpr (TK & 1) sts128(p.xw + TK / 2 * 512, tv[0][TK - 1], tv[0][TK], tv[1][TK - 1], tv[1][TK]);
    }
    if constexpr (F >= 0 && F % (2 * CV_GC) == CV_GC) {
        const uint4 x = lds128(p.xr + FK / 2 * 512);
        tv[0][FK - 1] = cv_fin<FK - 1>(d[0], x.x); tv[0][FK] = cv_fin<FK>(d[0], x.y);
        tv[1][FK - 1] = cv_fin<FK - 1>(d[1], x.z); tv[1][FK] = cv_fin<FK>(d[1], x.w);
    }
    if constexpr (G < GN - 1) wgmma_wait<CV_W>();
    if constexpr (G == GN - 1) wgmma_wait<0>();
    if constexpr (T >= 0 && T % (2 * CV_GC) == CV_GC) named_bar_sync(p.bar, 128);
    if constexpr (F < GN - CV_GC) cv_steps<G + 1>(d, a, tv, p);
}

#define CV_PF 7
#define Y_AT 4
#define P0_WAIT 0
#define PS2_EARLY 1
#define PS1_EARLY 1
#define FMOVE 1
#define W3_AT 1
struct MegaMaps {
    CUtensorMap q, act;
    CUtensorMap w1, w2, w3, w4;
    CUtensorMap k, v, y, w1p;
};

__global__ void __cluster_dims__(2, 1, 1) __launch_bounds__(384, 1)
mega_kernel(const __grid_constant__ MegaMaps tm, bf16* __restrict__ outp, bf16* act, const bf16* __restrict__ w1p, const bf16* __restrict__ w2p,
            const bf16* __restrict__ w3p, const bf16* __restrict__ xq, const bf16* __restrict__ kp, const bf16* __restrict__ vp,
            const bf16* __restrict__ shk, const bf16* __restrict__ ssk, const bf16* __restrict__ ssD) {
    extern __shared__ __align__(1024) uint8_t sgen[];
    const uint32_t sbase = smem_u32(sgen);
    const int warp = __shfl_sync(0xffffffffu, threadIdx.x >> 5, 0), lane = threadIdx.x & 31;
    const int rank = blockIdx.x & 1;
    const uint32_t s_bar = sbase + OFF_BAR;
    const uint32_t f5 = s_bar, e5 = s_bar + 64, f4 = s_bar + 144, e4 = s_bar + 104;
    const uint32_t b_rfull = s_bar + 176, b_role = s_bar + 184, b_stg = s_bar + 136, b_h2 = s_bar + 32;
    const uint32_t s_epi = sbase + OFF_EPI, s_stg = sbase + OFF_STG5, s_r = sbase + OFF_R;
    uint8_t* sm = sgen + CV_0;
    const uint32_t sb = sbase + CV_0;
    const int tid = threadIdx.x, wg = warp >> 2, w = warp & 3;
    const int d0 = blockIdx.x * CV_CH;
    const bool cv = blockIdx.x < D_ / CV_CH;
    const uint32_t b_full = sb + CV_BAR, b_rdy = b_full + 64, b_h = b_full + 128;
    GT(0);
    if (tid == 0) TM(0);
    auto row_at = [&](int r) { return sb + CV_SL + (r < 0 ? -8192 : 0) + ((r & 127) >> 5) * 1024 + (r & 7) * 128 + ((r >> 3) & 3) * 32 + ((r ^ rank) & 1) * 16; };
    auto load_kv = [&](int c) {
#pragma unroll
        for (int i = 0; i < 2; i++)
            asm volatile("cp.async.bulk.tensor.4d.shared::cluster.global.mbarrier::complete_tx::bytes.multicast::cluster [%0], [%1, {%3, %4, %4, %5}], [%2], %6;"
                         ::"r"(sb + (c + 1) * CV_SL + rank * 8192 + i * 4096), "l"((uint64_t)(i ? &tm.v : &tm.k)), "r"(b_full + 8 * c), "r"(d0 & ~15), "r"(0),
                         "r"(8 * c + 4 * rank), "h"((uint16_t)3) : "memory");
    };
    auto bulk = [&](uint32_t dst, const void* src, uint32_t n, uint32_t bar) {
        asm volatile("cp.async.bulk.shared::cluster.global.mbarrier::complete_tx::bytes [%0], [%1], %2, [%3];" ::"r"(dst), "l"(src), "r"(n), "r"(bar) : "memory");
    };
    auto put_h = [&](int ch) {
        const uint32_t dk = (tid & 127) ? 0 : *reinterpret_cast<const volatile uint32_t*>(sm + CV_BAR + 160 + 16 * wg + 2 * ch);
        uint4 v[4];
#pragma unroll
        for (int i = 0; i < 4; i++) v[i] = lds128(sbase + ch * 4096 + i * 2048 + (tid & 127) * 16);
        v[0].x = pack2(lo2f(v[0].x) + lo2f(dk), hi2f(v[0].x));
        v[2].x = pack2(lo2f(v[2].x) + hi2f(dk), hi2f(v[2].x));
#pragma unroll
        for (int i = 0; i < 4; i++)
            sts128(sb + CV_H + (2 * ch + (i & 2) + (tid & 1)) * CV_HPL + (127 - ((tid & 127) >> 1)) * 16 - (i & 1) * 1024, v[i].x, v[i].y, v[i].z, v[i].w);
    };
    auto store_y = [&](int ch) {
        const int d = d0 + ch;
        asm volatile("cp.async.bulk.tensor.5d.global.shared::cta.bulk_group [%0, {%3, %2, %2, %2, %4}], [%1];"
                     ::"l"((uint64_t)&tm.y), "r"(sb + ((ch + 1) & 7) * CV_SL + 12288), "r"(0), "r"(d & ~127), "r"(((d >> 1 & 60) + (d & 3)) ^ (d & 4) * 33) : "memory");
        asm volatile("cp.async.bulk.commit_group;" ::: "memory");
    };
    int bi, bj, m0, tb;
    uint32_t ep;
    auto get_role = [&]() {
        mbar_wait(b_role, 0);
        int role;
        asm volatile("ld.shared.v2.b32 {%0,%1}, [%2];" : "=r"(role), "=r"(ep) : "r"(s_bar + 192) : "memory");
        bi = (role >> 3) * 2 + rank; bj = role & 7; m0 = bi * BM; tb = (role >> 3) * 2048 + rank * 128;
        return role < 64;
    };

    uint32_t e1 = 0;
    auto set_role = [&](int role) {
#pragma unroll
        for (int i = 0; i < 2; i++)
            asm volatile("st.async.weak.shared::cluster.mbarrier::complete_tx::bytes.v2.b32 [%0], {%1, %2}, [%3];"
                         ::"r"(mapa_u32(s_bar + 192, i)), "r"(role), "r"(e1), "r"(mapa_u32(b_role, i)) : "memory");
    };
    auto ask_role = [&]() {
        cluster_wait();
        if (tid == 256 + rank * 1024) {
            uint32_t smid;
            asm volatile("mov.u32 %0, %%smid;" : "=r"(smid));
            const int t = smid >> 1, team = t < 32 ? t & 7 : t < 60 ? 1 + (t - 32) % 7 : t < 62 ? t - 54 : 0;
            e1 = (uint32_t)(atomicAdd(reinterpret_cast<unsigned long long*>(g_ticket + 16 * FL_PITCH), 1ull) / NCL) + 1;
            const int slot = atomicAdd(g_ticket + ((e1 & 1) * 8 + team) * FL_PITCH, 1u);
            atomicAdd(g_ticket + 17 * FL_PITCH, 1u);
            if (blockIdx.x < 16) g_ticket[((~e1 & 1) * 8 + (blockIdx.x >> 1)) * FL_PITCH] = 0;
            if (slot < 8) { set_role(team * 8 + slot); e1 = 0; }
        }
        __syncwarp();
    };
    if (warp >= 8) {
        asm volatile("setmaxnreg.dec.sync.aligned.u32 88;");
        cluster_arrive_relaxed();
        if (!cv) ask_role(); else {
            const int bt = tid - 256, g = lane >> 2, t = lane & 3;
            if (bt < 16) sts128(row_at((bt & 7) - 8) + (bt >> 3) * 4096, 0, 0, 0, 0);
#pragma unroll
            for (int i = 0; i < 4; i++)
                cp16(row_at(bt) + i * 4096, (i & 1 ? vp : kp) + (size_t)(bt + (i >> 1) * 128) * D_ + d0);
            DBG_S(16 + (3));
            uint2 wa;
            asm volatile("ld.global.nc.v2.b32 {%0,%1}, [%2];" : "=r"(wa.x), "=r"(wa.y) : "l"(shk + (d0 + g) * 4));
            const int mi = lane >> 3, r0 = 32 * w + 8 * ((lane >> 1) & 3) - (lane & 1);
            const uint32_t ka0 = row_at(r0 + 2 * mi - 3), ka1 = row_at(r0 + 2 * (mi & 1) + 5) + (mi >> 1) * 8192;
            const uint32_t va0 = row_at(r0 + 2 * mi + 1) + 4096, va1 = row_at(r0 - 1) + 4096 + (mi & 1) * 8192;
            const uint32_t qd = sb + g * CV_QG + (32 * w + 8 * t) * 8, qd0 = qd + (t & 2) * 16, qd1 = qd + (~t & 2) * 16;
            const uint32_t w0 = __byte_perm(wa.x, 0, 0x1010), w1 = __byte_perm(wa.x, 0, 0x3232), w2 = __byte_perm(wa.y, 0, 0x1010), w3 = __byte_perm(wa.y, 0, 0x3232);
            ask_role();
            DBG_S(16 + (5));
            asm volatile("cp.async.wait_all;" ::: "memory");
            named_bar_sync(7, 128);
            DBG_S(16 + (1));
            struct KV { uint32_t k[2][6], v[2][5]; };
            auto get = [&](KV& x, uint32_t so) {
                ldsm4t(x.k[0][0], x.k[0][1], x.k[0][2], x.k[0][3], ka0 + so);
                ldsm4t(x.k[0][4], x.k[0][5], x.k[1][4], x.k[1][5], ka1 + so);
                ldsm4t(x.k[1][0], x.k[1][1], x.k[1][2], x.k[1][3], ka0 + so + 8192);
                asm volatile("ldmatrix.sync.aligned.m8n8.x2.trans.shared.b16 {%0,%1}, [%2];" : "=r"(x.v[0][0]), "=r"(x.v[1][0]) : "r"(va1 + so));
                ldsm4t(x.v[0][1], x.v[0][2], x.v[0][3], x.v[0][4], va0 + so);
                ldsm4t(x.v[1][1], x.v[1][2], x.v[1][3], x.v[1][4], va0 + so + 8192);
            };
            auto build = [&](int c, const KV& x, KV& nx) {
                const uint32_t so = c * CV_SL;
                DBG_F(1);
                uint32_t early;
                asm volatile("{\n.reg .pred p;\nmbarrier.test_wait.parity.shared::cta.b64 p, [%1], 0;\nvote.sync.all.pred p, p, -1;\nselp.u32 %0, 1, 0, p;\n}"
                             : "=r"(early) : "r"(b_full + 8 * (c < 7 ? c + 1 : c)) : "memory");
                if (early) get(nx, so + CV_SL);
                DBG_F(2);
                uint32_t p[8][2];
#pragma unroll
                for (int sg = 0; sg < 2; sg++) {
                    uint32_t u[5], ke[6];
#pragma unroll
                    for (int i = 0; i < 6; i++) ke[i] = __byte_perm(x.k[sg][i], x.k[sg][i ? i - 1 : 0], 0x5432);
#pragma unroll
                    for (int i = 0; i < 5; i++) {
                        u[i] = bmul2(bfma2(x.k[sg][i + 1], w0, bfma2(ke[i + 1], w1, bfma2(x.k[sg][i], w2, bmul2(ke[i], w3)))), x.v[sg][i]);
                        if (i) { p[2 * i - 1][sg] = u[i]; p[2 * i - 2][sg] = __byte_perm(u[i], u[i - 1], 0x5432); }
                    }
                }
                DBG_F(3);
#pragma unroll
                for (int j = 0; j < 4; j++) sts128((j & 2 ? qd1 : qd0) + so + 16 * (j & 1), p[2 * j][0], p[2 * j][1], p[2 * j + 1][0], p[2 * j + 1][1]);
                __syncwarp();
                DBG_F(4);
                if (lane == 0) {
                    mbar_arrive(b_rdy + 8 * c);
                    if (c == w) {
                        if (c < 3) load_kv(c + 5);
                        else { bulk(sbase + 16384, ssk + (size_t)(d0 + 4) * S_, 16384, b_h + 16); bulk(b_full + 192, ssD + d0, 16, b_h + 16); }
                    }
                    if (c == w + 4 && (CV_PF >> w & 1)) {
                        const uint32_t n = w == 0 ? 32768 : w == 3 ? 57344 : 16384;
                        const char* src = reinterpret_cast<const char*>(w == 0 ? xq : w == 1 ? w1p : w == 2 ? w2p : w3p) + (size_t)blockIdx.x * n;
                        asm volatile("cp.async.bulk.prefetch.L2.global [%0], %1;" ::"l"(src), "r"(n) : "memory");
                    }
                }
                DBG_F(5);
                named_bar_sync(7, 128);
                DBG_F(6);
                DBG_S(16 + (c == 0 ? 4 : 5 + c));
                if (!early) { mbar_wait(b_full + 8 * c + 8, 0); get(nx, so + CV_SL); }
                DBG_F(7);
            };
            KV x0, x1;
            get(x0, 0);
#pragma unroll 1
            for (int c = 0; c < 8; c += 2) { build(c, x0, x1); build(c + 1, x1, x0); }
            mbar_wait(b_h + 16, 0);
            put_h(4); put_h(6);
            fence_async_smem();
            __syncwarp();
            if (lane == 0) mbar_arrive(b_full);
            named_bar_sync(7, 128);
            DBG_S(16 + (13));
        }
    } else {
        if (elect_one()) {
            mbar_init(b_full + 8 * warp, warp ? 1 : 4);
            mbar_init(b_rdy + 8 * warp, 4);
            if (warp) mbar_expect_tx(b_full + 8 * warp, 16384);
            if (w == 0 && cv) {
                mbar_init(b_h + 8 * wg, 1);
                mbar_expect_tx(b_h + 8 * wg, 8192 + 16);
                fence_async_smem();
                bulk(sbase + wg * 8192, ssk + (size_t)(d0 + 2 * wg) * S_, 8192, b_h + 8 * wg);
                bulk(b_full + 160 + 16 * wg, ssD + d0, 16, b_h + 8 * wg);
            }
            mbar_init(s_bar + 8 * warp, 1);
            mbar_init(s_bar + 64 + 8 * warp, 4);
            mbar_init(s_bar + 128 + 8 * warp, warp < 2 ? 4 << warp : 1);
            if (warp == 0) mbar_arrive(f5);
            if (warp == 7) mbar_expect_tx(b_role, 8);
            if (warp == 1) { mbar_init(b_h + 16, 1); mbar_expect_tx(b_h + 16, cv ? 16384 + 16 : 0); mbar_init(b_h + 24, 4); }
            if (w == 2) sts128(s_bar + 224 + 16 * wg, 0, 0, 0, 0);
            asm volatile("fence.mbarrier_init.release.cluster;" ::: "memory");
            if (warp == 2) { prefetch_tmap(&tm.k); prefetch_tmap(&tm.v); }
        }
        __syncwarp();
        DBG_W(1);
        cluster_arrive_relaxed();
        asm volatile("setmaxnreg.inc.sync.aligned.u32 208;");
        DBG_W(2);
        const int zi = (tid & 127) - 32;
        if (zi >= 0 && zi < 48) sts128(sb + CV_H + (4 * wg + (zi / 6 & 3) + (zi / 24) * 8) * CV_HPL + 2048 + (zi % 6) * 16, 0, 0, 0, 0);
        DBG_W(3);
        cluster_wait();
        DBG_W(5);
        if (cv) {
            if (tid == 32) {
#pragma unroll 1
                for (int c = 1; c < 5; c++) load_kv(c);
                prefetch_tmap(&tm.y);
            }
            __syncwarp();
            DBG_W(6);
            const int g = lane >> 2, t = lane & 3;
            const int x0 = 32 + 8 * w + g - 2 * t;
            CvAddr p;
            p.rdy = b_rdy;
            p.bar = 1 + wg;
            p.xr = sbase + (warp ^ 2) * 2048 + lane * 16;
            p.xw = sbase + warp * 2048 + (g * 4 + ((t - (w >> 1)) & 3)) * 16;
            p.wrap = t == 0 && w >= 2;
            mbar_wait(b_h + 8 * wg, 0);
            DBG_W(4);
            put_h(2 * wg);
            fence_async_smem();
            named_bar_sync(1 + wg, 128);
            float acc[2][64];
            zero_acc(acc[0]); zero_acc(acc[1]);
#pragma unroll 1
            for (int round = 0; round < 2; round++) {
                const int ch = round * 4 + 2 * wg;
                uint32_t a[CV_NA][4], tv[2][8];
#pragma unroll
                for (int e = 0; e < 2; e++) {
                    const int x = x0 - 8 * e;
                    p.neg[e] = x < 32;
                    p.pa[e] = sb + ch * CV_QG + 8 * (x ^ (x >> 2 & 4));
                    p.p0[2 * e] = p.pa[e] + (x < 32 ? 768 + 4 - CV_SL : -256);
                    p.p0[2 * e + 1] = p.pa[e] + (x < 32 ? 768 : -256 + 4);
                }
                p.db = (((sb + CV_H + ch * 2 * CV_HPL) & 0x3FFFF) >> 4) | ((CV_HPL / 16) << 16);
                if (round) mbar_wait(b_full, 0);
                DBG_S(7 + 3 * round);
                cv_steps<0>(acc, a, tv, p);
                DBG_S(8 + 3 * round);
                const int r128 = 4 * (lane >> 3) + 2 * (lane & 1) + ((~lane >> 2) & 1);
#pragma unroll
                for (int i = 0; i < 2; i++) {
                    const uint32_t ta = sb + ((ch + i + 1) & 7) * CV_SL + 12288 + r128 * 128 + ((((~lane & 2) * 2 + w) ^ (r128 & 7)) << 4);
                    stsm4t(ta, tv[i][0], tv[i][1], tv[i][2], tv[i][3]);
                    stsm4t(ta + 2048, tv[i][4], tv[i][5], tv[i][6], tv[i][7]);
                }
                fence_async_smem();
                named_bar_sync(1 + wg, 128);
                if ((tid & 127) < 2) { if (round) store_y(ch + (tid & 1)); else mbar_arrive(b_h + 24); }
                __syncwarp();
                DBG_S(9 + 3 * round);
            }
        }
    }
    int warp2 = warp;
    asm volatile("" : "+r"(warp2));
    if (warp2 >= 8) {
        asm volatile("setmaxnreg.dec.sync.aligned.u32 72;");
        if (cv && (tid & ~3) == 288) { mbar_wait(b_h + 24, 0); store_y(lane); put_y(1); }
        if (e1) {
            const long long t0 = clock64();
            while ((int)(*(volatile unsigned int*)(g_ticket + 17 * FL_PITCH) - e1 * NCL) < 0 && clock64() - t0 < 100000) {}
            int team = 0, slot;
            for (; team < 8; team++)
                if ((slot = atomicAdd(g_ticket + ((e1 & 1) * 8 + team) * FL_PITCH, 1u)) < 8) break;
            set_role(team * 8 + slot);
        }
        __syncwarp();
        const bool on = get_role();
        if (on) {
            const int g = lane >> 2, t = lane & 3;
            const uint32_t xs = sbase + 16384 + w * 4096, xh = 16384 + 8 * CV_SL;
            if (tid == 256) {
                TM(2);
                mbar_expect_tx(b_rfull, 32768);
                tma_load_2d(sbase + 16384, &tm.q, b_rfull, bj * 128, m0);
                tma_load_2d(sb + 8 * CV_SL, &tm.q, b_rfull, bj * 128 + 64, m0);
                prefetch_tmap(&tm.act); prefetch_tmap(&tm.w1p);
            }
            mbar_wait(b_rfull, 0);
            if (tid == 256) TM(-72);
#pragma unroll 1
            for (int i = 0; i < 2; i++) {
                uint32_t x[32];
#pragma unroll
                for (int jp = 0; jp < 8; jp++)
                    ldsm4(x[4 * jp], x[4 * jp + 1], x[4 * jp + 2], x[4 * jp + 3], xs + i * 2048 + (lane & 15) * 128 + ((((jp & 3) * 2 + (lane >> 4)) ^ (lane & 7)) << 4) + (jp >> 2) * xh);
                put_stats(x, g_stats + (bi * 8 + bj) * 128 + 32 * w + 16 * i + g, 1u << 31);
            }
            if (tid == 256) {
                TM(-71);
                if (cv) mbar_wait(b_h + 24, 0);
                wait_flag(flag_ptr(1, FL_CS, 8 + bj), 64 * ep);
                fence_proxy_async();
                mbar_expect_tx(b_h + 16, 16384);
                tma_load_2d(sb + CV_H, &tm.act, b_h + 16, bj * 128 + rank * 64, R_Y + (tb & ~255));
            }
            __syncwarp();
            float mean, var;
            row_stats(g_stats + bi * 1024 + 32 * w + lane, 1u << 31, mean, var);
            __syncwarp();
            if (tid == 256) TM(-70);
            const uint32_t r1 = split(frcp(bfr(fsqrt(bfr(bfr(var) + 1e-5f))))), m1 = pack2(mean, mean);
            const int yr = (lane & 4) * 4 + (lane >> 3) * 4 + (lane & 3);
            const uint32_t ya = sb + CV_H + (w >> 1) * 8192 + yr * 128 + ((((w & 1) * 4) ^ (yr & 7)) << 4);
            const uint32_t xa = xs + g * 128 + ((((t & 2) * 2) ^ g) << 4) + (t & 1) * 4;
            bf16* gp = act + (size_t)(R_XA + tb + 32 * w + g) * D_ + bj * 128 + (t & 1) * 32 + (t & 2) * 4;
            mbar_wait(b_h + 16, 1);
            if (tid == 256) TM(-69);
#pragma unroll 1
            for (int i = 0; i < 4; i++) {
                const uint32_t mb = __shfl_sync(0xffffffffu, m1, 8 * i + g), rd = __shfl_sync(0xffffffffu, r1, 8 * i + g);
                uint32_t x[8], y[8];
#pragma unroll
                for (int e = 0; e < 8; e++) asm volatile("ld.shared.b32 %0, [%1];" : "=r"(x[e]) : "r"(((xa + i * 1024) ^ ((e & 3) << 4)) + (e >> 2) * xh) : "memory");
                ldsm4t(y[0], y[1], y[2], y[3], ya ^ (i << 4));
                ldsm4t(y[4], y[5], y[6], y[7], (ya ^ (i << 4)) + 4096);
#pragma unroll
                for (int e = 0; e < 8; e++) x[e] = bfma2(norm2(x[e], mb, rd), y[e], x[e]);
                stg128(gp + i * 8 * D_, make_uint4(x[0], x[1], x[2], x[3]));
                stg128(gp + i * 8 * D_ + 16, make_uint4(x[4], x[5], x[6], x[7]));
            }
            if (tid == 256) TM(-68);
            asm volatile("fence.release.gpu;" ::: "memory");
            __syncwarp();
            if (lane == 0) asm volatile("red.relaxed.gpu.global.add.u32 [%0], 1;" ::"l"(flag_ptr(0, FL_XA, bi)) : "memory");
            if (tid == 256) TM(-67);
            named_bar_sync(7, 128);
        }
        if (warp == 8) { if (elect_one()) {
            if (on) {
            int s5 = 0, s4 = 0;
            uint32_t p5 = 0, p4 = 1;
            auto putB = [&](const CUtensorMap* tB, int kc, uint32_t bytes) {
                const uint32_t full = f5 + 8 * s5;
                mbar_wait(full + 64, (p5 >> s5) & 1);
                mbar_expect_tx(full, bytes);
                tma_load_2d_mc(s_r + 16384 + rank * 8192 + s5 * R5_STAGE, tB, full, bj * 128 + rank * 64, kc);
                p5 ^= 1u << s5;
            };
            auto putA = [&](int c, int r) {
                tma_load_2d(s_r + s5 * R5_STAGE, &tm.act, f5 + 8 * s5, c, r);
                if (++s5 == R5_N) s5 = 0;
            };
            prefetch_tmap(&tm.w1); prefetch_tmap(&tm.w2); prefetch_tmap(&tm.w3); prefetch_tmap(&tm.w4);
            auto own_first = [&](int it) {
                const int hf = it >= 9, c = it - 2 - 7 * hf;
                return (it < 2 ? 2 * bj + it : 2 * (c + (c >= bj)) + hf) * BK;
            };
            const unsigned int n8 = 8 * ep, nh = (bi == 0 || bi == 15) ? 2 * n8 : 3 * n8;
#pragma unroll 1
            for (int layer = 0; layer < 2; layer++) {
                auto getY = [&](int sl, int n) {
                    mbar_wait(e5 + 8 * sl, (p5 >> sl) & 1);
                    mbar_expect_tx(f5 + 8 * sl, n * 16384);
                    for (int i = 0; i < n; i++) tma_load_2d(s_r + sl * R5_STAGE + i * 16384, &tm.act, f5 + 8 * sl, bj * 128 + rank * 64, R_Y + (tb | 128) - i * 128);
                    p5 ^= 1 << sl;
                };
                if (layer == 0) {
                    s5 = 1;
#pragma unroll 1
                    for (int q = 0; q < 16; q++) {
                        if (q == Y_AT) { TM(1); wait_flag(flag_ptr(0, FL_CS, 8 + bj), 8 * n8); TM(4); fence_proxy_async(); getY(4, 1); TM(5); }
                        if (q == 3) s5 = 0;
                        const int hf = q == 6 || q >= 9, c = q < 6 ? q : q == 6 ? bj : q < 9 ? q - 1 : q - 9 + (q - 9 >= bj);
                        const uint32_t full = f5 + 8 * s5;
                        mbar_wait(full + 64, (p5 >> s5) & 1);
                        mbar_expect_tx(full, q == 6 ? 16384 : R5_STAGE);
                        asm volatile("cp.async.bulk.tensor.4d.shared::cluster.global.mbarrier::complete_tx::bytes.multicast::cluster [%0], [%1, {%3, %4, %5, %6}], [%2], %7;"
                                     ::"r"(s_r + 16384 + rank * 8192 + s5 * R5_STAGE), "l"((uint64_t)&tm.w1p), "r"(full), "r"(bj * 128 + rank * 64), "r"(0), "r"(16 * c), "r"(2 * hf),
                                     "h"((uint16_t)3) : "memory");
                        p5 ^= 1u << s5;
                        if (q == 0 || q == 9) {
                            wait_flag(flag_ptr(0, FL_XA + hf, bi), q ? n8 : 4 * n8);
                            TM(q ? 14 : -66);
                            fence_proxy_async();
                        }
                        if (q == 6) s5++; else putA(128 * c + 64 * hf, R_XA + tb);
                    }
                } else {
                    getY(1, 2);
                    s5 = 2;
#pragma unroll 1
                    for (int kk = 0; kk < 4; kk++) {
                        putB(&tm.w1, own_first(kk), kk < 2 ? 16384 : R5_STAGE);
                        if (++s5 == R5_N) s5 = 0;
                    }
                    s5 = 4;
#pragma unroll 1
                    for (int kk = 2; kk < 16; kk++) {
                        const int kc = own_first(kk);
                        if (kk >= 4) putB(&tm.w1, kc, R5_STAGE);
                        if (kk == 2 || kk == 9) {
                            wait_flag(flag_ptr(layer, FL_XA + (kk & 1), bi), n8);
                            DP(8 * (FL_XA + (kk & 1)) + 3);
                            fence_proxy_async();
                            DP(8 * (FL_XA + (kk & 1)) + 4);
                        }
                        putA(kc, R_XA + tb);
                    }
                }
                mbar_wait(e5 + 24, (p5 >> 3) & 1);
                mbar_arrive(f5 + 24);
                p5 ^= 8;
                s5 = 4;
#pragma unroll 1
                for (int kk = 0; kk < 5; kk++) { putB(&tm.w2, kk * 2 * BK, R5_STAGE); if (++s5 == R5_N) s5 = 0; }
#pragma unroll 1
                for (int kk = 0; kk < 16; kk++) {
                    const int kc = ((kk & 7) * 2 + (kk >> 3)) * BK;
                    if (kk >= 5) putB(&tm.w2, kc, R5_STAGE);
                    if ((kk & 7) == 0) {
                        wait_flag(flag_ptr(layer, FL_H + (kk >> 3), bi), nh);
                        DP(8 * (FL_H + (kk >> 3)) + 3);
                        fence_proxy_async();
                        DP(8 * (FL_H + (kk >> 3)) + 4);
                    }
                    putA(kc, R_H + layer * R_HP + m0 + (int)((0x4031u >> ((kk & 6) << 1)) & 7) - 2);
                }
#pragma unroll 1
                for (int it = 0; it < 32; it++) {
                    const int kc = it >= 16 ? (it - 16) * BK : own_first(it);
                    const int nb = it < 16 ? 4 : 3, n0 = bj * 448 + (it < 16 ? 0 : 256);
                    if (it > 0 && it < 4) {
                        const int i = (it - 1) * 3 >> 1;
                        mbar_wait(e5 + 8 * i, (p5 >> i) & 1);
                        mbar_wait(e5 + 8 * i + 8, (p5 >> (i + 1)) & 1);
                    }
                    mbar_wait(e4 + 8 * s4, p4);
                    if (it >= 16 && it < 19) mbar_wait(e4 + 8 * s4 + 8, p4);
                    uint32_t sa = s_r + s4 * (it < 16 ? R4_STAGE : R4B_STAGE), full = f4 + 8 * s4;
                    mbar_expect_tx(full, (it < 2 ? 0 : 16384) + nb * 8192);
#pragma unroll 1
                    for (int j = (it ^ rank) & 1; j < nb; j += 2) tma_load_2d_mc(sa + (it < 16 ? -32768 : 16384) + j * 8192, &tm.w3, full, n0 + j * 64, kc);
                    if (it == 3 || it == 9) {
                        wait_flag(flag_ptr(layer, FL_X1 + (it >> 3), bi), n8);
                        DP(8 * (FL_X1 + (it >> 3)) + 3);
                        fence_proxy_async();
                        DP(8 * (FL_X1 + (it >> 3)) + 4);
                        if (it == 3) tma_load_2d(s_r + 2 * R4_STAGE, &tm.act, f4 + 16, own_first(2), R_X1 + tb);
                    }
                    if (it >= 3) tma_load_2d(sa, &tm.act, full, kc, R_X1 + tb);
                    if (++s4 == R4_N) { s4 = 0; p4 ^= 1; }
                }
                wait_flag(flag_ptr(layer, FL_H2, bi), n8);
                fence_proxy_async();
                s5 = 0;
#pragma unroll 1
                for (int j = 0; j < 7; j++) {
                    if (j > 0 && (j & 1) == 0) {
                        mbar_wait(b_h2 + 4 * j, layer);
                        fence_proxy_async();
                    }
                    const int ra = R_H2 + (j >> 1) * 256 + tb;
#pragma unroll 1
                    for (int b = 0; b < 8; b++) {
                        if (j == 0 && b < R4_N) mbar_wait(e4 + 8 * b, p4);
                        putB(&tm.w4, (7 * b + j) * BK, R5_STAGE);
                        putA(((j & 1) * 8 + b) * BK, ra);
                    }
                }
            }
        } } } else {
            auto colsum = [&](bool is1, int bi, int bj) {
                const int pitch = is1 ? D_ : F_, c = is1 ? bj * 128 + (lane & 15) * 8 : bj * 448 + min((warp & 2) * 128 + lane * 8, 440);
                const bf16* p = (is1 ? w1p : w3p) + ((bi * 64 + (is1 ? (lane >> 4) * 32 : 0)) * pitch + c);
                float a[8];
#pragma unroll
                for (int i = 0; i < 8; i++) a[i] = 0.f;
#pragma unroll 1
                for (int r0 = is1 ? 32 : 0; r0 < 64; r0 += 8) {
                    uint4 v[8];
#pragma unroll
                    for (int r = 0; r < 8; r++, p += pitch) v[r] = __ldg(reinterpret_cast<const uint4*>(p));
#pragma unroll
                    for (int r = 0; r < 8; r++) {
                        a[0] += lo2f(v[r].x); a[1] += hi2f(v[r].x); a[2] += lo2f(v[r].y); a[3] += hi2f(v[r].y);
                        a[4] += lo2f(v[r].z); a[5] += hi2f(v[r].z); a[6] += lo2f(v[r].w); a[7] += hi2f(v[r].w);
                    }
                }
                if (is1) {
#pragma unroll
                    for (int i = 0; i < 8; i++) a[i] += __shfl_xor_sync(0xffffffffu, a[i], 16);
                }
                float4* dst = reinterpret_cast<float4*>(g_cpart + bi * (F_ + D_) + (is1 ? F_ : 0) + c);
                dst[0] = make_float4(a[0], a[1], a[2], a[3]);
                dst[1] = make_float4(a[4], a[5], a[6], a[7]);
                asm volatile("fence.release.gpu;" ::: "memory");
                __syncwarp();
                if (lane == 0) asm volatile("red.relaxed.gpu.global.add.u32 [%0], 1;" ::"l"(flag_ptr(!is1, FL_CS, bj)) : "memory");
            };
            if (cv && warp == 11) colsum(true, blockIdx.x >> 3, blockIdx.x & 7);
            float4 keep[2];
#pragma unroll 1
            for (int layer = on ? 0 : 2; layer < 2; layer++) {
                if (warp == 10) {
#pragma unroll 1
                    for (int kind = 0; kind < 6; kind += 2) {
                        const uint32_t src = kind == FL_H ? s_stg : s_epi;
                        const int r = kind == FL_H ? R_H + layer * R_HP + m0 : (kind == FL_XA ? R_XA : R_X1) + tb;
#pragma unroll 1
                        for (int hf = 0; hf < 2; hf++) {
                            named_bar_sync(5 + hf, 288);
                            if (lane == 0 && (layer | kind | hf)) {
                                if (FMOVE) fence_async_smem();
                                DP(8 * (kind + hf));
                                tma_store_2d(&tm.act, src + hf * 16384, bj * 128 + hf * 64, r);
                                asm volatile("cp.async.bulk.commit_group;" ::: "memory");
                                asm volatile("cp.async.bulk.wait_group 0;" ::: "memory");
                                DP(8 * (kind + hf) + 1);
                                DP(8 * (kind + hf) + 2);
                                unsigned int* fp = flag_ptr(layer, kind + hf, bi);
                                asm volatile("red.relaxed.gpu.global.add.u32 [%0], 1;" ::"l"(fp) : "memory");
                                if (kind == FL_H) {
                                    if (bi > 0) asm volatile("red.relaxed.gpu.global.add.u32 [%0], 1;" ::"l"(fp - FL_PITCH) : "memory");
                                    if (bi < 15) asm volatile("red.relaxed.gpu.global.add.u32 [%0], 1;" ::"l"(fp + FL_PITCH) : "memory");
                                }
                            }
                            __syncwarp();
                        }
                    }
                } else {
                    uint32_t* rs = reinterpret_cast<uint32_t*>(sgen + OFF_RS);
                    float* cs = reinterpret_cast<float*>(sgen + OFF_CS);
#pragma unroll 1
                    for (int which = 0; which < 2; which++) {
                        if (layer < which) {
                            if (warp == 11 && lane == 0) {
                                wait_flag(flag_ptr(0, FL_XA + W3_AT, bi), 8 * ep);
                                asm volatile("cp.async.bulk.prefetch.L2.global [%0], %1;" ::"l"(w3p + (bi * 8 + bj) * 28672), "r"(57344) : "memory");
                            }
                            __syncwarp();
                            colsum(false, bi, bj);
                        }
                        if (warp == 11) continue;
                        if (layer == 0) {
                            if (lane == 0) wait_flag(flag_ptr(which, FL_CS, bj), (16 << which) * ep);
                            __syncwarp();
#pragma unroll 1
                            for (int c = (which ? 384 : 768) + lane * 4; c < 896; c += 128) {
                                const float* cp = g_cpart + (which ? bj * 448 + min(c & 511, 444) : F_ + bj * 128 + lane * 4);
                                float4 a = make_float4(0.f, 0.f, 0.f, 0.f);
#pragma unroll
                                for (int r0 = 0; r0 < 16; r0 += 8) {
                                    float4 v[8];
#pragma unroll
                                    for (int r = 0; r < 8; r++) v[r] = __ldcg(reinterpret_cast<const float4*>(cp + (r0 + r) * (F_ + D_)));
#pragma unroll
                                    for (int r = 0; r < 8; r++) { a.x += v[r].x; a.y += v[r].y; a.z += v[r].z; a.w += v[r].w; }
                                }
                                if (c < 768) *reinterpret_cast<float4*>(cs + min(c & 511, 444)) = a;
                                keep[0] = a;
                            }
                        }
                        if (lane == 0 && (layer | which)) wait_flag(flag_ptr(layer, which == 0 ? FL_XA : FL_X1, bi), 8 * ep);
                        __syncwarp();
                        *reinterpret_cast<float4*>(cs + 256 + lane * 4) = keep[0];
                        { const float4 k0 = keep[0]; keep[0] = keep[1]; keep[1] = k0; }
#pragma unroll 1
                        for (int i = 0; i < 4; i++) {
                            const int r = i * 32 + lane;
                            float mean, var;
                            row_stats(g_stats + (1 + which) * S_ * 8 + bi * 1024 + r, ~layer << 31, mean, var);
                            const uint32_t c0 = pack2(mean, fsqrt(bfr(bfr(var) + 1e-5f)));
                            if (lane < 20 && (layer | which | i) == 0) asm volatile("mbarrier.inval.shared::cta.b64 [%0];" ::"r"(b_full + 8 * lane) : "memory");
                            __syncwarp();
                            rs[r] = c0;
                            const float rd = frcp(hi2f(c0));
                            rs[128 + r] = pack2((mean - lo2f(c0)) * rd, fsqrt(bfr(bfr(var * rd * rd) + 1e-5f)));
                        }
                        __syncwarp();
                        named_bar_arrive(3, 160);
                        named_bar_arrive(11, 160);
                    }
                }
                const uint32_t s_cnt = s_bar + 224;
                auto ticket = [&](uint32_t a) {
                    uint32_t v = 0;
                    if (lane == 0) asm volatile("atom.acq_rel.cta.shared.add.u32 %0, [%1], 1;" : "=r"(v) : "r"(a) : "memory");
                    return v;
                };
                mbar_wait(b_stg, 0);
                int u = __shfl_sync(0xffffffffu, ticket(s_cnt + 16 + 4 * layer), 0), step = 0;
#pragma unroll 1
                while (true) {
#pragma unroll 1
                    for (; step < 5 && u >= (int)((0x3830201810ull >> (8 * step)) & 255); step++) {
                        if (step == 1) { named_bar_arrive(4, 224); named_bar_arrive(12, 224); continue; }
                        const int part = step ? step - 1 : 0;
                        __syncwarp();
                        if (ticket(s_cnt + 4 * part) == 3 * layer + 2) {
                            asm volatile("fence.release.gpu;" ::: "memory");
                            unsigned int* fp = flag_ptr(layer, FL_H2 + part, bi);
                            asm volatile("red.relaxed.gpu.global.add.u32 [%0], 1;" ::"l"(fp) : "memory");
                            if (part > 0) { wait_flag(fp, 8 * ep); mbar_arrive(b_h2 + 8 * part); }
                        }
                        __syncwarp();
                        if (step == 2) mbar_wait(b_stg, 1);
                    }
                    if (u >= 56) break;
                    const uint32_t un = ticket(s_cnt + 16 + 4 * layer);
                    const int job = u >> 3, r = (u & 7) * 16 + (lane >> 3);
                    const uint32_t sp = sbase + ((job & 2) ? OFF_STG5 : OFF_EPI) + r * 256 + (job & 1) * 128;
                    bf16* gp = act + (size_t)(R_H2 + (job >> 1) * 256 + tb + r) * D_ + ((job & 1) * 8 + bj) * 64 + (lane & 7) * 8;
                    uint4 v[4];
#pragma unroll
                    for (int e = 0; e < 4; e++) v[e] = lds128(sp + e * 1024 + (((lane & 7) ^ ((r + 4 * e) & 7)) << 4));
#pragma unroll
                    for (int e = 0; e < 4; e++) stg128(gp + 4 * e * D_, gelu8h(v[e]));
                    u = __shfl_sync(0xffffffffu, un, 0);
                }
                if (layer == 0 && warp == 11) {
                    const char* ps = reinterpret_cast<const char*>(g_stats + bi * 1024) + lane * 128;
                    const char* py = reinterpret_cast<const char*>(act + (size_t)(R_Y + (tb & ~255) + lane) * D_ + bj * 128 + rank * 64);
#pragma unroll 1
                    for (int i = 0; i < 8; i++) {
                        asm volatile("prefetch.global.L2 [%0];" ::"l"(py + (size_t)i * 32 * D_ * 2) : "memory");
                        if (i >= 6) asm volatile("prefetch.global.L2 [%0];" ::"l"(ps + (i & 1) * 4096) : "memory");
                        __nanosleep(400);
                    }
                }
            }
        }
        __syncwarp();
        asm volatile("barrier.cluster.arrive.relaxed.aligned;\nbarrier.cluster.wait.acquire.aligned; // helpers" ::: "memory");
    } else {
        DT_DECL;
        DT(0);
        if ((tid & 127) < 2 && cv) put_y(0);
        __syncwarp();
        DT(24);
        asm volatile("setmaxnreg.inc.sync.aligned.u32 216;");
        if (get_role()) {
        const bool rel_on = (tid & 95) == 0;
        const uint32_t rel5 = mapa_u32(e5, (warp & 1) ^ rank), rel4 = rel5 + (e4 - e5);
        const uint32_t da0 = desc_a(s_r + wg * 8192), db0 = desc_b(s_r + BM * BK * 2), dae = da0 + (OFF_EPI - OFF_R) / 16, db4 = db0 - 49152 / 16;
        auto skip5 = [&](RingState& rs) {
            if (rel_on) mbar_arrive_cluster(rel5 + 8 * rs.st);
            rs.st++;
        };
        const int t = lane & 3;
        const int row = warp * 16 + (lane >> 2);
        const uint32_t st_w = (uint32_t)((warp * 16 + ((lane >> 3) & 1) * 8 + (lane & 7)) * 256 + (((lane >> 4) ^ (lane & 7)) << 4));
        const uint32_t fr = (uint32_t)((warp * 16 + ((lane >> 3) & 1) * 8 + (lane & 7)) * 128 + (((lane >> 4) ^ (lane & 7)) << 4));
        auto copy_out = [&](bf16* dst, uint32_t src) {
            const int r = warp * 16 + (lane >> 4);
            bf16* ox = dst + (size_t)(m0 + r) * D_ + bj * 128 + (lane & 15) * 8;
            const uint32_t ra = src + ((lane & 15) >> 3) * 16384 + r * 128;
            uint4 v[8];
#pragma unroll
            for (int it = 0; it < 8; it++) v[it] = lds128(ra + it * 256 + (((lane & 7) ^ ((2 * it + (lane >> 4)) & 7)) << 4));
#pragma unroll
            for (int it = 0; it < 8; it++) *reinterpret_cast<uint4*>(ox + (size_t)it * 2 * D_) = v[it];
        };
        float2* const stp = g_stats + (bi * 8 + bj) * 128 + row;
        const float* csp = reinterpret_cast<const float*>(sgen + OFF_CS) + 2 * t;
        float mrow[2], rrow[2];
        const uint32_t* rsp = reinterpret_cast<const uint32_t*>(sgen + OFF_RS) + row;
        auto row_consts = [&](bool twice) {
#pragma unroll
            for (int e = 0; e < 2; e++) {
                const uint32_t q0 = rsp[8 * e], q1 = rsp[128 + 8 * e];
                mrow[e] = twice ? fmaf(lo2f(q1), hi2f(q0), lo2f(q0)) : lo2f(q0);
                rrow[e] = 0.5f * frcp(twice ? hi2f(q0) * hi2f(q1) : hi2f(q0));
            }
        };
        auto keep_consts = [&](float2 (&cs)[8]) {
#pragma unroll
            for (int e = 0; e < 8; e++) asm volatile("" : "+f"(cs[e].x), "+f"(cs[e].y));
            asm volatile("" : "+f"(mrow[0]), "+f"(mrow[1]), "+f"(rrow[0]), "+f"(rrow[1]));
        };
        auto stage = [&](const float* acc, uint32_t dst, int j0, float2 (&cs)[8], const float* cnext) {
            float2 cn[8];
#pragma unroll
            for (int e = 0; e < 8; e++) cn[e] = *reinterpret_cast<const float2*>(cnext + 8 * e);
#pragma unroll
            for (int j = 0; j < 8; j += 2) {
                uint32_t w[4];
#pragma unroll
                for (int e = 0; e < 2; e++) {
                    const float* a = acc + 4 * (j + e);
                    w[2 * e] = pack2(fmaf(-mrow[0], cs[j + e].x, a[0]) * rrow[0], fmaf(-mrow[0], cs[j + e].y, a[1]) * rrow[0]);
                    w[2 * e + 1] = pack2(fmaf(-mrow[1], cs[j + e].x, a[2]) * rrow[1], fmaf(-mrow[1], cs[j + e].y, a[3]) * rrow[1]);
                }
                stsm4((dst + st_w) ^ (((j0 + j) & 15) << 4), w[0], w[1], w[2], w[3]);
            }
#pragma unroll
            for (int e = 0; e < 8; e++) cs[e] = cn[e];
        };
        RingState r5{1, 0}, r4{0, 0};
        DT(1);
        uint32_t x[32];
        mbar_wait(b_rfull, 0);
#pragma unroll
        for (int jp = 0; jp < 8; jp++) ldsm4(x[4 * jp], x[4 * jp + 1], x[4 * jp + 2], x[4 * jp + 3], sbase + 16384 + (fr ^ ((jp & 3) << 5)) + (jp >> 2) * (16384 + 8 * CV_SL));
#pragma unroll
        for (int e = 0; e < 32; e++) asm volatile("" : "+r"(x[e]));
        named_bar_sync(9 + wg, 128);
        if ((tid & 95) < R5_N) mbar_arrive_cluster(rel5 + 8 * lane);
#pragma unroll 1
        for (int layer = 0; layer < 2; layer++) {
            {
                float acc[64];
                DT(2 + 24 * layer);
                if (layer) put_stats(x, stp, 0);
                DT(20 + 24 * layer);
#pragma unroll
                for (int i = 0; i < 64; i++) asm volatile("mov.f32 %0, 0f00000000;" : "=f"(acc[i]));
                DT(22 + 24 * layer);
                uint32_t mb[2], rd[2];
                {
                    float mean, var;
                    row_stats(g_stats + bi * 1024 + warp * 16 + (lane & 15), ~layer << 31, mean, var);
                    __syncwarp();
                    const uint32_t r1 = split(frcp(bfr(fsqrt(bfr(bfr(var) + 1e-5f)))));
                    const uint32_t m1 = pack2(mean, mean);
#pragma unroll
                    for (int e = 0; e < 2; e++) { mb[e] = __shfl_sync(0xffffffffu, m1, (lane >> 2) + 8 * e); rd[e] = __shfl_sync(0xffffffffu, r1, (lane >> 2) + 8 * e); }
                }
                DT(21 + 24 * layer);
                if (layer == 0) {
                    kblock<128, 4>(acc, da0 + R5_STAGE / 16, db0 + R5_STAGE / 16, f5, r5);
                    DT(25);
#pragma unroll 1
                    for (int i = 1; i < 4; i++) {
                        kblock<128, 4>(acc, da0 + r5.st * (R5_STAGE / 16), db0 + r5.st * (R5_STAGE / 16), f5, r5);
                        wgmma_wait<1>();
                        if (rel_on) mbar_arrive_cluster(rel5 + 8 * i);
                    }
                    kblock<128, 4>(acc, da0 + R5_STAGE / 16, db0 + R5_STAGE / 16, f5, r5);
                    if (P0_WAIT) wgmma_wait<0>();
                }
                mbar_wait(f5 + 32 - 24 * layer, r5.ph & layer);
                DT(23 + 24 * layer);
                const int yr = ((lane >> 2 & 4) + (lane & 3)) ^ (lane & 4);
                const uint32_t ya = s_r + (4 - 3 * layer) * R5_STAGE + (~lane & 4) * 4096 + wg * 8192 + yr * 128 + ((((warp & 3) * 2 + ((lane >> 3) & 1)) ^ yr) << 4);
                uint32_t y[16];
#pragma unroll
                for (int e = 0; e < 32; e++) {
                    if ((e & 15) == 0) {
#pragma unroll
                        for (int jp = 0; jp < 4; jp++) ldsm4t(y[4 * jp], y[4 * jp + 1], y[4 * jp + 2], y[4 * jp + 3], ya + jp * 1024 + e * 256);
                    }
                    x[e] = bfma2(norm2(x[e], mb[e & 1], rd[e & 1]), y[e & 15], x[e]);
                    if ((e & 3) == 3 && layer) stsm4(s_epi + (fr ^ (((e >> 2) & 3) << 5)) + (e >> 4) * 16384, x[e - 3], x[e - 2], x[e - 1], x[e]);
                    if ((e & 7) >= 6 && layer < t >> 1)
                        sts128((s_epi + 16384 + row * 128 + ((((t & 1) * 4) ^ (row & 7)) << 4) ^ (e >> 3 << 4)) + (e & 1) * 1024, x[e - 6], x[e - 4], x[e - 2], x[e]);
                    if ((e & 15) == 15) { if (!FMOVE) fence_async_smem(); named_bar_arrive(5 + (e >> 4), 288); }
                    if (e == 15) mbar_wait(b_role, 0);
                }
                DT(19 + 24 * layer);
                if (FMOVE) fence_async_smem();
                if (PS1_EARLY) put_stats(x, stp + S_ * 8, ~layer << 31);
                wgmma_wait<0>();
                named_bar_sync(9 + wg, 128);
                if ((tid & 95) < 3 - 2 * layer) mbar_arrive_cluster(rel5 + (0x200008u >> 8 * lane & 255));
                DT(3 + 24 * layer);
                r5.st = 2;
                kblock<128, R5_N>(acc, layer ? dae : da0 + 2 * (R5_STAGE / 16), db0 + 2 * (R5_STAGE / 16), f5, r5);
                kblock<128, R5_N>(acc, dae + 1024, db0 + 3 * (R5_STAGE / 16), f5, r5);
                if (!PS1_EARLY) put_stats(x, stp + S_ * 8, ~layer << 31);
                wgmma_wait<1>();
                if (rel_on) mbar_arrive_cluster(rel5 + 16);
                float2 cs[8];
                mainloop<128, R5_N, R5_STAGE>(acc, 9 + 5 * layer, da0, db0, f5, rel5, rel_on, r5, 15 + 24 * layer, [&]() {
                    named_bar_sync(3 + 8 * wg, 160);
                    row_consts(true);
#pragma unroll
                    for (int e = 0; e < 8; e++) cs[e] = *reinterpret_cast<const float2*>(csp + 256 + 8 * e);
                    keep_consts(cs);
                } DT_ARG);
                DT(4 + 24 * layer);
#pragma unroll
                for (int j = 0; j < 16; j += 2) {
                    if (j == 8) {
#pragma unroll
                        for (int e = 0; e < 8; e++) cs[e] = *reinterpret_cast<const float2*>(csp + 256 + 8 * (j + e));
                    }
                    uint32_t w[4];
#pragma unroll
                    for (int e = 0; e < 4; e++) {
                        const float* a = acc + 4 * j + 2 * e;
                        const float2 c = cs[(j & 7) + (e >> 1)];
                        w[e] = gelu2h(pack2(fmaf(-mrow[e & 1], c.x, a[0]) * rrow[e & 1], fmaf(-mrow[e & 1], c.y, a[1]) * rrow[e & 1]));
                    }
                    stsm4(s_stg + (fr ^ ((j & 7) << 4)) + (j >> 3) * 16384, w[0], w[1], w[2], w[3]);
                    if ((j & 7) == 6) { if (!FMOVE) fence_async_smem(); named_bar_arrive(5 + (j >> 3), 288); }
                }
                DT(5 + 24 * layer);
            }
            {
                float acc[64];
                uint32_t u[32];
                {
                    uint32_t mb[2], rd[2];
#pragma unroll
                    for (int e = 0; e < 2; e++) { const uint32_t q0 = rsp[8 * e]; mb[e] = (q0 & 0xffffu) * 0x10001u; rd[e] = split(frcp(hi2f(q0))); }
#pragma unroll
                    for (int e = 0; e < 32; e++) {
                        u[e] = norm2(x[e], mb[e & 1], rd[e & 1]);
                        asm volatile("" : "+r"(u[e]));
                    }
                }
                mbar_wait(f5 + 24, r5.ph);
                skip5(r5);
                kblock<128, R5_N, 0>(acc, da0 + 4 * (R5_STAGE / 16), db0 + 4 * (R5_STAGE / 16), f5, r5);
                DT(16 + 24 * layer);
                mainloop<128, R5_N, R5_STAGE>(acc, 15, da0, db0, f5, rel5, rel_on, r5, -1, []() {} DT_ARG);
                DT(6 + 24 * layer);
#pragma unroll
                for (int j = 0; j < 16; j += 2) {
#pragma unroll
                    for (int e = 0; e < 4; e++) u[2 * j + e] = badd2(u[2 * j + e], pack2(acc[4 * j + 2 * e], acc[4 * j + 2 * e + 1]));
                    stsm4(s_epi + (fr ^ ((j & 7) << 4)) + (j >> 3) * 16384, u[2 * j], u[2 * j + 1], u[2 * j + 2], u[2 * j + 3]);
                    if ((j & 7) == 6) { if (!FMOVE) fence_async_smem(); named_bar_arrive(5 + (j >> 3), 288); mbar_wait(b_role, 0); }
                }
                if (FMOVE) fence_async_smem();
#pragma unroll
                for (int e = 0; e < 32; e++) x[e] = badd2(x[e], u[e]);
                put_stats(u, stp + 2 * S_ * 8, ~layer << 31);
                named_bar_sync(9 + wg, 128);
                DT(7 + 24 * layer);
            }
            {
                float2 cs[8];
                {
                    float acc[128];
                    kblock<256, R4_N, 0>(acc, dae, db4, f4, r4);
                    kblock<256, R4_N>(acc, dae + 1024, db4 + R4_STAGE / 16, f4, r4);
                    if (!PS2_EARLY) {
                        uint32_t w[32];
#pragma unroll
                        for (int jp = 0; jp < 8; jp++) ldsm4(w[4 * jp], w[4 * jp + 1], w[4 * jp + 2], w[4 * jp + 3], s_epi + (fr ^ ((jp & 3) << 5)) + (jp >> 2) * 16384);
                        put_stats(w, stp + 2 * S_ * 8, ~layer << 31);
                    }
                    wgmma_wait<1>();
                    if (rel_on) mbar_arrive_cluster(rel4);
                    mainloop<256, R4_N, R4_STAGE>(acc, 14, da0, db4, f4, rel4, rel_on, r4, 17 + 24 * layer, [&]() {
                        named_bar_sync(3 + 8 * wg, 160);
                        mbar_wait(e4, 1);
                        row_consts(false);
#pragma unroll
                        for (int e = 0; e < 8; e++) cs[e] = *reinterpret_cast<const float2*>(csp + 8 * e);
                        keep_consts(cs);
                    } DT_ARG);
                    DT(8 + 24 * layer);
#pragma unroll
                    for (int j = 0; j < 32; j += 8) stage(acc + 4 * j, j < 16 ? s_epi : s_stg, j, cs, csp + 8 * (j + 8));
                    __syncwarp();
                if (lane == 0) mbar_arrive(b_stg);
                }
                DT(9 + 24 * layer);
                float acc[96];
                kblock<192, R4_N, 0>(acc, da0, db0, f4, r4);
                mainloop<192, R4_N, R4B_STAGE>(acc, 15, da0, db0, f4, rel4, rel_on, r4, -1, [&]() {
                    named_bar_sync(4 + 8 * wg, 224);
                } DT_ARG);
                DT(10 + 24 * layer);
#pragma unroll
                for (int j = 0; j < 24; j += 8) stage(acc + 4 * j, j < 16 ? s_epi : s_stg, j, cs, csp + 256 + 8 * (j < 16 ? j + 8 : 0));
                __syncwarp();
                if (lane == 0) mbar_arrive(b_stg);
                DT(11 + 24 * layer);
            }
            {
                float acc[64];
#pragma unroll
                for (int i = 0; i < 32; i++) asm volatile("shl.b32 %0, %2, 16;\nand.b32 %1, %2, 0xffff0000;" : "=f"(acc[2 * i]), "=f"(acc[2 * i + 1]) : "r"(x[i]));
                kblock<128, R5_N>(acc, da0, db0, f5, r5);
                DT(18 + 24 * layer);
                mainloop<128, R5_N, R5_STAGE>(acc, 55, da0, db0, f5, rel5, rel_on, r5, 62 - 40 * (layer ^ 1), []() {} DT_ARG);
                DT(12 + 24 * layer);
#pragma unroll
                for (int i = 0; i < 32; i++) x[i] = pack2(acc[2 * i], acc[2 * i + 1]);
                DT(13 + 24 * layer);
                DT(14 + 24 * layer);
            }
        }
#pragma unroll
        for (int jp = 0; jp < 8; jp++) stsm4(s_epi + (fr ^ ((jp & 3) << 5)) + (jp >> 2) * 16384, x[4 * jp], x[4 * jp + 1], x[4 * jp + 2], x[4 * jp + 3]);
        __syncwarp();
        copy_out(outp, s_epi);
        DT(38);
        DT_DUMP;
        GT(4);
        }
        cluster_arrive_relaxed();
        cluster_wait();
    }
}

typedef CUresult (*PFN_encodeTiled)(CUtensorMap*, CUtensorMapDataType, cuuint32_t, void*, const cuuint64_t*, const cuuint64_t*,
                                    const cuuint32_t*, const cuuint32_t*, CUtensorMapInterleave, CUtensorMapSwizzle,
                                    CUtensorMapL2promotion, CUtensorMapFloatOOBfill);

static CUtensorMap make_map(PFN_encodeTiled enc, const void* ptr, int inner, int outer, int box_inner, int box_outer,
                            CUtensorMapSwizzle swz = CU_TENSOR_MAP_SWIZZLE_128B) {
    CUtensorMap m;
    cuuint64_t dims[2] = {(cuuint64_t)inner, (cuuint64_t)outer};
    cuuint64_t strides[1] = {(cuuint64_t)inner * 2};
    cuuint32_t box[2] = {(cuuint32_t)box_inner, (cuuint32_t)box_outer};
    cuuint32_t es[2] = {1, 1};
    enc(&m, CU_TENSOR_MAP_DATA_TYPE_BFLOAT16, 2, const_cast<void*>(ptr), dims, strides, box, es, CU_TENSOR_MAP_INTERLEAVE_NONE,
        swz, CU_TENSOR_MAP_L2_PROMOTION_L2_256B, CU_TENSOR_MAP_FLOAT_OOB_FILL_NONE);
    return m;
}

extern "C" void kernel_launch(void* const* d_in, const int* in_sizes, int n_in, void* d_out, int out_size) {
    const bf16* A_q = (const bf16*)d_in[0];
    const bf16* A_k = (const bf16*)d_in[1];
    const bf16* A_v = (const bf16*)d_in[2];
    const bf16* A_shk = (const bf16*)d_in[3];
    const bf16* A_ssk = (const bf16*)d_in[4];
    const bf16* A_ssD = (const bf16*)d_in[5];
    const bf16* w1 = (const bf16*)d_in[7];
    const bf16* w2 = (const bf16*)d_in[8];
    const bf16* w3 = (const bf16*)d_in[9];
    const bf16* w4 = (const bf16*)d_in[10];
    bf16* out = (bf16*)d_out;

    static PFN_encodeTiled enc = nullptr;
    static bool attr_done = false;
    if (!enc) {
        void* fn = nullptr;
        cudaDriverEntryPointQueryResult qr;
        cudaGetDriverEntryPoint("cuTensorMapEncodeTiled", &fn, cudaEnableDefault, &qr);
        enc = (PFN_encodeTiled)fn;
    }
    if (!attr_done) {
        cudaFuncSetAttribute(mega_kernel, cudaFuncAttributeMaxDynamicSharedMemorySize, MEGA_SMEM);
        attr_done = true;
    }
    void* p_act;
    cudaGetSymbolAddress(&p_act, g_act);
    bf16* act = (bf16*)(((uintptr_t)p_act + 0x1fffff) & ~(uintptr_t)0x1fffff);

    MegaMaps tm;
    tm.q = make_map(enc, A_q, D_, S_, 64, 128);
    tm.act = make_map(enc, act, D_, R_END, 64, 128);
    tm.w1 = make_map(enc, w1, D_, D_, 64, 64);
    tm.w2 = make_map(enc, w2, D_, D_, 64, 64);
    tm.w3 = make_map(enc, w3, F_, D_, 64, 64);
    tm.w4 = make_map(enc, w4, D_, F_, 64, 64);
    {
        cuuint64_t dims[5] = {D_, 2, 2, 8, 256}, strides[4] = {64 * D_ * 2, 128, (cuuint64_t)2048 * D_ * 2, D_ * 2};
        cuuint32_t box[5] = {64, 2, 2, 8, 1}, es[5] = {1, 1, 1, 1, 1};
        enc(&tm.y, CU_TENSOR_MAP_DATA_TYPE_BFLOAT16, 5, act + (size_t)R_Y * D_, dims, strides, box, es, CU_TENSOR_MAP_INTERLEAVE_NONE,
            CU_TENSOR_MAP_SWIZZLE_128B, CU_TENSOR_MAP_L2_PROMOTION_NONE, CU_TENSOR_MAP_FLOAT_OOB_FILL_NONE);
    }
    {
        cuuint64_t dims[4] = {D_, 2, D_ / 8, 4}, strides[3] = {D_ * 2, 8 * D_ * 2, 2 * D_ * 2};
        cuuint32_t box[4] = {64, 2, 16, 2}, es[4] = {1, 1, 1, 1};
        enc(&tm.w1p, CU_TENSOR_MAP_DATA_TYPE_BFLOAT16, 4, (void*)w1, dims, strides, box, es, CU_TENSOR_MAP_INTERLEAVE_NONE,
            CU_TENSOR_MAP_SWIZZLE_128B, CU_TENSOR_MAP_L2_PROMOTION_L2_256B, CU_TENSOR_MAP_FLOAT_OOB_FILL_NONE);
    }
    for (int i = 0; i < 2; i++) {
        cuuint64_t dims[4] = {D_, 4, 8, S_ / 32}, strides[3] = {8 * D_ * 2, D_ * 2, 32 * D_ * 2};
        cuuint32_t box[4] = {16, 4, 8, 4}, es[4] = {1, 1, 1, 1};
        enc(i ? &tm.v : &tm.k, CU_TENSOR_MAP_DATA_TYPE_BFLOAT16, 4, (void*)(i ? A_v : A_k), dims, strides, box, es, CU_TENSOR_MAP_INTERLEAVE_NONE,
            CU_TENSOR_MAP_SWIZZLE_32B, CU_TENSOR_MAP_L2_PROMOTION_NONE, CU_TENSOR_MAP_FLOAT_OOB_FILL_NONE);
    }
    mega_kernel<<<2 * NCL, 384, MEGA_SMEM, cudaStreamPerThread>>>(tm, out, act, w1, w2, w3, A_q, A_k, A_v, A_shk, A_ssk, A_ssD);
}
```

```cpp
#include <cuda_runtime.h>
#include <cuda_bf16.h>
#include <cuda.h>
#include <stdint.h>

typedef __nv_bfloat16 bf16;

constexpr int S_ = 2048;
constexpr int D_ = 1024;
constexpr int F_ = 3584;

constexpr int R_XA = 0, R_X1 = 256, R_H2 = 512, R_Y = 1536, R_H = 16384 + 8, R_HP = S_ + 8, R_END = R_H + 2 * R_HP;
__device__ __align__(1024) bf16 g_act[(size_t)(R_END + 1024) * D_];
__device__ __align__(16) float g_cpart[16 * (F_ + D_)];
__device__ __align__(128) float2 g_stats[3 * S_ * 8];
__device__ __align__(128) uint4 g_halo[2 * 144 * 64];

__device__ __forceinline__ float bfr(float x) { return __bfloat162float(__float2bfloat16_rn(x)); }
__device__ __forceinline__ uint32_t pack2(float lo, float hi) {
    __nv_bfloat162 v = __floats2bfloat162_rn(lo, hi);
    return *reinterpret_cast<uint32_t*>(&v);
}
__device__ __forceinline__ float lo2f(uint32_t v) { return __uint_as_float(v << 16); }
__device__ __forceinline__ float hi2f(uint32_t v) { return __uint_as_float(v & 0xffff0000u); }
__device__ __forceinline__ float frcp(float x) { float r; asm("rcp.approx.f32 %0, %1;" : "=f"(r) : "f"(x)); return r; }
__device__ __forceinline__ float fsqrt(float x) { float r; asm("sqrt.approx.f32 %0, %1;" : "=f"(r) : "f"(x)); return r; }
__device__ __forceinline__ uint32_t smem_u32(const void* p) { return (uint32_t)__cvta_generic_to_shared(p); }

__device__ __forceinline__ void mbar_init(uint32_t bar, uint32_t cnt) {
    asm volatile("mbarrier.init.shared::cta.b64 [%0], %1;" ::"r"(bar), "r"(cnt));
}
__device__ __forceinline__ void mbar_expect_tx(uint32_t bar, uint32_t bytes) {
    asm volatile("mbarrier.arrive.expect_tx.shared::cta.b64 _, [%0], %1;" ::"r"(bar), "r"(bytes) : "memory");
}
__device__ __forceinline__ void mbar_arrive(uint32_t bar) {
    asm volatile("mbarrier.arrive.shared::cta.b64 _, [%0];" ::"r"(bar) : "memory");
}
__device__ __forceinline__ void mbar_wait(uint32_t bar, uint32_t parity) {
    asm volatile(
        "{\n.reg .pred p;\n.reg .u32 n;\n"
        "mbarrier.try_wait.parity.shared::cta.b64 p, [%0], %1;\n"
        "@p bra LD;\n"
        "mov.u32 n, 0;\n"
        "LW:\n"
        "mbarrier.try_wait.parity.shared::cta.b64 p, [%0], %1;\n"
        "@p bra LD;\n"
        "add.u32 n, n, 1;\n"
        "setp.lt.u32 p, n, 0x400000;\n"
        "@p bra LW;\n"
        "LD:\n}\n"
        ::"r"(bar), "r"(parity) : "memory");
}
__device__ __forceinline__ void tma_load_2d(uint32_t dst, const CUtensorMap* tm, uint32_t bar, int c0, int c1) {
    asm volatile(
        "cp.async.bulk.tensor.2d.shared::cluster.global.mbarrier::complete_tx::bytes [%0], [%1, {%3, %4}], [%2];"
        ::"r"(dst), "l"((uint64_t)tm), "r"(bar), "r"(c0), "r"(c1) : "memory");
}
__device__ __forceinline__ void tma_load_2d_mc(uint32_t dst, const CUtensorMap* tm, uint32_t bar, int c0, int c1) {
    asm volatile(
        "cp.async.bulk.tensor.2d.shared::cluster.global.mbarrier::complete_tx::bytes.multicast::cluster [%0], [%1, {%3, %4}], [%2], %5;"
        ::"r"(dst), "l"((uint64_t)tm), "r"(bar), "r"(c0), "r"(c1), "h"((uint16_t)3) : "memory");
}
__device__ __forceinline__ void tma_prefetch_2d(const CUtensorMap* tm, int c0, int c1) {
    asm volatile("cp.async.bulk.prefetch.tensor.2d.L2.global.tile [%0, {%1, %2}];" ::"l"((uint64_t)tm), "r"(c0), "r"(c1) : "memory");
}
__device__ __forceinline__ void tma_store_2d(const CUtensorMap* tm, uint32_t src, int c0, int c1) {
    asm volatile("cp.async.bulk.tensor.2d.global.shared::cta.bulk_group [%0, {%2, %3}], [%1];"
                 ::"l"((uint64_t)tm), "r"(src), "r"(c0), "r"(c1) : "memory");
}
__device__ __forceinline__ void wgmma_fence() { asm volatile("wgmma.fence.sync.aligned;" ::: "memory"); }
__device__ __forceinline__ void wgmma_commit() { asm volatile("wgmma.commit_group.sync.aligned;" ::: "memory"); }
template <int N> __device__ __forceinline__ void wgmma_wait() { asm volatile("wgmma.wait_group.sync.aligned %0;" ::"n"(N) : "memory"); }
__device__ __forceinline__ void named_bar_arrive(int id, int n) { asm volatile("bar.arrive %0, %1;" ::"r"(id), "r"(n) : "memory"); }
__device__ __forceinline__ void named_bar_sync(int id, int n) { asm volatile("bar.sync %0, %1;" ::"r"(id), "r"(n) : "memory"); }

__device__ __forceinline__ uint32_t desc_a(uint32_t addr) { return ((addr & 0x3FFFF) >> 4) | (1u << 16); }
__device__ __forceinline__ uint32_t desc_b(uint32_t addr) { return ((addr & 0x3FFFF) >> 4) | (512u << 16); }

template <int ACC> __device__ __forceinline__ void wgmma_m64n192k16(float (&d)[96], uint32_t descA, uint32_t descB) {
  asm volatile("{\n.reg .pred p;\n.reg .b64 da, db;\nsetp.ne.b32 p, %99, 0;\nmov.b64 da, {%96, %98};\nmov.b64 db, {%97, %98};\n"
    "wgmma.mma_async.sync.aligned.m64n192k16.f32.bf16.bf16 "
    "{%0, %1, %2, %3, %4, %5, %6, %7, %8, %9, %10, %11, %12, %13, %14, %15, %16, %17, %18, %19, %20, %21, %22, %23, %24, %25, %26, %27, %28, %29, %30, %31, %32, %33, %34, %35, %36, %37, %38, %39, %40, %41, %42, %43, %44, %45, %46, %47, %48, %49, %50, %51, %52, %53, %54, %55, %56, %57, %58, %59, %60, %61, %62, %63, %64, %65, %66, %67, %68, %69, %70, %71, %72, %73, %74, %75, %76, %77, %78, %79, %80, %81, %82, %83, %84, %85, %86, %87, %88, %89, %90, %91, %92, %93, %94, %95}, "
    "da, db, p, 1, 1, 0, 1;\n}\n"
    : "+f"(d[0]), "+f"(d[1]), "+f"(d[2]), "+f"(d[3]), "+f"(d[4]), "+f"(d[5]), "+f"(d[6]), "+f"(d[7]), "+f"(d[8]), "+f"(d[9]), "+f"(d[10]), "+f"(d[11]), "+f"(d[12]), "+f"(d[13]), "+f"(d[14]), "+f"(d[15]), "+f"(d[16]), "+f"(d[17]), "+f"(d[18]), "+f"(d[19]), "+f"(d[20]), "+f"(d[21]), "+f"(d[22]), "+f"(d[23]), "+f"(d[24]), "+f"(d[25]), "+f"(d[26]), "+f"(d[27]), "+f"(d[28]), "+f"(d[29]), "+f"(d[30]), "+f"(d[31]), "+f"(d[32]), "+f"(d[33]), "+f"(d[34]), "+f"(d[35]), "+f"(d[36]), "+f"(d[37]), "+f"(d[38]), "+f"(d[39]), "+f"(d[40]), "+f"(d[41]), "+f"(d[42]), "+f"(d[43]), "+f"(d[44]), "+f"(d[45]), "+f"(d[46]), "+f"(d[47]), "+f"(d[48]), "+f"(d[49]), "+f"(d[50]), "+f"(d[51]), "+f"(d[52]), "+f"(d[53]), "+f"(d[54]), "+f"(d[55]), "+f"(d[56]), "+f"(d[57]), "+f"(d[58]), "+f"(d[59]), "+f"(d[60]), "+f"(d[61]), "+f"(d[62]), "+f"(d[63]), "+f"(d[64]), "+f"(d[65]), "+f"(d[66]), "+f"(d[67]), "+f"(d[68]), "+f"(d[69]), "+f"(d[70]), "+f"(d[71]), "+f"(d[72]), "+f"(d[73]), "+f"(d[74]), "+f"(d[75]), "+f"(d[76]), "+f"(d[77]), "+f"(d[78]), "+f"(d[79]), "+f"(d[80]), "+f"(d[81]), "+f"(d[82]), "+f"(d[83]), "+f"(d[84]), "+f"(d[85]), "+f"(d[86]), "+f"(d[87]), "+f"(d[88]), "+f"(d[89]), "+f"(d[90]), "+f"(d[91]), "+f"(d[92]), "+f"(d[93]), "+f"(d[94]), "+f"(d[95])
    : "r"(descA), "r"(descB), "r"(0x40000040u), "n"(ACC));
}

template <int ACC> __device__ __forceinline__ void wgmma_m64n256k16(float (&d)[128], uint32_t descA, uint32_t descB) {
  asm volatile("{\n.reg .pred p;\n.reg .b64 da, db;\nsetp.ne.b32 p, %131, 0;\nmov.b64 da, {%128, %130};\nmov.b64 db, {%129, %130};\n"
    "wgmma.mma_async.sync.aligned.m64n256k16.f32.bf16.bf16 "
    "{%0, %1, %2, %3, %4, %5, %6, %7, %8, %9, %10, %11, %12, %13, %14, %15, %16, %17, %18, %19, %20, %21, %22, %23, %24, %25, %26, %27, %28, %29, %30, %31, %32, %33, %34, %35, %36, %37, %38, %39, %40, %41, %42, %43, %44, %45, %46, %47, %48, %49, %50, %51, %52, %53, %54, %55, %56, %57, %58, %59, %60, %61, %62, %63, %64, %65, %66, %67, %68, %69, %70, %71, %72, %73, %74, %75, %76, %77, %78, %79, %80, %81, %82, %83, %84, %85, %86, %87, %88, %89, %90, %91, %92, %93, %94, %95, %96, %97, %98, %99, %100, %101, %102, %103, %104, %105, %106, %107, %108, %109, %110, %111, %112, %113, %114, %115, %116, %117, %118, %119, %120, %121, %122, %123, %124, %125, %126, %127}, "
    "da, db, p, 1, 1, 0, 1;\n}\n"
    : "+f"(d[0]), "+f"(d[1]), "+f"(d[2]), "+f"(d[3]), "+f"(d[4]), "+f"(d[5]), "+f"(d[6]), "+f"(d[7]), "+f"(d[8]), "+f"(d[9]), "+f"(d[10]), "+f"(d[11]), "+f"(d[12]), "+f"(d[13]), "+f"(d[14]), "+f"(d[15]), "+f"(d[16]), "+f"(d[17]), "+f"(d[18]), "+f"(d[19]), "+f"(d[20]), "+f"(d[21]), "+f"(d[22]), "+f"(d[23]), "+f"(d[24]), "+f"(d[25]), "+f"(d[26]), "+f"(d[27]), "+f"(d[28]), "+f"(d[29]), "+f"(d[30]), "+f"(d[31]), "+f"(d[32]), "+f"(d[33]), "+f"(d[34]), "+f"(d[35]), "+f"(d[36]), "+f"(d[37]), "+f"(d[38]), "+f"(d[39]), "+f"(d[40]), "+f"(d[41]), "+f"(d[42]), "+f"(d[43]), "+f"(d[44]), "+f"(d[45]), "+f"(d[46]), "+f"(d[47]), "+f"(d[48]), "+f"(d[49]), "+f"(d[50]), "+f"(d[51]), "+f"(d[52]), "+f"(d[53]), "+f"(d[54]), "+f"(d[55]), "+f"(d[56]), "+f"(d[57]), "+f"(d[58]), "+f"(d[59]), "+f"(d[60]), "+f"(d[61]), "+f"(d[62]), "+f"(d[63]), "+f"(d[64]), "+f"(d[65]), "+f"(d[66]), "+f"(d[67]), "+f"(d[68]), "+f"(d[69]), "+f"(d[70]), "+f"(d[71]), "+f"(d[72]), "+f"(d[73]), "+f"(d[74]), "+f"(d[75]), "+f"(d[76]), "+f"(d[77]), "+f"(d[78]), "+f"(d[79]), "+f"(d[80]), "+f"(d[81]), "+f"(d[82]), "+f"(d[83]), "+f"(d[84]), "+f"(d[85]), "+f"(d[86]), "+f"(d[87]), "+f"(d[88]), "+f"(d[89]), "+f"(d[90]), "+f"(d[91]), "+f"(d[92]), "+f"(d[93]), "+f"(d[94]), "+f"(d[95]), "+f"(d[96]), "+f"(d[97]), "+f"(d[98]), "+f"(d[99]), "+f"(d[100]), "+f"(d[101]), "+f"(d[102]), "+f"(d[103]), "+f"(d[104]), "+f"(d[105]), "+f"(d[106]), "+f"(d[107]), "+f"(d[108]), "+f"(d[109]), "+f"(d[110]), "+f"(d[111]), "+f"(d[112]), "+f"(d[113]), "+f"(d[114]), "+f"(d[115]), "+f"(d[116]), "+f"(d[117]), "+f"(d[118]), "+f"(d[119]), "+f"(d[120]), "+f"(d[121]), "+f"(d[122]), "+f"(d[123]), "+f"(d[124]), "+f"(d[125]), "+f"(d[126]), "+f"(d[127])
    : "r"(descA), "r"(descB), "r"(0x40000040u), "n"(ACC));
}

template <int ACC> __device__ __forceinline__ void wgmma_m64n128k16(float (&d)[64], uint32_t descA, uint32_t descB) {
  asm volatile("{\n.reg .pred p;\n.reg .b64 da, db;\nsetp.ne.b32 p, %67, 0;\nmov.b64 da, {%64, %66};\nmov.b64 db, {%65, %66};\n"
    "wgmma.mma_async.sync.aligned.m64n128k16.f32.bf16.bf16 "
    "{%0, %1, %2, %3, %4, %5, %6, %7, %8, %9, %10, %11, %12, %13, %14, %15, %16, %17, %18, %19, %20, %21, %22, %23, %24, %25, %26, %27, %28, %29, %30, %31, %32, %33, %34, %35, %36, %37, %38, %39, %40, %41, %42, %43, %44, %45, %46, %47, %48, %49, %50, %51, %52, %53, %54, %55, %56, %57, %58, %59, %60, %61, %62, %63}, "
    "da, db, p, 1, 1, 0, 1;\n}\n"
    : "+f"(d[0]), "+f"(d[1]), "+f"(d[2]), "+f"(d[3]), "+f"(d[4]), "+f"(d[5]), "+f"(d[6]), "+f"(d[7]), "+f"(d[8]), "+f"(d[9]), "+f"(d[10]), "+f"(d[11]), "+f"(d[12]), "+f"(d[13]), "+f"(d[14]), "+f"(d[15]), "+f"(d[16]), "+f"(d[17]), "+f"(d[18]), "+f"(d[19]), "+f"(d[20]), "+f"(d[21]), "+f"(d[22]), "+f"(d[23]), "+f"(d[24]), "+f"(d[25]), "+f"(d[26]), "+f"(d[27]), "+f"(d[28]), "+f"(d[29]), "+f"(d[30]), "+f"(d[31]), "+f"(d[32]), "+f"(d[33]), "+f"(d[34]), "+f"(d[35]), "+f"(d[36]), "+f"(d[37]), "+f"(d[38]), "+f"(d[39]), "+f"(d[40]), "+f"(d[41]), "+f"(d[42]), "+f"(d[43]), "+f"(d[44]), "+f"(d[45]), "+f"(d[46]), "+f"(d[47]), "+f"(d[48]), "+f"(d[49]), "+f"(d[50]), "+f"(d[51]), "+f"(d[52]), "+f"(d[53]), "+f"(d[54]), "+f"(d[55]), "+f"(d[56]), "+f"(d[57]), "+f"(d[58]), "+f"(d[59]), "+f"(d[60]), "+f"(d[61]), "+f"(d[62]), "+f"(d[63])
    : "r"(descA), "r"(descB), "r"(0x40000040u), "n"(ACC));
}

template <int BN> struct WG;
template <> struct WG<128> { template <int ACC> static __device__ __forceinline__ void mma(float (&d)[64], uint32_t a, uint32_t b) { wgmma_m64n128k16<ACC>(d, a, b); } };
template <> struct WG<256> { template <int ACC> static __device__ __forceinline__ void mma(float (&d)[128], uint32_t a, uint32_t b) { wgmma_m64n256k16<ACC>(d, a, b); } };
template <> struct WG<192> { template <int ACC> static __device__ __forceinline__ void mma(float (&d)[96], uint32_t a, uint32_t b) { wgmma_m64n192k16<ACC>(d, a, b); } };

#define DBG_T(i)
__device__ __forceinline__ void fence_async_smem() { asm volatile("fence.proxy.async.shared::cta;" ::: "memory"); }
__device__ __forceinline__ void prefetch_tmap(const CUtensorMap* tm) { asm volatile("prefetch.tensormap [%0];" ::"l"((uint64_t)tm) : "memory"); }
__device__ __forceinline__ uint32_t mapa_u32(uint32_t addr, uint32_t cta) {
    uint32_t r;
    asm volatile("mapa.shared::cluster.u32 %0, %1, %2;" : "=r"(r) : "r"(addr), "r"(cta));
    return r;
}
__device__ __forceinline__ void mbar_arrive_cluster(uint32_t cluster_addr) {
    asm volatile("mbarrier.arrive.shared::cluster.b64 _, [%0];" ::"r"(cluster_addr) : "memory");
}
__device__ __forceinline__ bool elect_one() {
    uint32_t p;
    asm volatile("{\n.reg .pred P;\nelect.sync _|P, 0xffffffff;\nselp.u32 %0, 1, 0, P;\n}\n" : "=r"(p));
    return p != 0;
}
__device__ __forceinline__ void cluster_arrive_relaxed() { asm volatile("barrier.cluster.arrive.relaxed.aligned;" ::: "memory"); }
__device__ __forceinline__ void cluster_wait() { asm volatile("barrier.cluster.wait.acquire.aligned;" ::: "memory"); }

__device__ __forceinline__ uint32_t bsub2(uint32_t a, uint32_t b) {
    __nv_bfloat162 r = __hsub2(*reinterpret_cast<__nv_bfloat162*>(&a), *reinterpret_cast<__nv_bfloat162*>(&b));
    return *reinterpret_cast<uint32_t*>(&r);
}
__device__ __forceinline__ uint32_t bmul2(uint32_t a, uint32_t b) {
    __nv_bfloat162 r = __hmul2(*reinterpret_cast<__nv_bfloat162*>(&a), *reinterpret_cast<__nv_bfloat162*>(&b));
    return *reinterpret_cast<uint32_t*>(&r);
}
__device__ __forceinline__ uint32_t badd2(uint32_t a, uint32_t b) {
    __nv_bfloat162 r = __hadd2(*reinterpret_cast<__nv_bfloat162*>(&a), *reinterpret_cast<__nv_bfloat162*>(&b));
    return *reinterpret_cast<uint32_t*>(&r);
}
constexpr int BM = 128, BK = 64;
constexpr int R5_STAGE = 32768, R5_N = 5;
constexpr int R4_STAGE = 49152, R4_N = 4;
constexpr int R4B_STAGE = 40960;
constexpr int OFF_STG5 = 0, OFF_R = 32768;
constexpr int OFF_EPI = 196608;
constexpr int OFF_BAR = OFF_EPI + 32768;
constexpr int OFF_RS = OFF_BAR + 256;
constexpr int OFF_CS = OFF_RS + 1024;
constexpr int MEGA_SMEM = OFF_CS + 1792;
enum { FL_XA = 0, FL_H = 2, FL_X1 = 4, FL_H2 = 6, FL_CS = 10, FL_KINDS = 11 };
constexpr int FL_PITCH = 64;
constexpr int FL_WORDS = 2 * FL_KINDS * 16 * FL_PITCH;
__device__ unsigned int g_flag[FL_WORDS];
__device__ __align__(8) unsigned int g_ticket[18 * FL_PITCH];
constexpr int NCL = 66;
__device__ __forceinline__ unsigned int* flag_ptr(int layer, int kind, int i) { return g_flag + ((layer * FL_KINDS + kind) * 16 + i) * FL_PITCH; }

__device__ __forceinline__ void wait_flag(const unsigned int* p, unsigned int target) {
    long long t0 = clock64();
    while (true) {
        unsigned int v;
        asm volatile("ld.relaxed.gpu.global.u32 %0, [%1];" : "=r"(v) : "l"(p) : "memory");
        if ((int)(v - target) >= 0) break;
        if (clock64() - t0 > 2000000000LL) break;
    }
    asm volatile("fence.acquire.gpu;" ::: "memory");
}
__device__ __forceinline__ void fence_proxy_async() {
    asm volatile("fence.proxy.async.global;" ::: "memory");
    asm volatile("fence.proxy.async.shared::cta;" ::: "memory");
}
__device__ __forceinline__ void stsm4(uint32_t addr, uint32_t r0, uint32_t r1, uint32_t r2, uint32_t r3) {
    asm volatile("stmatrix.sync.aligned.m8n8.x4.shared.b16 [%0], {%1,%2,%3,%4};" ::"r"(addr), "r"(r0), "r"(r1), "r"(r2), "r"(r3));
}
__device__ __forceinline__ uint4 lds128(uint32_t a) {
    uint4 v;
    asm volatile("ld.shared.v4.b32 {%0,%1,%2,%3}, [%4];" : "=r"(v.x), "=r"(v.y), "=r"(v.z), "=r"(v.w) : "r"(a) : "memory");
    return v;
}
__device__ __forceinline__ void stg128(void* p, uint4 v) {
    asm volatile("st.global.v4.b32 [%0], {%1,%2,%3,%4};" ::"l"(p), "r"(v.x), "r"(v.y), "r"(v.z), "r"(v.w) : "memory");
}
__device__ __forceinline__ float gelu_tanh_h(float hx) {
    float z = hx * fmaf(hx * hx, 8.0f * 0.035677408136300125f, 2.0f * 0.7978845608028654f);
    float t;
    asm("tanh.approx.f32 %0, %1;" : "=f"(t) : "f"(z));
    return fmaf(hx, t, hx);
}
__device__ __forceinline__ uint32_t gelu2h(uint32_t hx) {
    uint32_t r;
    asm("{\n.reg .b32 z;\nmul.rn.bf16x2 z, %1, %1;\nfma.rn.bf16x2 z, z, %2, %3;\nmul.rn.bf16x2 z, z, %1;\ntanh.approx.bf16x2 z, z;\nfma.rn.bf16x2 %0, %1, z, %1;\n}"
        : "=r"(r) : "r"(hx), "r"(0x3e923e92u), "r"(0x3fcc3fccu));
    return r;
}
__device__ __forceinline__ uint4 gelu8h(uint4 v) { return make_uint4(gelu2h(v.x), gelu2h(v.y), gelu2h(v.z), gelu2h(v.w)); }

__device__ __forceinline__ void row_stats(const float2* p, uint32_t tag, float& mean, float& var) {
    float2 v[8];
#pragma unroll 1
    for (int n = 0; n < (1 << 20); n++) {
#pragma unroll
        for (int i = 0; i < 8; i++)
            asm volatile("{\n.reg .b64 t;\nld.relaxed.gpu.global.b64 t, [%2];\nmov.b64 {%0, %1}, t;\n}" : "=f"(v[i].x), "=f"(v[i].y) : "l"(p + 128 * i) : "memory");
        uint32_t old = 0;
#pragma unroll
        for (int i = 0; i < 8; i++) old |= __float_as_uint(v[i].y) ^ tag;
        if ((int)old >= 0) break;
    }
    mean = (((v[0].x + v[1].x) + (v[2].x + v[3].x)) + ((v[4].x + v[5].x) + (v[6].x + v[7].x))) * 0.125f;
    float m2 = 0.f, d2 = 0.f;
#pragma unroll
    for (int i = 0; i < 8; i++) { m2 += fabsf(v[i].y); d2 = fmaf(v[i].x - mean, v[i].x - mean, d2); }
    var = fmaf(128.0f, d2, m2) * (1.0f / D_);
}
struct RingState { uint32_t st, ph; };

#define DT(i)
#define DT_DECL
#define DT_PAR
#define DT_ARG
#define DT_DUMP
#define DP(i)
#define GT(i)
#define TM(i)

template <int BN, int NST, int ACC = 1>
__device__ __forceinline__ void kblock(float (&acc)[BN / 2], uint32_t da, uint32_t db, uint32_t bfull, RingState& rs) {
    mbar_wait(bfull + 8 * rs.st, rs.ph);
    wgmma_fence();
    WG<BN>::template mma<ACC>(acc, da, db);
#pragma unroll
    for (int k = 1; k < 4; k++) WG<BN>::template mma<1>(acc, da + k * 2, db + k * 128);
    wgmma_commit();
    if (++rs.st == NST) { rs.st = 0; rs.ph ^= 1; }
}
#define SIG 0
#define PA3A 1
#define PA3B 1
template <int BN, int NST, int STAGE, int PAUSE = 0, class F>
__device__ __forceinline__ void mainloop(float (&acc)[BN / 2], int KB, uint32_t da0, uint32_t db0, uint32_t bfull, uint32_t rel, bool rel_on,
                                         RingState& rs, int dbg, F pre DT_PAR, int wg = 0) {
    uint32_t prev = rs.st ? rs.st - 1 : NST - 1;
    const int pause = wg ? KB - PAUSE : -1;
#pragma unroll 1
    for (int kk = 0; kk < KB; kk++) {
        const uint32_t cur = rs.st;
        if (PAUSE && kk == pause) {
            wgmma_wait<0>();
            if (rel_on) mbar_arrive_cluster(rel + 8 * prev);
            named_bar_sync(13, 256);
        }
        kblock<BN, NST>(acc, da0 + cur * (STAGE / 16), db0 + cur * (STAGE / 16), bfull, rs);
        if (PAUSE && SIG == 2 && wg == 0 && kk == KB - 1) named_bar_arrive(13, 256);
        wgmma_wait<1>();
        if (rel_on && !(PAUSE && kk == pause)) mbar_arrive_cluster(rel + 8 * prev);
        prev = cur;
    }
    if (PAUSE && SIG == 0 && wg == 0) named_bar_arrive(13, 256);
    pre();
    wgmma_wait<0>();
#pragma unroll
    for (int i = 0; i < BN / 2; i++) asm volatile("" : "+f"(acc[i])::"memory");
    if (PAUSE && SIG == 1 && wg == 0) named_bar_arrive(13, 256);
    if (rel_on) mbar_arrive_cluster(rel + 8 * prev);
}
__device__ __forceinline__ void hmma(float (&c)[4], uint32_t a0, uint32_t a1, uint32_t a2, uint32_t a3, uint32_t b0, uint32_t b1, bool first) {
    if (first) asm("{\n.reg .f32 z;\nmov.f32 z, 0f00000000;\nmma.sync.aligned.m16n8k16.row.col.f32.bf16.bf16.f32 {%0,%1,%2,%3}, {%4,%5,%6,%7}, {%8,%9}, {z,z,z,z};\n}"
        : "=f"(c[0]), "=f"(c[1]), "=f"(c[2]), "=f"(c[3]) : "r"(a0), "r"(a1), "r"(a2), "r"(a3), "r"(b0), "r"(b1));
    else
    asm("mma.sync.aligned.m16n8k16.row.col.f32.bf16.bf16.f32 {%0,%1,%2,%3}, {%4,%5,%6,%7}, {%8,%9}, {%0,%1,%2,%3};"
        : "+f"(c[0]), "+f"(c[1]), "+f"(c[2]), "+f"(c[3]) : "r"(a0), "r"(a1), "r"(a2), "r"(a3), "r"(b0), "r"(b1));
}
__device__ __forceinline__ void hmma8(float (&c)[4], uint32_t a0, uint32_t a1, uint32_t b0, bool first) {
    if (first) asm("{\n.reg .f32 z;\nmov.f32 z, 0f00000000;\nmma.sync.aligned.m16n8k8.row.col.f32.bf16.bf16.f32 {%0,%1,%2,%3}, {%4,%5}, {%6}, {z,z,z,z};\n}"
        : "=f"(c[0]), "=f"(c[1]), "=f"(c[2]), "=f"(c[3]) : "r"(a0), "r"(a1), "r"(b0));
    else
    asm("mma.sync.aligned.m16n8k8.row.col.f32.bf16.bf16.f32 {%0,%1,%2,%3}, {%4,%5}, {%6}, {%0,%1,%2,%3};"
        : "+f"(c[0]), "+f"(c[1]), "+f"(c[2]), "+f"(c[3]) : "r"(a0), "r"(a1), "r"(b0));
}
template <int N> __device__ __forceinline__ void zero_acc(float (&acc)[N]) {
#pragma unroll
    for (int i = 0; i < N; i++) acc[i] = 0.f;
}
__device__ __forceinline__ void ldsm4(uint32_t& r0, uint32_t& r1, uint32_t& r2, uint32_t& r3, uint32_t addr) {
    asm volatile("ldmatrix.sync.aligned.m8n8.x4.shared.b16 {%0,%1,%2,%3}, [%4];" : "=r"(r0), "=r"(r1), "=r"(r2), "=r"(r3) : "r"(addr));
}

__device__ __forceinline__ void ldsm4t(uint32_t& r0, uint32_t& r1, uint32_t& r2, uint32_t& r3, uint32_t addr) {
    asm volatile("ldmatrix.sync.aligned.m8n8.x4.trans.shared.b16 {%0,%1,%2,%3}, [%4];" : "=r"(r0), "=r"(r1), "=r"(r2), "=r"(r3) : "r"(addr));
}

#define DBG_S(i)
#define DBG_OUT(r, o)
#define DBG_F(i)
#define DBG_W(i)
constexpr int CV_CH = 8;
constexpr int CV_SL = 16384;
constexpr int CV_QG = 128 * 8 + 16;
constexpr int CV_HPL = 2048 + 192;
constexpr int CV_0 = 32768, CV_H = 9 * CV_SL, CV_BAR = OFF_RS - CV_0;

template <int K> __device__ __forceinline__ void cv_mma(float (&d)[64], const uint32_t (&a)[4], uint32_t db, int acc);
template <> __device__ __forceinline__ void cv_mma<0>(float (&d)[64], const uint32_t (&a)[4], uint32_t db, int acc) {
    asm volatile("{\n.reg .pred p;\n.reg .b64 b;\nsetp.ne.b32 p, %70, 0;\nmov.b64 b, {%68, %69};\n"
        "wgmma.mma_async.sync.aligned.m64n128k16.f32.bf16.bf16 {%0,%1,%2,%3,%4,%5,%6,%7,%8,%9,%10,%11,%12,%13,%14,%15,%16,%17,%18,%19,%20,%21,%22,%23,%24,%25,%26,%27,%28,%29,%30,%31,%32,%33,%34,%35,%36,%37,%38,%39,%40,%41,%42,%43,%44,%45,%46,%47,%48,%49,%50,%51,%52,%53,%54,%55,%56,%57,%58,%59,%60,%61,%62,%63}, {%64,%65,%66,%67}, b, p, 1, 1, 0;\n}\n"
        : "+f"(d[0]), "+f"(d[1]), "+f"(d[2]), "+f"(d[3]), "+f"(d[4]), "+f"(d[5]), "+f"(d[6]), "+f"(d[7]), "+f"(d[8]), "+f"(d[9]), "+f"(d[10]), "+f"(d[11]), "+f"(d[12]), "+f"(d[13]), "+f"(d[14]), "+f"(d[15]), "+f"(d[16]), "+f"(d[17]), "+f"(d[18]), "+f"(d[19]), "+f"(d[20]), "+f"(d[21]), "+f"(d[22]), "+f"(d[23]), "+f"(d[24]), "+f"(d[25]), "+f"(d[26]), "+f"(d[27]), "+f"(d[28]), "+f"(d[29]), "+f"(d[30]), "+f"(d[31]), "+f"(d[32]), "+f"(d[33]), "+f"(d[34]), "+f"(d[35]), "+f"(d[36]), "+f"(d[37]), "+f"(d[38]), "+f"(d[39]), "+f"(d[40]), "+f"(d[41]), "+f"(d[42]), "+f"(d[43]), "+f"(d[44]), "+f"(d[45]), "+f"(d[46]), "+f"(d[47]), "+f"(d[48]), "+f"(d[49]), "+f"(d[50]), "+f"(d[51]), "+f"(d[52]), "+f"(d[53]), "+f"(d[54]), "+f"(d[55]), "+f"(d[56]), "+f"(d[57]), "+f"(d[58]), "+f"(d[59]), "+f"(d[60]), "+f"(d[61]), "+f"(d[62]), "+f"(d[63])
        : "r"(a[0]), "r"(a[1]), "r"(a[2]), "r"(a[3]), "r"(db), "r"(8u), "r"(acc));
}
template <> __device__ __forceinline__ void cv_mma<1>(float (&d)[64], const uint32_t (&a)[4], uint32_t db, int acc) {
    asm volatile("{\n.reg .pred p;\n.reg .b64 b;\nsetp.ne.b32 p, %62, 0;\nmov.b64 b, {%60, %61};\n"
        "wgmma.mma_async.sync.aligned.m64n112k16.f32.bf16.bf16 {%0,%1,%2,%3,%4,%5,%6,%7,%8,%9,%10,%11,%12,%13,%14,%15,%16,%17,%18,%19,%20,%21,%22,%23,%24,%25,%26,%27,%28,%29,%30,%31,%32,%33,%34,%35,%36,%37,%38,%39,%40,%41,%42,%43,%44,%45,%46,%47,%48,%49,%50,%51,%52,%53,%54,%55}, {%56,%57,%58,%59}, b, p, 1, 1, 0;\n}\n"
        : "+f"(d[0]), "+f"(d[1]), "+f"(d[2]), "+f"(d[3]), "+f"(d[4]), "+f"(d[5]), "+f"(d[6]), "+f"(d[7]), "+f"(d[8]), "+f"(d[9]), "+f"(d[10]), "+f"(d[11]), "+f"(d[12]), "+f"(d[13]), "+f"(d[14]), "+f"(d[15]), "+f"(d[16]), "+f"(d[17]), "+f"(d[18]), "+f"(d[19]), "+f"(d[20]), "+f"(d[21]), "+f"(d[22]), "+f"(d[23]), "+f"(d[24]), "+f"(d[25]), "+f"(d[26]), "+f"(d[27]), "+f"(d[28]), "+f"(d[29]), "+f"(d[30]), "+f"(d[31]), "+f"(d[32]), "+f"(d[33]), "+f"(d[34]), "+f"(d[35]), "+f"(d[36]), "+f"(d[37]), "+f"(d[38]), "+f"(d[39]), "+f"(d[40]), "+f"(d[41]), "+f"(d[42]), "+f"(d[43]), "+f"(d[44]), "+f"(d[45]), "+f"(d[46]), "+f"(d[47]), "+f"(d[48]), "+f"(d[49]), "+f"(d[50]), "+f"(d[51]), "+f"(d[52]), "+f"(d[53]), "+f"(d[54]), "+f"(d[55])
        : "r"(a[0]), "r"(a[1]), "r"(a[2]), "r"(a[3]), "r"(db), "r"(8u), "r"(acc));
}
template <> __device__ __forceinline__ void cv_mma<2>(float (&d)[64], const uint32_t (&a)[4], uint32_t db, int acc) {
    asm volatile("{\n.reg .pred p;\n.reg .b64 b;\nsetp.ne.b32 p, %54, 0;\nmov.b64 b, {%52, %53};\n"
        "wgmma.mma_async.sync.aligned.m64n96k16.f32.bf16.bf16 {%0,%1,%2,%3,%4,%5,%6,%7,%8,%9,%10,%11,%12,%13,%14,%15,%16,%17,%18,%19,%20,%21,%22,%23,%24,%25,%26,%27,%28,%29,%30,%31,%32,%33,%34,%35,%36,%37,%38,%39,%40,%41,%42,%43,%44,%45,%46,%47}, {%48,%49,%50,%51}, b, p, 1, 1, 0;\n}\n"
        : "+f"(d[0]), "+f"(d[1]), "+f"(d[2]), "+f"(d[3]), "+f"(d[4]), "+f"(d[5]), "+f"(d[6]), "+f"(d[7]), "+f"(d[8]), "+f"(d[9]), "+f"(d[10]), "+f"(d[11]), "+f"(d[12]), "+f"(d[13]), "+f"(d[14]), "+f"(d[15]), "+f"(d[16]), "+f"(d[17]), "+f"(d[18]), "+f"(d[19]), "+f"(d[20]), "+f"(d[21]), "+f"(d[22]), "+f"(d[23]), "+f"(d[24]), "+f"(d[25]), "+f"(d[26]), "+f"(d[27]), "+f"(d[28]), "+f"(d[29]), "+f"(d[30]), "+f"(d[31]), "+f"(d[32]), "+f"(d[33]), "+f"(d[34]), "+f"(d[35]), "+f"(d[36]), "+f"(d[37]), "+f"(d[38]), "+f"(d[39]), "+f"(d[40]), "+f"(d[41]), "+f"(d[42]), "+f"(d[43]), "+f"(d[44]), "+f"(d[45]), "+f"(d[46]), "+f"(d[47])
        : "r"(a[0]), "r"(a[1]), "r"(a[2]), "r"(a[3]), "r"(db), "r"(8u), "r"(acc));
}
template <> __device__ __forceinline__ void cv_mma<3>(float (&d)[64], const uint32_t (&a)[4], uint32_t db, int acc) {
    asm volatile("{\n.reg .pred p;\n.reg .b64 b;\nsetp.ne.b32 p, %46, 0;\nmov.b64 b, {%44, %45};\n"
        "wgmma.mma_async.sync.aligned.m64n80k16.f32.bf16.bf16 {%0,%1,%2,%3,%4,%5,%6,%7,%8,%9,%10,%11,%12,%13,%14,%15,%16,%17,%18,%19,%20,%21,%22,%23,%24,%25,%26,%27,%28,%29,%30,%31,%32,%33,%34,%35,%36,%37,%38,%39}, {%40,%41,%42,%43}, b, p, 1, 1, 0;\n}\n"
        : "+f"(d[0]), "+f"(d[1]), "+f"(d[2]), "+f"(d[3]), "+f"(d[4]), "+f"(d[5]), "+f"(d[6]), "+f"(d[7]), "+f"(d[8]), "+f"(d[9]), "+f"(d[10]), "+f"(d[11]), "+f"(d[12]), "+f"(d[13]), "+f"(d[14]), "+f"(d[15]), "+f"(d[16]), "+f"(d[17]), "+f"(d[18]), "+f"(d[19]), "+f"(d[20]), "+f"(d[21]), "+f"(d[22]), "+f"(d[23]), "+f"(d[24]), "+f"(d[25]), "+f"(d[26]), "+f"(d[27]), "+f"(d[28]), "+f"(d[29]), "+f"(d[30]), "+f"(d[31]), "+f"(d[32]), "+f"(d[33]), "+f"(d[34]), "+f"(d[35]), "+f"(d[36]), "+f"(d[37]), "+f"(d[38]), "+f"(d[39])
        : "r"(a[0]), "r"(a[1]), "r"(a[2]), "r"(a[3]), "r"(db), "r"(8u), "r"(acc));
}
template <> __device__ __forceinline__ void cv_mma<4>(float (&d)[64], const uint32_t (&a)[4], uint32_t db, int acc) {
    asm volatile("{\n.reg .pred p;\n.reg .b64 b;\nsetp.ne.b32 p, %38, 0;\nmov.b64 b, {%36, %37};\n"
        "wgmma.mma_async.sync.aligned.m64n64k16.f32.bf16.bf16 {%0,%1,%2,%3,%4,%5,%6,%7,%8,%9,%10,%11,%12,%13,%14,%15,%16,%17,%18,%19,%20,%21,%22,%23,%24,%25,%26,%27,%28,%29,%30,%31}, {%32,%33,%34,%35}, b, p, 1, 1, 0;\n}\n"
        : "+f"(d[0]), "+f"(d[1]), "+f"(d[2]), "+f"(d[3]), "+f"(d[4]), "+f"(d[5]), "+f"(d[6]), "+f"(d[7]), "+f"(d[8]), "+f"(d[9]), "+f"(d[10]), "+f"(d[11]), "+f"(d[12]), "+f"(d[13]), "+f"(d[14]), "+f"(d[15]), "+f"(d[16]), "+f"(d[17]), "+f"(d[18]), "+f"(d[19]), "+f"(d[20]), "+f"(d[21]), "+f"(d[22]), "+f"(d[23]), "+f"(d[24]), "+f"(d[25]), "+f"(d[26]), "+f"(d[27]), "+f"(d[28]), "+f"(d[29]), "+f"(d[30]), "+f"(d[31])
        : "r"(a[0]), "r"(a[1]), "r"(a[2]), "r"(a[3]), "r"(db), "r"(8u), "r"(acc));
}
template <> __device__ __forceinline__ void cv_mma<5>(float (&d)[64], const uint32_t (&a)[4], uint32_t db, int acc) {
    asm volatile("{\n.reg .pred p;\n.reg .b64 b;\nsetp.ne.b32 p, %30, 0;\nmov.b64 b, {%28, %29};\n"
        "wgmma.mma_async.sync.aligned.m64n48k16.f32.bf16.bf16 {%0,%1,%2,%3,%4,%5,%6,%7,%8,%9,%10,%11,%12,%13,%14,%15,%16,%17,%18,%19,%20,%21,%22,%23}, {%24,%25,%26,%27}, b, p, 1, 1, 0;\n}\n"
        : "+f"(d[0]), "+f"(d[1]), "+f"(d[2]), "+f"(d[3]), "+f"(d[4]), "+f"(d[5]), "+f"(d[6]), "+f"(d[7]), "+f"(d[8]), "+f"(d[9]), "+f"(d[10]), "+f"(d[11]), "+f"(d[12]), "+f"(d[13]), "+f"(d[14]), "+f"(d[15]), "+f"(d[16]), "+f"(d[17]), "+f"(d[18]), "+f"(d[19]), "+f"(d[20]), "+f"(d[21]), "+f"(d[22]), "+f"(d[23])
        : "r"(a[0]), "r"(a[1]), "r"(a[2]), "r"(a[3]), "r"(db), "r"(8u), "r"(acc));
}
template <> __device__ __forceinline__ void cv_mma<6>(float (&d)[64], const uint32_t (&a)[4], uint32_t db, int acc) {
    asm volatile("{\n.reg .pred p;\n.reg .b64 b;\nsetp.ne.b32 p, %22, 0;\nmov.b64 b, {%20, %21};\n"
        "wgmma.mma_async.sync.aligned.m64n32k16.f32.bf16.bf16 {%0,%1,%2,%3,%4,%5,%6,%7,%8,%9,%10,%11,%12,%13,%14,%15}, {%16,%17,%18,%19}, b, p, 1, 1, 0;\n}\n"
        : "+f"(d[0]), "+f"(d[1]), "+f"(d[2]), "+f"(d[3]), "+f"(d[4]), "+f"(d[5]), "+f"(d[6]), "+f"(d[7]), "+f"(d[8]), "+f"(d[9]), "+f"(d[10]), "+f"(d[11]), "+f"(d[12]), "+f"(d[13]), "+f"(d[14]), "+f"(d[15])
        : "r"(a[0]), "r"(a[1]), "r"(a[2]), "r"(a[3]), "r"(db), "r"(8u), "r"(acc));
}
template <> __device__ __forceinline__ void cv_mma<7>(float (&d)[64], const uint32_t (&a)[4], uint32_t db, int acc) {
    asm volatile("{\n.reg .pred p;\n.reg .b64 b;\nsetp.ne.b32 p, %14, 0;\nmov.b64 b, {%12, %13};\n"
        "wgmma.mma_async.sync.aligned.m64n16k16.f32.bf16.bf16 {%0,%1,%2,%3,%4,%5,%6,%7}, {%8,%9,%10,%11}, b, p, 1, 1, 0;\n}\n"
        : "+f"(d[0]), "+f"(d[1]), "+f"(d[2]), "+f"(d[3]), "+f"(d[4]), "+f"(d[5]), "+f"(d[6]), "+f"(d[7])
        : "r"(a[0]), "r"(a[1]), "r"(a[2]), "r"(a[3]), "r"(db), "r"(8u), "r"(acc));
}
__device__ __forceinline__ void stsm4t(uint32_t addr, uint32_t r0, uint32_t r1, uint32_t r2, uint32_t r3) {
    asm volatile("stmatrix.sync.aligned.m8n8.x4.trans.shared.b16 [%0], {%1,%2,%3,%4};" ::"r"(addr), "r"(r0), "r"(r1), "r"(r2), "r"(r3) : "memory");
}
__device__ __forceinline__ void cp16(uint32_t dst, const void* src, int n = 16) {
    asm volatile("cp.async.cg.shared.global.L2::128B [%0], [%1], 16, %2;" ::"r"(dst), "l"(src), "r"(n) : "memory");
}
__device__ __forceinline__ void cp_arrive(uint32_t bar) { asm volatile("cp.async.mbarrier.arrive.noinc.shared::cta.b64 [%0];" ::"r"(bar) : "memory"); }
__device__ __forceinline__ void lds64(uint32_t& x, uint32_t& y, uint32_t a) { asm volatile("ld.shared.v2.b32 {%0,%1}, [%2];" : "=r"(x), "=r"(y) : "r"(a) : "memory"); }
__device__ __forceinline__ void sts128(uint32_t a, uint32_t x, uint32_t y, uint32_t z, uint32_t w) {
    asm volatile("st.shared.v4.b32 [%0], {%1,%2,%3,%4};" ::"r"(a), "r"(x), "r"(y), "r"(z), "r"(w) : "memory");
}
__device__ __forceinline__ uint32_t bfma2(uint32_t a, uint32_t b, uint32_t c) {
    uint32_t r;
    asm("fma.rn.bf16x2 %0, %1, %2, %3;" : "=r"(r) : "r"(a), "r"(b), "r"(c));
    return r;
}
#define CV_NS 4
#define CV_W 1
constexpr int CV_GC = 8 / CV_NS, CV_NA = (CV_W + 2) * CV_NS;
struct CvAddr { uint32_t pa[2], p0[4], db, rdy, xw, xr, bar; bool wrap, neg[2]; };
template <int G> __device__ __forceinline__ void cv_load(uint32_t (&a)[CV_NA][4], const CvAddr& p) {
    if constexpr (G % CV_GC == 0) mbar_wait(p.rdy + 8 * (G / CV_GC), 0);
#pragma unroll
    for (int i = G * CV_NS; i < (G + 1) * CV_NS; i++) {
        const int of = (i / 2 % 2) * CV_QG + (i / 8) * CV_SL + 256 * (i % 2 + (i / 2 & 2));
        if ((i & 5) == 0) {
#pragma unroll
            for (int e = 0; e < 4; e++) asm volatile("ld.shared.b32 %0, [%1];" : "=r"(a[i % CV_NA][e]) : "r"(p.p0[e] + of) : "memory");
            if (i < 8) { if (p.neg[0]) a[i % CV_NA][0] = 0; if (p.neg[1]) a[i % CV_NA][2] = 0; }
        } else {
            lds64(a[i % CV_NA][0], a[i % CV_NA][1], p.pa[0] + of - 256);
            lds64(a[i % CV_NA][2], a[i % CV_NA][3], p.pa[1] + of - 256);
        }
    }
}
__device__ __forceinline__ float vadd(float a, float b) {
    float r;
    asm volatile("add.f32 %0, %1, %2;" : "=f"(r) : "f"(a), "f"(b));
    return r;
}
template <int K> __device__ __forceinline__ uint32_t cv_tail(float (&d)[64], bool wrap) {
    float* z = d + 56 - 8 * K;
    z[4] = vadd(z[4], K > 0 ? z[10] : 0.f);
    if constexpr (K > 0) z[5] = vadd(z[5], z[11]);
    z[0] = vadd(z[0], z[6]);
    z[1] = vadd(z[1], z[7]);
    return pack2(wrap ? (K > 0 ? z[8] : 0.f) : z[4], wrap ? z[4] : z[0]);
}
template <int K> __device__ __forceinline__ uint32_t cv_fin(const float (&d)[64], uint32_t x) { return pack2(d[61 - 8 * K] + lo2f(x), d[57 - 8 * K] + hi2f(x)); }
template <int G>
__device__ __forceinline__ void cv_steps(float (&d)[2][64], uint32_t (&a)[CV_NA][4], uint32_t (&tv)[2][8], const CvAddr& p) {
    constexpr int K = G / CV_GC, GN = 8 * CV_GC;
    constexpr int T = G - CV_W - CV_GC, F = T - 1, TK = T / CV_GC, FK = F / CV_GC;
    if constexpr (G == 0) cv_load<0>(a, p);
    if constexpr (G < GN) {
        wgmma_fence();
#pragma unroll
        for (int i = G * CV_NS; i < (G + 1) * CV_NS; i++)
            cv_mma<K>(d[i / 2 % 2], a[i % CV_NA], p.db + (i / 2 % 2) * (CV_HPL / 8) + 16 * K + 2 * (i % 2 + (i / 2 & 2)), i & ~2 ? 1 : p.bar >> 8);
        wgmma_commit();
    }
    if constexpr (G < GN - 1) cv_load<G + 1>(a, p);
    if constexpr (T >= 0 && T % CV_GC == 0) {
        tv[0][TK] = cv_tail<TK>(d[0], p.wrap);
        tv[1][TK] = cv_tail<TK>(d[1], p.wrap);
        if constexpr (TK & 1) sts128(p.xw + TK / 2 * 512, tv[0][TK - 1], tv[0][TK], tv[1][TK - 1], tv[1][TK]);
    }
    if constexpr (F >= 0 && F % (2 * CV_GC) == CV_GC) {
        const uint4 x = lds128(p.xr + FK / 2 * 512);
        tv[0][FK - 1] = cv_fin<FK - 1>(d[0], x.x); tv[0][FK] = cv_fin<FK>(d[0], x.y);
        tv[1][FK - 1] = cv_fin<FK - 1>(d[1], x.z); tv[1][FK] = cv_fin<FK>(d[1], x.w);
    }
    if constexpr (G < GN - 1) wgmma_wait<CV_W>();
    if constexpr (G == GN - 1) wgmma_wait<0>();
    if constexpr (T >= 0 && T % (2 * CV_GC) == CV_GC) named_bar_sync(p.bar, 128);
    if constexpr (F < GN - CV_GC) cv_steps<G + 1>(d, a, tv, p);
}

#define CV_PF 7
#define Y_FIRST 1
#define Y_HOLD 0
#define PS2_EARLY 1
#define PS1_EARLY 1
#define FMOVE 1
#define SENDC 1
#define HDELAY 0
#define NH16 1
#define W3_AT 1
struct MegaMaps {
    CUtensorMap q, act;
    CUtensorMap w1, w2, w3, w4;
    CUtensorMap k, v, y;
};

__global__ void __cluster_dims__(2, 1, 1) __launch_bounds__(384, 1)
mega_kernel(const __grid_constant__ MegaMaps tm, bf16* __restrict__ outp, bf16* act, const bf16* __restrict__ w1p, const bf16* __restrict__ w2p,
            const bf16* __restrict__ w3p, const bf16* __restrict__ xq, const bf16* __restrict__ kp, const bf16* __restrict__ vp,
            const bf16* __restrict__ shk, const bf16* __restrict__ ssk, const bf16* __restrict__ ssD) {
    extern __shared__ __align__(1024) uint8_t sgen[];
    const uint32_t sbase = smem_u32(sgen);
    const int warp = __shfl_sync(0xffffffffu, threadIdx.x >> 5, 0), lane = threadIdx.x & 31;
    const int rank = blockIdx.x & 1;
    const uint32_t s_bar = sbase + OFF_BAR;
    const uint32_t f5 = s_bar, e5 = s_bar + 64, f4 = s_bar + 144, e4 = s_bar + 104;
    const uint32_t b_rfull = s_bar + 176, b_role = s_bar + 184, b_stg = s_bar + 136, b_h2 = s_bar + 32;
    const uint32_t s_epi = sbase + OFF_EPI, s_stg = sbase + OFF_STG5, s_r = sbase + OFF_R;
    uint8_t* sm = sgen + CV_0;
    const uint32_t sb = sbase + CV_0;
    const int tid = threadIdx.x, wg = warp >> 2, w = warp & 3;
    const int d0 = blockIdx.x * CV_CH;
    const bool cv = blockIdx.x < D_ / CV_CH;
    const uint32_t b_full = sb + CV_BAR, b_rdy = b_full + 64, b_h = b_full + 128;
    GT(0);
    if (tid == 0) TM(0);
    auto row_at = [&](int r) { return sb + CV_SL + (r < 0 ? -8192 : 0) + ((r & 127) >> 5) * 1024 + (r & 7) * 128 + ((r >> 3) & 3) * 32 + ((r ^ rank) & 1) * 16; };
    auto load_kv = [&](int c) {
#pragma unroll
        for (int i = 0; i < 2; i++)
            asm volatile("cp.async.bulk.tensor.4d.shared::cluster.global.mbarrier::complete_tx::bytes.multicast::cluster [%0], [%1, {%3, %4, %4, %5}], [%2], %6;"
                         ::"r"(sb + (c + 1) * CV_SL + rank * 8192 + i * 4096), "l"((uint64_t)(i ? &tm.v : &tm.k)), "r"(b_full + 8 * c), "r"(d0 & ~15), "r"(0),
                         "r"(8 * c + 4 * rank), "h"((uint16_t)3) : "memory");
    };
    auto bulk = [&](uint32_t dst, const void* src, uint32_t n, uint32_t bar) {
        asm volatile("cp.async.bulk.shared::cluster.global.mbarrier::complete_tx::bytes [%0], [%1], %2, [%3];" ::"r"(dst), "l"(src), "r"(n), "r"(bar) : "memory");
    };
    auto put_h = [&](int ch) {
        const uint32_t dk = (tid & 127) ? 0 : *reinterpret_cast<const volatile uint32_t*>(sm + CV_BAR + 160 + 16 * wg + 2 * ch);
        uint4 v[4];
#pragma unroll
        for (int i = 0; i < 4; i++) v[i] = lds128(sbase + ch * 4096 + i * 2048 + (tid & 127) * 16);
        v[0].x = pack2(lo2f(v[0].x) + lo2f(dk), hi2f(v[0].x));
        v[2].x = pack2(lo2f(v[2].x) + hi2f(dk), hi2f(v[2].x));
#pragma unroll
        for (int i = 0; i < 4; i++)
            sts128(sb + CV_H + (2 * ch + (i & 2) + (tid & 1)) * CV_HPL + (127 - ((tid & 127) >> 1)) * 16 - (i & 1) * 1024, v[i].x, v[i].y, v[i].z, v[i].w);
    };
    int bi, bj, m0, tb;
    uint32_t ep;
    auto get_role = [&]() {
        mbar_wait(b_role, 0);
        int role;
        asm volatile("ld.shared.v2.b32 {%0,%1}, [%2];" : "=r"(role), "=r"(ep) : "r"(s_bar + 192) : "memory");
        bi = (role >> 3) * 2 + rank; bj = role & 7; m0 = bi * BM; tb = (role >> 3) * 2048 + rank * 128;
        return role < 64;
    };

    if (warp >= 8) {
        asm volatile("setmaxnreg.dec.sync.aligned.u32 88;");
        cluster_arrive_relaxed();
        if (!cv) cluster_wait(); else {
            const int bt = tid - 256, g = lane >> 2, t = lane & 3;
            if (bt < 16) sts128(row_at((bt & 7) - 8) + (bt >> 3) * 4096, 0, 0, 0, 0);
#pragma unroll
            for (int i = 0; i < 4; i++)
                cp16(row_at(bt) + i * 4096, (i & 1 ? vp : kp) + (size_t)(bt + (i >> 1) * 128) * D_ + d0);
            DBG_S(16 + (3));
            uint2 wa;
            asm volatile("ld.global.nc.v2.b32 {%0,%1}, [%2];" : "=r"(wa.x), "=r"(wa.y) : "l"(shk + (d0 + g) * 4));
            const int mi = lane >> 3, r0 = 32 * w + 8 * ((lane >> 1) & 3) - (lane & 1);
            const uint32_t ka0 = row_at(r0 + 2 * mi - 3), ka1 = row_at(r0 + 2 * (mi & 1) + 5) + (mi >> 1) * 8192;
            const uint32_t va0 = row_at(r0 + 2 * mi + 1) + 4096, va1 = row_at(r0 - 1) + 4096 + (mi & 1) * 8192;
            const uint32_t qd = sb + g * CV_QG + (32 * w + 8 * t) * 8, qd0 = qd + (t & 2) * 16, qd1 = qd + (~t & 2) * 16;
            const uint32_t w0 = __byte_perm(wa.x, 0, 0x1010), w1 = __byte_perm(wa.x, 0, 0x3232), w2 = __byte_perm(wa.y, 0, 0x1010), w3 = __byte_perm(wa.y, 0, 0x3232);
            cluster_wait();
            DBG_S(16 + (5));
            asm volatile("cp.async.wait_all;" ::: "memory");
            named_bar_sync(7, 128);
            DBG_S(16 + (1));
            struct KV { uint32_t k[2][6], v[2][5]; };
            auto get = [&](KV& x, uint32_t so) {
                ldsm4t(x.k[0][0], x.k[0][1], x.k[0][2], x.k[0][3], ka0 + so);
                ldsm4t(x.k[0][4], x.k[0][5], x.k[1][4], x.k[1][5], ka1 + so);
                ldsm4t(x.k[1][0], x.k[1][1], x.k[1][2], x.k[1][3], ka0 + so + 8192);
                asm volatile("ldmatrix.sync.aligned.m8n8.x2.trans.shared.b16 {%0,%1}, [%2];" : "=r"(x.v[0][0]), "=r"(x.v[1][0]) : "r"(va1 + so));
                ldsm4t(x.v[0][1], x.v[0][2], x.v[0][3], x.v[0][4], va0 + so);
                ldsm4t(x.v[1][1], x.v[1][2], x.v[1][3], x.v[1][4], va0 + so + 8192);
            };
            auto build = [&](int c, const KV& x, KV& nx) {
                const uint32_t so = c * CV_SL;
                DBG_F(1);
                uint32_t early;
                asm volatile("{\n.reg .pred p;\nmbarrier.test_wait.parity.shared::cta.b64 p, [%1], 0;\nvote.sync.all.pred p, p, -1;\nselp.u32 %0, 1, 0, p;\n}"
                             : "=r"(early) : "r"(b_full + 8 * (c < 7 ? c + 1 : c)) : "memory");
                if (early) get(nx, so + CV_SL);
                DBG_F(2);
                uint32_t p[8][2];
#pragma unroll
                for (int sg = 0; sg < 2; sg++) {
                    uint32_t u[5], ke[6];
#pragma unroll
                    for (int i = 0; i < 6; i++) ke[i] = __byte_perm(x.k[sg][i], x.k[sg][i ? i - 1 : 0], 0x5432);
#pragma unroll
                    for (int i = 0; i < 5; i++) {
                        u[i] = bmul2(bfma2(x.k[sg][i + 1], w0, bfma2(ke[i + 1], w1, bfma2(x.k[sg][i], w2, bmul2(ke[i], w3)))), x.v[sg][i]);
                        if (i) { p[2 * i - 1][sg] = u[i]; p[2 * i - 2][sg] = __byte_perm(u[i], u[i - 1], 0x5432); }
                    }
                }
                DBG_F(3);
#pragma unroll
                for (int j = 0; j < 4; j++) sts128((j & 2 ? qd1 : qd0) + so + 16 * (j & 1), p[2 * j][0], p[2 * j][1], p[2 * j + 1][0], p[2 * j + 1][1]);
                __syncwarp();
                DBG_F(4);
                if (lane == 0) {
                    mbar_arrive(b_rdy + 8 * c);
                    if (c == w) {
                        if (c < 3) load_kv(c + 5);
                        else { bulk(sbase + 16384, ssk + (size_t)(d0 + 4) * S_, 16384, b_h + 16); bulk(b_full + 192, ssD + d0, 16, b_h + 16); }
                    }
                    if (c == w + 4 && (CV_PF >> w & 1)) {
                        const uint32_t n = w == 0 ? 32768 : w == 3 ? 57344 : 16384;
                        const char* src = reinterpret_cast<const char*>(w == 0 ? xq : w == 1 ? w1p : w == 2 ? w2p : w3p) + (size_t)blockIdx.x * n;
                        asm volatile("cp.async.bulk.prefetch.L2.global [%0], %1;" ::"l"(src), "r"(n) : "memory");
                    }
                }
                DBG_F(5);
                named_bar_sync(7, 128);
                DBG_F(6);
                DBG_S(16 + (c == 0 ? 4 : 5 + c));
                if (!early) { mbar_wait(b_full + 8 * c + 8, 0); get(nx, so + CV_SL); }
                DBG_F(7);
            };
            KV x0, x1;
            get(x0, 0);
#pragma unroll 1
            for (int c = 0; c < 8; c += 2) { build(c, x0, x1); build(c + 1, x1, x0); }
            mbar_wait(b_h + 16, 0);
            put_h(4); put_h(6);
            fence_async_smem();
            __syncwarp();
            if (lane == 0) mbar_arrive(b_full);
            named_bar_sync(7, 128);
            DBG_S(16 + (13));
        }
    } else {
        if (elect_one()) {
            mbar_init(b_full + 8 * warp, warp ? 1 : 4);
            mbar_init(b_rdy + 8 * warp, 4);
            if (warp) mbar_expect_tx(b_full + 8 * warp, 16384);
            if (w == 0 && cv) {
                mbar_init(b_h + 8 * wg, 1);
                mbar_expect_tx(b_h + 8 * wg, 8192 + 16);
                fence_async_smem();
                bulk(sbase + wg * 8192, ssk + (size_t)(d0 + 2 * wg) * S_, 8192, b_h + 8 * wg);
                bulk(b_full + 160 + 16 * wg, ssD + d0, 16, b_h + 8 * wg);
            }
            mbar_init(s_bar + 8 * warp, 1);
            mbar_init(s_bar + 64 + 8 * warp, 4);
            mbar_init(s_bar + 128 + 8 * warp, warp < 2 ? 4 << warp : warp == 6 ? 2 : 1);
            if (warp == 0) mbar_arrive(f5);
            if (warp == 7) mbar_expect_tx(b_role, 8);
            if (warp == 1) { mbar_init(b_h + 16, 1); mbar_expect_tx(b_h + 16, 16384 + 16); }
            if (w == 2) sts128(s_bar + 224 + 16 * wg, 0, 0, 0, 0);
            asm volatile("fence.mbarrier_init.release.cluster;" ::: "memory");
            if (warp == 2) { prefetch_tmap(&tm.k); prefetch_tmap(&tm.v); }
        }
        __syncwarp();
        DBG_W(1);
        cluster_arrive_relaxed();
        asm volatile("setmaxnreg.inc.sync.aligned.u32 208;");
        DBG_W(2);
        const int zi = (tid & 127) - 32;
        if (zi >= 0 && zi < 48) sts128(sb + CV_H + (4 * wg + (zi / 6 & 3) + (zi / 24) * 8) * CV_HPL + 2048 + (zi % 6) * 16, 0, 0, 0, 0);
        DBG_W(3);
        cluster_wait();
        DBG_W(5);
        if (cv) {
            if (tid == 32) {
#pragma unroll 1
                for (int c = 1; c < 5; c++) load_kv(c);
                prefetch_tmap(&tm.y);
            }
            __syncwarp();
            DBG_W(6);
            const int g = lane >> 2, t = lane & 3;
            const int x0 = 32 + 8 * w + g - 2 * t;
            CvAddr p;
            p.rdy = b_rdy;
            p.bar = 1 + wg;
            p.xr = sbase + (warp ^ 2) * 2048 + lane * 16;
            p.xw = sbase + warp * 2048 + (g * 4 + ((t - (w >> 1)) & 3)) * 16;
            p.wrap = t == 0 && w >= 2;
            mbar_wait(b_h + 8 * wg, 0);
            DBG_W(4);
            put_h(2 * wg);
            fence_async_smem();
            named_bar_sync(1 + wg, 128);
            float acc[2][64];
            zero_acc(acc[0]); zero_acc(acc[1]);
#pragma unroll 1
            for (int round = 0; round < 2; round++) {
                const int ch = round * 4 + 2 * wg;
                uint32_t a[CV_NA][4], tv[2][8];
#pragma unroll
                for (int e = 0; e < 2; e++) {
                    const int x = x0 - 8 * e;
                    p.neg[e] = x < 32;
                    p.pa[e] = sb + ch * CV_QG + 8 * (x ^ (x >> 2 & 4));
                    p.p0[2 * e] = p.pa[e] + (x < 32 ? 768 + 4 - CV_SL : -256);
                    p.p0[2 * e + 1] = p.pa[e] + (x < 32 ? 768 : -256 + 4);
                }
                p.db = (((sb + CV_H + ch * 2 * CV_HPL) & 0x3FFFF) >> 4) | ((CV_HPL / 16) << 16);
                if (round) mbar_wait(b_full, 0);
                DBG_S(7 + 3 * round);
                cv_steps<0>(acc, a, tv, p);
                DBG_S(8 + 3 * round);
                const int r128 = 4 * (lane >> 3) + 2 * (lane & 1) + ((~lane >> 2) & 1);
#pragma unroll
                for (int i = 0; i < 2; i++) {
                    const uint32_t ta = sb + ((ch + i + 1) & 7) * CV_SL + 12288 + r128 * 128 + ((((~lane & 2) * 2 + w) ^ (r128 & 7)) << 4);
                    stsm4t(ta, tv[i][0], tv[i][1], tv[i][2], tv[i][3]);
                    stsm4t(ta + 2048, tv[i][4], tv[i][5], tv[i][6], tv[i][7]);
                }
                fence_async_smem();
                named_bar_sync(1 + wg, 128);
                if ((tid & 127) < 2) {
                    const int d = d0 + ch + (tid & 1);
                    asm volatile("cp.async.bulk.tensor.4d.global.shared::cta.bulk_group [%0, {%2, %3, %4, %2}], [%1];"
                                 ::"l"((uint64_t)&tm.y), "r"(sb + ((ch + (tid & 1) + 1) & 7) * CV_SL + 12288), "r"(0), "r"(4 * (d >> 8)), "r"(d & 255) : "memory");
                    asm volatile("cp.async.bulk.commit_group;" ::: "memory");
                }
                __syncwarp();
                DBG_S(9 + 3 * round);
            }
        }
    }
    int warp2 = warp;
    asm volatile("" : "+r"(warp2));
    if (warp2 >= 8) {
        asm volatile("setmaxnreg.dec.sync.aligned.u32 72;");
        if (warp == 8) { if (elect_one()) {
            if (rank == 0) {
                uint32_t smid;
                asm volatile("mov.u32 %0, %%smid;" : "=r"(smid));
                const int t = smid >> 1;
                int team = t < 32 ? t & 7 : t < 60 ? 1 + (t - 32) % 7 : t < 62 ? t - 54 : 0;
                const unsigned long long arr = atomicAdd(reinterpret_cast<unsigned long long*>(g_ticket + 16 * FL_PITCH), 1ull);
                const uint32_t e1 = (uint32_t)(arr / NCL) + 1;
                unsigned int* tk = g_ticket + (e1 & 1) * 8 * FL_PITCH;
                int slot = atomicAdd(tk + team * FL_PITCH, 1u);
                atomicAdd(g_ticket + 17 * FL_PITCH, 1u);
                if (blockIdx.x < 16) g_ticket[((~e1 & 1) * 8 + (blockIdx.x >> 1)) * FL_PITCH] = 0;
                if (slot >= 8) {
                    const long long t0 = clock64();
                    while ((int)(*(volatile unsigned int*)(g_ticket + 17 * FL_PITCH) - e1 * NCL) < 0 && clock64() - t0 < 100000) {}
                    for (team = 0; team < 8; team++)
                        if ((slot = atomicAdd(tk + team * FL_PITCH, 1u)) < 8) break;
                }
#pragma unroll
                for (int i = 0; i < 2; i++)
                    asm volatile("st.async.weak.shared::cluster.mbarrier::complete_tx::bytes.v2.b32 [%0], {%1, %2}, [%3];"
                                 ::"r"(mapa_u32(s_bar + 192, i)), "r"(team * 8 + slot), "r"(e1), "r"(mapa_u32(b_role, i)) : "memory");
            }
            if (get_role()) {
            TM(2);
            mbar_expect_tx(b_rfull, 32768);
            tma_load_2d(sbase + 16384, &tm.q, b_rfull, bj * 128, m0);
            tma_load_2d(sb + 8 * CV_SL, &tm.q, b_rfull, bj * 128 + 64, m0);
            int s5 = 0, s4 = 0;
            uint32_t p5 = 0, p4 = 1;
            auto putB = [&](const CUtensorMap* tB, int kc, uint32_t bytes) {
                const uint32_t full = f5 + 8 * s5;
                mbar_wait(full + 64, (p5 >> s5) & 1);
                mbar_expect_tx(full, bytes);
                tma_load_2d_mc(s_r + 16384 + rank * 8192 + s5 * R5_STAGE, tB, full, bj * 128 + rank * 64, kc);
                p5 ^= 1u << s5;
            };
            auto putA = [&](int c, int r) {
                tma_load_2d(s_r + s5 * R5_STAGE, &tm.act, f5 + 8 * s5, c, r);
                if (++s5 == R5_N) s5 = 0;
            };
            prefetch_tmap(&tm.act); prefetch_tmap(&tm.w1); prefetch_tmap(&tm.w2); prefetch_tmap(&tm.w3); prefetch_tmap(&tm.w4);
            auto own_first = [&](int it) {
                const int hf = it >= 9, c = it - 2 - 7 * hf;
                return (it < 2 ? 2 * bj + it : 2 * (c + (c >= bj)) + hf) * BK;
            };
            const unsigned int n8 = 8 * ep, nh = NH16 ? ((bi == 0 || bi == 15) ? 12 * ep : 2 * n8) : (bi == 0 || bi == 15) ? 2 * n8 : 3 * n8;
#pragma unroll 1
            for (int layer = 0; layer < 2; layer++) {
                s5 = 2;
#pragma unroll 1
                for (int kk = -(layer | Y_FIRST); kk < 5 - (layer | Y_FIRST); kk++) {
                    if (kk & 4) {
                        if (layer == 0) { TM(1); wait_flag(flag_ptr(0, FL_CS, 8 + bj), 8 * n8); TM(4); fence_proxy_async(); }
                        mbar_wait(e5 + 8, (p5 >> 1) & 1);
                        mbar_expect_tx(f5 + 8, 32768);
                        tma_load_2d(s_r + R5_STAGE, &tm.act, f5 + 8, (bj >> 1) * 256 + rank * 128, R_Y + (tb & ~255) + (bj & 1) * 128);
                        tma_load_2d(s_r + R5_STAGE + 16384, &tm.act, f5 + 8, (bj >> 1) * 256 + rank * 128 + 64, R_Y + (tb & ~255) + (bj & 1) * 128);
                        p5 ^= 2;
                        if (layer == 0) TM(5);
                    } else {
                        if (kk == Y_HOLD && layer == 0) mbar_wait(f5 + 8, 0);
                        putB(&tm.w1, own_first(kk), kk < 2 ? 16384 : R5_STAGE);
                        if (++s5 == R5_N) s5 = 0;
                    }
                }
                s5 = 4;
#pragma unroll 1
                for (int kk = 2; kk < 16; kk++) {
                    const int kc = own_first(kk);
                    if (kk >= 4) putB(&tm.w1, kc, R5_STAGE);
                    if (kk == 2 || kk == 9) {
                        wait_flag(flag_ptr(layer, FL_XA + (kk & 1), bi), n8);
                        if (layer == 0 && kk == 2) TM(14);
                        DP(8 * (FL_XA + (kk & 1)) + 3);
                        fence_proxy_async();
                        DP(8 * (FL_XA + (kk & 1)) + 4);
                    }
                    putA(kc, R_XA + tb);
                }
                mbar_wait(e5 + 24, (p5 >> 3) & 1);
                mbar_arrive(f5 + 24);
                p5 ^= 8;
                s5 = 4;
#pragma unroll 1
                for (int kk = 0; kk < 5; kk++) { putB(&tm.w2, own_first(kk), kk < 2 ? 16384 : R5_STAGE); if (++s5 == R5_N) s5 = 0; }
                s5 = 1;
#pragma unroll 1
                for (int kk = 2; kk < 16; kk++) {
                    const int kc = own_first(kk);
                    if (kk >= 5) putB(&tm.w2, kc, R5_STAGE);
                    if (kk == 2 || kk == 9) {
                        wait_flag(flag_ptr(layer, FL_H + (kk & 1), bi), nh);
                        DP(8 * (FL_H + (kk & 1)) + 3);
                        fence_proxy_async();
                        DP(8 * (FL_H + (kk & 1)) + 4);
                    }
                    putA(kc, R_H + layer * R_HP + m0 + (int)((0x4031u >> (kc >> 6 & 12)) & 7) - 2);
                }
#pragma unroll 1
                for (int it = 0; it < 32; it++) {
                    const int kc = it >= 16 ? (it - 16) * BK : own_first(it);
                    const int nb = it < 16 ? 4 : 3, n0 = bj * 448 + (it < 16 ? 0 : 256);
                    if (it > 0 && it < 4) {
                        const int i = (it - 1) * 3 >> 1;
                        mbar_wait(e5 + 8 * i, (p5 >> i) & 1);
                        mbar_wait(e5 + 8 * i + 8, (p5 >> (i + 1)) & 1);
                    }
                    mbar_wait(e4 + 8 * s4, p4);
                    if (it >= 16 && it < 19) mbar_wait(e4 + 8 * s4 + 8, p4);
                    uint32_t sa = s_r + s4 * (it < 16 ? R4_STAGE : R4B_STAGE), full = f4 + 8 * s4;
                    mbar_expect_tx(full, (it < 2 ? 0 : 16384) + nb * 8192);
#pragma unroll 1
                    for (int j = (it ^ rank) & 1; j < nb; j += 2) tma_load_2d_mc(sa + (it < 16 ? -32768 : 16384) + j * 8192, &tm.w3, full, n0 + j * 64, kc);
                    if (it == 3 || it == 9) {
                        wait_flag(flag_ptr(layer, FL_X1 + (it >> 3), bi), n8);
                        DP(8 * (FL_X1 + (it >> 3)) + 3);
                        fence_proxy_async();
                        DP(8 * (FL_X1 + (it >> 3)) + 4);
                        if (it == 3) tma_load_2d(s_r + 2 * R4_STAGE, &tm.act, f4 + 16, own_first(2), R_X1 + tb);
                    }
                    if (it >= 3) tma_load_2d(sa, &tm.act, full, kc, R_X1 + tb);
                    if (++s4 == R4_N) { s4 = 0; p4 ^= 1; }
                }
                wait_flag(flag_ptr(layer, FL_H2, bi), n8);
                fence_proxy_async();
                s5 = 0;
#pragma unroll 1
                for (int j = 0; j < 7; j++) {
                    if (j > 0 && (j & 1) == 0) {
                        mbar_wait(b_h2 + 4 * j, layer);
                        fence_proxy_async();
                    }
                    const int ra = R_H2 + (j >> 1) * 256 + tb;
#pragma unroll 1
                    for (int b = 0; b < 8; b++) {
                        if (j == 0 && b < R4_N) mbar_wait(e4 + 8 * b, p4);
                        putB(&tm.w4, (7 * b + j) * BK, R5_STAGE);
                        putA(((j & 1) * 8 + b) * BK, ra);
                    }
                }
            }
        } } } else {
            auto colsum = [&](bool is1, int bi, int bj) {
                const int pitch = is1 ? D_ : F_, c = is1 ? bj * 128 + (lane & 15) * 8 : bj * 448 + min((warp & 2) * 128 + lane * 8, 440);
                const bf16* p = (is1 ? w1p : w3p) + ((bi * 64 + (is1 ? (lane >> 4) * 32 : 0)) * pitch + c);
                float a[8];
#pragma unroll
                for (int i = 0; i < 8; i++) a[i] = 0.f;
#pragma unroll 1
                for (int r0 = is1 ? 32 : 0; r0 < 64; r0 += 8) {
                    uint4 v[8];
#pragma unroll
                    for (int r = 0; r < 8; r++, p += pitch) v[r] = __ldg(reinterpret_cast<const uint4*>(p));
#pragma unroll
                    for (int r = 0; r < 8; r++) {
                        a[0] += lo2f(v[r].x); a[1] += hi2f(v[r].x); a[2] += lo2f(v[r].y); a[3] += hi2f(v[r].y);
                        a[4] += lo2f(v[r].z); a[5] += hi2f(v[r].z); a[6] += lo2f(v[r].w); a[7] += hi2f(v[r].w);
                    }
                }
                if (is1) {
#pragma unroll
                    for (int i = 0; i < 8; i++) a[i] += __shfl_xor_sync(0xffffffffu, a[i], 16);
                }
                float4* dst = reinterpret_cast<float4*>(g_cpart + bi * (F_ + D_) + (is1 ? F_ : 0) + c);
                dst[0] = make_float4(a[0], a[1], a[2], a[3]);
                dst[1] = make_float4(a[4], a[5], a[6], a[7]);
                asm volatile("fence.release.gpu;" ::: "memory");
                __syncwarp();
                if (lane == 0) asm volatile("red.relaxed.gpu.global.add.u32 [%0], 1;" ::"l"(flag_ptr(!is1, FL_CS, bj)) : "memory");
            };
            if (cv && warp == 10) colsum(true, blockIdx.x >> 3, blockIdx.x & 7);
            float4 keep[2];
            const bool on = get_role();
            if (on && warp == 11) {
                uint4* ps = reinterpret_cast<uint4*>(g_stats + (bi * 8 + bj) * 128) + lane;
                ps[0] = ps[32] = make_uint4(0, 0, 0, 0);
                asm volatile("fence.acq_rel.gpu;" ::: "memory");
                __syncwarp();
                if (lane == 0) mbar_arrive(b_rfull);
            }
#pragma unroll 1
            for (int layer = on ? 0 : 2; layer < 2; layer++) {
                if (warp == 10) {
#pragma unroll 1
                    for (int kind = 0; kind < 6; kind += 2) {
                        const uint32_t src = kind == FL_H ? s_stg + 1024 : s_epi, sd = kind == FL_H ? OFF_EPI : 16384;
                        const int dn = bj & 2 ? 1 : -1;
                        uint4* gh = g_halo + (layer * 144 + 8 + bi * 8 + bj) * 64 + lane;
                        const int r = kind == FL_H ? R_H + layer * R_HP + m0 : (kind == FL_XA ? R_XA : R_X1) + tb;
#pragma unroll 1
                        for (int hf = 0; hf < 2; hf++) {
                            named_bar_sync(5 + hf, 288);
                            if (lane == 0) {
                                if (FMOVE) fence_async_smem();
                                DP(8 * (kind + hf));
                                tma_store_2d(&tm.act, src + hf * sd, bj * 128 + hf * 64, r);
                                asm volatile("cp.async.bulk.commit_group;" ::: "memory");
                            }
                            __syncwarp();
                            if (kind == FL_H && !SENDC) {
                                uint32_t a, b;
                                lds64(a, b, src + hf * sd + (63 - 63 * dn) * 128 + 8 * lane);
                                asm volatile("{\n.reg .b64 u, v;\nmov.b64 u, {%1, %3};\nmov.b64 v, {%2, %3};\nst.relaxed.gpu.global.v2.b64 [%0], {u, v};\n}"
                                             ::"l"(gh - dn * 512 + hf * 32), "r"(a), "r"(b), "r"(ep) : "memory");
                            }
                            if (kind + hf == FL_H + 1) {
                                uint4 v[2] = {};
                                if (HDELAY) __nanosleep(HDELAY);
#pragma unroll 1
                                for (int n = (bi + dn) & 16 ? 1 << 20 : 0; n < (1 << 20); n++) {
#pragma unroll
                                    for (int i = 0; i < 2; i++)
                                        asm volatile("{\n.reg .b64 u, v;\nld.relaxed.gpu.global.v2.b64 {u, v}, [%4];\nmov.b64 {%0, %1}, u;\nmov.b64 {%2, %3}, v;\n}"
                                                     : "=r"(v[i].x), "=r"(v[i].y), "=r"(v[i].z), "=r"(v[i].w) : "l"(gh + 32 * i) : "memory");
                                    if (v[0].y == ep && v[0].w == ep && v[1].y == ep && v[1].w == ep) break;
                                }
#pragma unroll
                                for (int i = 0; i < 2; i++)
                                    asm volatile("st.shared.v2.b32 [%0], {%1, %2};" ::"r"(src + i * OFF_EPI + (63 + 65 * dn) * 128 + 8 * lane), "r"(v[i].x), "r"(v[i].z) : "memory");
                                fence_async_smem();
                                __syncwarp();
                                DP(8 * FL_H + 5);
                                named_bar_arrive(14, 160);
                            }
                            if (lane == 0) {
                                asm volatile("cp.async.bulk.wait_group 0;" ::: "memory");
                                DP(8 * (kind + hf) + 1);
                                DP(8 * (kind + hf) + 2);
                                unsigned int* fp = flag_ptr(layer, kind + hf, bi);
                                asm volatile("red.relaxed.gpu.global.add.u32 [%0], 1;" ::"l"(fp) : "memory");
                                if (kind == FL_H) {
                                    if (bi > 0 && (!NH16 || dn > 0)) asm volatile("red.relaxed.gpu.global.add.u32 [%0], 1;" ::"l"(fp - FL_PITCH) : "memory");
                                    if (bi < 15 && (!NH16 || dn < 0)) asm volatile("red.relaxed.gpu.global.add.u32 [%0], 1;" ::"l"(fp + FL_PITCH) : "memory");
                                }
                            }
                            __syncwarp();
                        }
                    }
                } else {
                    uint32_t* rs = reinterpret_cast<uint32_t*>(sgen + OFF_RS);
                    float* cs = reinterpret_cast<float*>(sgen + OFF_CS);
#pragma unroll 1
                    for (int which = 0; which < 2; which++) {
                        if (layer < which) {
                            if (warp == 11 && lane == 0) {
                                wait_flag(flag_ptr(0, FL_XA + W3_AT, bi), 8 * ep);
                                asm volatile("cp.async.bulk.prefetch.L2.global [%0], %1;" ::"l"(w3p + (bi * 8 + bj) * 28672), "r"(57344) : "memory");
                            }
                            __syncwarp();
                            colsum(false, bi, bj);
                        }
                        if (warp == 11) continue;
                        if (layer == 0) {
                            if (lane == 0) wait_flag(flag_ptr(which, FL_CS, bj), (16 << which) * ep);
                            __syncwarp();
#pragma unroll 1
                            for (int c = (which ? 384 : 768) + lane * 4; c < 896; c += 128) {
                                const float* cp = g_cpart + (which ? bj * 448 + min(c & 511, 444) : F_ + bj * 128 + lane * 4);
                                float4 a = make_float4(0.f, 0.f, 0.f, 0.f);
#pragma unroll
                                for (int r0 = 0; r0 < 16; r0 += 8) {
                                    float4 v[8];
#pragma unroll
                                    for (int r = 0; r < 8; r++) v[r] = __ldcg(reinterpret_cast<const float4*>(cp + (r0 + r) * (F_ + D_)));
#pragma unroll
                                    for (int r = 0; r < 8; r++) { a.x += v[r].x; a.y += v[r].y; a.z += v[r].z; a.w += v[r].w; }
                                }
                                if (c < 768) *reinterpret_cast<float4*>(cs + min(c & 511, 444)) = a;
                                keep[0] = a;
                            }
                        }
                        if (lane == 0 && (layer | which)) wait_flag(flag_ptr(layer, which == 0 ? FL_XA : FL_X1, bi), 8 * ep);
                        __syncwarp();
                        *reinterpret_cast<float4*>(cs + 256 + lane * 4) = keep[0];
                        { const float4 k0 = keep[0]; keep[0] = keep[1]; keep[1] = k0; }
#pragma unroll 1
                        for (int i = 0; i < 4; i++) {
                            const int r = i * 32 + lane;
                            float mean, var;
                            row_stats(g_stats + (1 + which) * S_ * 8 + bi * 1024 + r, ~layer << 31, mean, var);
                            const uint32_t c0 = pack2(mean, fsqrt(bfr(bfr(var) + 1e-5f)));
                            if (lane < 19 && (layer | which | i) == 0) asm volatile("mbarrier.inval.shared::cta.b64 [%0];" ::"r"(b_full + 8 * lane) : "memory");
                            __syncwarp();
                            rs[r] = c0;
                            const float rd = frcp(hi2f(c0));
                            rs[128 + r] = pack2((mean - lo2f(c0)) * rd, fsqrt(bfr(bfr(var * rd * rd) + 1e-5f)));
                        }
                        __syncwarp();
                        named_bar_arrive(3, 160);
                        named_bar_arrive(11, 160);
                    }
                }
                const uint32_t s_cnt = s_bar + 224;
                auto ticket = [&](uint32_t a) {
                    uint32_t v = 0;
                    if (lane == 0) asm volatile("atom.acq_rel.cta.shared.add.u32 %0, [%1], 1;" : "=r"(v) : "r"(a) : "memory");
                    return v;
                };
                mbar_wait(b_stg, 0);
                int u = __shfl_sync(0xffffffffu, ticket(s_cnt + 16 + 4 * layer), 0), step = 0;
#pragma unroll 1
                while (true) {
#pragma unroll 1
                    for (; step < 5 && u >= (int)((0x3830201810ull >> (8 * step)) & 255); step++) {
                        if (step == 1) { named_bar_arrive(4, 224); named_bar_arrive(12, 224); continue; }
                        const int part = step ? step - 1 : 0;
                        __syncwarp();
                        if (ticket(s_cnt + 4 * part) == 3 * layer + 2) {
                            asm volatile("fence.release.gpu;" ::: "memory");
                            unsigned int* fp = flag_ptr(layer, FL_H2 + part, bi);
                            asm volatile("red.relaxed.gpu.global.add.u32 [%0], 1;" ::"l"(fp) : "memory");
                            if (part > 0) { wait_flag(fp, 8 * ep); mbar_arrive(b_h2 + 8 * part); }
                        }
                        __syncwarp();
                        if (step == 2) mbar_wait(b_stg, 1);
                    }
                    if (u >= 56) break;
                    const uint32_t un = ticket(s_cnt + 16 + 4 * layer);
                    const int job = u >> 3, r = (u & 7) * 16 + (lane >> 3);
                    const uint32_t sp = sbase + ((job & 2) ? OFF_STG5 : OFF_EPI) + r * 256 + (job & 1) * 128;
                    bf16* gp = act + (size_t)(R_H2 + (job >> 1) * 256 + tb + r) * D_ + ((job & 1) * 8 + bj) * 64 + (lane & 7) * 8;
                    uint4 v[4];
#pragma unroll
                    for (int e = 0; e < 4; e++) v[e] = lds128(sp + e * 1024 + (((lane & 7) ^ ((r + 4 * e) & 7)) << 4));
#pragma unroll
                    for (int e = 0; e < 4; e++) stg128(gp + 4 * e * D_, gelu8h(v[e]));
                    u = __shfl_sync(0xffffffffu, un, 0);
                }
                if (layer == 0 && warp == 11) {
                    const char* ps = reinterpret_cast<const char*>(g_stats + bi * 1024) + lane * 128;
                    const char* py = reinterpret_cast<const char*>(act + (size_t)(R_Y + (tb & ~255) + (bj & 1) * 128 + (lane >> 1)) * D_ + (bj >> 1) * 256 + rank * 128) + (lane & 1) * 128;
#pragma unroll 1
                    for (int i = 0; i < 8; i++) {
                        asm volatile("prefetch.global.L2 [%0];" ::"l"(py + (size_t)i * 16 * D_ * 2) : "memory");
                        if (i >= 6) asm volatile("prefetch.global.L2 [%0];" ::"l"(ps + (i & 1) * 4096) : "memory");
                        __nanosleep(400);
                    }
                }
            }
        }
        __syncwarp();
        asm volatile("barrier.cluster.arrive.relaxed.aligned;\nbarrier.cluster.wait.acquire.aligned; // helpers" ::: "memory");
    } else {
        DT_DECL;
        DT(0);
        auto put_y = [&]() {
            if ((tid & 127) < 2 && cv) {
                asm volatile("cp.async.bulk.wait_group 0;" ::: "memory");
                asm volatile("red.relaxed.gpu.global.add.u32 [%0], 1;" ::"l"(flag_ptr(0, FL_CS, 8 + (blockIdx.x >> 4))) : "memory");
            }
            __syncwarp();
        };
        put_y();
        DT(24);
        asm volatile("setmaxnreg.inc.sync.aligned.u32 216;");
        if (get_role()) {
        const bool rel_on = (tid & 95) == 0;
        const uint32_t rel5 = mapa_u32(e5, (warp & 1) ^ rank), rel4 = rel5 + (e4 - e5);
        const uint32_t da0 = desc_a(s_r + wg * 8192), db0 = desc_b(s_r + BM * BK * 2), dae = da0 + (OFF_EPI - OFF_R) / 16, db4 = db0 - 49152 / 16;
        auto skip5 = [&](RingState& rs) {
            if (rel_on) mbar_arrive_cluster(rel5 + 8 * rs.st);
            rs.st++;
        };
        const int t = lane & 3;
        const int row = warp * 16 + (lane >> 2);
        const uint32_t st_w = (uint32_t)((warp * 16 + ((lane >> 3) & 1) * 8 + (lane & 7)) * 256 + (((lane >> 4) ^ (lane & 7)) << 4));
        const uint32_t fr = (uint32_t)((warp * 16 + ((lane >> 3) & 1) * 8 + (lane & 7)) * 128 + (((lane >> 4) ^ (lane & 7)) << 4));
        auto copy_out = [&](bf16* dst, uint32_t src) {
            const int r = warp * 16 + (lane >> 4);
            bf16* ox = dst + (size_t)(m0 + r) * D_ + bj * 128 + (lane & 15) * 8;
            const uint32_t ra = src + ((lane & 15) >> 3) * 16384 + r * 128;
            uint4 v[8];
#pragma unroll
            for (int it = 0; it < 8; it++) v[it] = lds128(ra + it * 256 + (((lane & 7) ^ ((2 * it + (lane >> 4)) & 7)) << 4));
#pragma unroll
            for (int it = 0; it < 8; it++) *reinterpret_cast<uint4*>(ox + (size_t)it * 2 * D_) = v[it];
        };
        auto put_stats = [&](const uint32_t (&w)[32], int which, int layer) {
            float c[6][4];
#pragma unroll
            for (int e = 0; e < 32; e++) {
                hmma8(c[e & 3], w[e & ~1], w[e | 1], w[e], e < 4);
                if ((e & 3) == 0) hmma(c[4 + (e >> 2 & 1)], w[e], w[e + 1], w[e + 2], w[e + 3], 0x3f803f80u, 0x3f803f80u, e < 8);
            }
            if (t == lane >> 3) {
#pragma unroll
                for (int e = 0; e < 2; e++) {
                    const float q1 = lane & 4 ? c[e][2 * e + 1] + c[e + 2][2 * e + 1] : c[e][2 * e] + c[e + 2][2 * e], s1 = c[4][2 * e] + c[5][2 * e], mu = s1 * (1.0f / 128);
                    asm volatile("{\n.reg .b64 t;\nmov.b64 t, {%1, %2};\nst.relaxed.gpu.global.b64 [%0], t;\n}"
                                 ::"l"(g_stats + which * S_ * 8 + (bi * 8 + bj) * 128 + row + 8 * e), "f"(mu), "r"(__float_as_uint(fmaxf(q1 - s1 * mu, 0.f)) | ~layer << 31) : "memory");
                }
            }
        };
        auto split = [](float r) { const float h = bfr(r); return pack2(h, r - h); };
        auto norm2 = [](uint32_t x, uint32_t m, uint32_t r) {
            const uint32_t d = bsub2(x, m);
            return bfma2(d, __byte_perm(r, 0, 0x1010), bmul2(d, __byte_perm(r, 0, 0x3232)));
        };
        const float* csp = reinterpret_cast<const float*>(sgen + OFF_CS) + 2 * t;
        float mrow[2], rrow[2];
        const uint32_t* rsp = reinterpret_cast<const uint32_t*>(sgen + OFF_RS) + row;
        auto row_consts = [&](bool twice) {
#pragma unroll
            for (int e = 0; e < 2; e++) {
                const uint32_t q0 = rsp[8 * e], q1 = rsp[128 + 8 * e];
                mrow[e] = twice ? fmaf(lo2f(q1), hi2f(q0), lo2f(q0)) : lo2f(q0);
                rrow[e] = 0.5f * frcp(twice ? hi2f(q0) * hi2f(q1) : hi2f(q0));
            }
        };
        auto keep_consts = [&](float2 (&cs)[8]) {
#pragma unroll
            for (int e = 0; e < 8; e++) asm volatile("" : "+f"(cs[e].x), "+f"(cs[e].y));
            asm volatile("" : "+f"(mrow[0]), "+f"(mrow[1]), "+f"(rrow[0]), "+f"(rrow[1]));
        };
        auto stage = [&](const float* acc, uint32_t dst, int j0, float2 (&cs)[8], const float* cnext) {
            float2 cn[8];
#pragma unroll
            for (int e = 0; e < 8; e++) cn[e] = *reinterpret_cast<const float2*>(cnext + 8 * e);
#pragma unroll
            for (int j = 0; j < 8; j += 2) {
                uint32_t w[4];
#pragma unroll
                for (int e = 0; e < 2; e++) {
                    const float* a = acc + 4 * (j + e);
                    w[2 * e] = pack2(fmaf(-mrow[0], cs[j + e].x, a[0]) * rrow[0], fmaf(-mrow[0], cs[j + e].y, a[1]) * rrow[0]);
                    w[2 * e + 1] = pack2(fmaf(-mrow[1], cs[j + e].x, a[2]) * rrow[1], fmaf(-mrow[1], cs[j + e].y, a[3]) * rrow[1]);
                }
                stsm4((dst + st_w) ^ (((j0 + j) & 15) << 4), w[0], w[1], w[2], w[3]);
            }
#pragma unroll
            for (int e = 0; e < 8; e++) cs[e] = cn[e];
        };
        RingState r5{1, 0}, r4{0, 0};
        DT(1);
        uint32_t x[32];
        mbar_wait(b_rfull, 0);
#pragma unroll
        for (int jp = 0; jp < 8; jp++) ldsm4(x[4 * jp], x[4 * jp + 1], x[4 * jp + 2], x[4 * jp + 3], sbase + 16384 + (fr ^ ((jp & 3) << 5)) + (jp >> 2) * (16384 + 8 * CV_SL));
#pragma unroll
        for (int e = 0; e < 32; e++) asm volatile("" : "+r"(x[e]));
        named_bar_sync(9 + wg, 128);
        if ((tid & 95) < R5_N) mbar_arrive_cluster(rel5 + 8 * lane);
#pragma unroll 1
        for (int layer = 0; layer < 2; layer++) {
            {
                DT(2 + 24 * layer);
                put_stats(x, 0, layer);
                DT(20 + 24 * layer);
                DT(22 + 24 * layer);
                uint32_t mb[2], rd[2];
                {
                    float mean, var;
                    row_stats(g_stats + bi * 1024 + warp * 16 + (lane & 15), ~layer << 31, mean, var);
                    __syncwarp();
                    const uint32_t r1 = split(frcp(bfr(fsqrt(bfr(bfr(var) + 1e-5f)))));
                    const uint32_t m1 = pack2(mean, mean);
#pragma unroll
                    for (int e = 0; e < 2; e++) { mb[e] = __shfl_sync(0xffffffffu, m1, (lane >> 2) + 8 * e); rd[e] = __shfl_sync(0xffffffffu, r1, (lane >> 2) + 8 * e); }
                }
                DT(21 + 24 * layer);
                mbar_wait(f5 + 8, r5.ph);
                DT(23 + 24 * layer);
                const uint32_t ya = s_r + R5_STAGE + wg * 16384 + ((lane >> 4) * 8 + (lane & 7)) * 128 + ((((warp & 3) * 2 + ((lane >> 3) & 1)) ^ (lane & 7)) << 4);
                uint32_t y[16];
#pragma unroll
                for (int e = 0; e < 32; e++) {
                    if ((e & 15) == 0) {
#pragma unroll
                        for (int jp = 0; jp < 4; jp++) ldsm4t(y[4 * jp], y[4 * jp + 1], y[4 * jp + 2], y[4 * jp + 3], ya + jp * 2048 + e * 512);
                    }
                    x[e] = bfma2(norm2(x[e], mb[e & 1], rd[e & 1]), y[e & 15], x[e]);
                    if ((e & 3) == 3) stsm4(s_epi + (fr ^ (((e >> 2) & 3) << 5)) + (e >> 4) * 16384, x[e - 3], x[e - 2], x[e - 1], x[e]);
                    if ((e & 15) == 15) { if (!FMOVE) fence_async_smem(); named_bar_arrive(5 + (e >> 4), 288); }
                    if (e == 15) mbar_wait(b_role, 0);
                }
                DT(19 + 24 * layer);
                if (FMOVE) fence_async_smem();
                if (PS1_EARLY) put_stats(x, 1, layer);
                named_bar_sync(9 + wg, 128);
                skip5(r5);
                DT(3 + 24 * layer);
            }
            {
                float acc[64];
                kblock<128, R5_N, 0>(acc, dae, db0 + 2 * (R5_STAGE / 16), f5, r5);
                kblock<128, R5_N>(acc, dae + 1024, db0 + 3 * (R5_STAGE / 16), f5, r5);
                if (!PS1_EARLY) put_stats(x, 1, layer);
                wgmma_wait<1>();
                if (rel_on) mbar_arrive_cluster(rel5 + 16);
                float2 cs[8];
                mainloop<128, R5_N, R5_STAGE>(acc, 14, da0, db0, f5, rel5, rel_on, r5, 15 + 24 * layer, [&]() {
                    named_bar_sync(3 + 8 * wg, 160);
                    row_consts(true);
#pragma unroll
                    for (int e = 0; e < 8; e++) cs[e] = *reinterpret_cast<const float2*>(csp + 256 + 8 * e);
                    keep_consts(cs);
                } DT_ARG);
                DT(4 + 24 * layer);
#pragma unroll
                for (int j = 0; j < 16; j += 2) {
                    if (j == 8) {
#pragma unroll
                        for (int e = 0; e < 8; e++) cs[e] = *reinterpret_cast<const float2*>(csp + 256 + 8 * (j + e));
                    }
                    uint32_t w[4];
#pragma unroll
                    for (int e = 0; e < 4; e++) {
                        const float* a = acc + 4 * j + 2 * e;
                        const float2 c = cs[(j & 7) + (e >> 1)];
                        w[e] = gelu2h(pack2(fmaf(-mrow[e & 1], c.x, a[0]) * rrow[e & 1], fmaf(-mrow[e & 1], c.y, a[1]) * rrow[e & 1]));
                    }
                    stsm4(s_stg + 1024 + (fr ^ ((j & 7) << 4)) + (j >> 3) * OFF_EPI, w[0], w[1], w[2], w[3]);
                    if ((j & 7) == 6) { if (!FMOVE) fence_async_smem(); named_bar_arrive(5 + (j >> 3), 288); }
                }
                if (SENDC && warp == (bj & 2 ? 0 : 7)) {
                    __syncwarp();
                    uint32_t a[4];
                    lds64(a[0], a[1], s_stg + 1024 + 18 * 128 * warp + 8 * lane);
                    lds64(a[2], a[3], s_epi + 1024 + 18 * 128 * warp + 8 * lane);
                    uint4* gh = g_halo + (layer * 144 + (warp & 2) * 8 + bi * 8 + bj) * 64 + lane;
#pragma unroll
                    for (int i = 0; i < 2; i++)
                        asm volatile("{\n.reg .b64 u, v;\nmov.b64 u, {%1, %3};\nmov.b64 v, {%2, %3};\nst.relaxed.gpu.global.v2.b64 [%0], {u, v};\n}"
                                     ::"l"(gh + i * 32), "r"(a[2 * i]), "r"(a[2 * i + 1]), "r"(ep) : "memory");
                }
                fence_async_smem();
                if (wg == (bj >> 1 & 1)) named_bar_arrive(13, 256);
                DT(5 + 24 * layer);
            }
            {
                float acc[64];
                uint32_t u[32];
                {
                    uint32_t mb[2], rd[2];
#pragma unroll
                    for (int e = 0; e < 2; e++) { const uint32_t q0 = rsp[8 * e]; mb[e] = (q0 & 0xffffu) * 0x10001u; rd[e] = split(frcp(hi2f(q0))); }
#pragma unroll
                    for (int e = 0; e < 32; e++) {
                        u[e] = norm2(x[e], mb[e & 1], rd[e & 1]);
                        asm volatile("" : "+r"(u[e]));
                    }
                }
                mbar_wait(f5 + 24, r5.ph);
                skip5(r5);
                {
                    const bool nb = wg == (bj >> 1 & 1);
                    named_bar_sync(nb ? 14 : 13, nb ? 160 : 256);
                }
                const uint32_t dah = da0 - (OFF_R - 1024 + 256) / 16 + ((0x4031u >> (2 * bj & 12)) & 7) * 8;
                kblock<128, R5_N, 0>(acc, dah, db0 + 4 * (R5_STAGE / 16), f5, r5);
                kblock<128, R5_N>(acc, dah + OFF_EPI / 16, db0, f5, r5);
                wgmma_wait<1>();
                if (rel_on) mbar_arrive_cluster(rel5 + 32);
                mainloop<128, R5_N, R5_STAGE>(acc, 14, da0, db0, f5, rel5, rel_on, r5, 16 + 24 * layer, []() {} DT_ARG);
                DT(6 + 24 * layer);
#pragma unroll
                for (int j = 0; j < 16; j += 2) {
#pragma unroll
                    for (int e = 0; e < 4; e++) u[2 * j + e] = badd2(u[2 * j + e], pack2(acc[4 * j + 2 * e], acc[4 * j + 2 * e + 1]));
                    stsm4(s_epi + (fr ^ ((j & 7) << 4)) + (j >> 3) * 16384, u[2 * j], u[2 * j + 1], u[2 * j + 2], u[2 * j + 3]);
                    if ((j & 7) == 6) { if (!FMOVE) fence_async_smem(); named_bar_arrive(5 + (j >> 3), 288); mbar_wait(b_role, 0); }
                }
                if (FMOVE) fence_async_smem();
#pragma unroll
                for (int e = 0; e < 32; e++) x[e] = badd2(x[e], u[e]);
                put_stats(u, 2, layer);
                named_bar_sync(9 + wg, 128);
                DT(7 + 24 * layer);
            }
            {
                float2 cs[8];
                {
                    float acc[128];
                    kblock<256, R4_N, 0>(acc, dae, db4, f4, r4);
                    kblock<256, R4_N>(acc, dae + 1024, db4 + R4_STAGE / 16, f4, r4);
                    if (!PS2_EARLY) {
                        uint32_t w[32];
#pragma unroll
                        for (int jp = 0; jp < 8; jp++) ldsm4(w[4 * jp], w[4 * jp + 1], w[4 * jp + 2], w[4 * jp + 3], s_epi + (fr ^ ((jp & 3) << 5)) + (jp >> 2) * 16384);
                        put_stats(w, 2, layer);
                    }
                    wgmma_wait<1>();
                    if (rel_on) mbar_arrive_cluster(rel4);
                    mainloop<256, R4_N, R4_STAGE, PA3A>(acc, 14, da0, db4, f4, rel4, rel_on, r4, 17 + 24 * layer, [&]() {
                        named_bar_sync(3 + 8 * wg, 160);
                        mbar_wait(e4, 1);
                        row_consts(false);
#pragma unroll
                        for (int e = 0; e < 8; e++) cs[e] = *reinterpret_cast<const float2*>(csp + 8 * e);
                        keep_consts(cs);
                    } DT_ARG, wg);
                    DT(8 + 24 * layer);
#pragma unroll
                    for (int j = 0; j < 32; j += 8) stage(acc + 4 * j, j < 16 ? s_epi : s_stg, j, cs, csp + 8 * (j + 8));
                    __syncwarp();
                if (lane == 0) mbar_arrive(b_stg);
                }
                DT(9 + 24 * layer);
                float acc[96];
                kblock<192, R4_N, 0>(acc, da0, db0, f4, r4);
                mainloop<192, R4_N, R4B_STAGE, PA3B>(acc, 15, da0, db0, f4, rel4, rel_on, r4, -1, [&]() {
                    named_bar_sync(4 + 8 * wg, 224);
                } DT_ARG, wg);
                DT(10 + 24 * layer);
#pragma unroll
                for (int j = 0; j < 24; j += 8) stage(acc + 4 * j, j < 16 ? s_epi : s_stg, j, cs, csp + 256 + 8 * (j < 16 ? j + 8 : 0));
                __syncwarp();
                if (lane == 0) mbar_arrive(b_stg);
                DT(11 + 24 * layer);
            }
            {
                float acc[64];
#pragma unroll
                for (int i = 0; i < 32; i++) asm volatile("shl.b32 %0, %2, 16;\nand.b32 %1, %2, 0xffff0000;" : "=f"(acc[2 * i]), "=f"(acc[2 * i + 1]) : "r"(x[i]));
                kblock<128, R5_N>(acc, da0, db0, f5, r5);
                DT(18 + 24 * layer);
                mainloop<128, R5_N, R5_STAGE>(acc, 55, da0, db0, f5, rel5, rel_on, r5, 62 - 40 * (layer ^ 1), []() {} DT_ARG);
                DT(12 + 24 * layer);
#pragma unroll
                for (int i = 0; i < 32; i++) x[i] = pack2(acc[2 * i], acc[2 * i + 1]);
                DT(13 + 24 * layer);
                DT(14 + 24 * layer);
            }
        }
#pragma unroll
        for (int jp = 0; jp < 8; jp++) stsm4(s_epi + (fr ^ ((jp & 3) << 5)) + (jp >> 2) * 16384, x[4 * jp], x[4 * jp + 1], x[4 * jp + 2], x[4 * jp + 3]);
        __syncwarp();
        copy_out(outp, s_epi);
        DT(38);
        DT_DUMP;
        GT(4);
        }
        cluster_arrive_relaxed();
        cluster_wait();
    }
}

typedef CUresult (*PFN_encodeTiled)(CUtensorMap*, CUtensorMapDataType, cuuint32_t, void*, const cuuint64_t*, const cuuint64_t*,
                                    const cuuint32_t*, const cuuint32_t*, CUtensorMapInterleave, CUtensorMapSwizzle,
                                    CUtensorMapL2promotion, CUtensorMapFloatOOBfill);

static CUtensorMap make_map(PFN_encodeTiled enc, const void* ptr, int inner, int outer, int box_inner, int box_outer,
                            CUtensorMapSwizzle swz = CU_TENSOR_MAP_SWIZZLE_128B) {
    CUtensorMap m;
    cuuint64_t dims[2] = {(cuuint64_t)inner, (cuuint64_t)outer};
    cuuint64_t strides[1] = {(cuuint64_t)inner * 2};
    cuuint32_t box[2] = {(cuuint32_t)box_inner, (cuuint32_t)box_outer};
    cuuint32_t es[2] = {1, 1};
    enc(&m, CU_TENSOR_MAP_DATA_TYPE_BFLOAT16, 2, const_cast<void*>(ptr), dims, strides, box, es, CU_TENSOR_MAP_INTERLEAVE_NONE,
        swz, CU_TENSOR_MAP_L2_PROMOTION_L2_256B, CU_TENSOR_MAP_FLOAT_OOB_FILL_NONE);
    return m;
}

extern "C" void kernel_launch(void* const* d_in, const int* in_sizes, int n_in, void* d_out, int out_size) {
    const bf16* A_q = (const bf16*)d_in[0];
    const bf16* A_k = (const bf16*)d_in[1];
    const bf16* A_v = (const bf16*)d_in[2];
    const bf16* A_shk = (const bf16*)d_in[3];
    const bf16* A_ssk = (const bf16*)d_in[4];
    const bf16* A_ssD = (const bf16*)d_in[5];
    const bf16* w1 = (const bf16*)d_in[7];
    const bf16* w2 = (const bf16*)d_in[8];
    const bf16* w3 = (const bf16*)d_in[9];
    const bf16* w4 = (const bf16*)d_in[10];
    bf16* out = (bf16*)d_out;

    static PFN_encodeTiled enc = nullptr;
    static bool attr_done = false;
    if (!enc) {
        void* fn = nullptr;
        cudaDriverEntryPointQueryResult qr;
        cudaGetDriverEntryPoint("cuTensorMapEncodeTiled", &fn, cudaEnableDefault, &qr);
        enc = (PFN_encodeTiled)fn;
    }
    if (!attr_done) {
        cudaFuncSetAttribute(mega_kernel, cudaFuncAttributeMaxDynamicSharedMemorySize, MEGA_SMEM);
        attr_done = true;
    }
    void* p_act;
    cudaGetSymbolAddress(&p_act, g_act);
    bf16* act = (bf16*)(((uintptr_t)p_act + 0x1fffff) & ~(uintptr_t)0x1fffff);

    MegaMaps tm;
    tm.q = make_map(enc, A_q, D_, S_, 64, 128);
    tm.act = make_map(enc, act, D_, R_END, 64, 128);
    tm.w1 = make_map(enc, w1, D_, D_, 64, 64);
    tm.w2 = make_map(enc, w2, D_, D_, 64, 64);
    tm.w3 = make_map(enc, w3, F_, D_, 64, 64);
    tm.w4 = make_map(enc, w4, D_, F_, 64, 64);
    {
        cuuint64_t dims[4] = {64, 16, 256, 8}, strides[3] = {128, D_ * 2, (cuuint64_t)2048 * D_ * 2};
        cuuint32_t box[4] = {64, 4, 1, 8}, es[4] = {1, 1, 1, 1};
        enc(&tm.y, CU_TENSOR_MAP_DATA_TYPE_BFLOAT16, 4, act + (size_t)R_Y * D_, dims, strides, box, es, CU_TENSOR_MAP_INTERLEAVE_NONE,
            CU_TENSOR_MAP_SWIZZLE_128B, CU_TENSOR_MAP_L2_PROMOTION_NONE, CU_TENSOR_MAP_FLOAT_OOB_FILL_NONE);
    }
    for (int i = 0; i < 2; i++) {
        cuuint64_t dims[4] = {D_, 4, 8, S_ / 32}, strides[3] = {8 * D_ * 2, D_ * 2, 32 * D_ * 2};
        cuuint32_t box[4] = {16, 4, 8, 4}, es[4] = {1, 1, 1, 1};
        enc(i ? &tm.v : &tm.k, CU_TENSOR_MAP_DATA_TYPE_BFLOAT16, 4, (void*)(i ? A_v : A_k), dims, strides, box, es, CU_TENSOR_MAP_INTERLEAVE_NONE,
            CU_TENSOR_MAP_SWIZZLE_32B, CU_TENSOR_MAP_L2_PROMOTION_NONE, CU_TENSOR_MAP_FLOAT_OOB_FILL_NONE);
    }
    mega_kernel<<<2 * NCL, 384, MEGA_SMEM, cudaStreamPerThread>>>(tm, out, act, w1, w2, w3, A_q, A_k, A_v, A_shk, A_ssk, A_ssD);
}
```

```cpp
#include <cuda_runtime.h>
#include <cuda_bf16.h>
#include <cuda.h>
#include <stdint.h>

typedef __nv_bfloat16 bf16;

constexpr int S_ = 2048;
constexpr int D_ = 1024;
constexpr int F_ = 3584;

constexpr int R_XA = 0, R_X1 = 256, R_H2 = 512, R_Y = 1536, R_H = 16384 + 8, R_HP = S_ + 8, R_END = R_H + 2 * R_HP;
__device__ __align__(1024) bf16 g_act[(size_t)(R_END + 1024) * D_];
__device__ __align__(16) float g_cpart[16 * (F_ + D_)];
__device__ __align__(128) float2 g_stats[3 * S_ * 8];
__device__ __align__(128) uint4 g_halo[2 * 144 * 64];

__device__ __forceinline__ float bfr(float x) { return __bfloat162float(__float2bfloat16_rn(x)); }
__device__ __forceinline__ uint32_t pack2(float lo, float hi) {
    __nv_bfloat162 v = __floats2bfloat162_rn(lo, hi);
    return *reinterpret_cast<uint32_t*>(&v);
}
__device__ __forceinline__ float lo2f(uint32_t v) { return __uint_as_float(v << 16); }
__device__ __forceinline__ float hi2f(uint32_t v) { return __uint_as_float(v & 0xffff0000u); }
__device__ __forceinline__ float frcp(float x) { float r; asm("rcp.approx.f32 %0, %1;" : "=f"(r) : "f"(x)); return r; }
__device__ __forceinline__ float fsqrt(float x) { float r; asm("sqrt.approx.f32 %0, %1;" : "=f"(r) : "f"(x)); return r; }
__device__ __forceinline__ uint32_t smem_u32(const void* p) { return (uint32_t)__cvta_generic_to_shared(p); }

__device__ __forceinline__ void mbar_init(uint32_t bar, uint32_t cnt) {
    asm volatile("mbarrier.init.shared::cta.b64 [%0], %1;" ::"r"(bar), "r"(cnt));
}
__device__ __forceinline__ void mbar_expect_tx(uint32_t bar, uint32_t bytes) {
    asm volatile("mbarrier.arrive.expect_tx.shared::cta.b64 _, [%0], %1;" ::"r"(bar), "r"(bytes) : "memory");
}
__device__ __forceinline__ void mbar_arrive(uint32_t bar) {
    asm volatile("mbarrier.arrive.shared::cta.b64 _, [%0];" ::"r"(bar) : "memory");
}
__device__ __forceinline__ void mbar_wait(uint32_t bar, uint32_t parity) {
    asm volatile(
        "{\n.reg .pred p;\n.reg .u32 n;\n"
        "mbarrier.try_wait.parity.shared::cta.b64 p, [%0], %1;\n"
        "@p bra LD;\n"
        "mov.u32 n, 0;\n"
        "LW:\n"
        "mbarrier.try_wait.parity.shared::cta.b64 p, [%0], %1;\n"
        "@p bra LD;\n"
        "add.u32 n, n, 1;\n"
        "setp.lt.u32 p, n, 0x400000;\n"
        "@p bra LW;\n"
        "LD:\n}\n"
        ::"r"(bar), "r"(parity) : "memory");
}
__device__ __forceinline__ void tma_load_2d(uint32_t dst, const CUtensorMap* tm, uint32_t bar, int c0, int c1) {
    asm volatile(
        "cp.async.bulk.tensor.2d.shared::cluster.global.mbarrier::complete_tx::bytes [%0], [%1, {%3, %4}], [%2];"
        ::"r"(dst), "l"((uint64_t)tm), "r"(bar), "r"(c0), "r"(c1) : "memory");
}
__device__ __forceinline__ void tma_load_2d_mc(uint32_t dst, const CUtensorMap* tm, uint32_t bar, int c0, int c1) {
    asm volatile(
        "cp.async.bulk.tensor.2d.shared::cluster.global.mbarrier::complete_tx::bytes.multicast::cluster [%0], [%1, {%3, %4}], [%2], %5;"
        ::"r"(dst), "l"((uint64_t)tm), "r"(bar), "r"(c0), "r"(c1), "h"((uint16_t)3) : "memory");
}
__device__ __forceinline__ void tma_prefetch_2d(const CUtensorMap* tm, int c0, int c1) {
    asm volatile("cp.async.bulk.prefetch.tensor.2d.L2.global.tile [%0, {%1, %2}];" ::"l"((uint64_t)tm), "r"(c0), "r"(c1) : "memory");
}
__device__ __forceinline__ void tma_store_2d(const CUtensorMap* tm, uint32_t src, int c0, int c1) {
    asm volatile("cp.async.bulk.tensor.2d.global.shared::cta.bulk_group [%0, {%2, %3}], [%1];"
                 ::"l"((uint64_t)tm), "r"(src), "r"(c0), "r"(c1) : "memory");
}
__device__ __forceinline__ void wgmma_fence() { asm volatile("wgmma.fence.sync.aligned;" ::: "memory"); }
__device__ __forceinline__ void wgmma_commit() { asm volatile("wgmma.commit_group.sync.aligned;" ::: "memory"); }
template <int N> __device__ __forceinline__ void wgmma_wait() { asm volatile("wgmma.wait_group.sync.aligned %0;" ::"n"(N) : "memory"); }
__device__ __forceinline__ void named_bar_arrive(int id, int n) { asm volatile("bar.arrive %0, %1;" ::"r"(id), "r"(n) : "memory"); }
__device__ __forceinline__ void named_bar_sync(int id, int n) { asm volatile("bar.sync %0, %1;" ::"r"(id), "r"(n) : "memory"); }

__device__ __forceinline__ uint32_t desc_a(uint32_t addr) { return ((addr & 0x3FFFF) >> 4) | (1u << 16); }
__device__ __forceinline__ uint32_t desc_b(uint32_t addr) { return ((addr & 0x3FFFF) >> 4) | (512u << 16); }

template <int ACC> __device__ __forceinline__ void wgmma_m64n192k16(float (&d)[96], uint32_t descA, uint32_t descB) {
  asm volatile("{\n.reg .pred p;\n.reg .b64 da, db;\nsetp.ne.b32 p, %99, 0;\nmov.b64 da, {%96, %98};\nmov.b64 db, {%97, %98};\n"
    "wgmma.mma_async.sync.aligned.m64n192k16.f32.bf16.bf16 "
    "{%0, %1, %2, %3, %4, %5, %6, %7, %8, %9, %10, %11, %12, %13, %14, %15, %16, %17, %18, %19, %20, %21, %22, %23, %24, %25, %26, %27, %28, %29, %30, %31, %32, %33, %34, %35, %36, %37, %38, %39, %40, %41, %42, %43, %44, %45, %46, %47, %48, %49, %50, %51, %52, %53, %54, %55, %56, %57, %58, %59, %60, %61, %62, %63, %64, %65, %66, %67, %68, %69, %70, %71, %72, %73, %74, %75, %76, %77, %78, %79, %80, %81, %82, %83, %84, %85, %86, %87, %88, %89, %90, %91, %92, %93, %94, %95}, "
    "da, db, p, 1, 1, 0, 1;\n}\n"
    : "+f"(d[0]), "+f"(d[1]), "+f"(d[2]), "+f"(d[3]), "+f"(d[4]), "+f"(d[5]), "+f"(d[6]), "+f"(d[7]), "+f"(d[8]), "+f"(d[9]), "+f"(d[10]), "+f"(d[11]), "+f"(d[12]), "+f"(d[13]), "+f"(d[14]), "+f"(d[15]), "+f"(d[16]), "+f"(d[17]), "+f"(d[18]), "+f"(d[19]), "+f"(d[20]), "+f"(d[21]), "+f"(d[22]), "+f"(d[23]), "+f"(d[24]), "+f"(d[25]), "+f"(d[26]), "+f"(d[27]), "+f"(d[28]), "+f"(d[29]), "+f"(d[30]), "+f"(d[31]), "+f"(d[32]), "+f"(d[33]), "+f"(d[34]), "+f"(d[35]), "+f"(d[36]), "+f"(d[37]), "+f"(d[38]), "+f"(d[39]), "+f"(d[40]), "+f"(d[41]), "+f"(d[42]), "+f"(d[43]), "+f"(d[44]), "+f"(d[45]), "+f"(d[46]), "+f"(d[47]), "+f"(d[48]), "+f"(d[49]), "+f"(d[50]), "+f"(d[51]), "+f"(d[52]), "+f"(d[53]), "+f"(d[54]), "+f"(d[55]), "+f"(d[56]), "+f"(d[57]), "+f"(d[58]), "+f"(d[59]), "+f"(d[60]), "+f"(d[61]), "+f"(d[62]), "+f"(d[63]), "+f"(d[64]), "+f"(d[65]), "+f"(d[66]), "+f"(d[67]), "+f"(d[68]), "+f"(d[69]), "+f"(d[70]), "+f"(d[71]), "+f"(d[72]), "+f"(d[73]), "+f"(d[74]), "+f"(d[75]), "+f"(d[76]), "+f"(d[77]), "+f"(d[78]), "+f"(d[79]), "+f"(d[80]), "+f"(d[81]), "+f"(d[82]), "+f"(d[83]), "+f"(d[84]), "+f"(d[85]), "+f"(d[86]), "+f"(d[87]), "+f"(d[88]), "+f"(d[89]), "+f"(d[90]), "+f"(d[91]), "+f"(d[92]), "+f"(d[93]), "+f"(d[94]), "+f"(d[95])
    : "r"(descA), "r"(descB), "r"(0x40000040u), "n"(ACC));
}

template <int ACC> __device__ __forceinline__ void wgmma_m64n256k16(float (&d)[128], uint32_t descA, uint32_t descB) {
  asm volatile("{\n.reg .pred p;\n.reg .b64 da, db;\nsetp.ne.b32 p, %131, 0;\nmov.b64 da, {%128, %130};\nmov.b64 db, {%129, %130};\n"
    "wgmma.mma_async.sync.aligned.m64n256k16.f32.bf16.bf16 "
    "{%0, %1, %2, %3, %4, %5, %6, %7, %8, %9, %10, %11, %12, %13, %14, %15, %16, %17, %18, %19, %20, %21, %22, %23, %24, %25, %26, %27, %28, %29, %30, %31, %32, %33, %34, %35, %36, %37, %38, %39, %40, %41, %42, %43, %44, %45, %46, %47, %48, %49, %50, %51, %52, %53, %54, %55, %56, %57, %58, %59, %60, %61, %62, %63, %64, %65, %66, %67, %68, %69, %70, %71, %72, %73, %74, %75, %76, %77, %78, %79, %80, %81, %82, %83, %84, %85, %86, %87, %88, %89, %90, %91, %92, %93, %94, %95, %96, %97, %98, %99, %100, %101, %102, %103, %104, %105, %106, %107, %108, %109, %110, %111, %112, %113, %114, %115, %116, %117, %118, %119, %120, %121, %122, %123, %124, %125, %126, %127}, "
    "da, db, p, 1, 1, 0, 1;\n}\n"
    : "+f"(d[0]), "+f"(d[1]), "+f"(d[2]), "+f"(d[3]), "+f"(d[4]), "+f"(d[5]), "+f"(d[6]), "+f"(d[7]), "+f"(d[8]), "+f"(d[9]), "+f"(d[10]), "+f"(d[11]), "+f"(d[12]), "+f"(d[13]), "+f"(d[14]), "+f"(d[15]), "+f"(d[16]), "+f"(d[17]), "+f"(d[18]), "+f"(d[19]), "+f"(d[20]), "+f"(d[21]), "+f"(d[22]), "+f"(d[23]), "+f"(d[24]), "+f"(d[25]), "+f"(d[26]), "+f"(d[27]), "+f"(d[28]), "+f"(d[29]), "+f"(d[30]), "+f"(d[31]), "+f"(d[32]), "+f"(d[33]), "+f"(d[34]), "+f"(d[35]), "+f"(d[36]), "+f"(d[37]), "+f"(d[38]), "+f"(d[39]), "+f"(d[40]), "+f"(d[41]), "+f"(d[42]), "+f"(d[43]), "+f"(d[44]), "+f"(d[45]), "+f"(d[46]), "+f"(d[47]), "+f"(d[48]), "+f"(d[49]), "+f"(d[50]), "+f"(d[51]), "+f"(d[52]), "+f"(d[53]), "+f"(d[54]), "+f"(d[55]), "+f"(d[56]), "+f"(d[57]), "+f"(d[58]), "+f"(d[59]), "+f"(d[60]), "+f"(d[61]), "+f"(d[62]), "+f"(d[63]), "+f"(d[64]), "+f"(d[65]), "+f"(d[66]), "+f"(d[67]), "+f"(d[68]), "+f"(d[69]), "+f"(d[70]), "+f"(d[71]), "+f"(d[72]), "+f"(d[73]), "+f"(d[74]), "+f"(d[75]), "+f"(d[76]), "+f"(d[77]), "+f"(d[78]), "+f"(d[79]), "+f"(d[80]), "+f"(d[81]), "+f"(d[82]), "+f"(d[83]), "+f"(d[84]), "+f"(d[85]), "+f"(d[86]), "+f"(d[87]), "+f"(d[88]), "+f"(d[89]), "+f"(d[90]), "+f"(d[91]), "+f"(d[92]), "+f"(d[93]), "+f"(d[94]), "+f"(d[95]), "+f"(d[96]), "+f"(d[97]), "+f"(d[98]), "+f"(d[99]), "+f"(d[100]), "+f"(d[101]), "+f"(d[102]), "+f"(d[103]), "+f"(d[104]), "+f"(d[105]), "+f"(d[106]), "+f"(d[107]), "+f"(d[108]), "+f"(d[109]), "+f"(d[110]), "+f"(d[111]), "+f"(d[112]), "+f"(d[113]), "+f"(d[114]), "+f"(d[115]), "+f"(d[116]), "+f"(d[117]), "+f"(d[118]), "+f"(d[119]), "+f"(d[120]), "+f"(d[121]), "+f"(d[122]), "+f"(d[123]), "+f"(d[124]), "+f"(d[125]), "+f"(d[126]), "+f"(d[127])
    : "r"(descA), "r"(descB), "r"(0x40000040u), "n"(ACC));
}

template <int ACC> __device__ __forceinline__ void wgmma_m64n128k16(float (&d)[64], uint32_t descA, uint32_t descB) {
  asm volatile("{\n.reg .pred p;\n.reg .b64 da, db;\nsetp.ne.b32 p, %67, 0;\nmov.b64 da, {%64, %66};\nmov.b64 db, {%65, %66};\n"
    "wgmma.mma_async.sync.aligned.m64n128k16.f32.bf16.bf16 "
    "{%0, %1, %2, %3, %4, %5, %6, %7, %8, %9, %10, %11, %12, %13, %14, %15, %16, %17, %18, %19, %20, %21, %22, %23, %24, %25, %26, %27, %28, %29, %30, %31, %32, %33, %34, %35, %36, %37, %38, %39, %40, %41, %42, %43, %44, %45, %46, %47, %48, %49, %50, %51, %52, %53, %54, %55, %56, %57, %58, %59, %60, %61, %62, %63}, "
    "da, db, p, 1, 1, 0, 1;\n}\n"
    : "+f"(d[0]), "+f"(d[1]), "+f"(d[2]), "+f"(d[3]), "+f"(d[4]), "+f"(d[5]), "+f"(d[6]), "+f"(d[7]), "+f"(d[8]), "+f"(d[9]), "+f"(d[10]), "+f"(d[11]), "+f"(d[12]), "+f"(d[13]), "+f"(d[14]), "+f"(d[15]), "+f"(d[16]), "+f"(d[17]), "+f"(d[18]), "+f"(d[19]), "+f"(d[20]), "+f"(d[21]), "+f"(d[22]), "+f"(d[23]), "+f"(d[24]), "+f"(d[25]), "+f"(d[26]), "+f"(d[27]), "+f"(d[28]), "+f"(d[29]), "+f"(d[30]), "+f"(d[31]), "+f"(d[32]), "+f"(d[33]), "+f"(d[34]), "+f"(d[35]), "+f"(d[36]), "+f"(d[37]), "+f"(d[38]), "+f"(d[39]), "+f"(d[40]), "+f"(d[41]), "+f"(d[42]), "+f"(d[43]), "+f"(d[44]), "+f"(d[45]), "+f"(d[46]), "+f"(d[47]), "+f"(d[48]), "+f"(d[49]), "+f"(d[50]), "+f"(d[51]), "+f"(d[52]), "+f"(d[53]), "+f"(d[54]), "+f"(d[55]), "+f"(d[56]), "+f"(d[57]), "+f"(d[58]), "+f"(d[59]), "+f"(d[60]), "+f"(d[61]), "+f"(d[62]), "+f"(d[63])
    : "r"(descA), "r"(descB), "r"(0x40000040u), "n"(ACC));
}

template <int BN> struct WG;
template <> struct WG<128> { template <int ACC> static __device__ __forceinline__ void mma(float (&d)[64], uint32_t a, uint32_t b) { wgmma_m64n128k16<ACC>(d, a, b); } };
template <> struct WG<256> { template <int ACC> static __device__ __forceinline__ void mma(float (&d)[128], uint32_t a, uint32_t b) { wgmma_m64n256k16<ACC>(d, a, b); } };
template <> struct WG<192> { template <int ACC> static __device__ __forceinline__ void mma(float (&d)[96], uint32_t a, uint32_t b) { wgmma_m64n192k16<ACC>(d, a, b); } };

#define DBG_T(i)
__device__ __forceinline__ void fence_async_smem() { asm volatile("fence.proxy.async.shared::cta;" ::: "memory"); }
__device__ __forceinline__ void prefetch_tmap(const CUtensorMap* tm) { asm volatile("prefetch.tensormap [%0];" ::"l"((uint64_t)tm) : "memory"); }
__device__ __forceinline__ uint32_t mapa_u32(uint32_t addr, uint32_t cta) {
    uint32_t r;
    asm volatile("mapa.shared::cluster.u32 %0, %1, %2;" : "=r"(r) : "r"(addr), "r"(cta));
    return r;
}
__device__ __forceinline__ void mbar_arrive_cluster(uint32_t cluster_addr) {
    asm volatile("mbarrier.arrive.shared::cluster.b64 _, [%0];" ::"r"(cluster_addr) : "memory");
}
__device__ __forceinline__ bool elect_one() {
    uint32_t p;
    asm volatile("{\n.reg .pred P;\nelect.sync _|P, 0xffffffff;\nselp.u32 %0, 1, 0, P;\n}\n" : "=r"(p));
    return p != 0;
}
__device__ __forceinline__ void cluster_arrive_relaxed() { asm volatile("barrier.cluster.arrive.relaxed.aligned;" ::: "memory"); }
__device__ __forceinline__ void cluster_wait() { asm volatile("barrier.cluster.wait.acquire.aligned;" ::: "memory"); }

__device__ __forceinline__ uint32_t bsub2(uint32_t a, uint32_t b) {
    __nv_bfloat162 r = __hsub2(*reinterpret_cast<__nv_bfloat162*>(&a), *reinterpret_cast<__nv_bfloat162*>(&b));
    return *reinterpret_cast<uint32_t*>(&r);
}
__device__ __forceinline__ uint32_t bmul2(uint32_t a, uint32_t b) {
    __nv_bfloat162 r = __hmul2(*reinterpret_cast<__nv_bfloat162*>(&a), *reinterpret_cast<__nv_bfloat162*>(&b));
    return *reinterpret_cast<uint32_t*>(&r);
}
__device__ __forceinline__ uint32_t badd2(uint32_t a, uint32_t b) {
    __nv_bfloat162 r = __hadd2(*reinterpret_cast<__nv_bfloat162*>(&a), *reinterpret_cast<__nv_bfloat162*>(&b));
    return *reinterpret_cast<uint32_t*>(&r);
}
constexpr int BM = 128, BK = 64;
constexpr int R5_STAGE = 32768, R5_N = 5;
constexpr int R4_STAGE = 49152, R4_N = 4;
constexpr int R4B_STAGE = 40960;
constexpr int OFF_STG5 = 0, OFF_R = 32768;
constexpr int OFF_EPI = 196608;
constexpr int OFF_BAR = OFF_EPI + 32768;
constexpr int OFF_RS = OFF_BAR + 256;
constexpr int OFF_CS = OFF_RS + 1024;
constexpr int MEGA_SMEM = OFF_CS + 1792;
enum { FL_XA = 0, FL_H = 2, FL_X1 = 4, FL_H2 = 6, FL_CS = 10, FL_KINDS = 11 };
constexpr int FL_PITCH = 64;
constexpr int FL_WORDS = 2 * FL_KINDS * 16 * FL_PITCH;
__device__ unsigned int g_flag[FL_WORDS];
__device__ __align__(8) unsigned int g_ticket[18 * FL_PITCH];
constexpr int NCL = 66;
__device__ __forceinline__ unsigned int* flag_ptr(int layer, int kind, int i) { return g_flag + ((layer * FL_KINDS + kind) * 16 + i) * FL_PITCH; }

__device__ __forceinline__ void wait_flag(const unsigned int* p, unsigned int target) {
    long long t0 = clock64();
    while (true) {
        unsigned int v;
        asm volatile("ld.relaxed.gpu.global.u32 %0, [%1];" : "=r"(v) : "l"(p) : "memory");
        if ((int)(v - target) >= 0) break;
        if (clock64() - t0 > 2000000000LL) break;
    }
    asm volatile("fence.acquire.gpu;" ::: "memory");
}
__device__ __forceinline__ void fence_proxy_async() {
    asm volatile("fence.proxy.async.global;" ::: "memory");
    asm volatile("fence.proxy.async.shared::cta;" ::: "memory");
}
__device__ __forceinline__ void stsm4(uint32_t addr, uint32_t r0, uint32_t r1, uint32_t r2, uint32_t r3) {
    asm volatile("stmatrix.sync.aligned.m8n8.x4.shared.b16 [%0], {%1,%2,%3,%4};" ::"r"(addr), "r"(r0), "r"(r1), "r"(r2), "r"(r3));
}
__device__ __forceinline__ uint4 lds128(uint32_t a) {
    uint4 v;
    asm volatile("ld.shared.v4.b32 {%0,%1,%2,%3}, [%4];" : "=r"(v.x), "=r"(v.y), "=r"(v.z), "=r"(v.w) : "r"(a) : "memory");
    return v;
}
__device__ __forceinline__ void stg128(void* p, uint4 v) {
    asm volatile("st.global.v4.b32 [%0], {%1,%2,%3,%4};" ::"l"(p), "r"(v.x), "r"(v.y), "r"(v.z), "r"(v.w) : "memory");
}
__device__ __forceinline__ float gelu_tanh_h(float hx) {
    float z = hx * fmaf(hx * hx, 8.0f * 0.035677408136300125f, 2.0f * 0.7978845608028654f);
    float t;
    asm("tanh.approx.f32 %0, %1;" : "=f"(t) : "f"(z));
    return fmaf(hx, t, hx);
}
__device__ __forceinline__ uint32_t gelu2h(uint32_t hx) {
    uint32_t r;
    asm("{\n.reg .b32 z;\nmul.rn.bf16x2 z, %1, %1;\nfma.rn.bf16x2 z, z, %2, %3;\nmul.rn.bf16x2 z, z, %1;\ntanh.approx.bf16x2 z, z;\nfma.rn.bf16x2 %0, %1, z, %1;\n}"
        : "=r"(r) : "r"(hx), "r"(0x3e923e92u), "r"(0x3fcc3fccu));
    return r;
}
__device__ __forceinline__ uint4 gelu8h(uint4 v) { return make_uint4(gelu2h(v.x), gelu2h(v.y), gelu2h(v.z), gelu2h(v.w)); }

__device__ __forceinline__ void row_stats(const float2* p, uint32_t tag, float& mean, float& var) {
    float2 v[8];
#pragma unroll 1
    for (int n = 0; n < (1 << 20); n++) {
#pragma unroll
        for (int i = 0; i < 8; i++)
            asm volatile("{\n.reg .b64 t;\nld.relaxed.gpu.global.b64 t, [%2];\nmov.b64 {%0, %1}, t;\n}" : "=f"(v[i].x), "=f"(v[i].y) : "l"(p + 128 * i) : "memory");
        uint32_t old = 0;
#pragma unroll
        for (int i = 0; i < 8; i++) old |= __float_as_uint(v[i].y) ^ tag;
        if ((int)old >= 0) break;
    }
    mean = (((v[0].x + v[1].x) + (v[2].x + v[3].x)) + ((v[4].x + v[5].x) + (v[6].x + v[7].x))) * 0.125f;
    float m2 = 0.f, d2 = 0.f;
#pragma unroll
    for (int i = 0; i < 8; i++) { m2 += fabsf(v[i].y); d2 = fmaf(v[i].x - mean, v[i].x - mean, d2); }
    var = fmaf(128.0f, d2, m2) * (1.0f / D_);
}
struct RingState { uint32_t st, ph; };

#define DT(i)
#define DT_DECL
#define DT_PAR
#define DT_ARG
#define DT_DUMP
#define DP(i)
#define GT(i)
#define TM(i)

template <int BN, int NST, int ACC = 1>
__device__ __forceinline__ void kblock(float (&acc)[BN / 2], uint32_t da, uint32_t db, uint32_t bfull, RingState& rs) {
    mbar_wait(bfull + 8 * rs.st, rs.ph);
    wgmma_fence();
    WG<BN>::template mma<ACC>(acc, da, db);
#pragma unroll
    for (int k = 1; k < 4; k++) WG<BN>::template mma<1>(acc, da + k * 2, db + k * 128);
    wgmma_commit();
    if (++rs.st == NST) { rs.st = 0; rs.ph ^= 1; }
}
#define SIG 0
#define PA3A 1
#define RLX 1
#define PPK 2
template <int V> struct IC { static constexpr int v = V; };
#define PA3B 0
template <int BN, int NST, int STAGE, int PAUSE = 0, int TW = 0, class F>
__device__ __forceinline__ void mainloop(float (&acc)[BN / 2], int KB, uint32_t da0, uint32_t db0, uint32_t bfull, uint32_t rel, bool rel_on,
                                         RingState& rs, int dbg, F pre DT_PAR, int wg = 0) {
    uint32_t prev = rs.st ? rs.st - 1 : NST - 1;
    const int pause = wg ? KB - PAUSE : -1;
#pragma unroll 1
    for (int kk = 0; kk < KB; kk++) {
        const uint32_t cur = rs.st;
        if (PAUSE && kk == pause) {
            wgmma_wait<0>();
            if (rel_on) mbar_arrive_cluster(rel + 8 * prev);
            named_bar_sync(13, 256);
        }
        kblock<BN, NST>(acc, da0 + cur * (STAGE / 16), db0 + cur * (STAGE / 16), bfull, rs);
        if (PAUSE && SIG == 2 && wg == 0 && kk == KB - 1) named_bar_arrive(13, 256);
        wgmma_wait<1>();
        if (rel_on && !(PAUSE && kk == pause)) mbar_arrive_cluster(rel + 8 * prev);
        prev = cur;
    }
    if (PAUSE && SIG == 0 && wg == 0) named_bar_arrive(13, 256);
    pre();
    wgmma_wait<TW>();
#pragma unroll
    for (int i = 0; i < BN / 2; i++) asm volatile("" : "+f"(acc[i])::"memory");
    if (PAUSE && SIG == 1 && wg == 0) named_bar_arrive(13, 256);
    if (rel_on) mbar_arrive_cluster(rel + 8 * prev);
}
__device__ __forceinline__ void hmma(float (&c)[4], uint32_t a0, uint32_t a1, uint32_t a2, uint32_t a3, uint32_t b0, uint32_t b1, bool first) {
    if (first) asm("{\n.reg .f32 z;\nmov.f32 z, 0f00000000;\nmma.sync.aligned.m16n8k16.row.col.f32.bf16.bf16.f32 {%0,%1,%2,%3}, {%4,%5,%6,%7}, {%8,%9}, {z,z,z,z};\n}"
        : "=f"(c[0]), "=f"(c[1]), "=f"(c[2]), "=f"(c[3]) : "r"(a0), "r"(a1), "r"(a2), "r"(a3), "r"(b0), "r"(b1));
    else
    asm("mma.sync.aligned.m16n8k16.row.col.f32.bf16.bf16.f32 {%0,%1,%2,%3}, {%4,%5,%6,%7}, {%8,%9}, {%0,%1,%2,%3};"
        : "+f"(c[0]), "+f"(c[1]), "+f"(c[2]), "+f"(c[3]) : "r"(a0), "r"(a1), "r"(a2), "r"(a3), "r"(b0), "r"(b1));
}
__device__ __forceinline__ void hmma8(float (&c)[4], uint32_t a0, uint32_t a1, uint32_t b0, bool first) {
    if (first) asm("{\n.reg .f32 z;\nmov.f32 z, 0f00000000;\nmma.sync.aligned.m16n8k8.row.col.f32.bf16.bf16.f32 {%0,%1,%2,%3}, {%4,%5}, {%6}, {z,z,z,z};\n}"
        : "=f"(c[0]), "=f"(c[1]), "=f"(c[2]), "=f"(c[3]) : "r"(a0), "r"(a1), "r"(b0));
    else
    asm("mma.sync.aligned.m16n8k8.row.col.f32.bf16.bf16.f32 {%0,%1,%2,%3}, {%4,%5}, {%6}, {%0,%1,%2,%3};"
        : "+f"(c[0]), "+f"(c[1]), "+f"(c[2]), "+f"(c[3]) : "r"(a0), "r"(a1), "r"(b0));
}
template <int N> __device__ __forceinline__ void zero_acc(float (&acc)[N]) {
#pragma unroll
    for (int i = 0; i < N; i++) acc[i] = 0.f;
}
__device__ __forceinline__ void ldsm4(uint32_t& r0, uint32_t& r1, uint32_t& r2, uint32_t& r3, uint32_t addr) {
    asm volatile("ldmatrix.sync.aligned.m8n8.x4.shared.b16 {%0,%1,%2,%3}, [%4];" : "=r"(r0), "=r"(r1), "=r"(r2), "=r"(r3) : "r"(addr));
}

__device__ __forceinline__ void ldsm4t(uint32_t& r0, uint32_t& r1, uint32_t& r2, uint32_t& r3, uint32_t addr) {
    asm volatile("ldmatrix.sync.aligned.m8n8.x4.trans.shared.b16 {%0,%1,%2,%3}, [%4];" : "=r"(r0), "=r"(r1), "=r"(r2), "=r"(r3) : "r"(addr));
}

#define DBG_S(i)
#define DBG_OUT(r, o)
#define DBG_F(i)
#define DBG_W(i)
constexpr int CV_CH = 8;
constexpr int CV_SL = 16384;
constexpr int CV_QG = 128 * 8 + 16;
constexpr int CV_HPL = 2048 + 192;
constexpr int CV_0 = 32768, CV_H = 9 * CV_SL, CV_BAR = OFF_RS - CV_0;

template <int K> __device__ __forceinline__ void cv_mma(float (&d)[64], const uint32_t (&a)[4], uint32_t db, int acc);
template <> __device__ __forceinline__ void cv_mma<0>(float (&d)[64], const uint32_t (&a)[4], uint32_t db, int acc) {
    asm volatile("{\n.reg .pred p;\n.reg .b64 b;\nsetp.ne.b32 p, %70, 0;\nmov.b64 b, {%68, %69};\n"
        "wgmma.mma_async.sync.aligned.m64n128k16.f32.bf16.bf16 {%0,%1,%2,%3,%4,%5,%6,%7,%8,%9,%10,%11,%12,%13,%14,%15,%16,%17,%18,%19,%20,%21,%22,%23,%24,%25,%26,%27,%28,%29,%30,%31,%32,%33,%34,%35,%36,%37,%38,%39,%40,%41,%42,%43,%44,%45,%46,%47,%48,%49,%50,%51,%52,%53,%54,%55,%56,%57,%58,%59,%60,%61,%62,%63}, {%64,%65,%66,%67}, b, p, 1, 1, 0;\n}\n"
        : "+f"(d[0]), "+f"(d[1]), "+f"(d[2]), "+f"(d[3]), "+f"(d[4]), "+f"(d[5]), "+f"(d[6]), "+f"(d[7]), "+f"(d[8]), "+f"(d[9]), "+f"(d[10]), "+f"(d[11]), "+f"(d[12]), "+f"(d[13]), "+f"(d[14]), "+f"(d[15]), "+f"(d[16]), "+f"(d[17]), "+f"(d[18]), "+f"(d[19]), "+f"(d[20]), "+f"(d[21]), "+f"(d[22]), "+f"(d[23]), "+f"(d[24]), "+f"(d[25]), "+f"(d[26]), "+f"(d[27]), "+f"(d[28]), "+f"(d[29]), "+f"(d[30]), "+f"(d[31]), "+f"(d[32]), "+f"(d[33]), "+f"(d[34]), "+f"(d[35]), "+f"(d[36]), "+f"(d[37]), "+f"(d[38]), "+f"(d[39]), "+f"(d[40]), "+f"(d[41]), "+f"(d[42]), "+f"(d[43]), "+f"(d[44]), "+f"(d[45]), "+f"(d[46]), "+f"(d[47]), "+f"(d[48]), "+f"(d[49]), "+f"(d[50]), "+f"(d[51]), "+f"(d[52]), "+f"(d[53]), "+f"(d[54]), "+f"(d[55]), "+f"(d[56]), "+f"(d[57]), "+f"(d[58]), "+f"(d[59]), "+f"(d[60]), "+f"(d[61]), "+f"(d[62]), "+f"(d[63])
        : "r"(a[0]), "r"(a[1]), "r"(a[2]), "r"(a[3]), "r"(db), "r"(8u), "r"(acc));
}
template <> __device__ __forceinline__ void cv_mma<1>(float (&d)[64], const uint32_t (&a)[4], uint32_t db, int acc) {
    asm volatile("{\n.reg .pred p;\n.reg .b64 b;\nsetp.ne.b32 p, %62, 0;\nmov.b64 b, {%60, %61};\n"
        "wgmma.mma_async.sync.aligned.m64n112k16.f32.bf16.bf16 {%0,%1,%2,%3,%4,%5,%6,%7,%8,%9,%10,%11,%12,%13,%14,%15,%16,%17,%18,%19,%20,%21,%22,%23,%24,%25,%26,%27,%28,%29,%30,%31,%32,%33,%34,%35,%36,%37,%38,%39,%40,%41,%42,%43,%44,%45,%46,%47,%48,%49,%50,%51,%52,%53,%54,%55}, {%56,%57,%58,%59}, b, p, 1, 1, 0;\n}\n"
        : "+f"(d[0]), "+f"(d[1]), "+f"(d[2]), "+f"(d[3]), "+f"(d[4]), "+f"(d[5]), "+f"(d[6]), "+f"(d[7]), "+f"(d[8]), "+f"(d[9]), "+f"(d[10]), "+f"(d[11]), "+f"(d[12]), "+f"(d[13]), "+f"(d[14]), "+f"(d[15]), "+f"(d[16]), "+f"(d[17]), "+f"(d[18]), "+f"(d[19]), "+f"(d[20]), "+f"(d[21]), "+f"(d[22]), "+f"(d[23]), "+f"(d[24]), "+f"(d[25]), "+f"(d[26]), "+f"(d[27]), "+f"(d[28]), "+f"(d[29]), "+f"(d[30]), "+f"(d[31]), "+f"(d[32]), "+f"(d[33]), "+f"(d[34]), "+f"(d[35]), "+f"(d[36]), "+f"(d[37]), "+f"(d[38]), "+f"(d[39]), "+f"(d[40]), "+f"(d[41]), "+f"(d[42]), "+f"(d[43]), "+f"(d[44]), "+f"(d[45]), "+f"(d[46]), "+f"(d[47]), "+f"(d[48]), "+f"(d[49]), "+f"(d[50]), "+f"(d[51]), "+f"(d[52]), "+f"(d[53]), "+f"(d[54]), "+f"(d[55])
        : "r"(a[0]), "r"(a[1]), "r"(a[2]), "r"(a[3]), "r"(db), "r"(8u), "r"(acc));
}
template <> __device__ __forceinline__ void cv_mma<2>(float (&d)[64], const uint32_t (&a)[4], uint32_t db, int acc) {
    asm volatile("{\n.reg .pred p;\n.reg .b64 b;\nsetp.ne.b32 p, %54, 0;\nmov.b64 b, {%52, %53};\n"
        "wgmma.mma_async.sync.aligned.m64n96k16.f32.bf16.bf16 {%0,%1,%2,%3,%4,%5,%6,%7,%8,%9,%10,%11,%12,%13,%14,%15,%16,%17,%18,%19,%20,%21,%22,%23,%24,%25,%26,%27,%28,%29,%30,%31,%32,%33,%34,%35,%36,%37,%38,%39,%40,%41,%42,%43,%44,%45,%46,%47}, {%48,%49,%50,%51}, b, p, 1, 1, 0;\n}\n"
        : "+f"(d[0]), "+f"(d[1]), "+f"(d[2]), "+f"(d[3]), "+f"(d[4]), "+f"(d[5]), "+f"(d[6]), "+f"(d[7]), "+f"(d[8]), "+f"(d[9]), "+f"(d[10]), "+f"(d[11]), "+f"(d[12]), "+f"(d[13]), "+f"(d[14]), "+f"(d[15]), "+f"(d[16]), "+f"(d[17]), "+f"(d[18]), "+f"(d[19]), "+f"(d[20]), "+f"(d[21]), "+f"(d[22]), "+f"(d[23]), "+f"(d[24]), "+f"(d[25]), "+f"(d[26]), "+f"(d[27]), "+f"(d[28]), "+f"(d[29]), "+f"(d[30]), "+f"(d[31]), "+f"(d[32]), "+f"(d[33]), "+f"(d[34]), "+f"(d[35]), "+f"(d[36]), "+f"(d[37]), "+f"(d[38]), "+f"(d[39]), "+f"(d[40]), "+f"(d[41]), "+f"(d[42]), "+f"(d[43]), "+f"(d[44]), "+f"(d[45]), "+f"(d[46]), "+f"(d[47])
        : "r"(a[0]), "r"(a[1]), "r"(a[2]), "r"(a[3]), "r"(db), "r"(8u), "r"(acc));
}
template <> __device__ __forceinline__ void cv_mma<3>(float (&d)[64], const uint32_t (&a)[4], uint32_t db, int acc) {
    asm volatile("{\n.reg .pred p;\n.reg .b64 b;\nsetp.ne.b32 p, %46, 0;\nmov.b64 b, {%44, %45};\n"
        "wgmma.mma_async.sync.aligned.m64n80k16.f32.bf16.bf16 {%0,%1,%2,%3,%4,%5,%6,%7,%8,%9,%10,%11,%12,%13,%14,%15,%16,%17,%18,%19,%20,%21,%22,%23,%24,%25,%26,%27,%28,%29,%30,%31,%32,%33,%34,%35,%36,%37,%38,%39}, {%40,%41,%42,%43}, b, p, 1, 1, 0;\n}\n"
        : "+f"(d[0]), "+f"(d[1]), "+f"(d[2]), "+f"(d[3]), "+f"(d[4]), "+f"(d[5]), "+f"(d[6]), "+f"(d[7]), "+f"(d[8]), "+f"(d[9]), "+f"(d[10]), "+f"(d[11]), "+f"(d[12]), "+f"(d[13]), "+f"(d[14]), "+f"(d[15]), "+f"(d[16]), "+f"(d[17]), "+f"(d[18]), "+f"(d[19]), "+f"(d[20]), "+f"(d[21]), "+f"(d[22]), "+f"(d[23]), "+f"(d[24]), "+f"(d[25]), "+f"(d[26]), "+f"(d[27]), "+f"(d[28]), "+f"(d[29]), "+f"(d[30]), "+f"(d[31]), "+f"(d[32]), "+f"(d[33]), "+f"(d[34]), "+f"(d[35]), "+f"(d[36]), "+f"(d[37]), "+f"(d[38]), "+f"(d[39])
        : "r"(a[0]), "r"(a[1]), "r"(a[2]), "r"(a[3]), "r"(db), "r"(8u), "r"(acc));
}
template <> __device__ __forceinline__ void cv_mma<4>(float (&d)[64], const uint32_t (&a)[4], uint32_t db, int acc) {
    asm volatile("{\n.reg .pred p;\n.reg .b64 b;\nsetp.ne.b32 p, %38, 0;\nmov.b64 b, {%36, %37};\n"
        "wgmma.mma_async.sync.aligned.m64n64k16.f32.bf16.bf16 {%0,%1,%2,%3,%4,%5,%6,%7,%8,%9,%10,%11,%12,%13,%14,%15,%16,%17,%18,%19,%20,%21,%22,%23,%24,%25,%26,%27,%28,%29,%30,%31}, {%32,%33,%34,%35}, b, p, 1, 1, 0;\n}\n"
        : "+f"(d[0]), "+f"(d[1]), "+f"(d[2]), "+f"(d[3]), "+f"(d[4]), "+f"(d[5]), "+f"(d[6]), "+f"(d[7]), "+f"(d[8]), "+f"(d[9]), "+f"(d[10]), "+f"(d[11]), "+f"(d[12]), "+f"(d[13]), "+f"(d[14]), "+f"(d[15]), "+f"(d[16]), "+f"(d[17]), "+f"(d[18]), "+f"(d[19]), "+f"(d[20]), "+f"(d[21]), "+f"(d[22]), "+f"(d[23]), "+f"(d[24]), "+f"(d[25]), "+f"(d[26]), "+f"(d[27]), "+f"(d[28]), "+f"(d[29]), "+f"(d[30]), "+f"(d[31])
        : "r"(a[0]), "r"(a[1]), "r"(a[2]), "r"(a[3]), "r"(db), "r"(8u), "r"(acc));
}
template <> __device__ __forceinline__ void cv_mma<5>(float (&d)[64], const uint32_t (&a)[4], uint32_t db, int acc) {
    asm volatile("{\n.reg .pred p;\n.reg .b64 b;\nsetp.ne.b32 p, %30, 0;\nmov.b64 b, {%28, %29};\n"
        "wgmma.mma_async.sync.aligned.m64n48k16.f32.bf16.bf16 {%0,%1,%2,%3,%4,%5,%6,%7,%8,%9,%10,%11,%12,%13,%14,%15,%16,%17,%18,%19,%20,%21,%22,%23}, {%24,%25,%26,%27}, b, p, 1, 1, 0;\n}\n"
        : "+f"(d[0]), "+f"(d[1]), "+f"(d[2]), "+f"(d[3]), "+f"(d[4]), "+f"(d[5]), "+f"(d[6]), "+f"(d[7]), "+f"(d[8]), "+f"(d[9]), "+f"(d[10]), "+f"(d[11]), "+f"(d[12]), "+f"(d[13]), "+f"(d[14]), "+f"(d[15]), "+f"(d[16]), "+f"(d[17]), "+f"(d[18]), "+f"(d[19]), "+f"(d[20]), "+f"(d[21]), "+f"(d[22]), "+f"(d[23])
        : "r"(a[0]), "r"(a[1]), "r"(a[2]), "r"(a[3]), "r"(db), "r"(8u), "r"(acc));
}
template <> __device__ __forceinline__ void cv_mma<6>(float (&d)[64], const uint32_t (&a)[4], uint32_t db, int acc) {
    asm volatile("{\n.reg .pred p;\n.reg .b64 b;\nsetp.ne.b32 p, %22, 0;\nmov.b64 b, {%20, %21};\n"
        "wgmma.mma_async.sync.aligned.m64n32k16.f32.bf16.bf16 {%0,%1,%2,%3,%4,%5,%6,%7,%8,%9,%10,%11,%12,%13,%14,%15}, {%16,%17,%18,%19}, b, p, 1, 1, 0;\n}\n"
        : "+f"(d[0]), "+f"(d[1]), "+f"(d[2]), "+f"(d[3]), "+f"(d[4]), "+f"(d[5]), "+f"(d[6]), "+f"(d[7]), "+f"(d[8]), "+f"(d[9]), "+f"(d[10]), "+f"(d[11]), "+f"(d[12]), "+f"(d[13]), "+f"(d[14]), "+f"(d[15])
        : "r"(a[0]), "r"(a[1]), "r"(a[2]), "r"(a[3]), "r"(db), "r"(8u), "r"(acc));
}
template <> __device__ __forceinline__ void cv_mma<7>(float (&d)[64], const uint32_t (&a)[4], uint32_t db, int acc) {
    asm volatile("{\n.reg .pred p;\n.reg .b64 b;\nsetp.ne.b32 p, %14, 0;\nmov.b64 b, {%12, %13};\n"
        "wgmma.mma_async.sync.aligned.m64n16k16.f32.bf16.bf16 {%0,%1,%2,%3,%4,%5,%6,%7}, {%8,%9,%10,%11}, b, p, 1, 1, 0;\n}\n"
        : "+f"(d[0]), "+f"(d[1]), "+f"(d[2]), "+f"(d[3]), "+f"(d[4]), "+f"(d[5]), "+f"(d[6]), "+f"(d[7])
        : "r"(a[0]), "r"(a[1]), "r"(a[2]), "r"(a[3]), "r"(db), "r"(8u), "r"(acc));
}
__device__ __forceinline__ void stsm4t(uint32_t addr, uint32_t r0, uint32_t r1, uint32_t r2, uint32_t r3) {
    asm volatile("stmatrix.sync.aligned.m8n8.x4.trans.shared.b16 [%0], {%1,%2,%3,%4};" ::"r"(addr), "r"(r0), "r"(r1), "r"(r2), "r"(r3) : "memory");
}
__device__ __forceinline__ void cp16(uint32_t dst, const void* src, int n = 16) {
    asm volatile("cp.async.cg.shared.global.L2::128B [%0], [%1], 16, %2;" ::"r"(dst), "l"(src), "r"(n) : "memory");
}
__device__ __forceinline__ void cp_arrive(uint32_t bar) { asm volatile("cp.async.mbarrier.arrive.noinc.shared::cta.b64 [%0];" ::"r"(bar) : "memory"); }
__device__ __forceinline__ void lds64(uint32_t& x, uint32_t& y, uint32_t a) { asm volatile("ld.shared.v2.b32 {%0,%1}, [%2];" : "=r"(x), "=r"(y) : "r"(a) : "memory"); }
__device__ __forceinline__ void sts128(uint32_t a, uint32_t x, uint32_t y, uint32_t z, uint32_t w) {
    asm volatile("st.shared.v4.b32 [%0], {%1,%2,%3,%4};" ::"r"(a), "r"(x), "r"(y), "r"(z), "r"(w) : "memory");
}
__device__ __forceinline__ uint32_t bfma2(uint32_t a, uint32_t b, uint32_t c) {
    uint32_t r;
    asm("fma.rn.bf16x2 %0, %1, %2, %3;" : "=r"(r) : "r"(a), "r"(b), "r"(c));
    return r;
}
#define CV_NS 4
#define CV_W 1
constexpr int CV_GC = 8 / CV_NS, CV_NA = (CV_W + 2) * CV_NS;
struct CvAddr { uint32_t pa[2], p0[4], db, rdy, xw, xr, bar; bool wrap, neg[2]; };
template <int G> __device__ __forceinline__ void cv_load(uint32_t (&a)[CV_NA][4], const CvAddr& p) {
    if constexpr (G % CV_GC == 0) mbar_wait(p.rdy + 8 * (G / CV_GC), 0);
#pragma unroll
    for (int i = G * CV_NS; i < (G + 1) * CV_NS; i++) {
        const int of = (i / 2 % 2) * CV_QG + (i / 8) * CV_SL + 256 * (i % 2 + (i / 2 & 2));
        if ((i & 5) == 0) {
#pragma unroll
            for (int e = 0; e < 4; e++) asm volatile("ld.shared.b32 %0, [%1];" : "=r"(a[i % CV_NA][e]) : "r"(p.p0[e] + of) : "memory");
            if (i < 8) { if (p.neg[0]) a[i % CV_NA][0] = 0; if (p.neg[1]) a[i % CV_NA][2] = 0; }
        } else {
            lds64(a[i % CV_NA][0], a[i % CV_NA][1], p.pa[0] + of - 256);
            lds64(a[i % CV_NA][2], a[i % CV_NA][3], p.pa[1] + of - 256);
        }
    }
}
__device__ __forceinline__ float vadd(float a, float b) {
    float r;
    asm volatile("add.f32 %0, %1, %2;" : "=f"(r) : "f"(a), "f"(b));
    return r;
}
template <int K> __device__ __forceinline__ uint32_t cv_tail(float (&d)[64], bool wrap) {
    float* z = d + 56 - 8 * K;
    z[4] = vadd(z[4], K > 0 ? z[10] : 0.f);
    if constexpr (K > 0) z[5] = vadd(z[5], z[11]);
    z[0] = vadd(z[0], z[6]);
    z[1] = vadd(z[1], z[7]);
    return pack2(wrap ? (K > 0 ? z[8] : 0.f) : z[4], wrap ? z[4] : z[0]);
}
template <int K> __device__ __forceinline__ uint32_t cv_fin(const float (&d)[64], uint32_t x) { return pack2(d[61 - 8 * K] + lo2f(x), d[57 - 8 * K] + hi2f(x)); }
template <int G>
__device__ __forceinline__ void cv_steps(float (&d)[2][64], uint32_t (&a)[CV_NA][4], uint32_t (&tv)[2][8], const CvAddr& p) {
    constexpr int K = G / CV_GC, GN = 8 * CV_GC;
    constexpr int T = G - CV_W - CV_GC, F = T - 1, TK = T / CV_GC, FK = F / CV_GC;
    if constexpr (G == 0) cv_load<0>(a, p);
    if constexpr (G < GN) {
        wgmma_fence();
#pragma unroll
        for (int i = G * CV_NS; i < (G + 1) * CV_NS; i++)
            cv_mma<K>(d[i / 2 % 2], a[i % CV_NA], p.db + (i / 2 % 2) * (CV_HPL / 8) + 16 * K + 2 * (i % 2 + (i / 2 & 2)), i & ~2 ? 1 : p.bar >> 8);
        wgmma_commit();
    }
    if constexpr (G < GN - 1) cv_load<G + 1>(a, p);
    if constexpr (T >= 0 && T % CV_GC == 0) {
        tv[0][TK] = cv_tail<TK>(d[0], p.wrap);
        tv[1][TK] = cv_tail<TK>(d[1], p.wrap);
        if constexpr (TK & 1) sts128(p.xw + TK / 2 * 512, tv[0][TK - 1], tv[0][TK], tv[1][TK - 1], tv[1][TK]);
    }
    if constexpr (F >= 0 && F % (2 * CV_GC) == CV_GC) {
        const uint4 x = lds128(p.xr + FK / 2 * 512);
        tv[0][FK - 1] = cv_fin<FK - 1>(d[0], x.x); tv[0][FK] = cv_fin<FK>(d[0], x.y);
        tv[1][FK - 1] = cv_fin<FK - 1>(d[1], x.z); tv[1][FK] = cv_fin<FK>(d[1], x.w);
    }
    if constexpr (G < GN - 1) wgmma_wait<CV_W>();
    if constexpr (G == GN - 1) wgmma_wait<0>();
    if constexpr (T >= 0 && T % (2 * CV_GC) == CV_GC) named_bar_sync(p.bar, 128);
    if constexpr (F < GN - CV_GC) cv_steps<G + 1>(d, a, tv, p);
}

#define CV_PF 7
#define Y_FIRST 1
#define Y_HOLD 0
#define PS2_EARLY 1
#define PS1_EARLY 1
#define FMOVE 1
#define SENDC 1
#define HDELAY 0
#define NH16 1
#define W3_AT 1
struct MegaMaps {
    CUtensorMap q, act;
    CUtensorMap w1, w2, w3, w4;
    CUtensorMap k, v, y;
};

__global__ void __cluster_dims__(2, 1, 1) __launch_bounds__(384, 1)
mega_kernel(const __grid_constant__ MegaMaps tm, bf16* __restrict__ outp, bf16* act, const bf16* __restrict__ w1p, const bf16* __restrict__ w2p,
            const bf16* __restrict__ w3p, const bf16* __restrict__ xq, const bf16* __restrict__ kp, const bf16* __restrict__ vp,
            const bf16* __restrict__ shk, const bf16* __restrict__ ssk, const bf16* __restrict__ ssD) {
    extern __shared__ __align__(1024) uint8_t sgen[];
    const uint32_t sbase = smem_u32(sgen);
    const int warp = __shfl_sync(0xffffffffu, threadIdx.x >> 5, 0), lane = threadIdx.x & 31;
    const int rank = blockIdx.x & 1;
    const uint32_t s_bar = sbase + OFF_BAR;
    const uint32_t f5 = s_bar, e5 = s_bar + 64, f4 = s_bar + 144, e4 = s_bar + 104;
    const uint32_t b_rfull = s_bar + 176, b_role = s_bar + 184, b_stg = s_bar + 136, b_h2 = s_bar + 32;
    const uint32_t s_epi = sbase + OFF_EPI, s_stg = sbase + OFF_STG5, s_r = sbase + OFF_R;
    uint8_t* sm = sgen + CV_0;
    const uint32_t sb = sbase + CV_0;
    const int tid = threadIdx.x, wg = warp >> 2, w = warp & 3;
    const int d0 = blockIdx.x * CV_CH;
    const bool cv = blockIdx.x < D_ / CV_CH;
    const uint32_t b_full = sb + CV_BAR, b_rdy = b_full + 64, b_h = b_full + 128;
    GT(0);
    if (tid == 0) TM(0);
    auto row_at = [&](int r) { return sb + CV_SL + (r < 0 ? -8192 : 0) + ((r & 127) >> 5) * 1024 + (r & 7) * 128 + ((r >> 3) & 3) * 32 + ((r ^ rank) & 1) * 16; };
    auto load_kv = [&](int c) {
#pragma unroll
        for (int i = 0; i < 2; i++)
            asm volatile("cp.async.bulk.tensor.4d.shared::cluster.global.mbarrier::complete_tx::bytes.multicast::cluster [%0], [%1, {%3, %4, %4, %5}], [%2], %6;"
                         ::"r"(sb + (c + 1) * CV_SL + rank * 8192 + i * 4096), "l"((uint64_t)(i ? &tm.v : &tm.k)), "r"(b_full + 8 * c), "r"(d0 & ~15), "r"(0),
                         "r"(8 * c + 4 * rank), "h"((uint16_t)3) : "memory");
    };
    auto bulk = [&](uint32_t dst, const void* src, uint32_t n, uint32_t bar) {
        asm volatile("cp.async.bulk.shared::cluster.global.mbarrier::complete_tx::bytes [%0], [%1], %2, [%3];" ::"r"(dst), "l"(src), "r"(n), "r"(bar) : "memory");
    };
    auto put_h = [&](int ch) {
        const uint32_t dk = (tid & 127) ? 0 : *reinterpret_cast<const volatile uint32_t*>(sm + CV_BAR + 160 + 16 * wg + 2 * ch);
        uint4 v[4];
#pragma unroll
        for (int i = 0; i < 4; i++) v[i] = lds128(sbase + ch * 4096 + i * 2048 + (tid & 127) * 16);
        v[0].x = pack2(lo2f(v[0].x) + lo2f(dk), hi2f(v[0].x));
        v[2].x = pack2(lo2f(v[2].x) + hi2f(dk), hi2f(v[2].x));
#pragma unroll
        for (int i = 0; i < 4; i++)
            sts128(sb + CV_H + (2 * ch + (i & 2) + (tid & 1)) * CV_HPL + (127 - ((tid & 127) >> 1)) * 16 - (i & 1) * 1024, v[i].x, v[i].y, v[i].z, v[i].w);
    };
    int bi, bj, m0, tb;
    uint32_t ep;
    auto get_role = [&]() {
        mbar_wait(b_role, 0);
        int role;
        asm volatile("ld.shared.v2.b32 {%0,%1}, [%2];" : "=r"(role), "=r"(ep) : "r"(s_bar + 248) : "memory");
        bi = (role >> 3) * 2 + rank; bj = role & 7; m0 = bi * BM; tb = (role >> 3) * 2048 + rank * 128;
        return role < 64;
    };

    if (warp >= 8) {
        asm volatile("setmaxnreg.dec.sync.aligned.u32 88;");
        cluster_arrive_relaxed();
        if (!cv) cluster_wait(); else {
            const int bt = tid - 256, g = lane >> 2, t = lane & 3;
            if (bt < 16) sts128(row_at((bt & 7) - 8) + (bt >> 3) * 4096, 0, 0, 0, 0);
#pragma unroll
            for (int i = 0; i < 4; i++)
                cp16(row_at(bt) + i * 4096, (i & 1 ? vp : kp) + (size_t)(bt + (i >> 1) * 128) * D_ + d0);
            DBG_S(16 + (3));
            uint2 wa;
            asm volatile("ld.global.nc.v2.b32 {%0,%1}, [%2];" : "=r"(wa.x), "=r"(wa.y) : "l"(shk + (d0 + g) * 4));
            const int mi = lane >> 3, r0 = 32 * w + 8 * ((lane >> 1) & 3) - (lane & 1);
            const uint32_t ka0 = row_at(r0 + 2 * mi - 3), ka1 = row_at(r0 + 2 * (mi & 1) + 5) + (mi >> 1) * 8192;
            const uint32_t va0 = row_at(r0 + 2 * mi + 1) + 4096, va1 = row_at(r0 - 1) + 4096 + (mi & 1) * 8192;
            const uint32_t qd = sb + g * CV_QG + (32 * w + 8 * t) * 8, qd0 = qd + (t & 2) * 16, qd1 = qd + (~t & 2) * 16;
            const uint32_t w0 = __byte_perm(wa.x, 0, 0x1010), w1 = __byte_perm(wa.x, 0, 0x3232), w2 = __byte_perm(wa.y, 0, 0x1010), w3 = __byte_perm(wa.y, 0, 0x3232);
            cluster_wait();
            DBG_S(16 + (5));
            asm volatile("cp.async.wait_all;" ::: "memory");
            named_bar_sync(7, 128);
            DBG_S(16 + (1));
            struct KV { uint32_t k[2][6], v[2][5]; };
            auto get = [&](KV& x, uint32_t so) {
                ldsm4t(x.k[0][0], x.k[0][1], x.k[0][2], x.k[0][3], ka0 + so);
                ldsm4t(x.k[0][4], x.k[0][5], x.k[1][4], x.k[1][5], ka1 + so);
                ldsm4t(x.k[1][0], x.k[1][1], x.k[1][2], x.k[1][3], ka0 + so + 8192);
                asm volatile("ldmatrix.sync.aligned.m8n8.x2.trans.shared.b16 {%0,%1}, [%2];" : "=r"(x.v[0][0]), "=r"(x.v[1][0]) : "r"(va1 + so));
                ldsm4t(x.v[0][1], x.v[0][2], x.v[0][3], x.v[0][4], va0 + so);
                ldsm4t(x.v[1][1], x.v[1][2], x.v[1][3], x.v[1][4], va0 + so + 8192);
            };
            auto build = [&](int c, const KV& x, KV& nx) {
                const uint32_t so = c * CV_SL;
                DBG_F(1);
                uint32_t early;
                asm volatile("{\n.reg .pred p;\nmbarrier.test_wait.parity.shared::cta.b64 p, [%1], 0;\nvote.sync.all.pred p, p, -1;\nselp.u32 %0, 1, 0, p;\n}"
                             : "=r"(early) : "r"(b_full + 8 * (c < 7 ? c + 1 : c)) : "memory");
                if (early) get(nx, so + CV_SL);
                DBG_F(2);
                uint32_t p[8][2];
#pragma unroll
                for (int sg = 0; sg < 2; sg++) {
                    uint32_t u[5], ke[6];
#pragma unroll
                    for (int i = 0; i < 6; i++) ke[i] = __byte_perm(x.k[sg][i], x.k[sg][i ? i - 1 : 0], 0x5432);
#pragma unroll
                    for (int i = 0; i < 5; i++) {
                        u[i] = bmul2(bfma2(x.k[sg][i + 1], w0, bfma2(ke[i + 1], w1, bfma2(x.k[sg][i], w2, bmul2(ke[i], w3)))), x.v[sg][i]);
                        if (i) { p[2 * i - 1][sg] = u[i]; p[2 * i - 2][sg] = __byte_perm(u[i], u[i - 1], 0x5432); }
                    }
                }
                DBG_F(3);
#pragma unroll
                for (int j = 0; j < 4; j++) sts128((j & 2 ? qd1 : qd0) + so + 16 * (j & 1), p[2 * j][0], p[2 * j][1], p[2 * j + 1][0], p[2 * j + 1][1]);
                __syncwarp();
                DBG_F(4);
                if (lane == 0) {
                    mbar_arrive(b_rdy + 8 * c);
                    if (c == w) {
                        if (c < 3) load_kv(c + 5);
                        else { bulk(sbase + 16384, ssk + (size_t)(d0 + 4) * S_, 16384, b_h + 16); bulk(b_full + 192, ssD + d0, 16, b_h + 16); }
                    }
                    if (c == w + 4 && (CV_PF >> w & 1)) {
                        const uint32_t n = w == 0 ? 32768 : w == 3 ? 57344 : 16384;
                        const char* src = reinterpret_cast<const char*>(w == 0 ? xq : w == 1 ? w1p : w == 2 ? w2p : w3p) + (size_t)blockIdx.x * n;
                        asm volatile("cp.async.bulk.prefetch.L2.global [%0], %1;" ::"l"(src), "r"(n) : "memory");
                    }
                }
                DBG_F(5);
                named_bar_sync(7, 128);
                DBG_F(6);
                DBG_S(16 + (c == 0 ? 4 : 5 + c));
                if (!early) { mbar_wait(b_full + 8 * c + 8, 0); get(nx, so + CV_SL); }
                DBG_F(7);
            };
            KV x0, x1;
            get(x0, 0);
#pragma unroll 1
            for (int c = 0; c < 8; c += 2) { build(c, x0, x1); build(c + 1, x1, x0); }
            mbar_wait(b_h + 16, 0);
            put_h(4); put_h(6);
            fence_async_smem();
            __syncwarp();
            if (lane == 0) mbar_arrive(b_full);
            named_bar_sync(7, 128);
            DBG_S(16 + (13));
        }
    } else {
        if (elect_one()) {
            mbar_init(b_full + 8 * warp, warp ? 1 : 4);
            mbar_init(b_rdy + 8 * warp, 4);
            if (warp) mbar_expect_tx(b_full + 8 * warp, 16384);
            if (w == 0 && cv) {
                mbar_init(b_h + 8 * wg, 1);
                mbar_expect_tx(b_h + 8 * wg, 8192 + 16);
                fence_async_smem();
                bulk(sbase + wg * 8192, ssk + (size_t)(d0 + 2 * wg) * S_, 8192, b_h + 8 * wg);
                bulk(b_full + 160 + 16 * wg, ssD + d0, 16, b_h + 8 * wg);
            }
            mbar_init(s_bar + 8 * warp, 1);
            mbar_init(s_bar + 64 + 8 * warp, 4);
            mbar_init(s_bar + 128 + 8 * warp, warp < 2 ? 4 << warp : warp == 6 ? 2 : 1);
            if (warp > 4) mbar_init(s_bar + 160 + 8 * warp, 8);
            if (warp == 0) mbar_arrive(f5);
            if (warp == 7) mbar_expect_tx(b_role, 8);
            if (warp == 1) { mbar_init(b_h + 16, 1); mbar_expect_tx(b_h + 16, 16384 + 16); }
            if (w == 2) sts128(s_bar + 224 + 16 * wg, 0, 0, 0, 0);
            asm volatile("fence.mbarrier_init.release.cluster;" ::: "memory");
            if (warp == 2) { prefetch_tmap(&tm.k); prefetch_tmap(&tm.v); }
        }
        __syncwarp();
        DBG_W(1);
        cluster_arrive_relaxed();
        asm volatile("setmaxnreg.inc.sync.aligned.u32 208;");
        DBG_W(2);
        const int zi = (tid & 127) - 32;
        if (zi >= 0 && zi < 48) sts128(sb + CV_H + (4 * wg + (zi / 6 & 3) + (zi / 24) * 8) * CV_HPL + 2048 + (zi % 6) * 16, 0, 0, 0, 0);
        DBG_W(3);
        cluster_wait();
        DBG_W(5);
        if (cv) {
            if (tid == 32) {
#pragma unroll 1
                for (int c = 1; c < 5; c++) load_kv(c);
                prefetch_tmap(&tm.y);
            }
            __syncwarp();
            DBG_W(6);
            const int g = lane >> 2, t = lane & 3;
            const int x0 = 32 + 8 * w + g - 2 * t;
            CvAddr p;
            p.rdy = b_rdy;
            p.bar = 1 + wg;
            p.xr = sbase + (warp ^ 2) * 2048 + lane * 16;
            p.xw = sbase + warp * 2048 + (g * 4 + ((t - (w >> 1)) & 3)) * 16;
            p.wrap = t == 0 && w >= 2;
            mbar_wait(b_h + 8 * wg, 0);
            DBG_W(4);
            put_h(2 * wg);
            fence_async_smem();
            named_bar_sync(1 + wg, 128);
            float acc[2][64];
            zero_acc(acc[0]); zero_acc(acc[1]);
#pragma unroll 1
            for (int round = 0; round < 2; round++) {
                const int ch = round * 4 + 2 * wg;
                uint32_t a[CV_NA][4], tv[2][8];
#pragma unroll
                for (int e = 0; e < 2; e++) {
                    const int x = x0 - 8 * e;
                    p.neg[e] = x < 32;
                    p.pa[e] = sb + ch * CV_QG + 8 * (x ^ (x >> 2 & 4));
                    p.p0[2 * e] = p.pa[e] + (x < 32 ? 768 + 4 - CV_SL : -256);
                    p.p0[2 * e + 1] = p.pa[e] + (x < 32 ? 768 : -256 + 4);
                }
                p.db = (((sb + CV_H + ch * 2 * CV_HPL) & 0x3FFFF) >> 4) | ((CV_HPL / 16) << 16);
                if (round) mbar_wait(b_full, 0);
                DBG_S(7 + 3 * round);
                cv_steps<0>(acc, a, tv, p);
                DBG_S(8 + 3 * round);
                const int r128 = 4 * (lane >> 3) + 2 * (lane & 1) + ((~lane >> 2) & 1);
#pragma unroll
                for (int i = 0; i < 2; i++) {
                    const uint32_t ta = sb + ((ch + i + 1) & 7) * CV_SL + 12288 + r128 * 128 + ((((~lane & 2) * 2 + w) ^ (r128 & 7)) << 4);
                    stsm4t(ta, tv[i][0], tv[i][1], tv[i][2], tv[i][3]);
                    stsm4t(ta + 2048, tv[i][4], tv[i][5], tv[i][6], tv[i][7]);
                }
                fence_async_smem();
                named_bar_sync(1 + wg, 128);
                if ((tid & 127) < 2) {
                    const int d = d0 + ch + (tid & 1);
                    asm volatile("cp.async.bulk.tensor.4d.global.shared::cta.bulk_group [%0, {%2, %3, %4, %2}], [%1];"
                                 ::"l"((uint64_t)&tm.y), "r"(sb + ((ch + (tid & 1) + 1) & 7) * CV_SL + 12288), "r"(0), "r"(4 * (d >> 8)), "r"(d & 255) : "memory");
                    asm volatile("cp.async.bulk.commit_group;" ::: "memory");
                }
                __syncwarp();
                DBG_S(9 + 3 * round);
            }
        }
    }
    int warp2 = warp;
    asm volatile("" : "+r"(warp2));
    if (warp2 >= 8) {
        asm volatile("setmaxnreg.dec.sync.aligned.u32 72;");
        if (warp == 8) { if (elect_one()) {
            if (rank == 0) {
                uint32_t smid;
                asm volatile("mov.u32 %0, %%smid;" : "=r"(smid));
                const int t = smid >> 1;
                int team = t < 32 ? t & 7 : t < 60 ? 1 + (t - 32) % 7 : t < 62 ? t - 54 : 0;
                const unsigned long long arr = atomicAdd(reinterpret_cast<unsigned long long*>(g_ticket + 16 * FL_PITCH), 1ull);
                const uint32_t e1 = (uint32_t)(arr / NCL) + 1;
                unsigned int* tk = g_ticket + (e1 & 1) * 8 * FL_PITCH;
                int slot = atomicAdd(tk + team * FL_PITCH, 1u);
                atomicAdd(g_ticket + 17 * FL_PITCH, 1u);
                if (blockIdx.x < 16) g_ticket[((~e1 & 1) * 8 + (blockIdx.x >> 1)) * FL_PITCH] = 0;
                if (slot >= 8) {
                    const long long t0 = clock64();
                    while ((int)(*(volatile unsigned int*)(g_ticket + 17 * FL_PITCH) - e1 * NCL) < 0 && clock64() - t0 < 100000) {}
                    for (team = 0; team < 8; team++)
                        if ((slot = atomicAdd(tk + team * FL_PITCH, 1u)) < 8) break;
                }
#pragma unroll
                for (int i = 0; i < 2; i++)
                    asm volatile("st.async.weak.shared::cluster.mbarrier::complete_tx::bytes.v2.b32 [%0], {%1, %2}, [%3];"
                                 ::"r"(mapa_u32(s_bar + 248, i)), "r"(team * 8 + slot), "r"(e1), "r"(mapa_u32(b_role, i)) : "memory");
            }
            if (get_role()) {
            TM(2);
            mbar_expect_tx(b_rfull, 32768);
            tma_load_2d(sbase + 16384, &tm.q, b_rfull, bj * 128, m0);
            tma_load_2d(sb + 8 * CV_SL, &tm.q, b_rfull, bj * 128 + 64, m0);
            int s5 = 0, s4 = 0;
            uint32_t p5 = 0, p4 = 1;
            auto putB = [&](const CUtensorMap* tB, int kc, uint32_t bytes) {
                const uint32_t full = f5 + 8 * s5;
                mbar_wait(full + 64, (p5 >> s5) & 1);
                mbar_expect_tx(full, bytes);
                tma_load_2d_mc(s_r + 16384 + rank * 8192 + s5 * R5_STAGE, tB, full, bj * 128 + rank * 64, kc);
                p5 ^= 1u << s5;
            };
            auto putA = [&](int c, int r) {
                tma_load_2d(s_r + s5 * R5_STAGE, &tm.act, f5 + 8 * s5, c, r);
                if (++s5 == R5_N) s5 = 0;
            };
            prefetch_tmap(&tm.act); prefetch_tmap(&tm.w1); prefetch_tmap(&tm.w2); prefetch_tmap(&tm.w3); prefetch_tmap(&tm.w4);
            auto own_first = [&](int it) {
                const int hf = it >= 9, c = it - 2 - 7 * hf;
                return (it < 2 ? 2 * bj + it : 2 * (c + (c >= bj)) + hf) * BK;
            };
            const unsigned int n8 = 8 * ep, nh = NH16 ? ((bi == 0 || bi == 15) ? 12 * ep : 2 * n8) : (bi == 0 || bi == 15) ? 2 * n8 : 3 * n8;
#pragma unroll 1
            for (int layer = 0; layer < 2; layer++) {
                s5 = 2;
#pragma unroll 1
                for (int kk = -(layer | Y_FIRST); kk < 5 - (layer | Y_FIRST); kk++) {
                    if (kk & 4) {
                        if (layer == 0) { TM(1); wait_flag(flag_ptr(0, FL_CS, 8 + bj), 8 * n8); TM(4); fence_proxy_async(); }
                        mbar_wait(e5 + 8, (p5 >> 1) & 1);
                        mbar_expect_tx(f5 + 8, 32768);
                        tma_load_2d(s_r + R5_STAGE, &tm.act, f5 + 8, (bj >> 1) * 256 + rank * 128, R_Y + (tb & ~255) + (bj & 1) * 128);
                        tma_load_2d(s_r + R5_STAGE + 16384, &tm.act, f5 + 8, (bj >> 1) * 256 + rank * 128 + 64, R_Y + (tb & ~255) + (bj & 1) * 128);
                        p5 ^= 2;
                        if (layer == 0) TM(5);
                    } else {
                        if (kk == Y_HOLD && layer == 0) mbar_wait(f5 + 8, 0);
                        putB(&tm.w1, own_first(kk), kk < 2 ? 16384 : R5_STAGE);
                        if (++s5 == R5_N) s5 = 0;
                    }
                }
                s5 = 4;
#pragma unroll 1
                for (int kk = 2; kk < 16; kk++) {
                    const int kc = own_first(kk);
                    if (kk >= 4) putB(&tm.w1, kc, R5_STAGE);
                    if (kk == 2 || kk == 9) {
                        wait_flag(flag_ptr(layer, FL_XA + (kk & 1), bi), n8);
                        if (layer == 0 && kk == 2) TM(14);
                        DP(8 * (FL_XA + (kk & 1)) + 3);
                        fence_proxy_async();
                        DP(8 * (FL_XA + (kk & 1)) + 4);
                    }
                    putA(kc, R_XA + tb);
                }
                mbar_wait(e5 + 24, (p5 >> 3) & 1);
                mbar_arrive(f5 + 24);
                p5 ^= 8;
                s5 = 4;
#pragma unroll 1
                for (int kk = 0; kk < 5; kk++) { putB(&tm.w2, own_first(kk), kk < 2 ? 16384 : R5_STAGE); if (++s5 == R5_N) s5 = 0; }
                s5 = 1;
#pragma unroll 1
                for (int kk = 2; kk < 16; kk++) {
                    const int kc = own_first(kk);
                    if (kk >= 5) putB(&tm.w2, kc, R5_STAGE);
                    if (kk == 2 || kk == 9) {
                        wait_flag(flag_ptr(layer, FL_H + (kk & 1), bi), nh);
                        DP(8 * (FL_H + (kk & 1)) + 3);
                        fence_proxy_async();
                        DP(8 * (FL_H + (kk & 1)) + 4);
                    }
                    putA(kc, R_H + layer * R_HP + m0 + (int)((0x4031u >> (kc >> 6 & 12)) & 7) - 2);
                }
#pragma unroll 1
                for (int it = 0; it < 32; it++) {
                    const int kc = it >= 16 ? (it - 16) * BK : own_first(it);
                    const int nb = it < 16 ? 4 : 3, n0 = bj * 448 + (it < 16 ? 0 : 256);
                    if (it > 0 && it < 4) {
                        const int i = (it - 1) * 3 >> 1;
                        mbar_wait(e5 + 8 * i, (p5 >> i) & 1);
                        mbar_wait(e5 + 8 * i + 8, (p5 >> (i + 1)) & 1);
                    }
                    mbar_wait(e4 + 8 * s4, p4);
                    if (it >= 16 && it < 19) mbar_wait(e4 + 8 * s4 + 8, p4);
                    uint32_t sa = s_r + s4 * (it < 16 ? R4_STAGE : R4B_STAGE), full = f4 + 8 * s4;
                    mbar_expect_tx(full, (it < 2 ? 0 : 16384) + nb * 8192);
#pragma unroll 1
                    for (int j = (it ^ rank) & 1; j < nb; j += 2) tma_load_2d_mc(sa + (it < 16 ? -32768 : 16384) + j * 8192, &tm.w3, full, n0 + j * 64, kc);
                    if (it == 3 || it == 9) {
                        wait_flag(flag_ptr(layer, FL_X1 + (it >> 3), bi), n8);
                        DP(8 * (FL_X1 + (it >> 3)) + 3);
                        fence_proxy_async();
                        DP(8 * (FL_X1 + (it >> 3)) + 4);
                        if (it == 3) tma_load_2d(s_r + 2 * R4_STAGE, &tm.act, f4 + 16, own_first(2), R_X1 + tb);
                    }
                    if (it >= 3) tma_load_2d(sa, &tm.act, full, kc, R_X1 + tb);
                    if (++s4 == R4_N) { s4 = 0; p4 ^= 1; }
                }
                wait_flag(flag_ptr(layer, FL_H2, bi), n8);
                fence_proxy_async();
                s5 = 0;
#pragma unroll 1
                for (int j = 0; j < 7; j++) {
                    if (j > 0 && (j & 1) == 0) {
                        mbar_wait(b_h2 + 4 * j, layer);
                        fence_proxy_async();
                    }
                    const int ra = R_H2 + (j >> 1) * 256 + tb;
#pragma unroll 1
                    for (int b = 0; b < 8; b++) {
                        if (j == 0 && b < R4_N) mbar_wait(e4 + 8 * b, p4);
                        putB(&tm.w4, (7 * b + j) * BK, R5_STAGE);
                        putA(((j & 1) * 8 + b) * BK, ra);
                    }
                }
            }
        } } } else {
            auto colsum = [&](bool is1, int bi, int bj) {
                const int pitch = is1 ? D_ : F_, c = is1 ? bj * 128 + (lane & 15) * 8 : bj * 448 + min((warp & 2) * 128 + lane * 8, 440);
                const bf16* p = (is1 ? w1p : w3p) + ((bi * 64 + (is1 ? (lane >> 4) * 32 : 0)) * pitch + c);
                float a[8];
#pragma unroll
                for (int i = 0; i < 8; i++) a[i] = 0.f;
#pragma unroll 1
                for (int r0 = is1 ? 32 : 0; r0 < 64; r0 += 8) {
                    uint4 v[8];
#pragma unroll
                    for (int r = 0; r < 8; r++, p += pitch) v[r] = __ldg(reinterpret_cast<const uint4*>(p));
#pragma unroll
                    for (int r = 0; r < 8; r++) {
                        a[0] += lo2f(v[r].x); a[1] += hi2f(v[r].x); a[2] += lo2f(v[r].y); a[3] += hi2f(v[r].y);
                        a[4] += lo2f(v[r].z); a[5] += hi2f(v[r].z); a[6] += lo2f(v[r].w); a[7] += hi2f(v[r].w);
                    }
                }
                if (is1) {
#pragma unroll
                    for (int i = 0; i < 8; i++) a[i] += __shfl_xor_sync(0xffffffffu, a[i], 16);
                }
                float4* dst = reinterpret_cast<float4*>(g_cpart + bi * (F_ + D_) + (is1 ? F_ : 0) + c);
                dst[0] = make_float4(a[0], a[1], a[2], a[3]);
                dst[1] = make_float4(a[4], a[5], a[6], a[7]);
                asm volatile("fence.release.gpu;" ::: "memory");
                __syncwarp();
                if (lane == 0) asm volatile("red.relaxed.gpu.global.add.u32 [%0], 1;" ::"l"(flag_ptr(!is1, FL_CS, bj)) : "memory");
            };
            if (cv && warp == 10) colsum(true, blockIdx.x >> 3, blockIdx.x & 7);
            float4 keep[2];
            const bool on = get_role();
            if (on && warp == 11) {
                uint4* ps = reinterpret_cast<uint4*>(g_stats + (bi * 8 + bj) * 128) + lane;
                ps[0] = ps[32] = make_uint4(0, 0, 0, 0);
                asm volatile("fence.acq_rel.gpu;" ::: "memory");
                __syncwarp();
                if (lane == 0) mbar_arrive(b_rfull);
            }
#pragma unroll 1
            for (int layer = on ? 0 : 2; layer < 2; layer++) {
                if (warp == 10) {
#pragma unroll 1
                    for (int kind = 0; kind < 6; kind += 2) {
                        const uint32_t src = kind == FL_H ? s_stg + 1024 : s_epi, sd = kind == FL_H ? OFF_EPI : 16384;
                        const int dn = bj & 2 ? 1 : -1;
                        uint4* gh = g_halo + (layer * 144 + 8 + bi * 8 + bj) * 64 + lane;
                        const int r = kind == FL_H ? R_H + layer * R_HP + m0 : (kind == FL_XA ? R_XA : R_X1) + tb;
#pragma unroll 1
                        for (int hf = 0; hf < 2; hf++) {
                            named_bar_sync(5 + hf, 288);
                            if (lane == 0) {
                                if (FMOVE) fence_async_smem();
                                DP(8 * (kind + hf));
                                tma_store_2d(&tm.act, src + hf * sd, bj * 128 + hf * 64, r);
                                asm volatile("cp.async.bulk.commit_group;" ::: "memory");
                            }
                            __syncwarp();
                            if (kind == FL_H && !SENDC) {
                                uint32_t a, b;
                                lds64(a, b, src + hf * sd + (63 - 63 * dn) * 128 + 8 * lane);
                                asm volatile("{\n.reg .b64 u, v;\nmov.b64 u, {%1, %3};\nmov.b64 v, {%2, %3};\nst.relaxed.gpu.global.v2.b64 [%0], {u, v};\n}"
                                             ::"l"(gh - dn * 512 + hf * 32), "r"(a), "r"(b), "r"(ep) : "memory");
                            }
                            if (kind + hf == FL_H + 1) {
                                uint4 v[2] = {};
                                if (HDELAY) __nanosleep(HDELAY);
#pragma unroll 1
                                for (int n = (bi + dn) & 16 ? 1 << 20 : 0; n < (1 << 20); n++) {
#pragma unroll
                                    for (int i = 0; i < 2; i++)
                                        asm volatile("{\n.reg .b64 u, v;\nld.relaxed.gpu.global.v2.b64 {u, v}, [%4];\nmov.b64 {%0, %1}, u;\nmov.b64 {%2, %3}, v;\n}"
                                                     : "=r"(v[i].x), "=r"(v[i].y), "=r"(v[i].z), "=r"(v[i].w) : "l"(gh + 32 * i) : "memory");
                                    if (v[0].y == ep && v[0].w == ep && v[1].y == ep && v[1].w == ep) break;
                                }
#pragma unroll
                                for (int i = 0; i < 2; i++)
                                    asm volatile("st.shared.v2.b32 [%0], {%1, %2};" ::"r"(src + i * OFF_EPI + (63 + 65 * dn) * 128 + 8 * lane), "r"(v[i].x), "r"(v[i].z) : "memory");
                                fence_async_smem();
                                __syncwarp();
                                DP(8 * FL_H + 5);
                                named_bar_arrive(14, 160);
                            }
                            if (lane == 0) {
                                asm volatile("cp.async.bulk.wait_group 0;" ::: "memory");
                                DP(8 * (kind + hf) + 1);
                                DP(8 * (kind + hf) + 2);
                                unsigned int* fp = flag_ptr(layer, kind + hf, bi);
                                asm volatile("red.relaxed.gpu.global.add.u32 [%0], 1;" ::"l"(fp) : "memory");
                                if (kind == FL_H) {
                                    if (bi > 0 && (!NH16 || dn > 0)) asm volatile("red.relaxed.gpu.global.add.u32 [%0], 1;" ::"l"(fp - FL_PITCH) : "memory");
                                    if (bi < 15 && (!NH16 || dn < 0)) asm volatile("red.relaxed.gpu.global.add.u32 [%0], 1;" ::"l"(fp + FL_PITCH) : "memory");
                                }
                            }
                            __syncwarp();
                        }
                    }
                } else {
                    uint32_t* rs = reinterpret_cast<uint32_t*>(sgen + OFF_RS);
                    float* cs = reinterpret_cast<float*>(sgen + OFF_CS);
#pragma unroll 1
                    for (int which = 0; which < 2; which++) {
                        if (layer < which) {
                            if (warp == 11 && lane == 0) {
                                wait_flag(flag_ptr(0, FL_XA + W3_AT, bi), 8 * ep);
                                asm volatile("cp.async.bulk.prefetch.L2.global [%0], %1;" ::"l"(w3p + (bi * 8 + bj) * 28672), "r"(57344) : "memory");
                            }
                            __syncwarp();
                            colsum(false, bi, bj);
                        }
                        if (warp == 11) continue;
                        if (layer == 0) {
                            if (lane == 0) wait_flag(flag_ptr(which, FL_CS, bj), (16 << which) * ep);
                            __syncwarp();
#pragma unroll 1
                            for (int c = (which ? 384 : 768) + lane * 4; c < 896; c += 128) {
                                const float* cp = g_cpart + (which ? bj * 448 + min(c & 511, 444) : F_ + bj * 128 + lane * 4);
                                float4 a = make_float4(0.f, 0.f, 0.f, 0.f);
#pragma unroll
                                for (int r0 = 0; r0 < 16; r0 += 8) {
                                    float4 v[8];
#pragma unroll
                                    for (int r = 0; r < 8; r++) v[r] = __ldcg(reinterpret_cast<const float4*>(cp + (r0 + r) * (F_ + D_)));
#pragma unroll
                                    for (int r = 0; r < 8; r++) { a.x += v[r].x; a.y += v[r].y; a.z += v[r].z; a.w += v[r].w; }
                                }
                                if (c < 768) *reinterpret_cast<float4*>(cs + min(c & 511, 444)) = a;
                                keep[0] = a;
                            }
                        }
                        if (lane == 0 && (layer | which)) wait_flag(flag_ptr(layer, which == 0 ? FL_XA : FL_X1, bi), 8 * ep);
                        __syncwarp();
                        *reinterpret_cast<float4*>(cs + 256 + lane * 4) = keep[0];
                        { const float4 k0 = keep[0]; keep[0] = keep[1]; keep[1] = k0; }
#pragma unroll 1
                        for (int i = 0; i < 4; i++) {
                            const int r = i * 32 + lane;
                            float mean, var;
                            row_stats(g_stats + (1 + which) * S_ * 8 + bi * 1024 + r, ~layer << 31, mean, var);
                            const uint32_t c0 = pack2(mean, fsqrt(bfr(bfr(var) + 1e-5f)));
                            if (lane < 19 && (layer | which | i) == 0) asm volatile("mbarrier.inval.shared::cta.b64 [%0];" ::"r"(b_full + 8 * lane) : "memory");
                            __syncwarp();
                            rs[r] = c0;
                            const float rd = frcp(hi2f(c0));
                            rs[128 + r] = pack2((mean - lo2f(c0)) * rd, fsqrt(bfr(bfr(var * rd * rd) + 1e-5f)));
                        }
                        __syncwarp();
                        named_bar_arrive(3, 160);
                        named_bar_arrive(11, 160);
                    }
                }
                const uint32_t s_cnt = s_bar + 224;
                auto ticket = [&](uint32_t a) {
                    uint32_t v = 0;
                    if (lane == 0) asm volatile("atom.acq_rel.cta.shared.add.u32 %0, [%1], 1;" : "=r"(v) : "r"(a) : "memory");
                    return v;
                };
                auto next = [&]() {
                    uint32_t v = 0;
                    if (lane == 0) asm volatile("atom.relaxed.cta.shared.add.u32 %0, [%1], 1;" : "=r"(v) : "r"(s_cnt + 16 + 4 * layer) : "memory");
                    return v;
                };
                mbar_wait(b_stg, layer);
                int u = __shfl_sync(0xffffffffu, next(), 0), step = 0;
#pragma unroll 1
                while (true) {
#pragma unroll 1
                    for (; step < 5 && u >= (int)((0x3830201810ull >> (8 * step)) & 255); step++) {
                        if (step == 1) { named_bar_arrive(4, 224); named_bar_arrive(12, 224); continue; }
                        const int part = step ? step - 1 : 0;
                        __syncwarp();
                        if (ticket(s_cnt + 4 * part) == 3 * layer + 2) {
                            asm volatile("fence.release.gpu;" ::: "memory");
                            unsigned int* fp = flag_ptr(layer, FL_H2 + part, bi);
                            asm volatile("red.relaxed.gpu.global.add.u32 [%0], 1;" ::"l"(fp) : "memory");
                            if (part > 0) { wait_flag(fp, 8 * ep); mbar_arrive(b_h2 + 8 * part); }
                        }
                        __syncwarp();
                    }
                    if (u >= 56) break;
                    const uint32_t un = next();
                    const int job = u >> 3, r = (u & 7) * 16 + (lane >> 3);
                    if (job >= 4) mbar_wait(s_bar + 168 + 8 * job, layer);
                    const uint32_t sp = sbase + ((job & 2) ? OFF_STG5 : OFF_EPI) + r * 256 + (job & 1) * 128;
                    bf16* gp = act + (size_t)(R_H2 + (job >> 1) * 256 + tb + r) * D_ + ((job & 1) * 8 + bj) * 64 + (lane & 7) * 8;
                    uint4 v[4];
#pragma unroll
                    for (int e = 0; e < 4; e++) v[e] = lds128(sp + e * 1024 + (((lane & 7) ^ ((r + 4 * e) & 7)) << 4));
#pragma unroll
                    for (int e = 0; e < 4; e++) stg128(gp + 4 * e * D_, gelu8h(v[e]));
                    u = __shfl_sync(0xffffffffu, un, 0);
                }
                if (layer == 0 && warp == 11) {
                    const char* ps = reinterpret_cast<const char*>(g_stats + bi * 1024) + lane * 128;
                    const char* py = reinterpret_cast<const char*>(act + (size_t)(R_Y + (tb & ~255) + (bj & 1) * 128 + (lane >> 1)) * D_ + (bj >> 1) * 256 + rank * 128) + (lane & 1) * 128;
#pragma unroll 1
                    for (int i = 0; i < 8; i++) {
                        asm volatile("prefetch.global.L2 [%0];" ::"l"(py + (size_t)i * 16 * D_ * 2) : "memory");
                        if (i >= 6) asm volatile("prefetch.global.L2 [%0];" ::"l"(ps + (i & 1) * 4096) : "memory");
                        __nanosleep(400);
                    }
                }
            }
        }
        __syncwarp();
        asm volatile("barrier.cluster.arrive.relaxed.aligned;\nbarrier.cluster.wait.acquire.aligned; // helpers" ::: "memory");
    } else {
        DT_DECL;
        DT(0);
        auto put_y = [&]() {
            if ((tid & 127) < 2 && cv) {
                asm volatile("cp.async.bulk.wait_group 0;" ::: "memory");
                asm volatile("red.relaxed.gpu.global.add.u32 [%0], 1;" ::"l"(flag_ptr(0, FL_CS, 8 + (blockIdx.x >> 4))) : "memory");
            }
            __syncwarp();
        };
        put_y();
        DT(24);
        asm volatile("setmaxnreg.inc.sync.aligned.u32 216;");
        if (get_role()) {
        const bool rel_on = (tid & 95) == 0;
        const uint32_t rel5 = mapa_u32(e5, (warp & 1) ^ rank), rel4 = rel5 + (e4 - e5);
        const uint32_t da0 = desc_a(s_r + wg * 8192), db0 = desc_b(s_r + BM * BK * 2), dae = da0 + (OFF_EPI - OFF_R) / 16, db4 = db0 - 49152 / 16;
        auto skip5 = [&](RingState& rs) {
            if (rel_on) mbar_arrive_cluster(rel5 + 8 * rs.st);
            rs.st++;
        };
        const int t = lane & 3;
        const int row = warp * 16 + (lane >> 2);
        const uint32_t st_w = (uint32_t)((warp * 16 + ((lane >> 3) & 1) * 8 + (lane & 7)) * 256 + (((lane >> 4) ^ (lane & 7)) << 4));
        const uint32_t fr = (uint32_t)((warp * 16 + ((lane >> 3) & 1) * 8 + (lane & 7)) * 128 + (((lane >> 4) ^ (lane & 7)) << 4));
        auto copy_out = [&](bf16* dst, uint32_t src) {
            const int r = warp * 16 + (lane >> 4);
            bf16* ox = dst + (size_t)(m0 + r) * D_ + bj * 128 + (lane & 15) * 8;
            const uint32_t ra = src + ((lane & 15) >> 3) * 16384 + r * 128;
            uint4 v[8];
#pragma unroll
            for (int it = 0; it < 8; it++) v[it] = lds128(ra + it * 256 + (((lane & 7) ^ ((2 * it + (lane >> 4)) & 7)) << 4));
#pragma unroll
            for (int it = 0; it < 8; it++) *reinterpret_cast<uint4*>(ox + (size_t)it * 2 * D_) = v[it];
        };
        auto put_stats = [&](const uint32_t (&w)[32], int which, int layer) {
            float c[6][4];
#pragma unroll
            for (int e = 0; e < 32; e++) {
                hmma8(c[e & 3], w[e & ~1], w[e | 1], w[e], e < 4);
                if ((e & 3) == 0) hmma(c[4 + (e >> 2 & 1)], w[e], w[e + 1], w[e + 2], w[e + 3], 0x3f803f80u, 0x3f803f80u, e < 8);
            }
            if (t == lane >> 3) {
#pragma unroll
                for (int e = 0; e < 2; e++) {
                    const float q1 = lane & 4 ? c[e][2 * e + 1] + c[e + 2][2 * e + 1] : c[e][2 * e] + c[e + 2][2 * e], s1 = c[4][2 * e] + c[5][2 * e], mu = s1 * (1.0f / 128);
                    asm volatile("{\n.reg .b64 t;\nmov.b64 t, {%1, %2};\nst.relaxed.gpu.global.b64 [%0], t;\n}"
                                 ::"l"(g_stats + which * S_ * 8 + (bi * 8 + bj) * 128 + row + 8 * e), "f"(mu), "r"(__float_as_uint(fmaxf(q1 - s1 * mu, 0.f)) | ~layer << 31) : "memory");
                }
            }
        };
        auto split = [](float r) { const float h = bfr(r); return pack2(h, r - h); };
        auto norm2 = [](uint32_t x, uint32_t m, uint32_t r) {
            const uint32_t d = bsub2(x, m);
            return bfma2(d, __byte_perm(r, 0, 0x1010), bmul2(d, __byte_perm(r, 0, 0x3232)));
        };
        const float* csp = reinterpret_cast<const float*>(sgen + OFF_CS) + 2 * t;
        float mrow[2], rrow[2];
        const uint32_t* rsp = reinterpret_cast<const uint32_t*>(sgen + OFF_RS) + row;
        auto row_consts = [&](bool twice) {
#pragma unroll
            for (int e = 0; e < 2; e++) {
                const uint32_t q0 = rsp[8 * e], q1 = rsp[128 + 8 * e];
                mrow[e] = twice ? fmaf(lo2f(q1), hi2f(q0), lo2f(q0)) : lo2f(q0);
                rrow[e] = 0.5f * frcp(twice ? hi2f(q0) * hi2f(q1) : hi2f(q0));
            }
        };
        auto keep_consts = [&](float2 (&cs)[8]) {
#pragma unroll
            for (int e = 0; e < 8; e++) asm volatile("" : "+f"(cs[e].x), "+f"(cs[e].y));
            asm volatile("" : "+f"(mrow[0]), "+f"(mrow[1]), "+f"(rrow[0]), "+f"(rrow[1]));
        };
        auto stage = [&](const float* acc, uint32_t dst, int j0, float2 (&cs)[8], const float* cnext) {
            float2 cn[8];
#pragma unroll
            for (int e = 0; e < 8; e++) cn[e] = *reinterpret_cast<const float2*>(cnext + 8 * e);
#pragma unroll
            for (int j = 0; j < 8; j += 2) {
                uint32_t w[4];
#pragma unroll
                for (int e = 0; e < 2; e++) {
                    const float* a = acc + 4 * (j + e);
                    w[2 * e] = pack2(fmaf(-mrow[0], cs[j + e].x, a[0]) * rrow[0], fmaf(-mrow[0], cs[j + e].y, a[1]) * rrow[0]);
                    w[2 * e + 1] = pack2(fmaf(-mrow[1], cs[j + e].x, a[2]) * rrow[1], fmaf(-mrow[1], cs[j + e].y, a[3]) * rrow[1]);
                }
                stsm4((dst + st_w) ^ (((j0 + j) & 15) << 4), w[0], w[1], w[2], w[3]);
            }
#pragma unroll
            for (int e = 0; e < 8; e++) cs[e] = cn[e];
        };
        RingState r5{1, 0}, r4{0, 0};
        DT(1);
        uint32_t x[32];
        mbar_wait(b_rfull, 0);
#pragma unroll
        for (int jp = 0; jp < 8; jp++) ldsm4(x[4 * jp], x[4 * jp + 1], x[4 * jp + 2], x[4 * jp + 3], sbase + 16384 + (fr ^ ((jp & 3) << 5)) + (jp >> 2) * (16384 + 8 * CV_SL));
#pragma unroll
        for (int e = 0; e < 32; e++) asm volatile("" : "+r"(x[e]));
        named_bar_sync(9 + wg, 128);
        if ((tid & 95) < R5_N) mbar_arrive_cluster(rel5 + 8 * lane);
#pragma unroll 1
        for (int layer = 0; layer < 2; layer++) {
            {
                DT(2 + 24 * layer);
                put_stats(x, 0, layer);
                DT(20 + 24 * layer);
                DT(22 + 24 * layer);
                uint32_t mb[2], rd[2];
                {
                    float mean, var;
                    row_stats(g_stats + bi * 1024 + warp * 16 + (lane & 15), ~layer << 31, mean, var);
                    __syncwarp();
                    const uint32_t r1 = split(frcp(bfr(fsqrt(bfr(bfr(var) + 1e-5f)))));
                    const uint32_t m1 = pack2(mean, mean);
#pragma unroll
                    for (int e = 0; e < 2; e++) { mb[e] = __shfl_sync(0xffffffffu, m1, (lane >> 2) + 8 * e); rd[e] = __shfl_sync(0xffffffffu, r1, (lane >> 2) + 8 * e); }
                }
                DT(21 + 24 * layer);
                mbar_wait(f5 + 8, r5.ph);
                DT(23 + 24 * layer);
                const uint32_t ya = s_r + R5_STAGE + wg * 16384 + ((lane >> 4) * 8 + (lane & 7)) * 128 + ((((warp & 3) * 2 + ((lane >> 3) & 1)) ^ (lane & 7)) << 4);
                uint32_t y[16];
#pragma unroll
                for (int e = 0; e < 32; e++) {
                    if ((e & 15) == 0) {
#pragma unroll
                        for (int jp = 0; jp < 4; jp++) ldsm4t(y[4 * jp], y[4 * jp + 1], y[4 * jp + 2], y[4 * jp + 3], ya + jp * 2048 + e * 512);
                    }
                    x[e] = bfma2(norm2(x[e], mb[e & 1], rd[e & 1]), y[e & 15], x[e]);
                    if ((e & 3) == 3) stsm4(s_epi + (fr ^ (((e >> 2) & 3) << 5)) + (e >> 4) * 16384, x[e - 3], x[e - 2], x[e - 1], x[e]);
                    if ((e & 15) == 15) { if (!FMOVE) fence_async_smem(); named_bar_arrive(5 + (e >> 4), 288); }
                    if (e == 15) mbar_wait(b_role, 0);
                }
                DT(19 + 24 * layer);
                if (FMOVE) fence_async_smem();
                if (PS1_EARLY) put_stats(x, 1, layer);
                named_bar_sync(9 + wg, 128);
                skip5(r5);
                DT(3 + 24 * layer);
            }
            {
                float acc[64];
                kblock<128, R5_N, 0>(acc, dae, db0 + 2 * (R5_STAGE / 16), f5, r5);
                kblock<128, R5_N>(acc, dae + 1024, db0 + 3 * (R5_STAGE / 16), f5, r5);
                if (!PS1_EARLY) put_stats(x, 1, layer);
                wgmma_wait<1>();
                if (rel_on) mbar_arrive_cluster(rel5 + 16);
                float2 cs[8];
                mainloop<128, R5_N, R5_STAGE>(acc, 14, da0, db0, f5, rel5, rel_on, r5, 15 + 24 * layer, [&]() {
                    named_bar_sync(3 + 8 * wg, 160);
                    row_consts(true);
#pragma unroll
                    for (int e = 0; e < 8; e++) cs[e] = *reinterpret_cast<const float2*>(csp + 256 + 8 * e);
                    keep_consts(cs);
                } DT_ARG);
                DT(4 + 24 * layer);
#pragma unroll
                for (int j = 0; j < 16; j += 2) {
                    if (j == 8) {
#pragma unroll
                        for (int e = 0; e < 8; e++) cs[e] = *reinterpret_cast<const float2*>(csp + 256 + 8 * (j + e));
                    }
                    uint32_t w[4];
#pragma unroll
                    for (int e = 0; e < 4; e++) {
                        const float* a = acc + 4 * j + 2 * e;
                        const float2 c = cs[(j & 7) + (e >> 1)];
                        w[e] = gelu2h(pack2(fmaf(-mrow[e & 1], c.x, a[0]) * rrow[e & 1], fmaf(-mrow[e & 1], c.y, a[1]) * rrow[e & 1]));
                    }
                    stsm4(s_stg + 1024 + (fr ^ ((j & 7) << 4)) + (j >> 3) * OFF_EPI, w[0], w[1], w[2], w[3]);
                    if ((j & 7) == 6) { if (!FMOVE) fence_async_smem(); named_bar_arrive(5 + (j >> 3), 288); }
                }
                if (SENDC && warp == (bj & 2 ? 0 : 7)) {
                    __syncwarp();
                    uint32_t a[4];
                    lds64(a[0], a[1], s_stg + 1024 + 18 * 128 * warp + 8 * lane);
                    lds64(a[2], a[3], s_epi + 1024 + 18 * 128 * warp + 8 * lane);
                    uint4* gh = g_halo + (layer * 144 + (warp & 2) * 8 + bi * 8 + bj) * 64 + lane;
#pragma unroll
                    for (int i = 0; i < 2; i++)
                        asm volatile("{\n.reg .b64 u, v;\nmov.b64 u, {%1, %3};\nmov.b64 v, {%2, %3};\nst.relaxed.gpu.global.v2.b64 [%0], {u, v};\n}"
                                     ::"l"(gh + i * 32), "r"(a[2 * i]), "r"(a[2 * i + 1]), "r"(ep) : "memory");
                }
                fence_async_smem();
                if (wg == (bj >> 1 & 1)) named_bar_arrive(13, 256);
                DT(5 + 24 * layer);
            }
            {
                float acc[64];
                uint32_t u[32];
                {
                    uint32_t mb[2], rd[2];
#pragma unroll
                    for (int e = 0; e < 2; e++) { const uint32_t q0 = rsp[8 * e]; mb[e] = (q0 & 0xffffu) * 0x10001u; rd[e] = split(frcp(hi2f(q0))); }
#pragma unroll
                    for (int e = 0; e < 32; e++) {
                        u[e] = norm2(x[e], mb[e & 1], rd[e & 1]);
                        asm volatile("" : "+r"(u[e]));
                    }
                }
                if (!(warp & 2)) mbar_wait(f5 + 24, r5.ph);
                skip5(r5);
                {
                    const bool nb = wg == (bj >> 1 & 1);
                    named_bar_sync(nb ? 14 : 13, nb ? 160 : 256);
                }
                const uint32_t dah = da0 - (OFF_R - 1024 + 256) / 16 + ((0x4031u >> (2 * bj & 12)) & 7) * 8;
                kblock<128, R5_N, 0>(acc, dah, db0 + 4 * (R5_STAGE / 16), f5, r5);
                kblock<128, R5_N>(acc, dah + OFF_EPI / 16, db0, f5, r5);
                wgmma_wait<1>();
                if (rel_on) mbar_arrive_cluster(rel5 + 32);
                mainloop<128, R5_N, R5_STAGE>(acc, 14, da0, db0, f5, rel5, rel_on, r5, 16 + 24 * layer, []() {} DT_ARG);
                DT(6 + 24 * layer);
#pragma unroll
                for (int j = 0; j < 16; j += 2) {
#pragma unroll
                    for (int e = 0; e < 4; e++) u[2 * j + e] = badd2(u[2 * j + e], pack2(acc[4 * j + 2 * e], acc[4 * j + 2 * e + 1]));
                    stsm4(s_epi + (fr ^ ((j & 7) << 4)) + (j >> 3) * 16384, u[2 * j], u[2 * j + 1], u[2 * j + 2], u[2 * j + 3]);
                    if ((j & 7) == 6) { if (!FMOVE) fence_async_smem(); named_bar_arrive(5 + (j >> 3), 288); mbar_wait(b_role, 0); }
                }
                if (FMOVE) fence_async_smem();
#pragma unroll
                for (int e = 0; e < 32; e++) x[e] = badd2(x[e], u[e]);
                put_stats(u, 2, layer);
                named_bar_sync(9 + wg, 128);
                DT(7 + 24 * layer);
            }
            {
                float2 cs[8];
                {
                    float acc[128];
                    kblock<256, R4_N, 0>(acc, dae, db4, f4, r4);
                    kblock<256, R4_N>(acc, dae + 1024, db4 + R4_STAGE / 16, f4, r4);
                    if (!PS2_EARLY) {
                        uint32_t w[32];
#pragma unroll
                        for (int jp = 0; jp < 8; jp++) ldsm4(w[4 * jp], w[4 * jp + 1], w[4 * jp + 2], w[4 * jp + 3], s_epi + (fr ^ ((jp & 3) << 5)) + (jp >> 2) * 16384);
                        put_stats(w, 2, layer);
                    }
                    wgmma_wait<1>();
                    if (rel_on) mbar_arrive_cluster(rel4);
                    mainloop<256, R4_N, R4_STAGE, PA3A>(acc, 14, da0, db4, f4, rel4, rel_on, r4, 17 + 24 * layer, [&]() {
                        named_bar_sync(3 + 8 * wg, 160);
                        mbar_wait(e4, 1);
                        row_consts(false);
#pragma unroll
                        for (int e = 0; e < 8; e++) cs[e] = *reinterpret_cast<const float2*>(csp + 8 * e);
                        keep_consts(cs);
                    } DT_ARG, wg);
                    DT(8 + 24 * layer);
#pragma unroll
                    for (int j = 0; j < 32; j += 8) stage(acc + 4 * j, j < 16 ? s_epi : s_stg, j, cs, csp + 8 * (j + 8));
                    __syncwarp();
                if (lane == 0) mbar_arrive(b_stg);
                }
                DT(9 + 24 * layer);
                float acc[96];
                kblock<192, R4_N, 0>(acc, da0, db0, f4, r4);
                float ac4[64];
                mainloop<192, R4_N, R4B_STAGE, PA3B, 1>(acc, 15, da0, db0, f4, rel4, rel_on, r4, -1, [&]() {
#pragma unroll
                    for (int i = 0; i < 32; i++) asm volatile("shl.b32 %0, %2, 16;\nand.b32 %1, %2, 0xffff0000;" : "=f"(ac4[2 * i]), "=f"(ac4[2 * i + 1]) : "r"(x[i]));
                    kblock<128, R5_N>(ac4, da0, db0, f5, r5);
                } DT_ARG, wg);
                DT(10 + 24 * layer);
                named_bar_sync(4 + 8 * wg, 224);
                auto chunk = [&](auto jc) {
                    constexpr int j = 2 * decltype(jc)::v;
                    uint32_t w[4];
#pragma unroll
                    for (int e = 0; e < 2; e++) {
                        const float* a = acc + 4 * (j + e);
                        const float2 cc = cs[(j + e) & 7];
                        w[2 * e] = pack2(fmaf(-mrow[0], cc.x, a[0]) * rrow[0], fmaf(-mrow[0], cc.y, a[1]) * rrow[0]);
                        w[2 * e + 1] = pack2(fmaf(-mrow[1], cc.x, a[2]) * rrow[1], fmaf(-mrow[1], cc.y, a[3]) * rrow[1]);
                    }
                    stsm4(((j < 16 ? s_epi : s_stg) + st_w) ^ ((j & 15) << 4), w[0], w[1], w[2], w[3]);
                    if (j < 16) {
#pragma unroll
                        for (int e = 0; e < 2; e++) { uint32_t u0, u1; lds64(u0, u1, smem_u32(csp + 256 + 8 * (j + e + 8))); cs[(j + e) & 7] = make_float2(__uint_as_float(u0), __uint_as_float(u1)); }
                    }
                    if ((j & 7) == 6) {
                        __syncwarp();
                        if (lane == 0) mbar_arrive(s_bar + 200 + (j & 24));
                    }
                };
                auto step = [&](auto cc) {
                    constexpr int c = decltype(cc)::v, q = PPK * (c - 1) + 1;
                    const uint32_t da = da0 + (c % 5) * (R5_STAGE / 16), db = db0 + (c % 5) * (R5_STAGE / 16);
                    mbar_wait(f5 + 8 * (c % 5), r5.ph);
                    wgmma_fence();
                    WG<128>::mma<1>(ac4, da, db);
                    if constexpr (PPK == 4) chunk(IC<q>());
                    WG<128>::mma<1>(ac4, da + 2, db + 128);
                    chunk(IC<q + (PPK == 4)>());
                    WG<128>::mma<1>(ac4, da + 4, db + 256);
                    if constexpr (PPK >= 3 && q + PPK - 2 < 12) chunk(IC<q + PPK - 2>());
                    WG<128>::mma<1>(ac4, da + 6, db + 384);
                    wgmma_commit();
                    if (c % 5 == 4) r5.ph ^= 1;
                    wgmma_wait<1>();
                    if (rel_on) mbar_arrive_cluster(rel5 + 8 * ((c - 1) % 5));
                    if constexpr (q + PPK - 1 < 12) chunk(IC<q + PPK - 1>());
                };
                chunk(IC<0>());
                step(IC<1>()); step(IC<2>()); step(IC<3>());
                if constexpr (PPK < 4) step(IC<4>());
                if constexpr (PPK < 3) { step(IC<5>()); step(IC<6>()); }
                r5.st = (12 / PPK + 1) % 5;
                DT(11 + 24 * layer);
                DT(18 + 24 * layer);
                mainloop<128, R5_N, R5_STAGE>(ac4, 55 - 12 / PPK, da0, db0, f5, rel5, rel_on, r5, 62 - 40 * (layer ^ 1), []() {} DT_ARG);
                DT(12 + 24 * layer);
#pragma unroll
                for (int i = 0; i < 32; i++) x[i] = pack2(ac4[2 * i], ac4[2 * i + 1]);
                DT(13 + 24 * layer);
                DT(14 + 24 * layer);
            }
        }
#pragma unroll
        for (int jp = 0; jp < 8; jp++) stsm4(s_epi + (fr ^ ((jp & 3) << 5)) + (jp >> 2) * 16384, x[4 * jp], x[4 * jp + 1], x[4 * jp + 2], x[4 * jp + 3]);
        __syncwarp();
        copy_out(outp, s_epi);
        DT(38);
        DT_DUMP;
        GT(4);
        }
        cluster_arrive_relaxed();
        cluster_wait();
    }
}

typedef CUresult (*PFN_encodeTiled)(CUtensorMap*, CUtensorMapDataType, cuuint32_t, void*, const cuuint64_t*, const cuuint64_t*,
                                    const cuuint32_t*, const cuuint32_t*, CUtensorMapInterleave, CUtensorMapSwizzle,
                                    CUtensorMapL2promotion, CUtensorMapFloatOOBfill);

static CUtensorMap make_map(PFN_encodeTiled enc, const void* ptr, int inner, int outer, int box_inner, int box_outer,
                            CUtensorMapSwizzle swz = CU_TENSOR_MAP_SWIZZLE_128B) {
    CUtensorMap m;
    cuuint64_t dims[2] = {(cuuint64_t)inner, (cuuint64_t)outer};
    cuuint64_t strides[1] = {(cuuint64_t)inner * 2};
    cuuint32_t box[2] = {(cuuint32_t)box_inner, (cuuint32_t)box_outer};
    cuuint32_t es[2] = {1, 1};
    enc(&m, CU_TENSOR_MAP_DATA_TYPE_BFLOAT16, 2, const_cast<void*>(ptr), dims, strides, box, es, CU_TENSOR_MAP_INTERLEAVE_NONE,
        swz, CU_TENSOR_MAP_L2_PROMOTION_L2_256B, CU_TENSOR_MAP_FLOAT_OOB_FILL_NONE);
    return m;
}

extern "C" void kernel_launch(void* const* d_in, const int* in_sizes, int n_in, void* d_out, int out_size) {
    const bf16* A_q = (const bf16*)d_in[0];
    const bf16* A_k = (const bf16*)d_in[1];
    const bf16* A_v = (const bf16*)d_in[2];
    const bf16* A_shk = (const bf16*)d_in[3];
    const bf16* A_ssk = (const bf16*)d_in[4];
    const bf16* A_ssD = (const bf16*)d_in[5];
    const bf16* w1 = (const bf16*)d_in[7];
    const bf16* w2 = (const bf16*)d_in[8];
    const bf16* w3 = (const bf16*)d_in[9];
    const bf16* w4 = (const bf16*)d_in[10];
    bf16* out = (bf16*)d_out;

    static PFN_encodeTiled enc = nullptr;
    static bool attr_done = false;
    if (!enc) {
        void* fn = nullptr;
        cudaDriverEntryPointQueryResult qr;
        cudaGetDriverEntryPoint("cuTensorMapEncodeTiled", &fn, cudaEnableDefault, &qr);
        enc = (PFN_encodeTiled)fn;
    }
    if (!attr_done) {
        cudaFuncSetAttribute(mega_kernel, cudaFuncAttributeMaxDynamicSharedMemorySize, MEGA_SMEM);
        attr_done = true;
    }
    void* p_act;
    cudaGetSymbolAddress(&p_act, g_act);
    bf16* act = (bf16*)(((uintptr_t)p_act + 0x1fffff) & ~(uintptr_t)0x1fffff);

    MegaMaps tm;
    tm.q = make_map(enc, A_q, D_, S_, 64, 128);
    tm.act = make_map(enc, act, D_, R_END, 64, 128);
    tm.w1 = make_map(enc, w1, D_, D_, 64, 64);
    tm.w2 = make_map(enc, w2, D_, D_, 64, 64);
    tm.w3 = make_map(enc, w3, F_, D_, 64, 64);
    tm.w4 = make_map(enc, w4, D_, F_, 64, 64);
    {
        cuuint64_t dims[4] = {64, 16, 256, 8}, strides[3] = {128, D_ * 2, (cuuint64_t)2048 * D_ * 2};
        cuuint32_t box[4] = {64, 4, 1, 8}, es[4] = {1, 1, 1, 1};
        enc(&tm.y, CU_TENSOR_MAP_DATA_TYPE_BFLOAT16, 4, act + (size_t)R_Y * D_, dims, strides, box, es, CU_TENSOR_MAP_INTERLEAVE_NONE,
            CU_TENSOR_MAP_SWIZZLE_128B, CU_TENSOR_MAP_L2_PROMOTION_NONE, CU_TENSOR_MAP_FLOAT_OOB_FILL_NONE);
    }
    for (int i = 0; i < 2; i++) {
        cuuint64_t dims[4] = {D_, 4, 8, S_ / 32}, strides[3] = {8 * D_ * 2, D_ * 2, 32 * D_ * 2};
        cuuint32_t box[4] = {16, 4, 8, 4}, es[4] = {1, 1, 1, 1};
        enc(i ? &tm.v : &tm.k, CU_TENSOR_MAP_DATA_TYPE_BFLOAT16, 4, (void*)(i ? A_v : A_k), dims, strides, box, es, CU_TENSOR_MAP_INTERLEAVE_NONE,
            CU_TENSOR_MAP_SWIZZLE_32B, CU_TENSOR_MAP_L2_PROMOTION_NONE, CU_TENSOR_MAP_FLOAT_OOB_FILL_NONE);
    }
    mega_kernel<<<2 * NCL, 384, MEGA_SMEM, cudaStreamPerThread>>>(tm, out, act, w1, w2, w3, A_q, A_k, A_v, A_shk, A_ssk, A_ssD);
}
```

```cpp
#include <cuda_runtime.h>
#include <cuda_bf16.h>
#include <cuda.h>
#include <stdint.h>

typedef __nv_bfloat16 bf16;

constexpr int S_ = 2048;
constexpr int D_ = 1024;
constexpr int F_ = 3584;

constexpr int R_XA = 0, R_X1 = 256, R_H2 = 512, R_Y = 1536, R_H = 16384 + 8, R_HP = S_ + 8, R_END = R_H + 2 * R_HP;
__device__ __align__(1024) bf16 g_act[(size_t)(R_END + 1024) * D_];
__device__ __align__(16) float g_cpart[16 * (F_ + D_)];
__device__ __align__(128) float2 g_stats[3 * S_ * 8];
__device__ __align__(128) uint4 g_halo[2 * 144 * 64];

__device__ __forceinline__ float bfr(float x) { return __bfloat162float(__float2bfloat16_rn(x)); }
__device__ __forceinline__ uint32_t pack2(float lo, float hi) {
    __nv_bfloat162 v = __floats2bfloat162_rn(lo, hi);
    return *reinterpret_cast<uint32_t*>(&v);
}
__device__ __forceinline__ float lo2f(uint32_t v) { return __uint_as_float(v << 16); }
__device__ __forceinline__ float hi2f(uint32_t v) { return __uint_as_float(v & 0xffff0000u); }
__device__ __forceinline__ float frcp(float x) { float r; asm("rcp.approx.f32 %0, %1;" : "=f"(r) : "f"(x)); return r; }
__device__ __forceinline__ float fsqrt(float x) { float r; asm("sqrt.approx.f32 %0, %1;" : "=f"(r) : "f"(x)); return r; }
__device__ __forceinline__ uint32_t smem_u32(const void* p) { return (uint32_t)__cvta_generic_to_shared(p); }

__device__ __forceinline__ void mbar_init(uint32_t bar, uint32_t cnt) {
    asm volatile("mbarrier.init.shared::cta.b64 [%0], %1;" ::"r"(bar), "r"(cnt));
}
__device__ __forceinline__ void mbar_expect_tx(uint32_t bar, uint32_t bytes) {
    asm volatile("mbarrier.arrive.expect_tx.shared::cta.b64 _, [%0], %1;" ::"r"(bar), "r"(bytes) : "memory");
}
__device__ __forceinline__ void mbar_arrive(uint32_t bar) {
    asm volatile("mbarrier.arrive.shared::cta.b64 _, [%0];" ::"r"(bar) : "memory");
}
__device__ __forceinline__ void mbar_wait(uint32_t bar, uint32_t parity) {
    asm volatile(
        "{\n.reg .pred p;\n.reg .u32 n;\n"
        "mbarrier.try_wait.parity.shared::cta.b64 p, [%0], %1;\n"
        "@p bra LD;\n"
        "mov.u32 n, 0;\n"
        "LW:\n"
        "mbarrier.try_wait.parity.shared::cta.b64 p, [%0], %1;\n"
        "@p bra LD;\n"
        "add.u32 n, n, 1;\n"
        "setp.lt.u32 p, n, 0x400000;\n"
        "@p bra LW;\n"
        "LD:\n}\n"
        ::"r"(bar), "r"(parity) : "memory");
}
__device__ __forceinline__ void tma_load_2d(uint32_t dst, const CUtensorMap* tm, uint32_t bar, int c0, int c1) {
    asm volatile(
        "cp.async.bulk.tensor.2d.shared::cluster.global.mbarrier::complete_tx::bytes [%0], [%1, {%3, %4}], [%2];"
        ::"r"(dst), "l"((uint64_t)tm), "r"(bar), "r"(c0), "r"(c1) : "memory");
}
__device__ __forceinline__ void tma_load_2d_mc(uint32_t dst, const CUtensorMap* tm, uint32_t bar, int c0, int c1) {
    asm volatile(
        "cp.async.bulk.tensor.2d.shared::cluster.global.mbarrier::complete_tx::bytes.multicast::cluster [%0], [%1, {%3, %4}], [%2], %5;"
        ::"r"(dst), "l"((uint64_t)tm), "r"(bar), "r"(c0), "r"(c1), "h"((uint16_t)3) : "memory");
}
__device__ __forceinline__ void tma_prefetch_2d(const CUtensorMap* tm, int c0, int c1) {
    asm volatile("cp.async.bulk.prefetch.tensor.2d.L2.global.tile [%0, {%1, %2}];" ::"l"((uint64_t)tm), "r"(c0), "r"(c1) : "memory");
}
__device__ __forceinline__ void tma_store_2d(const CUtensorMap* tm, uint32_t src, int c0, int c1) {
    asm volatile("cp.async.bulk.tensor.2d.global.shared::cta.bulk_group [%0, {%2, %3}], [%1];"
                 ::"l"((uint64_t)tm), "r"(src), "r"(c0), "r"(c1) : "memory");
}
__device__ __forceinline__ void wgmma_fence() { asm volatile("wgmma.fence.sync.aligned;" ::: "memory"); }
__device__ __forceinline__ void wgmma_commit() { asm volatile("wgmma.commit_group.sync.aligned;" ::: "memory"); }
template <int N> __device__ __forceinline__ void wgmma_wait() { asm volatile("wgmma.wait_group.sync.aligned %0;" ::"n"(N) : "memory"); }
__device__ __forceinline__ void named_bar_arrive(int id, int n) { asm volatile("bar.arrive %0, %1;" ::"r"(id), "r"(n) : "memory"); }
__device__ __forceinline__ void named_bar_sync(int id, int n) { asm volatile("bar.sync %0, %1;" ::"r"(id), "r"(n) : "memory"); }

__device__ __forceinline__ uint32_t desc_a(uint32_t addr) { return ((addr & 0x3FFFF) >> 4) | (1u << 16); }
__device__ __forceinline__ uint32_t desc_b(uint32_t addr) { return ((addr & 0x3FFFF) >> 4) | (512u << 16); }

template <int ACC> __device__ __forceinline__ void wgmma_m64n192k16(float (&d)[96], uint32_t descA, uint32_t descB) {
  asm volatile("{\n.reg .pred p;\n.reg .b64 da, db;\nsetp.ne.b32 p, %99, 0;\nmov.b64 da, {%96, %98};\nmov.b64 db, {%97, %98};\n"
    "wgmma.mma_async.sync.aligned.m64n192k16.f32.bf16.bf16 "
    "{%0, %1, %2, %3, %4, %5, %6, %7, %8, %9, %10, %11, %12, %13, %14, %15, %16, %17, %18, %19, %20, %21, %22, %23, %24, %25, %26, %27, %28, %29, %30, %31, %32, %33, %34, %35, %36, %37, %38, %39, %40, %41, %42, %43, %44, %45, %46, %47, %48, %49, %50, %51, %52, %53, %54, %55, %56, %57, %58, %59, %60, %61, %62, %63, %64, %65, %66, %67, %68, %69, %70, %71, %72, %73, %74, %75, %76, %77, %78, %79, %80, %81, %82, %83, %84, %85, %86, %87, %88, %89, %90, %91, %92, %93, %94, %95}, "
    "da, db, p, 1, 1, 0, 1;\n}\n"
    : "+f"(d[0]), "+f"(d[1]), "+f"(d[2]), "+f"(d[3]), "+f"(d[4]), "+f"(d[5]), "+f"(d[6]), "+f"(d[7]), "+f"(d[8]), "+f"(d[9]), "+f"(d[10]), "+f"(d[11]), "+f"(d[12]), "+f"(d[13]), "+f"(d[14]), "+f"(d[15]), "+f"(d[16]), "+f"(d[17]), "+f"(d[18]), "+f"(d[19]), "+f"(d[20]), "+f"(d[21]), "+f"(d[22]), "+f"(d[23]), "+f"(d[24]), "+f"(d[25]), "+f"(d[26]), "+f"(d[27]), "+f"(d[28]), "+f"(d[29]), "+f"(d[30]), "+f"(d[31]), "+f"(d[32]), "+f"(d[33]), "+f"(d[34]), "+f"(d[35]), "+f"(d[36]), "+f"(d[37]), "+f"(d[38]), "+f"(d[39]), "+f"(d[40]), "+f"(d[41]), "+f"(d[42]), "+f"(d[43]), "+f"(d[44]), "+f"(d[45]), "+f"(d[46]), "+f"(d[47]), "+f"(d[48]), "+f"(d[49]), "+f"(d[50]), "+f"(d[51]), "+f"(d[52]), "+f"(d[53]), "+f"(d[54]), "+f"(d[55]), "+f"(d[56]), "+f"(d[57]), "+f"(d[58]), "+f"(d[59]), "+f"(d[60]), "+f"(d[61]), "+f"(d[62]), "+f"(d[63]), "+f"(d[64]), "+f"(d[65]), "+f"(d[66]), "+f"(d[67]), "+f"(d[68]), "+f"(d[69]), "+f"(d[70]), "+f"(d[71]), "+f"(d[72]), "+f"(d[73]), "+f"(d[74]), "+f"(d[75]), "+f"(d[76]), "+f"(d[77]), "+f"(d[78]), "+f"(d[79]), "+f"(d[80]), "+f"(d[81]), "+f"(d[82]), "+f"(d[83]), "+f"(d[84]), "+f"(d[85]), "+f"(d[86]), "+f"(d[87]), "+f"(d[88]), "+f"(d[89]), "+f"(d[90]), "+f"(d[91]), "+f"(d[92]), "+f"(d[93]), "+f"(d[94]), "+f"(d[95])
    : "r"(descA), "r"(descB), "r"(0x40000040u), "n"(ACC));
}

template <int ACC> __device__ __forceinline__ void wgmma_m64n256k16(float (&d)[128], uint32_t descA, uint32_t descB) {
  asm volatile("{\n.reg .pred p;\n.reg .b64 da, db;\nsetp.ne.b32 p, %131, 0;\nmov.b64 da, {%128, %130};\nmov.b64 db, {%129, %130};\n"
    "wgmma.mma_async.sync.aligned.m64n256k16.f32.bf16.bf16 "
    "{%0, %1, %2, %3, %4, %5, %6, %7, %8, %9, %10, %11, %12, %13, %14, %15, %16, %17, %18, %19, %20, %21, %22, %23, %24, %25, %26, %27, %28, %29, %30, %31, %32, %33, %34, %35, %36, %37, %38, %39, %40, %41, %42, %43, %44, %45, %46, %47, %48, %49, %50, %51, %52, %53, %54, %55, %56, %57, %58, %59, %60, %61, %62, %63, %64, %65, %66, %67, %68, %69, %70, %71, %72, %73, %74, %75, %76, %77, %78, %79, %80, %81, %82, %83, %84, %85, %86, %87, %88, %89, %90, %91, %92, %93, %94, %95, %96, %97, %98, %99, %100, %101, %102, %103, %104, %105, %106, %107, %108, %109, %110, %111, %112, %113, %114, %115, %116, %117, %118, %119, %120, %121, %122, %123, %124, %125, %126, %127}, "
    "da, db, p, 1, 1, 0, 1;\n}\n"
    : "+f"(d[0]), "+f"(d[1]), "+f"(d[2]), "+f"(d[3]), "+f"(d[4]), "+f"(d[5]), "+f"(d[6]), "+f"(d[7]), "+f"(d[8]), "+f"(d[9]), "+f"(d[10]), "+f"(d[11]), "+f"(d[12]), "+f"(d[13]), "+f"(d[14]), "+f"(d[15]), "+f"(d[16]), "+f"(d[17]), "+f"(d[18]), "+f"(d[19]), "+f"(d[20]), "+f"(d[21]), "+f"(d[22]), "+f"(d[23]), "+f"(d[24]), "+f"(d[25]), "+f"(d[26]), "+f"(d[27]), "+f"(d[28]), "+f"(d[29]), "+f"(d[30]), "+f"(d[31]), "+f"(d[32]), "+f"(d[33]), "+f"(d[34]), "+f"(d[35]), "+f"(d[36]), "+f"(d[37]), "+f"(d[38]), "+f"(d[39]), "+f"(d[40]), "+f"(d[41]), "+f"(d[42]), "+f"(d[43]), "+f"(d[44]), "+f"(d[45]), "+f"(d[46]), "+f"(d[47]), "+f"(d[48]), "+f"(d[49]), "+f"(d[50]), "+f"(d[51]), "+f"(d[52]), "+f"(d[53]), "+f"(d[54]), "+f"(d[55]), "+f"(d[56]), "+f"(d[57]), "+f"(d[58]), "+f"(d[59]), "+f"(d[60]), "+f"(d[61]), "+f"(d[62]), "+f"(d[63]), "+f"(d[64]), "+f"(d[65]), "+f"(d[66]), "+f"(d[67]), "+f"(d[68]), "+f"(d[69]), "+f"(d[70]), "+f"(d[71]), "+f"(d[72]), "+f"(d[73]), "+f"(d[74]), "+f"(d[75]), "+f"(d[76]), "+f"(d[77]), "+f"(d[78]), "+f"(d[79]), "+f"(d[80]), "+f"(d[81]), "+f"(d[82]), "+f"(d[83]), "+f"(d[84]), "+f"(d[85]), "+f"(d[86]), "+f"(d[87]), "+f"(d[88]), "+f"(d[89]), "+f"(d[90]), "+f"(d[91]), "+f"(d[92]), "+f"(d[93]), "+f"(d[94]), "+f"(d[95]), "+f"(d[96]), "+f"(d[97]), "+f"(d[98]), "+f"(d[99]), "+f"(d[100]), "+f"(d[101]), "+f"(d[102]), "+f"(d[103]), "+f"(d[104]), "+f"(d[105]), "+f"(d[106]), "+f"(d[107]), "+f"(d[108]), "+f"(d[109]), "+f"(d[110]), "+f"(d[111]), "+f"(d[112]), "+f"(d[113]), "+f"(d[114]), "+f"(d[115]), "+f"(d[116]), "+f"(d[117]), "+f"(d[118]), "+f"(d[119]), "+f"(d[120]), "+f"(d[121]), "+f"(d[122]), "+f"(d[123]), "+f"(d[124]), "+f"(d[125]), "+f"(d[126]), "+f"(d[127])
    : "r"(descA), "r"(descB), "r"(0x40000040u), "n"(ACC));
}

template <int ACC> __device__ __forceinline__ void wgmma_m64n128k16(float (&d)[64], uint32_t descA, uint32_t descB) {
  asm volatile("{\n.reg .pred p;\n.reg .b64 da, db;\nsetp.ne.b32 p, %67, 0;\nmov.b64 da, {%64, %66};\nmov.b64 db, {%65, %66};\n"
    "wgmma.mma_async.sync.aligned.m64n128k16.f32.bf16.bf16 "
    "{%0, %1, %2, %3, %4, %5, %6, %7, %8, %9, %10, %11, %12, %13, %14, %15, %16, %17, %18, %19, %20, %21, %22, %23, %24, %25, %26, %27, %28, %29, %30, %31, %32, %33, %34, %35, %36, %37, %38, %39, %40, %41, %42, %43, %44, %45, %46, %47, %48, %49, %50, %51, %52, %53, %54, %55, %56, %57, %58, %59, %60, %61, %62, %63}, "
    "da, db, p, 1, 1, 0, 1;\n}\n"
    : "+f"(d[0]), "+f"(d[1]), "+f"(d[2]), "+f"(d[3]), "+f"(d[4]), "+f"(d[5]), "+f"(d[6]), "+f"(d[7]), "+f"(d[8]), "+f"(d[9]), "+f"(d[10]), "+f"(d[11]), "+f"(d[12]), "+f"(d[13]), "+f"(d[14]), "+f"(d[15]), "+f"(d[16]), "+f"(d[17]), "+f"(d[18]), "+f"(d[19]), "+f"(d[20]), "+f"(d[21]), "+f"(d[22]), "+f"(d[23]), "+f"(d[24]), "+f"(d[25]), "+f"(d[26]), "+f"(d[27]), "+f"(d[28]), "+f"(d[29]), "+f"(d[30]), "+f"(d[31]), "+f"(d[32]), "+f"(d[33]), "+f"(d[34]), "+f"(d[35]), "+f"(d[36]), "+f"(d[37]), "+f"(d[38]), "+f"(d[39]), "+f"(d[40]), "+f"(d[41]), "+f"(d[42]), "+f"(d[43]), "+f"(d[44]), "+f"(d[45]), "+f"(d[46]), "+f"(d[47]), "+f"(d[48]), "+f"(d[49]), "+f"(d[50]), "+f"(d[51]), "+f"(d[52]), "+f"(d[53]), "+f"(d[54]), "+f"(d[55]), "+f"(d[56]), "+f"(d[57]), "+f"(d[58]), "+f"(d[59]), "+f"(d[60]), "+f"(d[61]), "+f"(d[62]), "+f"(d[63])
    : "r"(descA), "r"(descB), "r"(0x40000040u), "n"(ACC));
}

template <int BN> struct WG;
template <> struct WG<128> { template <int ACC> static __device__ __forceinline__ void mma(float (&d)[64], uint32_t a, uint32_t b) { wgmma_m64n128k16<ACC>(d, a, b); } };
template <> struct WG<256> { template <int ACC> static __device__ __forceinline__ void mma(float (&d)[128], uint32_t a, uint32_t b) { wgmma_m64n256k16<ACC>(d, a, b); } };
template <> struct WG<192> { template <int ACC> static __device__ __forceinline__ void mma(float (&d)[96], uint32_t a, uint32_t b) { wgmma_m64n192k16<ACC>(d, a, b); } };

#define DBG_T(i)
__device__ __forceinline__ void fence_async_smem() { asm volatile("fence.proxy.async.shared::cta;" ::: "memory"); }
__device__ __forceinline__ void prefetch_tmap(const CUtensorMap* tm) { asm volatile("prefetch.tensormap [%0];" ::"l"((uint64_t)tm) : "memory"); }
__device__ __forceinline__ uint32_t mapa_u32(uint32_t addr, uint32_t cta) {
    uint32_t r;
    asm volatile("mapa.shared::cluster.u32 %0, %1, %2;" : "=r"(r) : "r"(addr), "r"(cta));
    return r;
}
__device__ __forceinline__ void mbar_arrive_cluster(uint32_t cluster_addr) {
    asm volatile("mbarrier.arrive.shared::cluster.b64 _, [%0];" ::"r"(cluster_addr) : "memory");
}
__device__ __forceinline__ bool elect_one() {
    uint32_t p;
    asm volatile("{\n.reg .pred P;\nelect.sync _|P, 0xffffffff;\nselp.u32 %0, 1, 0, P;\n}\n" : "=r"(p));
    return p != 0;
}
__device__ __forceinline__ void cluster_arrive_relaxed() { asm volatile("barrier.cluster.arrive.relaxed.aligned;" ::: "memory"); }
__device__ __forceinline__ void cluster_wait() { asm volatile("barrier.cluster.wait.acquire.aligned;" ::: "memory"); }

__device__ __forceinline__ uint32_t bsub2(uint32_t a, uint32_t b) {
    __nv_bfloat162 r = __hsub2(*reinterpret_cast<__nv_bfloat162*>(&a), *reinterpret_cast<__nv_bfloat162*>(&b));
    return *reinterpret_cast<uint32_t*>(&r);
}
__device__ __forceinline__ uint32_t bmul2(uint32_t a, uint32_t b) {
    __nv_bfloat162 r = __hmul2(*reinterpret_cast<__nv_bfloat162*>(&a), *reinterpret_cast<__nv_bfloat162*>(&b));
    return *reinterpret_cast<uint32_t*>(&r);
}
__device__ __forceinline__ uint32_t badd2(uint32_t a, uint32_t b) {
    __nv_bfloat162 r = __hadd2(*reinterpret_cast<__nv_bfloat162*>(&a), *reinterpret_cast<__nv_bfloat162*>(&b));
    return *reinterpret_cast<uint32_t*>(&r);
}
constexpr int BM = 128, BK = 64;
constexpr int R5_STAGE = 32768, R5_N = 5;
constexpr int R4_STAGE = 49152, R4_N = 4;
constexpr int R4B_STAGE = 40960;
constexpr int OFF_STG5 = 0, OFF_R = 32768;
constexpr int OFF_EPI = 196608;
constexpr int OFF_BAR = OFF_EPI + 32768;
constexpr int OFF_RS = OFF_BAR + 256;
constexpr int OFF_CS = OFF_RS + 1024;
constexpr int MEGA_SMEM = OFF_CS + 1792;
enum { FL_XA = 0, FL_H = 2, FL_X1 = 4, FL_H2 = 6, FL_CS = 10, FL_KINDS = 11 };
constexpr int FL_PITCH = 64;
constexpr int FL_WORDS = 2 * FL_KINDS * 16 * FL_PITCH;
__device__ unsigned int g_flag[FL_WORDS];
__device__ __align__(8) unsigned int g_ticket[18 * FL_PITCH];
constexpr int NCL = 66;
__device__ __forceinline__ unsigned int* flag_ptr(int layer, int kind, int i) { return g_flag + ((layer * FL_KINDS + kind) * 16 + i) * FL_PITCH; }

__device__ __forceinline__ void wait_flag(const unsigned int* p, unsigned int target) {
    long long t0 = clock64();
    while (true) {
        unsigned int v;
        asm volatile("ld.relaxed.gpu.global.u32 %0, [%1];" : "=r"(v) : "l"(p) : "memory");
        if ((int)(v - target) >= 0) break;
        if (clock64() - t0 > 2000000000LL) break;
    }
    asm volatile("fence.acquire.gpu;" ::: "memory");
}
__device__ __forceinline__ void fence_proxy_async() {
    asm volatile("fence.proxy.async.global;" ::: "memory");
    asm volatile("fence.proxy.async.shared::cta;" ::: "memory");
}
__device__ __forceinline__ void stsm4(uint32_t addr, uint32_t r0, uint32_t r1, uint32_t r2, uint32_t r3) {
    asm volatile("stmatrix.sync.aligned.m8n8.x4.shared.b16 [%0], {%1,%2,%3,%4};" ::"r"(addr), "r"(r0), "r"(r1), "r"(r2), "r"(r3));
}
__device__ __forceinline__ uint4 lds128(uint32_t a) {
    uint4 v;
    asm volatile("ld.shared.v4.b32 {%0,%1,%2,%3}, [%4];" : "=r"(v.x), "=r"(v.y), "=r"(v.z), "=r"(v.w) : "r"(a) : "memory");
    return v;
}
__device__ __forceinline__ void stg128(void* p, uint4 v) {
    asm volatile("st.global.v4.b32 [%0], {%1,%2,%3,%4};" ::"l"(p), "r"(v.x), "r"(v.y), "r"(v.z), "r"(v.w) : "memory");
}
__device__ __forceinline__ float gelu_tanh_h(float hx) {
    float z = hx * fmaf(hx * hx, 8.0f * 0.035677408136300125f, 2.0f * 0.7978845608028654f);
    float t;
    asm("tanh.approx.f32 %0, %1;" : "=f"(t) : "f"(z));
    return fmaf(hx, t, hx);
}
__device__ __forceinline__ uint32_t gelu2h(uint32_t hx) {
    uint32_t r;
    asm("{\n.reg .b32 z;\nmul.rn.bf16x2 z, %1, %1;\nfma.rn.bf16x2 z, z, %2, %3;\nmul.rn.bf16x2 z, z, %1;\ntanh.approx.bf16x2 z, z;\nfma.rn.bf16x2 %0, %1, z, %1;\n}"
        : "=r"(r) : "r"(hx), "r"(0x3e923e92u), "r"(0x3fcc3fccu));
    return r;
}
__device__ __forceinline__ uint4 gelu8h(uint4 v) { return make_uint4(gelu2h(v.x), gelu2h(v.y), gelu2h(v.z), gelu2h(v.w)); }

__device__ __forceinline__ void row_stats(const float2* p, uint32_t tag, float& mean, float& var) {
    float2 v[8];
#pragma unroll 1
    for (int n = 0; n < (1 << 20); n++) {
#pragma unroll
        for (int i = 0; i < 8; i++)
            asm volatile("{\n.reg .b64 t;\nld.relaxed.gpu.global.b64 t, [%2];\nmov.b64 {%0, %1}, t;\n}" : "=f"(v[i].x), "=f"(v[i].y) : "l"(p + 128 * i) : "memory");
        uint32_t old = 0;
#pragma unroll
        for (int i = 0; i < 8; i++) old |= __float_as_uint(v[i].y) ^ tag;
        if ((int)old >= 0) break;
    }
    mean = (((v[0].x + v[1].x) + (v[2].x + v[3].x)) + ((v[4].x + v[5].x) + (v[6].x + v[7].x))) * 0.125f;
    float m2 = 0.f, d2 = 0.f;
#pragma unroll
    for (int i = 0; i < 8; i++) { m2 += fabsf(v[i].y); d2 = fmaf(v[i].x - mean, v[i].x - mean, d2); }
    var = fmaf(128.0f, d2, m2) * (1.0f / D_);
}
struct RingState { uint32_t st, ph; };

#define DT(i)
#define DT_DECL
#define DT_PAR
#define DT_ARG
#define DT_DUMP
#define DP(i)
#define GT(i)
#define TM(i)

template <int BN, int NST, int ACC = 1>
__device__ __forceinline__ void kblock(float (&acc)[BN / 2], uint32_t da, uint32_t db, uint32_t bfull, RingState& rs) {
    mbar_wait(bfull + 8 * rs.st, rs.ph);
    wgmma_fence();
    WG<BN>::template mma<ACC>(acc, da, db);
#pragma unroll
    for (int k = 1; k < 4; k++) WG<BN>::template mma<1>(acc, da + k * 2, db + k * 128);
    wgmma_commit();
    if (++rs.st == NST) { rs.st = 0; rs.ph ^= 1; }
}
#define PA3A 1
#define RLX 1
#define NPRE 12
#define PP3 2
#define NCS 8
template <int V> struct IC { static constexpr int v = V; };
template <int A, int B, class F> __device__ __forceinline__ void static_for(F f) {
    if constexpr (A < B) { f(IC<A>()); static_for<A + 1, B>(f); }
}
#define SPL 21
#define PF4A 22
#define PF4N 1
#define XCS 0
#define PA1 45
#define PA2 33
#define PA4 33
#define LAGX 1
#define PA3B 0
template <int BN, int NST, int STAGE, int PS = 0, int TW = 0, class F>
__device__ __forceinline__ void mainloop(float (&acc)[BN / 2], int KB, uint32_t da0, uint32_t db0, uint32_t bfull, uint32_t rel, bool rel_on,
                                         RingState& rs, int dbg, F pre DT_PAR, int wg = 0) {
    constexpr int SG = PS / 10, PAUSE = PS % 10;
    uint32_t prev = rs.st ? rs.st - 1 : NST - 1;
    const int pause = wg ? KB - PAUSE : -1;
#pragma unroll 1
    for (int kk = 0; kk < KB; kk++) {
        const uint32_t cur = rs.st;
        if (PAUSE && kk == pause) {
            wgmma_wait<0>();
            if (rel_on) mbar_arrive_cluster(rel + 8 * prev);
            named_bar_sync(15, 256);
        }
        kblock<BN, NST>(acc, da0 + cur * (STAGE / 16), db0 + cur * (STAGE / 16), bfull, rs);
        if (PAUSE && SG >= 2 && wg == 0 && kk == KB + 1 - SG) named_bar_arrive(15, 256);
        wgmma_wait<1>();
        if (rel_on && !(PAUSE && kk == pause)) mbar_arrive_cluster(rel + 8 * prev);
        prev = cur;
    }
    if (PAUSE && SG == 0 && wg == 0) named_bar_arrive(15, 256);
    pre();
    wgmma_wait<TW>();
#pragma unroll
    for (int i = 0; i < BN / 2; i++) asm volatile("" : "+f"(acc[i])::"memory");
    if (PAUSE && SG == 1 && wg == 0) named_bar_arrive(15, 256);
    if (rel_on) mbar_arrive_cluster(rel + 8 * prev);
}
__device__ __forceinline__ void hmma(float (&c)[4], uint32_t a0, uint32_t a1, uint32_t a2, uint32_t a3, uint32_t b0, uint32_t b1, bool first) {
    if (first) asm("{\n.reg .f32 z;\nmov.f32 z, 0f00000000;\nmma.sync.aligned.m16n8k16.row.col.f32.bf16.bf16.f32 {%0,%1,%2,%3}, {%4,%5,%6,%7}, {%8,%9}, {z,z,z,z};\n}"
        : "=f"(c[0]), "=f"(c[1]), "=f"(c[2]), "=f"(c[3]) : "r"(a0), "r"(a1), "r"(a2), "r"(a3), "r"(b0), "r"(b1));
    else
    asm("mma.sync.aligned.m16n8k16.row.col.f32.bf16.bf16.f32 {%0,%1,%2,%3}, {%4,%5,%6,%7}, {%8,%9}, {%0,%1,%2,%3};"
        : "+f"(c[0]), "+f"(c[1]), "+f"(c[2]), "+f"(c[3]) : "r"(a0), "r"(a1), "r"(a2), "r"(a3), "r"(b0), "r"(b1));
}
__device__ __forceinline__ void hmma8(float (&c)[4], uint32_t a0, uint32_t a1, uint32_t b0, bool first) {
    if (first) asm("{\n.reg .f32 z;\nmov.f32 z, 0f00000000;\nmma.sync.aligned.m16n8k8.row.col.f32.bf16.bf16.f32 {%0,%1,%2,%3}, {%4,%5}, {%6}, {z,z,z,z};\n}"
        : "=f"(c[0]), "=f"(c[1]), "=f"(c[2]), "=f"(c[3]) : "r"(a0), "r"(a1), "r"(b0));
    else
    asm("mma.sync.aligned.m16n8k8.row.col.f32.bf16.bf16.f32 {%0,%1,%2,%3}, {%4,%5}, {%6}, {%0,%1,%2,%3};"
        : "+f"(c[0]), "+f"(c[1]), "+f"(c[2]), "+f"(c[3]) : "r"(a0), "r"(a1), "r"(b0));
}
template <int N> __device__ __forceinline__ void zero_acc(float (&acc)[N]) {
#pragma unroll
    for (int i = 0; i < N; i++) acc[i] = 0.f;
}
__device__ __forceinline__ void ldsm4(uint32_t& r0, uint32_t& r1, uint32_t& r2, uint32_t& r3, uint32_t addr) {
    asm volatile("ldmatrix.sync.aligned.m8n8.x4.shared.b16 {%0,%1,%2,%3}, [%4];" : "=r"(r0), "=r"(r1), "=r"(r2), "=r"(r3) : "r"(addr));
}

__device__ __forceinline__ void ldsm4t(uint32_t& r0, uint32_t& r1, uint32_t& r2, uint32_t& r3, uint32_t addr) {
    asm volatile("ldmatrix.sync.aligned.m8n8.x4.trans.shared.b16 {%0,%1,%2,%3}, [%4];" : "=r"(r0), "=r"(r1), "=r"(r2), "=r"(r3) : "r"(addr));
}

#define DBG_S(i)
#define DBG_OUT(r, o)
#define DBG_F(i)
#define DBG_W(i)
constexpr int CV_CH = 8;
constexpr int CV_SL = 16384;
constexpr int CV_QG = 128 * 8 + 16;
constexpr int CV_HPL = 2048 + 192;
constexpr int CV_0 = 32768, CV_H = 9 * CV_SL, CV_BAR = OFF_RS - CV_0;

template <int K> __device__ __forceinline__ void cv_mma(float (&d)[64], const uint32_t (&a)[4], uint32_t db, int acc);
template <> __device__ __forceinline__ void cv_mma<0>(float (&d)[64], const uint32_t (&a)[4], uint32_t db, int acc) {
    asm volatile("{\n.reg .pred p;\n.reg .b64 b;\nsetp.ne.b32 p, %70, 0;\nmov.b64 b, {%68, %69};\n"
        "wgmma.mma_async.sync.aligned.m64n128k16.f32.bf16.bf16 {%0,%1,%2,%3,%4,%5,%6,%7,%8,%9,%10,%11,%12,%13,%14,%15,%16,%17,%18,%19,%20,%21,%22,%23,%24,%25,%26,%27,%28,%29,%30,%31,%32,%33,%34,%35,%36,%37,%38,%39,%40,%41,%42,%43,%44,%45,%46,%47,%48,%49,%50,%51,%52,%53,%54,%55,%56,%57,%58,%59,%60,%61,%62,%63}, {%64,%65,%66,%67}, b, p, 1, 1, 0;\n}\n"
        : "+f"(d[0]), "+f"(d[1]), "+f"(d[2]), "+f"(d[3]), "+f"(d[4]), "+f"(d[5]), "+f"(d[6]), "+f"(d[7]), "+f"(d[8]), "+f"(d[9]), "+f"(d[10]), "+f"(d[11]), "+f"(d[12]), "+f"(d[13]), "+f"(d[14]), "+f"(d[15]), "+f"(d[16]), "+f"(d[17]), "+f"(d[18]), "+f"(d[19]), "+f"(d[20]), "+f"(d[21]), "+f"(d[22]), "+f"(d[23]), "+f"(d[24]), "+f"(d[25]), "+f"(d[26]), "+f"(d[27]), "+f"(d[28]), "+f"(d[29]), "+f"(d[30]), "+f"(d[31]), "+f"(d[32]), "+f"(d[33]), "+f"(d[34]), "+f"(d[35]), "+f"(d[36]), "+f"(d[37]), "+f"(d[38]), "+f"(d[39]), "+f"(d[40]), "+f"(d[41]), "+f"(d[42]), "+f"(d[43]), "+f"(d[44]), "+f"(d[45]), "+f"(d[46]), "+f"(d[47]), "+f"(d[48]), "+f"(d[49]), "+f"(d[50]), "+f"(d[51]), "+f"(d[52]), "+f"(d[53]), "+f"(d[54]), "+f"(d[55]), "+f"(d[56]), "+f"(d[57]), "+f"(d[58]), "+f"(d[59]), "+f"(d[60]), "+f"(d[61]), "+f"(d[62]), "+f"(d[63])
        : "r"(a[0]), "r"(a[1]), "r"(a[2]), "r"(a[3]), "r"(db), "r"(8u), "r"(acc));
}
template <> __device__ __forceinline__ void cv_mma<1>(float (&d)[64], const uint32_t (&a)[4], uint32_t db, int acc) {
    asm volatile("{\n.reg .pred p;\n.reg .b64 b;\nsetp.ne.b32 p, %62, 0;\nmov.b64 b, {%60, %61};\n"
        "wgmma.mma_async.sync.aligned.m64n112k16.f32.bf16.bf16 {%0,%1,%2,%3,%4,%5,%6,%7,%8,%9,%10,%11,%12,%13,%14,%15,%16,%17,%18,%19,%20,%21,%22,%23,%24,%25,%26,%27,%28,%29,%30,%31,%32,%33,%34,%35,%36,%37,%38,%39,%40,%41,%42,%43,%44,%45,%46,%47,%48,%49,%50,%51,%52,%53,%54,%55}, {%56,%57,%58,%59}, b, p, 1, 1, 0;\n}\n"
        : "+f"(d[0]), "+f"(d[1]), "+f"(d[2]), "+f"(d[3]), "+f"(d[4]), "+f"(d[5]), "+f"(d[6]), "+f"(d[7]), "+f"(d[8]), "+f"(d[9]), "+f"(d[10]), "+f"(d[11]), "+f"(d[12]), "+f"(d[13]), "+f"(d[14]), "+f"(d[15]), "+f"(d[16]), "+f"(d[17]), "+f"(d[18]), "+f"(d[19]), "+f"(d[20]), "+f"(d[21]), "+f"(d[22]), "+f"(d[23]), "+f"(d[24]), "+f"(d[25]), "+f"(d[26]), "+f"(d[27]), "+f"(d[28]), "+f"(d[29]), "+f"(d[30]), "+f"(d[31]), "+f"(d[32]), "+f"(d[33]), "+f"(d[34]), "+f"(d[35]), "+f"(d[36]), "+f"(d[37]), "+f"(d[38]), "+f"(d[39]), "+f"(d[40]), "+f"(d[41]), "+f"(d[42]), "+f"(d[43]), "+f"(d[44]), "+f"(d[45]), "+f"(d[46]), "+f"(d[47]), "+f"(d[48]), "+f"(d[49]), "+f"(d[50]), "+f"(d[51]), "+f"(d[52]), "+f"(d[53]), "+f"(d[54]), "+f"(d[55])
        : "r"(a[0]), "r"(a[1]), "r"(a[2]), "r"(a[3]), "r"(db), "r"(8u), "r"(acc));
}
template <> __device__ __forceinline__ void cv_mma<2>(float (&d)[64], const uint32_t (&a)[4], uint32_t db, int acc) {
    asm volatile("{\n.reg .pred p;\n.reg .b64 b;\nsetp.ne.b32 p, %54, 0;\nmov.b64 b, {%52, %53};\n"
        "wgmma.mma_async.sync.aligned.m64n96k16.f32.bf16.bf16 {%0,%1,%2,%3,%4,%5,%6,%7,%8,%9,%10,%11,%12,%13,%14,%15,%16,%17,%18,%19,%20,%21,%22,%23,%24,%25,%26,%27,%28,%29,%30,%31,%32,%33,%34,%35,%36,%37,%38,%39,%40,%41,%42,%43,%44,%45,%46,%47}, {%48,%49,%50,%51}, b, p, 1, 1, 0;\n}\n"
        : "+f"(d[0]), "+f"(d[1]), "+f"(d[2]), "+f"(d[3]), "+f"(d[4]), "+f"(d[5]), "+f"(d[6]), "+f"(d[7]), "+f"(d[8]), "+f"(d[9]), "+f"(d[10]), "+f"(d[11]), "+f"(d[12]), "+f"(d[13]), "+f"(d[14]), "+f"(d[15]), "+f"(d[16]), "+f"(d[17]), "+f"(d[18]), "+f"(d[19]), "+f"(d[20]), "+f"(d[21]), "+f"(d[22]), "+f"(d[23]), "+f"(d[24]), "+f"(d[25]), "+f"(d[26]), "+f"(d[27]), "+f"(d[28]), "+f"(d[29]), "+f"(d[30]), "+f"(d[31]), "+f"(d[32]), "+f"(d[33]), "+f"(d[34]), "+f"(d[35]), "+f"(d[36]), "+f"(d[37]), "+f"(d[38]), "+f"(d[39]), "+f"(d[40]), "+f"(d[41]), "+f"(d[42]), "+f"(d[43]), "+f"(d[44]), "+f"(d[45]), "+f"(d[46]), "+f"(d[47])
        : "r"(a[0]), "r"(a[1]), "r"(a[2]), "r"(a[3]), "r"(db), "r"(8u), "r"(acc));
}
template <> __device__ __forceinline__ void cv_mma<3>(float (&d)[64], const uint32_t (&a)[4], uint32_t db, int acc) {
    asm volatile("{\n.reg .pred p;\n.reg .b64 b;\nsetp.ne.b32 p, %46, 0;\nmov.b64 b, {%44, %45};\n"
        "wgmma.mma_async.sync.aligned.m64n80k16.f32.bf16.bf16 {%0,%1,%2,%3,%4,%5,%6,%7,%8,%9,%10,%11,%12,%13,%14,%15,%16,%17,%18,%19,%20,%21,%22,%23,%24,%25,%26,%27,%28,%29,%30,%31,%32,%33,%34,%35,%36,%37,%38,%39}, {%40,%41,%42,%43}, b, p, 1, 1, 0;\n}\n"
        : "+f"(d[0]), "+f"(d[1]), "+f"(d[2]), "+f"(d[3]), "+f"(d[4]), "+f"(d[5]), "+f"(d[6]), "+f"(d[7]), "+f"(d[8]), "+f"(d[9]), "+f"(d[10]), "+f"(d[11]), "+f"(d[12]), "+f"(d[13]), "+f"(d[14]), "+f"(d[15]), "+f"(d[16]), "+f"(d[17]), "+f"(d[18]), "+f"(d[19]), "+f"(d[20]), "+f"(d[21]), "+f"(d[22]), "+f"(d[23]), "+f"(d[24]), "+f"(d[25]), "+f"(d[26]), "+f"(d[27]), "+f"(d[28]), "+f"(d[29]), "+f"(d[30]), "+f"(d[31]), "+f"(d[32]), "+f"(d[33]), "+f"(d[34]), "+f"(d[35]), "+f"(d[36]), "+f"(d[37]), "+f"(d[38]), "+f"(d[39])
        : "r"(a[0]), "r"(a[1]), "r"(a[2]), "r"(a[3]), "r"(db), "r"(8u), "r"(acc));
}
template <> __device__ __forceinline__ void cv_mma<4>(float (&d)[64], const uint32_t (&a)[4], uint32_t db, int acc) {
    asm volatile("{\n.reg .pred p;\n.reg .b64 b;\nsetp.ne.b32 p, %38, 0;\nmov.b64 b, {%36, %37};\n"
        "wgmma.mma_async.sync.aligned.m64n64k16.f32.bf16.bf16 {%0,%1,%2,%3,%4,%5,%6,%7,%8,%9,%10,%11,%12,%13,%14,%15,%16,%17,%18,%19,%20,%21,%22,%23,%24,%25,%26,%27,%28,%29,%30,%31}, {%32,%33,%34,%35}, b, p, 1, 1, 0;\n}\n"
        : "+f"(d[0]), "+f"(d[1]), "+f"(d[2]), "+f"(d[3]), "+f"(d[4]), "+f"(d[5]), "+f"(d[6]), "+f"(d[7]), "+f"(d[8]), "+f"(d[9]), "+f"(d[10]), "+f"(d[11]), "+f"(d[12]), "+f"(d[13]), "+f"(d[14]), "+f"(d[15]), "+f"(d[16]), "+f"(d[17]), "+f"(d[18]), "+f"(d[19]), "+f"(d[20]), "+f"(d[21]), "+f"(d[22]), "+f"(d[23]), "+f"(d[24]), "+f"(d[25]), "+f"(d[26]), "+f"(d[27]), "+f"(d[28]), "+f"(d[29]), "+f"(d[30]), "+f"(d[31])
        : "r"(a[0]), "r"(a[1]), "r"(a[2]), "r"(a[3]), "r"(db), "r"(8u), "r"(acc));
}
template <> __device__ __forceinline__ void cv_mma<5>(float (&d)[64], const uint32_t (&a)[4], uint32_t db, int acc) {
    asm volatile("{\n.reg .pred p;\n.reg .b64 b;\nsetp.ne.b32 p, %30, 0;\nmov.b64 b, {%28, %29};\n"
        "wgmma.mma_async.sync.aligned.m64n48k16.f32.bf16.bf16 {%0,%1,%2,%3,%4,%5,%6,%7,%8,%9,%10,%11,%12,%13,%14,%15,%16,%17,%18,%19,%20,%21,%22,%23}, {%24,%25,%26,%27}, b, p, 1, 1, 0;\n}\n"
        : "+f"(d[0]), "+f"(d[1]), "+f"(d[2]), "+f"(d[3]), "+f"(d[4]), "+f"(d[5]), "+f"(d[6]), "+f"(d[7]), "+f"(d[8]), "+f"(d[9]), "+f"(d[10]), "+f"(d[11]), "+f"(d[12]), "+f"(d[13]), "+f"(d[14]), "+f"(d[15]), "+f"(d[16]), "+f"(d[17]), "+f"(d[18]), "+f"(d[19]), "+f"(d[20]), "+f"(d[21]), "+f"(d[22]), "+f"(d[23])
        : "r"(a[0]), "r"(a[1]), "r"(a[2]), "r"(a[3]), "r"(db), "r"(8u), "r"(acc));
}
template <> __device__ __forceinline__ void cv_mma<6>(float (&d)[64], const uint32_t (&a)[4], uint32_t db, int acc) {
    asm volatile("{\n.reg .pred p;\n.reg .b64 b;\nsetp.ne.b32 p, %22, 0;\nmov.b64 b, {%20, %21};\n"
        "wgmma.mma_async.sync.aligned.m64n32k16.f32.bf16.bf16 {%0,%1,%2,%3,%4,%5,%6,%7,%8,%9,%10,%11,%12,%13,%14,%15}, {%16,%17,%18,%19}, b, p, 1, 1, 0;\n}\n"
        : "+f"(d[0]), "+f"(d[1]), "+f"(d[2]), "+f"(d[3]), "+f"(d[4]), "+f"(d[5]), "+f"(d[6]), "+f"(d[7]), "+f"(d[8]), "+f"(d[9]), "+f"(d[10]), "+f"(d[11]), "+f"(d[12]), "+f"(d[13]), "+f"(d[14]), "+f"(d[15])
        : "r"(a[0]), "r"(a[1]), "r"(a[2]), "r"(a[3]), "r"(db), "r"(8u), "r"(acc));
}
template <> __device__ __forceinline__ void cv_mma<7>(float (&d)[64], const uint32_t (&a)[4], uint32_t db, int acc) {
    asm volatile("{\n.reg .pred p;\n.reg .b64 b;\nsetp.ne.b32 p, %14, 0;\nmov.b64 b, {%12, %13};\n"
        "wgmma.mma_async.sync.aligned.m64n16k16.f32.bf16.bf16 {%0,%1,%2,%3,%4,%5,%6,%7}, {%8,%9,%10,%11}, b, p, 1, 1, 0;\n}\n"
        : "+f"(d[0]), "+f"(d[1]), "+f"(d[2]), "+f"(d[3]), "+f"(d[4]), "+f"(d[5]), "+f"(d[6]), "+f"(d[7])
        : "r"(a[0]), "r"(a[1]), "r"(a[2]), "r"(a[3]), "r"(db), "r"(8u), "r"(acc));
}
__device__ __forceinline__ void stsm4t(uint32_t addr, uint32_t r0, uint32_t r1, uint32_t r2, uint32_t r3) {
    asm volatile("stmatrix.sync.aligned.m8n8.x4.trans.shared.b16 [%0], {%1,%2,%3,%4};" ::"r"(addr), "r"(r0), "r"(r1), "r"(r2), "r"(r3) : "memory");
}
__device__ __forceinline__ void cp16(uint32_t dst, const void* src, int n = 16) {
    asm volatile("cp.async.cg.shared.global.L2::128B [%0], [%1], 16, %2;" ::"r"(dst), "l"(src), "r"(n) : "memory");
}
__device__ __forceinline__ void cp_arrive(uint32_t bar) { asm volatile("cp.async.mbarrier.arrive.noinc.shared::cta.b64 [%0];" ::"r"(bar) : "memory"); }
__device__ __forceinline__ void lds64(uint32_t& x, uint32_t& y, uint32_t a) { asm volatile("ld.shared.v2.b32 {%0,%1}, [%2];" : "=r"(x), "=r"(y) : "r"(a) : "memory"); }
__device__ __forceinline__ void sts128(uint32_t a, uint32_t x, uint32_t y, uint32_t z, uint32_t w) {
    asm volatile("st.shared.v4.b32 [%0], {%1,%2,%3,%4};" ::"r"(a), "r"(x), "r"(y), "r"(z), "r"(w) : "memory");
}
__device__ __forceinline__ uint32_t bfma2(uint32_t a, uint32_t b, uint32_t c) {
    uint32_t r;
    asm("fma.rn.bf16x2 %0, %1, %2, %3;" : "=r"(r) : "r"(a), "r"(b), "r"(c));
    return r;
}
#define CV_NS 4
#define CV_W 1
constexpr int CV_GC = 8 / CV_NS, CV_NA = (CV_W + 2) * CV_NS;
struct CvAddr { uint32_t pa[2], p0[4], db, rdy, xw, xr, bar; bool wrap, neg[2]; };
template <int G> __device__ __forceinline__ void cv_load(uint32_t (&a)[CV_NA][4], const CvAddr& p) {
    if constexpr (G % CV_GC == 0) mbar_wait(p.rdy + 8 * (G / CV_GC), 0);
#pragma unroll
    for (int i = G * CV_NS; i < (G + 1) * CV_NS; i++) {
        const int of = (i / 2 % 2) * CV_QG + (i / 8) * CV_SL + 256 * (i % 2 + (i / 2 & 2));
        if ((i & 5) == 0) {
#pragma unroll
            for (int e = 0; e < 4; e++) asm volatile("ld.shared.b32 %0, [%1];" : "=r"(a[i % CV_NA][e]) : "r"(p.p0[e] + of) : "memory");
            if (i < 8) { if (p.neg[0]) a[i % CV_NA][0] = 0; if (p.neg[1]) a[i % CV_NA][2] = 0; }
        } else {
            lds64(a[i % CV_NA][0], a[i % CV_NA][1], p.pa[0] + of - 256);
            lds64(a[i % CV_NA][2], a[i % CV_NA][3], p.pa[1] + of - 256);
        }
    }
}
__device__ __forceinline__ float vadd(float a, float b) {
    float r;
    asm volatile("add.f32 %0, %1, %2;" : "=f"(r) : "f"(a), "f"(b));
    return r;
}
template <int K> __device__ __forceinline__ uint32_t cv_tail(float (&d)[64], bool wrap) {
    float* z = d + 56 - 8 * K;
    z[4] = vadd(z[4], K > 0 ? z[10] : 0.f);
    if constexpr (K > 0) z[5] = vadd(z[5], z[11]);
    z[0] = vadd(z[0], z[6]);
    z[1] = vadd(z[1], z[7]);
    return pack2(wrap ? (K > 0 ? z[8] : 0.f) : z[4], wrap ? z[4] : z[0]);
}
template <int K> __device__ __forceinline__ uint32_t cv_fin(const float (&d)[64], uint32_t x) { return pack2(d[61 - 8 * K] + lo2f(x), d[57 - 8 * K] + hi2f(x)); }
template <int G>
__device__ __forceinline__ void cv_steps(float (&d)[2][64], uint32_t (&a)[CV_NA][4], uint32_t (&tv)[2][8], const CvAddr& p) {
    constexpr int K = G / CV_GC, GN = 8 * CV_GC;
    constexpr int T = G - CV_W - CV_GC, F = T - 1, TK = T / CV_GC, FK = F / CV_GC;
    if constexpr (G == 0) cv_load<0>(a, p);
    if constexpr (G < GN) {
        wgmma_fence();
#pragma unroll
        for (int i = G * CV_NS; i < (G + 1) * CV_NS; i++)
            cv_mma<K>(d[i / 2 % 2], a[i % CV_NA], p.db + (i / 2 % 2) * (CV_HPL / 8) + 16 * K + 2 * (i % 2 + (i / 2 & 2)), i & ~2 ? 1 : p.bar >> 8);
        wgmma_commit();
    }
    if constexpr (G < GN - 1) cv_load<G + 1>(a, p);
    if constexpr (T >= 0 && T % CV_GC == 0) {
        tv[0][TK] = cv_tail<TK>(d[0], p.wrap);
        tv[1][TK] = cv_tail<TK>(d[1], p.wrap);
        if constexpr (TK & 1) sts128(p.xw + TK / 2 * 512, tv[0][TK - 1], tv[0][TK], tv[1][TK - 1], tv[1][TK]);
    }
    if constexpr (F >= 0 && F % (2 * CV_GC) == CV_GC) {
        const uint4 x = lds128(p.xr + FK / 2 * 512);
        tv[0][FK - 1] = cv_fin<FK - 1>(d[0], x.x); tv[0][FK] = cv_fin<FK>(d[0], x.y);
        tv[1][FK - 1] = cv_fin<FK - 1>(d[1], x.z); tv[1][FK] = cv_fin<FK>(d[1], x.w);
    }
    if constexpr (G < GN - 1) wgmma_wait<CV_W>();
    if constexpr (G == GN - 1) wgmma_wait<0>();
    if constexpr (T >= 0 && T % (2 * CV_GC) == CV_GC) named_bar_sync(p.bar, 128);
    if constexpr (F < GN - CV_GC) cv_steps<G + 1>(d, a, tv, p);
}

#define CV_PF 7
#define Y_FIRST 1
#define Y_HOLD 0
#define PS2_EARLY 1
#define PS1_EARLY 1
#define FMOVE 1
#define SENDC 1
#define HDELAY 0
#define NH16 1
#define REL 3
#define W3_AT -1
struct MegaMaps {
    CUtensorMap q, act;
    CUtensorMap a64, w1, w2, w3, w4;
    CUtensorMap k, v, y;
};

__global__ void __cluster_dims__(2, 1, 1) __launch_bounds__(384, 1)
mega_kernel(const __grid_constant__ MegaMaps tm, bf16* __restrict__ outp, bf16* act, const bf16* __restrict__ w1p, const bf16* __restrict__ w2p,
            const bf16* __restrict__ w3p, const bf16* __restrict__ xq, const bf16* __restrict__ kp, const bf16* __restrict__ vp,
            const bf16* __restrict__ shk, const bf16* __restrict__ ssk, const bf16* __restrict__ ssD) {
    extern __shared__ __align__(1024) uint8_t sgen[];
    const uint32_t sbase = smem_u32(sgen);
    const int warp = __shfl_sync(0xffffffffu, threadIdx.x >> 5, 0), lane = threadIdx.x & 31;
    const int rank = blockIdx.x & 1;
    const uint32_t s_bar = sbase + OFF_BAR;
    const uint32_t f5 = s_bar, e5 = s_bar + 64, f4 = s_bar + 144, e4 = s_bar + 104;
    const uint32_t b_rfull = s_bar + 176, b_role = s_bar + 184, b_stg = s_bar + 136, b_h2 = s_bar + 32;
    const uint32_t s_epi = sbase + OFF_EPI, s_stg = sbase + OFF_STG5, s_r = sbase + OFF_R;
    uint8_t* sm = sgen + CV_0;
    const uint32_t sb = sbase + CV_0;
    const int tid = threadIdx.x, wg = warp >> 2, w = warp & 3;
    const int d0 = blockIdx.x * CV_CH;
    const bool cv = blockIdx.x < D_ / CV_CH;
    const uint32_t b_full = sb + CV_BAR, b_rdy = b_full + 64, b_h = b_full + 128;
    GT(0);
    if (tid == 0) TM(0);
    auto row_at = [&](int r) { return sb + CV_SL + (r < 0 ? -8192 : 0) + ((r & 127) >> 5) * 1024 + (r & 7) * 128 + ((r >> 3) & 3) * 32 + ((r ^ rank) & 1) * 16; };
    auto load_kv = [&](int c) {
#pragma unroll
        for (int i = 0; i < 2; i++)
            asm volatile("cp.async.bulk.tensor.4d.shared::cluster.global.mbarrier::complete_tx::bytes.multicast::cluster [%0], [%1, {%3, %4, %4, %5}], [%2], %6;"
                         ::"r"(sb + (c + 1) * CV_SL + rank * 8192 + i * 4096), "l"((uint64_t)(i ? &tm.v : &tm.k)), "r"(b_full + 8 * c), "r"(d0 & ~15), "r"(0),
                         "r"(8 * c + 4 * rank), "h"((uint16_t)3) : "memory");
    };
    auto bulk = [&](uint32_t dst, const void* src, uint32_t n, uint32_t bar) {
        asm volatile("cp.async.bulk.shared::cluster.global.mbarrier::complete_tx::bytes [%0], [%1], %2, [%3];" ::"r"(dst), "l"(src), "r"(n), "r"(bar) : "memory");
    };
    auto put_h = [&](int ch) {
        const uint32_t dk = (tid & 127) ? 0 : *reinterpret_cast<const volatile uint32_t*>(sm + CV_BAR + 160 + 16 * wg + 2 * ch);
        uint4 v[4];
#pragma unroll
        for (int i = 0; i < 4; i++) v[i] = lds128(sbase + ch * 4096 + i * 2048 + (tid & 127) * 16);
        v[0].x = pack2(lo2f(v[0].x) + lo2f(dk), hi2f(v[0].x));
        v[2].x = pack2(lo2f(v[2].x) + hi2f(dk), hi2f(v[2].x));
#pragma unroll
        for (int i = 0; i < 4; i++)
            sts128(sb + CV_H + (2 * ch + (i & 2) + (tid & 1)) * CV_HPL + (127 - ((tid & 127) >> 1)) * 16 - (i & 1) * 1024, v[i].x, v[i].y, v[i].z, v[i].w);
    };
    int bi, bj, m0, tb;
    uint32_t ep;
    auto get_role = [&]() {
        mbar_wait(b_role, 0);
        int role;
        asm volatile("ld.shared.v2.b32 {%0,%1}, [%2];" : "=r"(role), "=r"(ep) : "r"(s_bar + 248) : "memory");
        bi = (role >> 3) * 2 + rank; bj = role & 7; m0 = bi * BM; tb = (role >> 3) * 2048 + rank * 128;
        return role < 64;
    };

    if (warp >= 8) {
        asm volatile("setmaxnreg.dec.sync.aligned.u32 88;");
        cluster_arrive_relaxed();
        if (!cv) cluster_wait(); else {
            const int bt = tid - 256, g = lane >> 2, t = lane & 3;
            if (bt < 16) sts128(row_at((bt & 7) - 8) + (bt >> 3) * 4096, 0, 0, 0, 0);
#pragma unroll
            for (int i = 0; i < 4; i++)
                cp16(row_at(bt) + i * 4096, (i & 1 ? vp : kp) + (size_t)(bt + (i >> 1) * 128) * D_ + d0);
            DBG_S(16 + (3));
            uint2 wa;
            asm volatile("ld.global.nc.v2.b32 {%0,%1}, [%2];" : "=r"(wa.x), "=r"(wa.y) : "l"(shk + (d0 + g) * 4));
            const int mi = lane >> 3, r0 = 32 * w + 8 * ((lane >> 1) & 3) - (lane & 1);
            const uint32_t ka0 = row_at(r0 + 2 * mi - 3), ka1 = row_at(r0 + 2 * (mi & 1) + 5) + (mi >> 1) * 8192;
            const uint32_t va0 = row_at(r0 + 2 * mi + 1) + 4096, va1 = row_at(r0 - 1) + 4096 + (mi & 1) * 8192;
            const uint32_t qd = sb + g * CV_QG + (32 * w + 8 * t) * 8, qd0 = qd + (t & 2) * 16, qd1 = qd + (~t & 2) * 16;
            const uint32_t w0 = __byte_perm(wa.x, 0, 0x1010), w1 = __byte_perm(wa.x, 0, 0x3232), w2 = __byte_perm(wa.y, 0, 0x1010), w3 = __byte_perm(wa.y, 0, 0x3232);
            cluster_wait();
            DBG_S(16 + (5));
            asm volatile("cp.async.wait_all;" ::: "memory");
            named_bar_sync(7, 128);
            DBG_S(16 + (1));
            struct KV { uint32_t k[2][6], v[2][5]; };
            auto get = [&](KV& x, uint32_t so) {
                ldsm4t(x.k[0][0], x.k[0][1], x.k[0][2], x.k[0][3], ka0 + so);
                ldsm4t(x.k[0][4], x.k[0][5], x.k[1][4], x.k[1][5], ka1 + so);
                ldsm4t(x.k[1][0], x.k[1][1], x.k[1][2], x.k[1][3], ka0 + so + 8192);
                asm volatile("ldmatrix.sync.aligned.m8n8.x2.trans.shared.b16 {%0,%1}, [%2];" : "=r"(x.v[0][0]), "=r"(x.v[1][0]) : "r"(va1 + so));
                ldsm4t(x.v[0][1], x.v[0][2], x.v[0][3], x.v[0][4], va0 + so);
                ldsm4t(x.v[1][1], x.v[1][2], x.v[1][3], x.v[1][4], va0 + so + 8192);
            };
            auto build = [&](int c, const KV& x, KV& nx) {
                const uint32_t so = c * CV_SL;
                DBG_F(1);
                uint32_t early;
                asm volatile("{\n.reg .pred p;\nmbarrier.test_wait.parity.shared::cta.b64 p, [%1], 0;\nvote.sync.all.pred p, p, -1;\nselp.u32 %0, 1, 0, p;\n}"
                             : "=r"(early) : "r"(b_full + 8 * (c < 7 ? c + 1 : c)) : "memory");
                if (early) get(nx, so + CV_SL);
                DBG_F(2);
                uint32_t p[8][2];
#pragma unroll
                for (int sg = 0; sg < 2; sg++) {
                    uint32_t u[5], ke[6];
#pragma unroll
                    for (int i = 0; i < 6; i++) ke[i] = __byte_perm(x.k[sg][i], x.k[sg][i ? i - 1 : 0], 0x5432);
#pragma unroll
                    for (int i = 0; i < 5; i++) {
                        u[i] = bmul2(bfma2(x.k[sg][i + 1], w0, bfma2(ke[i + 1], w1, bfma2(x.k[sg][i], w2, bmul2(ke[i], w3)))), x.v[sg][i]);
                        if (i) { p[2 * i - 1][sg] = u[i]; p[2 * i - 2][sg] = __byte_perm(u[i], u[i - 1], 0x5432); }
                    }
                }
                DBG_F(3);
#pragma unroll
                for (int j = 0; j < 4; j++) sts128((j & 2 ? qd1 : qd0) + so + 16 * (j & 1), p[2 * j][0], p[2 * j][1], p[2 * j + 1][0], p[2 * j + 1][1]);
                __syncwarp();
                DBG_F(4);
                if (lane == 0) {
                    mbar_arrive(b_rdy + 8 * c);
                    if (c == w) {
                        if (c < 3) load_kv(c + 5);
                        else { bulk(sbase + 16384, ssk + (size_t)(d0 + 4) * S_, 16384, b_h + 16); bulk(b_full + 192, ssD + d0, 16, b_h + 16); }
                    }
                    if (c == w + 4 && (CV_PF >> w & 1)) {
                        const uint32_t n = w == 0 ? 32768 : w == 3 ? 57344 : 16384;
                        const char* src = reinterpret_cast<const char*>(w == 0 ? xq : w == 1 ? w1p : w == 2 ? w2p : w3p) + (size_t)blockIdx.x * n;
                        asm volatile("cp.async.bulk.prefetch.L2.global [%0], %1;" ::"l"(src), "r"(n) : "memory");
                    }
                }
                DBG_F(5);
                named_bar_sync(7, 128);
                DBG_F(6);
                DBG_S(16 + (c == 0 ? 4 : 5 + c));
                if (!early) { mbar_wait(b_full + 8 * c + 8, 0); get(nx, so + CV_SL); }
                DBG_F(7);
            };
            KV x0, x1;
            get(x0, 0);
#pragma unroll 1
            for (int c = 0; c < 8; c += 2) { build(c, x0, x1); build(c + 1, x1, x0); }
            mbar_wait(b_h + 16, 0);
            put_h(4); put_h(6);
            fence_async_smem();
            __syncwarp();
            if (lane == 0) mbar_arrive(b_full);
            named_bar_sync(7, 128);
            DBG_S(16 + (13));
        }
    } else {
        if (elect_one()) {
            mbar_init(b_full + 8 * warp, warp ? 1 : 4);
            mbar_init(b_rdy + 8 * warp, 4);
            if (warp) mbar_expect_tx(b_full + 8 * warp, 16384);
            if (w == 0 && cv) {
                mbar_init(b_h + 8 * wg, 1);
                mbar_expect_tx(b_h + 8 * wg, 8192 + 16);
                fence_async_smem();
                bulk(sbase + wg * 8192, ssk + (size_t)(d0 + 2 * wg) * S_, 8192, b_h + 8 * wg);
                bulk(b_full + 160 + 16 * wg, ssD + d0, 16, b_h + 8 * wg);
            }
            mbar_init(s_bar + 8 * warp, 1);
            mbar_init(s_bar + 64 + 8 * warp, 4);
            mbar_init(s_bar + 128 + 8 * warp, warp < 2 ? 4 << warp : warp == 6 ? 2 : 1);
            if (wg) mbar_init(s_bar + 160 + 8 * warp, 8);
            if (warp == 0) mbar_arrive(f5);
            if (warp == 7) mbar_expect_tx(b_role, 8);
            if (warp == 1) { mbar_init(b_h + 16, 1); mbar_expect_tx(b_h + 16, 16384 + 16); }
            if (w == 2) sts128(s_bar + 224 + 16 * wg, 0, 0, 0, 0);
            asm volatile("fence.mbarrier_init.release.cluster;" ::: "memory");
            if (warp == 2) { prefetch_tmap(&tm.k); prefetch_tmap(&tm.v); }
        }
        __syncwarp();
        DBG_W(1);
        cluster_arrive_relaxed();
        asm volatile("setmaxnreg.inc.sync.aligned.u32 208;");
        DBG_W(2);
        const int zi = (tid & 127) - 32;
        if (zi >= 0 && zi < 48) sts128(sb + CV_H + (4 * wg + (zi / 6 & 3) + (zi / 24) * 8) * CV_HPL + 2048 + (zi % 6) * 16, 0, 0, 0, 0);
        DBG_W(3);
        cluster_wait();
        DBG_W(5);
        if (cv) {
            if (tid == 32) {
#pragma unroll 1
                for (int c = 1; c < 5; c++) load_kv(c);
                prefetch_tmap(&tm.y);
            }
            __syncwarp();
            DBG_W(6);
            const int g = lane >> 2, t = lane & 3;
            const int x0 = 32 + 8 * w + g - 2 * t;
            CvAddr p;
            p.rdy = b_rdy;
            p.bar = 1 + wg;
            p.xr = sbase + (warp ^ 2) * 2048 + lane * 16;
            p.xw = sbase + warp * 2048 + (g * 4 + ((t - (w >> 1)) & 3)) * 16;
            p.wrap = t == 0 && w >= 2;
            mbar_wait(b_h + 8 * wg, 0);
            DBG_W(4);
            put_h(2 * wg);
            fence_async_smem();
            named_bar_sync(1 + wg, 128);
            float acc[2][64];
            zero_acc(acc[0]); zero_acc(acc[1]);
#pragma unroll 1
            for (int round = 0; round < 2; round++) {
                const int ch = round * 4 + 2 * wg;
                uint32_t a[CV_NA][4], tv[2][8];
#pragma unroll
                for (int e = 0; e < 2; e++) {
                    const int x = x0 - 8 * e;
                    p.neg[e] = x < 32;
                    p.pa[e] = sb + ch * CV_QG + 8 * (x ^ (x >> 2 & 4));
                    p.p0[2 * e] = p.pa[e] + (x < 32 ? 768 + 4 - CV_SL : -256);
                    p.p0[2 * e + 1] = p.pa[e] + (x < 32 ? 768 : -256 + 4);
                }
                p.db = (((sb + CV_H + ch * 2 * CV_HPL) & 0x3FFFF) >> 4) | ((CV_HPL / 16) << 16);
                if (round) mbar_wait(b_full, 0);
                DBG_S(7 + 3 * round);
                cv_steps<0>(acc, a, tv, p);
                DBG_S(8 + 3 * round);
                const int r128 = 4 * (lane >> 3) + 2 * (lane & 1) + ((~lane >> 2) & 1);
#pragma unroll
                for (int i = 0; i < 2; i++) {
                    const uint32_t ta = sb + ((ch + i + 1) & 7) * CV_SL + 12288 + r128 * 128 + ((((~lane & 2) * 2 + w) ^ (r128 & 7)) << 4);
                    stsm4t(ta, tv[i][0], tv[i][1], tv[i][2], tv[i][3]);
                    stsm4t(ta + 2048, tv[i][4], tv[i][5], tv[i][6], tv[i][7]);
                }
                fence_async_smem();
                named_bar_sync(1 + wg, 128);
                if ((tid & 127) < 2) {
                    const int d = d0 + ch + (tid & 1);
                    asm volatile("cp.async.bulk.tensor.4d.global.shared::cta.bulk_group [%0, {%2, %3, %4, %2}], [%1];"
                                 ::"l"((uint64_t)&tm.y), "r"(sb + ((ch + (tid & 1) + 1) & 7) * CV_SL + 12288), "r"(0), "r"(4 * (d >> 8)), "r"(d & 255) : "memory");
                    asm volatile("cp.async.bulk.commit_group;" ::: "memory");
                }
                __syncwarp();
                DBG_S(9 + 3 * round);
            }
        }
    }
    int warp2 = warp;
    asm volatile("" : "+r"(warp2));
    if (warp2 >= 8) {
        asm volatile("setmaxnreg.dec.sync.aligned.u32 72;");
        if (warp == 8) { if (elect_one()) {
            if (rank == 0) {
                uint32_t smid;
                asm volatile("mov.u32 %0, %%smid;" : "=r"(smid));
                const int t = smid >> 1;
                int team = t < 32 ? t & 7 : t < 60 ? 1 + (t - 32) % 7 : t < 62 ? t - 54 : 0;
                const unsigned long long arr = atomicAdd(reinterpret_cast<unsigned long long*>(g_ticket + 16 * FL_PITCH), 1ull);
                const uint32_t e1 = (uint32_t)(arr / NCL) + 1;
                unsigned int* tk = g_ticket + (e1 & 1) * 8 * FL_PITCH;
                int slot = atomicAdd(tk + team * FL_PITCH, 1u);
                atomicAdd(g_ticket + 17 * FL_PITCH, 1u);
                if (blockIdx.x < 16) g_ticket[((~e1 & 1) * 8 + (blockIdx.x >> 1)) * FL_PITCH] = 0;
                if (slot >= 8) {
                    const long long t0 = clock64();
                    while ((int)(*(volatile unsigned int*)(g_ticket + 17 * FL_PITCH) - e1 * NCL) < 0 && clock64() - t0 < 100000) {}
                    for (team = 0; team < 8; team++)
                        if ((slot = atomicAdd(tk + team * FL_PITCH, 1u)) < 8) break;
                }
#pragma unroll
                for (int i = 0; i < 2; i++)
                    asm volatile("st.async.weak.shared::cluster.mbarrier::complete_tx::bytes.v2.b32 [%0], {%1, %2}, [%3];"
                                 ::"r"(mapa_u32(s_bar + 248, i)), "r"(team * 8 + slot), "r"(e1), "r"(mapa_u32(b_role, i)) : "memory");
            }
            if (get_role()) {
            TM(2);
            mbar_expect_tx(b_rfull, 32768);
            tma_load_2d(sbase + 16384, &tm.q, b_rfull, bj * 128, m0);
            tma_load_2d(sb + 8 * CV_SL, &tm.q, b_rfull, bj * 128 + 64, m0);
            int s5 = 0, s4 = 0;
            uint32_t p5 = 0, p4 = 1;
            auto putB = [&](const CUtensorMap* tB, int kc, uint32_t bytes) {
                const uint32_t full = f5 + 8 * s5;
                mbar_wait(full + 64, (p5 >> s5) & 1);
                mbar_expect_tx(full, bytes);
                tma_load_2d_mc(s_r + 16384 + rank * 8192 + s5 * R5_STAGE, tB, full, bj * 128 + rank * 64, kc);
                p5 ^= 1u << s5;
            };
            auto putA = [&](int c, int r) {
                tma_load_2d(s_r + s5 * R5_STAGE, &tm.act, f5 + 8 * s5, c, r);
                if (++s5 == R5_N) s5 = 0;
            };
            prefetch_tmap(&tm.act); prefetch_tmap(&tm.w1); prefetch_tmap(&tm.w2); prefetch_tmap(&tm.w3); prefetch_tmap(&tm.w4); prefetch_tmap(&tm.a64);
            auto own_first = [&](int it) {
                const int hf = it >= 9, c = it - 2 - 7 * hf;
                return (it < 2 ? 2 * bj + it : 2 * (c + (c >= bj)) + hf) * BK;
            };
            const unsigned int n8 = 8 * ep, nh = NH16 ? ((bi == 0 || bi == 15) ? 12 * ep : 2 * n8) : (bi == 0 || bi == 15) ? 2 * n8 : 3 * n8;
#pragma unroll 1
            for (int layer = 0; layer < 2; layer++) {
                s5 = 2;
#pragma unroll 1
                for (int kk = -(layer | Y_FIRST); kk < 5 - (layer | Y_FIRST); kk++) {
                    if (kk & 4) {
                        if (layer == 0) { TM(1); wait_flag(flag_ptr(0, FL_CS, 8 + bj), 8 * n8); TM(4); fence_proxy_async(); }
                        mbar_wait(e5 + 8, (p5 >> 1) & 1);
                        mbar_expect_tx(f5 + 8, 32768);
                        tma_load_2d(s_r + R5_STAGE, &tm.act, f5 + 8, (bj >> 1) * 256 + rank * 128, R_Y + (tb & ~255) + (bj & 1) * 128);
                        tma_load_2d(s_r + R5_STAGE + 16384, &tm.act, f5 + 8, (bj >> 1) * 256 + rank * 128 + 64, R_Y + (tb & ~255) + (bj & 1) * 128);
                        p5 ^= 2;
                        if (layer == 0) TM(5);
                    } else {
                        if (kk == Y_HOLD && layer == 0) mbar_wait(f5 + 8, 0);
                        putB(&tm.w1, own_first(kk), kk < 2 ? 16384 : R5_STAGE);
                        if (++s5 == R5_N) s5 = 0;
                    }
                }
                s5 = 4;
#pragma unroll 1
                for (int kk = 2; kk < 16; kk++) {
                    const int kc = own_first(kk);
                    if (kk >= 4) putB(&tm.w1, kc, R5_STAGE);
                    if (kk == 2 || kk == 9) {
                        wait_flag(flag_ptr(layer, FL_XA + (kk & 1), bi), n8);
                        if (layer == 0 && kk == 2) TM(14);
                        DP(8 * (FL_XA + (kk & 1)) + 3);
                        fence_proxy_async();
                        DP(8 * (FL_XA + (kk & 1)) + 4);
                    }
                    putA(kc, R_XA + tb);
                }
                mbar_wait(e5 + 24, (p5 >> 3) & 1);
                mbar_arrive(f5 + 24);
                p5 ^= 8;
                s5 = 4;
#pragma unroll 1
                for (int kk = 0; kk < 5; kk++) { putB(&tm.w2, own_first(kk), kk < 2 ? 16384 : R5_STAGE); if (++s5 == R5_N) s5 = 0; }
                s5 = 1;
#pragma unroll 1
                for (int kk = 2; kk < 16; kk++) {
                    const int kc = own_first(kk);
                    if (kk >= 5) putB(&tm.w2, kc, R5_STAGE);
                    if (kk == 2 || kk == 9) {
                        wait_flag(flag_ptr(layer, FL_H + (kk & 1), bi), nh);
                        DP(8 * (FL_H + (kk & 1)) + 3);
                        fence_proxy_async();
                        DP(8 * (FL_H + (kk & 1)) + 4);
                    }
                    putA(kc, R_H + layer * R_HP + m0 + (int)((0x4031u >> (kc >> 6 & 12)) & 7) - 2);
                }
#pragma unroll 1
                for (int it = 0; it < 32; it++) {
                    const int kc = it >= 16 ? (it - 16) * BK : own_first(it);
                    const int nb = it < 16 ? 4 : 3, n0 = bj * 448 + (it < 16 ? 0 : 256);
                    if (it > 0 && it < 4) {
                        const int i = (it - 1) * 3 >> 1;
                        mbar_wait(e5 + 8 * i, (p5 >> i) & 1);
                        mbar_wait(e5 + 8 * i + 8, (p5 >> (i + 1)) & 1);
                    }
                    mbar_wait(e4 + 8 * s4, p4);
                    if (it >= 16 && it < 19) mbar_wait(e4 + 8 * s4 + 8, p4);
                    uint32_t sa = s_r + s4 * (it < 16 ? R4_STAGE : R4B_STAGE), full = f4 + 8 * s4;
                    mbar_expect_tx(full, (it < 2 ? 0 : 16384) + nb * 8192);
#pragma unroll 1
                    for (int j = (it ^ rank) & 1; j < nb; j += 2) tma_load_2d_mc(sa + (it < 16 ? -32768 : 16384) + j * 8192, &tm.w3, full, n0 + j * 64, kc);
                    if (it == 3 || it == 9) {
                        wait_flag(flag_ptr(layer, FL_X1 + (it >> 3), bi), n8);
                        DP(8 * (FL_X1 + (it >> 3)) + 3);
                        fence_proxy_async();
                        DP(8 * (FL_X1 + (it >> 3)) + 4);
                        if (it == 3) tma_load_2d(s_r + 2 * R4_STAGE, &tm.act, f4 + 16, own_first(2), R_X1 + tb);
                    }
                    if (it >= 3) tma_load_2d(sa, &tm.act, full, kc, R_X1 + tb);
                    if (it >= PF4A && it < PF4A + PF4N && layer == 0) tma_prefetch_2d(&tm.w4, bj * 128 + rank * 64, (7 * (bi >> 1) + it - PF4A) * BK);
                    if (++s4 == R4_N) { s4 = 0; p4 ^= 1; }
                }
                wait_flag(flag_ptr(layer, FL_H2, bi), n8);
                fence_proxy_async();
                s5 = 0;
#pragma unroll 1
                for (int j = 0; j < 7; j++) {
                    if (j > 0 && (j & 1) == 0) {
                        mbar_wait(b_h2 + 4 * j, layer);
                        fence_proxy_async();
                    }
                    const int ra = R_H2 + (j >> 1) * 256 + tb;
#pragma unroll 1
                    for (int b = 0; b < 8; b++) {
                        if (j == 0 && b < R4_N) mbar_wait(e4 + 8 * b, p4);
                        putB(&tm.w4, (7 * b + j) * BK, R5_STAGE);
                        putA(((j & 1) * 8 + b) * BK, ra);
                    }
                }
            }
        } } } else {
            auto colsum = [&](bool is1, int bi, int bj) {
                const int pitch = is1 ? D_ : F_, c = is1 ? bj * 128 + (lane & 15) * 8 : bj * 448 + min((warp & 2) * 128 + lane * 8, 440);
                const bf16* p = (is1 ? w1p : w3p) + ((bi * 64 + (is1 ? (lane >> 4) * 32 : 0)) * pitch + c);
                float a[8];
#pragma unroll
                for (int i = 0; i < 8; i++) a[i] = 0.f;
#pragma unroll 1
                for (int r0 = is1 ? 32 : XCS; r0 < 64; r0 += 8) {
                    uint4 v[8];
#pragma unroll
                    for (int r = 0; r < 8; r++, p += pitch) v[r] = __ldg(reinterpret_cast<const uint4*>(p));
#pragma unroll
                    for (int r = 0; r < 8; r++) {
                        a[0] += lo2f(v[r].x); a[1] += hi2f(v[r].x); a[2] += lo2f(v[r].y); a[3] += hi2f(v[r].y);
                        a[4] += lo2f(v[r].z); a[5] += hi2f(v[r].z); a[6] += lo2f(v[r].w); a[7] += hi2f(v[r].w);
                    }
                }
                if (is1) {
#pragma unroll
                    for (int i = 0; i < 8; i++) a[i] += __shfl_xor_sync(0xffffffffu, a[i], 16);
                }
                float4* dst = reinterpret_cast<float4*>(g_cpart + bi * (F_ + D_) + (is1 ? F_ : 0) + c);
                dst[0] = make_float4(a[0], a[1], a[2], a[3]);
                dst[1] = make_float4(a[4], a[5], a[6], a[7]);
                asm volatile("fence.release.gpu;" ::: "memory");
                __syncwarp();
                if (lane == 0) asm volatile("red.relaxed.gpu.global.add.u32 [%0], 1;" ::"l"(flag_ptr(!is1, FL_CS, bj)) : "memory");
            };
            if (cv && warp == 10) colsum(true, blockIdx.x >> 3, blockIdx.x & 7);
            float4 keep[2];
            const bool on = get_role();
            if (on && warp == 11) {
                uint4* ps = reinterpret_cast<uint4*>(g_stats + (bi * 8 + bj) * 128) + lane;
                ps[0] = ps[32] = make_uint4(0, 0, 0, 0);
                asm volatile("fence.acq_rel.gpu;" ::: "memory");
                __syncwarp();
                if (lane == 0) mbar_arrive(b_rfull);
            }
#pragma unroll 1
            for (int layer = on ? 0 : 2; layer < 2; layer++) {
                if (warp == 10) {
#pragma unroll 1
                    for (int kind = 0; kind < 6; kind += 2) {
                        const uint32_t src = kind == FL_H ? s_stg + 1024 : s_epi, sd = kind == FL_H ? OFF_EPI : 16384;
                        const int dn = bj & 2 ? 1 : -1;
                        uint4* gh = g_halo + (layer * 144 + 8 + bi * 8 + bj) * 64 + lane;
                        const int r = kind == FL_H ? R_H + layer * R_HP + m0 : (kind == FL_XA ? R_XA : R_X1) + tb;
#pragma unroll 1
                        for (int hf = 0; hf < 2; hf++) {
                            const bool sp = hf == 0 && (SPL >> kind & 1);
                            const int lw = kind == FL_H && dn < 0 ? 64 : 0;
                            if (sp) {
                                named_bar_sync(7, 160);
                                if (lane == 0) {
                                    fence_async_smem();
                                    tma_store_2d(&tm.a64, src + lw * 128, bj * 128, r + lw);
                                }
                                __syncwarp();
                            }
                            named_bar_sync(5 + hf, sp ? 160 : 288);
                            if (lane == 0) {
                                if (FMOVE) fence_async_smem();
                                DP(8 * (kind + hf));
                                tma_store_2d(sp ? &tm.a64 : &tm.act, src + (sp ? (lw ^ 64) * 128 : hf * sd), bj * 128 + hf * 64, sp ? r + (lw ^ 64) : r);
                                asm volatile("cp.async.bulk.commit_group;" ::: "memory");
                            }
                            __syncwarp();
                            if (kind == FL_H && !SENDC) {
                                uint32_t a, b;
                                lds64(a, b, src + hf * sd + (63 - 63 * dn) * 128 + 8 * lane);
                                asm volatile("{\n.reg .b64 u, v;\nmov.b64 u, {%1, %3};\nmov.b64 v, {%2, %3};\nst.relaxed.gpu.global.v2.b64 [%0], {u, v};\n}"
                                             ::"l"(gh - dn * 512 + hf * 32), "r"(a), "r"(b), "r"(ep) : "memory");
                            }
                            if (kind + hf == FL_H + 1) {
                                uint4 v[2] = {};
                                if (HDELAY) __nanosleep(HDELAY);
#pragma unroll 1
                                for (int n = (bi + dn) & 16 ? 1 << 20 : 0; n < (1 << 20); n++) {
#pragma unroll
                                    for (int i = 0; i < 2; i++)
                                        asm volatile("{\n.reg .b64 u, v;\nld.relaxed.gpu.global.v2.b64 {u, v}, [%4];\nmov.b64 {%0, %1}, u;\nmov.b64 {%2, %3}, v;\n}"
                                                     : "=r"(v[i].x), "=r"(v[i].y), "=r"(v[i].z), "=r"(v[i].w) : "l"(gh + 32 * i) : "memory");
                                    if (v[0].y == ep && v[0].w == ep && v[1].y == ep && v[1].w == ep) break;
                                }
#pragma unroll
                                for (int i = 0; i < 2; i++)
                                    asm volatile("st.shared.v2.b32 [%0], {%1, %2};" ::"r"(src + i * OFF_EPI + (63 + 65 * dn) * 128 + 8 * lane), "r"(v[i].x), "r"(v[i].z) : "memory");
                                fence_async_smem();
                                __syncwarp();
                                DP(8 * FL_H + 5);
                                named_bar_arrive(14, 160);
                            }
                            if (lane == 0) {
                                asm volatile("cp.async.bulk.wait_group 0;" ::: "memory");
                                DP(8 * (kind + hf) + 1);
                                if (REL & 1) asm volatile("fence.release.gpu;" ::: "memory");
                                DP(8 * (kind + hf) + 2);
                                unsigned int* fp = flag_ptr(layer, kind + hf, bi);
                                asm volatile("red.relaxed.gpu.global.add.u32 [%0], 1;" ::"l"(fp) : "memory");
                                if (kind == FL_H) {
                                    if (bi > 0 && (!NH16 || dn > 0)) asm volatile("red.relaxed.gpu.global.add.u32 [%0], 1;" ::"l"(fp - FL_PITCH) : "memory");
                                    if (bi < 15 && (!NH16 || dn < 0)) asm volatile("red.relaxed.gpu.global.add.u32 [%0], 1;" ::"l"(fp + FL_PITCH) : "memory");
                                }
                            }
                            __syncwarp();
                        }
                    }
                } else {
                    uint32_t* rs = reinterpret_cast<uint32_t*>(sgen + OFF_RS);
                    float* cs = reinterpret_cast<float*>(sgen + OFF_CS);
#pragma unroll 1
                    for (int which = 0; which < 2; which++) {
                        if (layer < which) {
                            if (warp == 11 && lane == 0) {
                                if (W3_AT >= 0) wait_flag(flag_ptr(0, FL_XA + (W3_AT & 1), bi), 8 * ep);
                                asm volatile("cp.async.bulk.prefetch.L2.global [%0], %1;" ::"l"(w3p + (bi * 8 + bj) * 28672), "r"(57344) : "memory");
                            }
                            __syncwarp();
                            colsum(false, bi, bj);
                        }
                        if (warp == 11) continue;
                        if (layer == 0) {
                            if (lane == 0) wait_flag(flag_ptr(which, FL_CS, bj), (16 << which) * ep);
                            __syncwarp();
#pragma unroll 1
                            for (int c = (which ? 384 : 768) + lane * 4; c < 896; c += 128) {
                                const float* cp = g_cpart + (which ? bj * 448 + min(c & 511, 444) : F_ + bj * 128 + lane * 4);
                                float4 a = make_float4(0.f, 0.f, 0.f, 0.f);
#pragma unroll
                                for (int r0 = 0; r0 < 16; r0 += 8) {
                                    float4 v[8];
#pragma unroll
                                    for (int r = 0; r < 8; r++) v[r] = __ldcg(reinterpret_cast<const float4*>(cp + (r0 + r) * (F_ + D_)));
#pragma unroll
                                    for (int r = 0; r < 8; r++) { a.x += v[r].x; a.y += v[r].y; a.z += v[r].z; a.w += v[r].w; }
                                }
                                if (c < 768) *reinterpret_cast<float4*>(cs + min(c & 511, 444)) = a;
                                keep[0] = a;
                            }
                        }
                        if (lane == 0 && (layer | which)) wait_flag(flag_ptr(layer, which == 0 ? FL_XA : FL_X1, bi), 8 * ep);
                        __syncwarp();
                        *reinterpret_cast<float4*>(cs + 256 + lane * 4) = keep[0];
                        { const float4 k0 = keep[0]; keep[0] = keep[1]; keep[1] = k0; }
#pragma unroll 1
                        for (int i = 0; i < 4; i++) {
                            const int r = i * 32 + lane;
                            float mean, var;
                            row_stats(g_stats + (1 + which) * S_ * 8 + bi * 1024 + r, ~layer << 31, mean, var);
                            const uint32_t c0 = pack2(mean, fsqrt(bfr(bfr(var) + 1e-5f)));
                            if (lane < 19 && (layer | which | i) == 0) asm volatile("mbarrier.inval.shared::cta.b64 [%0];" ::"r"(b_full + 8 * lane) : "memory");
                            __syncwarp();
                            rs[r] = c0;
                            const float rd = frcp(hi2f(c0));
                            rs[128 + r] = pack2((mean - lo2f(c0)) * rd, fsqrt(bfr(bfr(var * rd * rd) + 1e-5f)));
                        }
                        __syncwarp();
                        named_bar_arrive(3, 160);
                        named_bar_arrive(11, 160);
                    }
                }
                const uint32_t s_cnt = s_bar + 224;
                auto ticket = [&](uint32_t a) {
                    uint32_t v = 0;
                    if (lane == 0) asm volatile("atom.acq_rel.cta.shared.add.u32 %0, [%1], 1;" : "=r"(v) : "r"(a) : "memory");
                    return v;
                };
                auto next = [&]() {
                    uint32_t v = 0;
                    if (lane == 0) asm volatile("atom.relaxed.cta.shared.add.u32 %0, [%1], 1;" : "=r"(v) : "r"(s_cnt + 16 + 4 * layer) : "memory");
                    return v;
                };
                mbar_wait(b_stg, layer);
                int u = __shfl_sync(0xffffffffu, next(), 0), step = 0;
#pragma unroll 1
                while (true) {
#pragma unroll 1
                    for (; step < 5 && u >= (int)((0x3830201810ull >> (8 * step)) & 255); step++) {
                        if (step == 1) { named_bar_arrive(4, 224); named_bar_arrive(12, 224); continue; }
                        const int part = step ? step - 1 : 0;
                        __syncwarp();
                        if (ticket(s_cnt + 4 * part) == 3 * layer + 2) {
                            asm volatile("fence.release.gpu;" ::: "memory");
                            unsigned int* fp = flag_ptr(layer, FL_H2 + part, bi);
                            asm volatile("red.relaxed.gpu.global.add.u32 [%0], 1;" ::"l"(fp) : "memory");
                            if (part > 0) { wait_flag(fp, 8 * ep); mbar_arrive(b_h2 + 8 * part); }
                        }
                        __syncwarp();
                    }
                    if (u >= 56) break;
                    const uint32_t un = next();
                    const int job = u >> 3, r = (u & 7) * 16 + (lane >> 3);
                    if (job >= 2) mbar_wait(s_bar + 168 + 8 * max(job, 3), layer);
                    const uint32_t sp = sbase + ((job & 2) ? OFF_STG5 : OFF_EPI) + r * 256 + (job & 1) * 128;
                    bf16* gp = act + (size_t)(R_H2 + (job >> 1) * 256 + tb + r) * D_ + ((job & 1) * 8 + bj) * 64 + (lane & 7) * 8;
                    uint4 v[4];
#pragma unroll
                    for (int e = 0; e < 4; e++) v[e] = lds128(sp + e * 1024 + (((lane & 7) ^ ((r + 4 * e) & 7)) << 4));
#pragma unroll
                    for (int e = 0; e < 4; e++) stg128(gp + 4 * e * D_, gelu8h(v[e]));
                    u = __shfl_sync(0xffffffffu, un, 0);
                }
                if (layer == 0 && warp == 11) {
                    const char* ps = reinterpret_cast<const char*>(g_stats + bi * 1024) + lane * 128;
                    const char* py = reinterpret_cast<const char*>(act + (size_t)(R_Y + (tb & ~255) + (bj & 1) * 128 + (lane >> 1)) * D_ + (bj >> 1) * 256 + rank * 128) + (lane & 1) * 128;
#pragma unroll 1
                    for (int i = 0; i < 8; i++) {
                        asm volatile("prefetch.global.L2 [%0];" ::"l"(py + (size_t)i * 16 * D_ * 2) : "memory");
                        if (i >= 6) asm volatile("prefetch.global.L2 [%0];" ::"l"(ps + (i & 1) * 4096) : "memory");
                        __nanosleep(400);
                    }
                }
            }
        }
        __syncwarp();
        asm volatile("barrier.cluster.arrive.relaxed.aligned;\nbarrier.cluster.wait.acquire.aligned; // helpers" ::: "memory");
    } else {
        DT_DECL;
        DT(0);
        auto put_y = [&]() {
            if ((tid & 127) < 2 && cv) {
                asm volatile("cp.async.bulk.wait_group 0;" ::: "memory");
                if (REL & 2) asm volatile("fence.release.gpu;" ::: "memory");
                asm volatile("red.relaxed.gpu.global.add.u32 [%0], 1;" ::"l"(flag_ptr(0, FL_CS, 8 + (blockIdx.x >> 4))) : "memory");
            }
            __syncwarp();
        };
        put_y();
        DT(24);
        asm volatile("setmaxnreg.inc.sync.aligned.u32 216;");
        if (get_role()) {
        const bool rel_on = (tid & 95) == 0;
        const uint32_t rel5 = mapa_u32(e5, (warp & 1) ^ rank), rel4 = rel5 + (e4 - e5);
        const uint32_t da0 = desc_a(s_r + wg * 8192), db0 = desc_b(s_r + BM * BK * 2), dae = da0 + (OFF_EPI - OFF_R) / 16, db4 = db0 - 49152 / 16;
        auto skip5 = [&](RingState& rs) {
            if (rel_on) mbar_arrive_cluster(rel5 + 8 * rs.st);
            rs.st++;
        };
        const int t = lane & 3;
        const int row = warp * 16 + (lane >> 2);
        const uint32_t st_w = (uint32_t)((warp * 16 + ((lane >> 3) & 1) * 8 + (lane & 7)) * 256 + (((lane >> 4) ^ (lane & 7)) << 4));
        const uint32_t fr = (uint32_t)((warp * 16 + ((lane >> 3) & 1) * 8 + (lane & 7)) * 128 + (((lane >> 4) ^ (lane & 7)) << 4));
        auto copy_out = [&](bf16* dst, uint32_t src) {
            const int r = warp * 16 + (lane >> 4);
            bf16* ox = dst + (size_t)(m0 + r) * D_ + bj * 128 + (lane & 15) * 8;
            const uint32_t ra = src + ((lane & 15) >> 3) * 16384 + r * 128;
            uint4 v[8];
#pragma unroll
            for (int it = 0; it < 8; it++) v[it] = lds128(ra + it * 256 + (((lane & 7) ^ ((2 * it + (lane >> 4)) & 7)) << 4));
#pragma unroll
            for (int it = 0; it < 8; it++) *reinterpret_cast<uint4*>(ox + (size_t)it * 2 * D_) = v[it];
        };
        auto put_stats = [&](const uint32_t (&w)[32], int which, int layer) {
            float c[6][4];
#pragma unroll
            for (int e = 0; e < 32; e++) {
                hmma8(c[e & 3], w[e & ~1], w[e | 1], w[e], e < 4);
                if ((e & 3) == 0) hmma(c[4 + (e >> 2 & 1)], w[e], w[e + 1], w[e + 2], w[e + 3], 0x3f803f80u, 0x3f803f80u, e < 8);
            }
            if (t == lane >> 3) {
#pragma unroll
                for (int e = 0; e < 2; e++) {
                    const float q1 = lane & 4 ? c[e][2 * e + 1] + c[e + 2][2 * e + 1] : c[e][2 * e] + c[e + 2][2 * e], s1 = c[4][2 * e] + c[5][2 * e], mu = s1 * (1.0f / 128);
                    asm volatile("{\n.reg .b64 t;\nmov.b64 t, {%1, %2};\nst.relaxed.gpu.global.b64 [%0], t;\n}"
                                 ::"l"(g_stats + which * S_ * 8 + (bi * 8 + bj) * 128 + row + 8 * e), "f"(mu), "r"(__float_as_uint(fmaxf(q1 - s1 * mu, 0.f)) | ~layer << 31) : "memory");
                }
            }
        };
        auto split = [](float r) { const float h = bfr(r); return pack2(h, r - h); };
        auto norm2 = [](uint32_t x, uint32_t m, uint32_t r) {
            const uint32_t d = bsub2(x, m);
            return bfma2(d, __byte_perm(r, 0, 0x1010), bmul2(d, __byte_perm(r, 0, 0x3232)));
        };
        const float* csp = reinterpret_cast<const float*>(sgen + OFF_CS) + 2 * t;
        float mrow[2], rrow[2];
        const uint32_t* rsp = reinterpret_cast<const uint32_t*>(sgen + OFF_RS) + row;
        auto row_consts = [&](bool twice) {
#pragma unroll
            for (int e = 0; e < 2; e++) {
                const uint32_t q0 = rsp[8 * e], q1 = rsp[128 + 8 * e];
                mrow[e] = twice ? fmaf(lo2f(q1), hi2f(q0), lo2f(q0)) : lo2f(q0);
                rrow[e] = 0.5f * frcp(twice ? hi2f(q0) * hi2f(q1) : hi2f(q0));
            }
        };
        auto keep_consts = [&](float2 (&cs)[8]) {
#pragma unroll
            for (int e = 0; e < 8; e++) asm volatile("" : "+f"(cs[e].x), "+f"(cs[e].y));
            asm volatile("" : "+f"(mrow[0]), "+f"(mrow[1]), "+f"(rrow[0]), "+f"(rrow[1]));
        };
        RingState r5{1, 0}, r4{0, 0};
        DT(1);
        uint32_t x[32];
        mbar_wait(b_rfull, 0);
#pragma unroll
        for (int jp = 0; jp < 8; jp++) ldsm4(x[4 * jp], x[4 * jp + 1], x[4 * jp + 2], x[4 * jp + 3], sbase + 16384 + (fr ^ ((jp & 3) << 5)) + (jp >> 2) * (16384 + 8 * CV_SL));
#pragma unroll
        for (int e = 0; e < 32; e++) asm volatile("" : "+r"(x[e]));
        named_bar_sync(9 + wg, 128);
        if ((tid & 95) < R5_N) mbar_arrive_cluster(rel5 + 8 * lane);
#pragma unroll 1
        for (int layer = 0; layer < 2; layer++) {
            {
                DT(2 + 24 * layer);
                put_stats(x, 0, layer);
                DT(20 + 24 * layer);
                DT(22 + 24 * layer);
                uint32_t mb[2], rd[2];
                {
                    float mean, var;
                    row_stats(g_stats + bi * 1024 + warp * 16 + (lane & 15), ~layer << 31, mean, var);
                    __syncwarp();
                    const uint32_t r1 = split(frcp(bfr(fsqrt(bfr(bfr(var) + 1e-5f)))));
                    const uint32_t m1 = pack2(mean, mean);
#pragma unroll
                    for (int e = 0; e < 2; e++) { mb[e] = __shfl_sync(0xffffffffu, m1, (lane >> 2) + 8 * e); rd[e] = __shfl_sync(0xffffffffu, r1, (lane >> 2) + 8 * e); }
                }
                DT(21 + 24 * layer);
                mbar_wait(f5 + 8, r5.ph);
                DT(23 + 24 * layer);
                const uint32_t ya = s_r + R5_STAGE + wg * 16384 + ((lane >> 4) * 8 + (lane & 7)) * 128 + ((((warp & 3) * 2 + ((lane >> 3) & 1)) ^ (lane & 7)) << 4);
                uint32_t y[16];
#pragma unroll
                for (int e = 0; e < 32; e++) {
                    if ((e & 15) == 0) {
#pragma unroll
                        for (int jp = 0; jp < 4; jp++) ldsm4t(y[4 * jp], y[4 * jp + 1], y[4 * jp + 2], y[4 * jp + 3], ya + jp * 2048 + e * 512);
                    }
                    x[e] = bfma2(norm2(x[e], mb[e & 1], rd[e & 1]), y[e & 15], x[e]);
                    if ((e & 3) == 3) stsm4(s_epi + (fr ^ (((e >> 2) & 3) << 5)) + (e >> 4) * 16384, x[e - 3], x[e - 2], x[e - 1], x[e]);
                    if ((e & 15) == 15) { if (e == 15 && (SPL & 1)) named_bar_arrive(7 - 2 * wg, 160); else named_bar_arrive(5 + (e >> 4), 288); }
                    if (e == 15) mbar_wait(b_role, 0);
                }
                DT(19 + 24 * layer);
                if (FMOVE) fence_async_smem();
                if (PS1_EARLY) put_stats(x, 1, layer);
                named_bar_sync(9 + wg, 128);
                skip5(r5);
                DT(3 + 24 * layer);
            }
            {
                float acc[64];
                kblock<128, R5_N, 0>(acc, dae, db0 + 2 * (R5_STAGE / 16), f5, r5);
                kblock<128, R5_N>(acc, dae + 1024, db0 + 3 * (R5_STAGE / 16), f5, r5);
                if (!PS1_EARLY) put_stats(x, 1, layer);
                wgmma_wait<1>();
                if (rel_on) mbar_arrive_cluster(rel5 + 16);
                float2 cs[8];
                mainloop<128, R5_N, R5_STAGE, PA1>(acc, 14, da0, db0, f5, rel5, rel_on, r5, 15 + 24 * layer, [&]() {
                    named_bar_sync(3 + 8 * wg, 160);
                    row_consts(true);
#pragma unroll
                    for (int e = 0; e < 8; e++) cs[e] = *reinterpret_cast<const float2*>(csp + 256 + 8 * e);
                    keep_consts(cs);
                } DT_ARG, (wg ^ bj >> 1 ^ LAGX) & 1);
                DT(4 + 24 * layer);
#pragma unroll
                for (int j = 0; j < 16; j += 2) {
                    if (j == 8) {
#pragma unroll
                        for (int e = 0; e < 8; e++) cs[e] = *reinterpret_cast<const float2*>(csp + 256 + 8 * (j + e));
                    }
                    uint32_t w[4];
#pragma unroll
                    for (int e = 0; e < 4; e++) {
                        const float* a = acc + 4 * j + 2 * e;
                        const float2 c = cs[(j & 7) + (e >> 1)];
                        w[e] = gelu2h(pack2(fmaf(-mrow[e & 1], c.x, a[0]) * rrow[e & 1], fmaf(-mrow[e & 1], c.y, a[1]) * rrow[e & 1]));
                    }
                    stsm4(s_stg + 1024 + (fr ^ ((j & 7) << 4)) + (j >> 3) * OFF_EPI, w[0], w[1], w[2], w[3]);
                    if ((j & 7) == 6) { if (j == 6 && (SPL & 4)) named_bar_arrive(7 - 2 * ((wg ^ bj >> 1 ^ 1) & 1), 160); else named_bar_arrive(5 + (j >> 3), 288); }
                }
                if (SENDC && warp == (bj & 2 ? 0 : 7)) {
                    __syncwarp();
                    uint32_t a[4];
                    lds64(a[0], a[1], s_stg + 1024 + 18 * 128 * warp + 8 * lane);
                    lds64(a[2], a[3], s_epi + 1024 + 18 * 128 * warp + 8 * lane);
                    uint4* gh = g_halo + (layer * 144 + (warp & 2) * 8 + bi * 8 + bj) * 64 + lane;
#pragma unroll
                    for (int i = 0; i < 2; i++)
                        asm volatile("{\n.reg .b64 u, v;\nmov.b64 u, {%1, %3};\nmov.b64 v, {%2, %3};\nst.relaxed.gpu.global.v2.b64 [%0], {u, v};\n}"
                                     ::"l"(gh + i * 32), "r"(a[2 * i]), "r"(a[2 * i + 1]), "r"(ep) : "memory");
                }
                fence_async_smem();
                if (wg == (bj >> 1 & 1)) named_bar_arrive(13, 256);
                DT(5 + 24 * layer);
            }
            {
                float acc[64];
                uint32_t u[32];
                {
                    uint32_t mb[2], rd[2];
#pragma unroll
                    for (int e = 0; e < 2; e++) { const uint32_t q0 = rsp[8 * e]; mb[e] = (q0 & 0xffffu) * 0x10001u; rd[e] = split(frcp(hi2f(q0))); }
#pragma unroll
                    for (int e = 0; e < 32; e++) {
                        u[e] = norm2(x[e], mb[e & 1], rd[e & 1]);
                        asm volatile("" : "+r"(u[e]));
                    }
                }
                if (!(warp & 2)) mbar_wait(f5 + 24, r5.ph);
                skip5(r5);
                {
                    const bool nb = wg == (bj >> 1 & 1);
                    named_bar_sync(nb ? 14 : 13, nb ? 160 : 256);
                }
                const uint32_t dah = da0 - (OFF_R - 1024 + 256) / 16 + ((0x4031u >> (2 * bj & 12)) & 7) * 8;
                kblock<128, R5_N, 0>(acc, dah, db0 + 4 * (R5_STAGE / 16), f5, r5);
                kblock<128, R5_N>(acc, dah + OFF_EPI / 16, db0, f5, r5);
                wgmma_wait<1>();
                if (rel_on) mbar_arrive_cluster(rel5 + 32);
                mainloop<128, R5_N, R5_STAGE, PA2>(acc, 14, da0, db0, f5, rel5, rel_on, r5, 16 + 24 * layer, []() {} DT_ARG, wg);
                DT(6 + 24 * layer);
#pragma unroll
                for (int j = 0; j < 16; j += 2) {
#pragma unroll
                    for (int e = 0; e < 4; e++) u[2 * j + e] = badd2(u[2 * j + e], pack2(acc[4 * j + 2 * e], acc[4 * j + 2 * e + 1]));
                    stsm4(s_epi + (fr ^ ((j & 7) << 4)) + (j >> 3) * 16384, u[2 * j], u[2 * j + 1], u[2 * j + 2], u[2 * j + 3]);
                    if ((j & 7) == 6) { if (j == 6 && (SPL & 16)) named_bar_arrive(7 - 2 * wg, 160); else named_bar_arrive(5 + (j >> 3), 288); mbar_wait(b_role, 0); }
                }
                if (FMOVE) fence_async_smem();
#pragma unroll
                for (int e = 0; e < 32; e++) x[e] = badd2(x[e], u[e]);
                put_stats(u, 2, layer);
                named_bar_sync(9 + wg, 128);
                DT(7 + 24 * layer);
            }
            {
                float2 cs[NCS];
                auto piece = [&](const float* acc, auto pc) {
                    constexpr int j = 2 * decltype(pc)::v, jl = j & 31;
                    uint32_t w[4];
#pragma unroll
                    for (int e = 0; e < 2; e++) {
                        const float* a = acc + 4 * (jl + e);
                        const float2 cc = cs[(j + e) % NCS];
                        w[2 * e] = pack2(fmaf(-mrow[0], cc.x, a[0]) * rrow[0], fmaf(-mrow[0], cc.y, a[1]) * rrow[0]);
                        w[2 * e + 1] = pack2(fmaf(-mrow[1], cc.x, a[2]) * rrow[1], fmaf(-mrow[1], cc.y, a[3]) * rrow[1]);
                    }
                    stsm4(((jl < 16 ? s_epi : s_stg) + st_w) ^ ((j & 15) << 4), w[0], w[1], w[2], w[3]);
                    if (j + NCS < 56) {
#pragma unroll
                        for (int e = 0; e < 2; e++) { uint32_t u0, u1; lds64(u0, u1, smem_u32(csp + 8 * (j + e + NCS))); cs[(j + e) % NCS] = make_float2(__uint_as_float(u0), __uint_as_float(u1)); }
                    }
                    if (j == 14 || (j >= 30 && (j & 7) == 6)) {
                        __syncwarp();
                        if (lane == 0) mbar_arrive(j == 14 ? b_stg : s_bar + 168 + (j & 56));
                    }
                };
                auto pieces = [&](const float* acc, auto p0, auto p1) {
                    constexpr int a = decltype(p0)::v, b = decltype(p1)::v;
                    static_for<a, b>([&](auto i) { piece(acc, i); });
                };
                float ac3[128];
                kblock<256, R4_N, 0>(ac3, dae, db4, f4, r4);
                kblock<256, R4_N>(ac3, dae + 1024, db4 + R4_STAGE / 16, f4, r4);
                wgmma_wait<1>();
                if (rel_on) mbar_arrive_cluster(rel4);
                mainloop<256, R4_N, R4_STAGE, PA3A>(ac3, 14, da0, db4, f4, rel4, rel_on, r4, 17 + 24 * layer, [&]() {
                    named_bar_sync(3 + 8 * wg, 160);
                    mbar_wait(e4, 1);
                    row_consts(false);
#pragma unroll
                    for (int e = 0; e < NCS; e++) {
                        cs[e] = *reinterpret_cast<const float2*>(csp + 8 * e);
                        asm volatile("" : "+f"(cs[e].x), "+f"(cs[e].y));
                    }
                    asm volatile("" : "+f"(mrow[0]), "+f"(mrow[1]), "+f"(rrow[0]), "+f"(rrow[1]));
                } DT_ARG, wg);
                DT(8 + 24 * layer);
                pieces(ac3, IC<0>(), IC<NPRE>());
                DT(9 + 24 * layer);
                float acc[96];
                constexpr int NS3 = NPRE == 16 ? 1 : (16 - NPRE + PP3 - 1) / PP3;
                static_for<0, NS3>([&](auto cc) {
                    constexpr int c = decltype(cc)::v, q = NPRE + PP3 * c;
                    const uint32_t da = da0 + c * (R4B_STAGE / 16), db = db0 + c * (R4B_STAGE / 16);
                    mbar_wait(f4 + 8 * c, r4.ph);
                    wgmma_fence();
                    static_for<0, 4>([&](auto ic) {
                        constexpr int i = decltype(ic)::v, q0 = q + i * PP3 / 4, q1 = q + (i + 1) * PP3 / 4;
                        WG<192>::mma<(c | i) != 0>(acc, da + 2 * i, db + 128 * i);
                        if (i == 3) {
                            wgmma_commit();
                            if (c) {
                                wgmma_wait<1>();
                                if (rel_on) mbar_arrive_cluster(rel4 + 8 * ((c + 3) & 3));
                            }
                        }
                        pieces(ac3, IC<(q0 < 16 ? q0 : 16)>(), IC<(q1 < 16 ? q1 : 16)>());
                    });
                });
                r4.st = NS3 & 3;
                if (NS3 == 4) r4.ph ^= 1;
                float ac4[64];
                mainloop<192, R4_N, R4B_STAGE, PA3B, 1>(acc, 16 - NS3, da0, db0, f4, rel4, rel_on, r4, -1, [&]() {
#pragma unroll
                    for (int i = 0; i < 32; i++) asm volatile("shl.b32 %0, %2, 16;\nand.b32 %1, %2, 0xffff0000;" : "=f"(ac4[2 * i]), "=f"(ac4[2 * i + 1]) : "r"(x[i]));
                    kblock<128, R5_N>(ac4, da0, db0, f5, r5);
                } DT_ARG, wg);
                DT(10 + 24 * layer);
                named_bar_sync(4 + 8 * wg, 224);
                piece(acc, IC<16>());
                static_for<1, 7>([&](auto cc) {
                    constexpr int c = decltype(cc)::v;
                    const uint32_t da = da0 + (c % 5) * (R5_STAGE / 16), db = db0 + (c % 5) * (R5_STAGE / 16);
                    mbar_wait(f5 + 8 * (c % 5), r5.ph);
                    wgmma_fence();
                    WG<128>::mma<1>(ac4, da, db);
                    WG<128>::mma<1>(ac4, da + 2, db + 128);
                    piece(acc, IC<15 + 2 * c>());
                    WG<128>::mma<1>(ac4, da + 4, db + 256);
                    WG<128>::mma<1>(ac4, da + 6, db + 384);
                    wgmma_commit();
                    if (c % 5 == 4) r5.ph ^= 1;
                    wgmma_wait<1>();
                    if (rel_on) mbar_arrive_cluster(rel5 + 8 * ((c - 1) % 5));
                    if constexpr (c < 6) piece(acc, IC<16 + 2 * c>());
                });
                r5.st = 2;
                DT(11 + 24 * layer);
                DT(18 + 24 * layer);
                mainloop<128, R5_N, R5_STAGE, PA4>(ac4, 49, da0, db0, f5, rel5, rel_on, r5, 62 - 40 * (layer ^ 1), []() {} DT_ARG, wg);
                DT(12 + 24 * layer);
#pragma unroll
                for (int i = 0; i < 32; i++) x[i] = pack2(ac4[2 * i], ac4[2 * i + 1]);
                DT(13 + 24 * layer);
                DT(14 + 24 * layer);
            }
        }
#pragma unroll
        for (int jp = 0; jp < 8; jp++) stsm4(s_epi + (fr ^ ((jp & 3) << 5)) + (jp >> 2) * 16384, x[4 * jp], x[4 * jp + 1], x[4 * jp + 2], x[4 * jp + 3]);
        __syncwarp();
        copy_out(outp, s_epi);
        DT(38);
        DT_DUMP;
        GT(4);
        }
        cluster_arrive_relaxed();
        cluster_wait();
    }
}

typedef CUresult (*PFN_encodeTiled)(CUtensorMap*, CUtensorMapDataType, cuuint32_t, void*, const cuuint64_t*, const cuuint64_t*,
                                    const cuuint32_t*, const cuuint32_t*, CUtensorMapInterleave, CUtensorMapSwizzle,
                                    CUtensorMapL2promotion, CUtensorMapFloatOOBfill);

static CUtensorMap make_map(PFN_encodeTiled enc, const void* ptr, int inner, int outer, int box_inner, int box_outer,
                            CUtensorMapSwizzle swz = CU_TENSOR_MAP_SWIZZLE_128B) {
    CUtensorMap m;
    cuuint64_t dims[2] = {(cuuint64_t)inner, (cuuint64_t)outer};
    cuuint64_t strides[1] = {(cuuint64_t)inner * 2};
    cuuint32_t box[2] = {(cuuint32_t)box_inner, (cuuint32_t)box_outer};
    cuuint32_t es[2] = {1, 1};
    enc(&m, CU_TENSOR_MAP_DATA_TYPE_BFLOAT16, 2, const_cast<void*>(ptr), dims, strides, box, es, CU_TENSOR_MAP_INTERLEAVE_NONE,
        swz, CU_TENSOR_MAP_L2_PROMOTION_L2_256B, CU_TENSOR_MAP_FLOAT_OOB_FILL_NONE);
    return m;
}

extern "C" void kernel_launch(void* const* d_in, const int* in_sizes, int n_in, void* d_out, int out_size) {
    const bf16* A_q = (const bf16*)d_in[0];
    const bf16* A_k = (const bf16*)d_in[1];
    const bf16* A_v = (const bf16*)d_in[2];
    const bf16* A_shk = (const bf16*)d_in[3];
    const bf16* A_ssk = (const bf16*)d_in[4];
    const bf16* A_ssD = (const bf16*)d_in[5];
    const bf16* w1 = (const bf16*)d_in[7];
    const bf16* w2 = (const bf16*)d_in[8];
    const bf16* w3 = (const bf16*)d_in[9];
    const bf16* w4 = (const bf16*)d_in[10];
    bf16* out = (bf16*)d_out;

    static PFN_encodeTiled enc = nullptr;
    static bool attr_done = false;
    if (!enc) {
        void* fn = nullptr;
        cudaDriverEntryPointQueryResult qr;
        cudaGetDriverEntryPoint("cuTensorMapEncodeTiled", &fn, cudaEnableDefault, &qr);
        enc = (PFN_encodeTiled)fn;
    }
    if (!attr_done) {
        cudaFuncSetAttribute(mega_kernel, cudaFuncAttributeMaxDynamicSharedMemorySize, MEGA_SMEM);
        attr_done = true;
    }
    void* p_act;
    cudaGetSymbolAddress(&p_act, g_act);
    bf16* act = (bf16*)(((uintptr_t)p_act + 0x1fffff) & ~(uintptr_t)0x1fffff);

    MegaMaps tm;
    tm.q = make_map(enc, A_q, D_, S_, 64, 128);
    tm.act = make_map(enc, act, D_, R_END, 64, 128);
    tm.a64 = make_map(enc, act, D_, R_END, 64, 64);
    tm.w1 = make_map(enc, w1, D_, D_, 64, 64);
    tm.w2 = make_map(enc, w2, D_, D_, 64, 64);
    tm.w3 = make_map(enc, w3, F_, D_, 64, 64);
    tm.w4 = make_map(enc, w4, D_, F_, 64, 64);
    {
        cuuint64_t dims[4] = {64, 16, 256, 8}, strides[3] = {128, D_ * 2, (cuuint64_t)2048 * D_ * 2};
        cuuint32_t box[4] = {64, 4, 1, 8}, es[4] = {1, 1, 1, 1};
        enc(&tm.y, CU_TENSOR_MAP_DATA_TYPE_BFLOAT16, 4, act + (size_t)R_Y * D_, dims, strides, box, es, CU_TENSOR_MAP_INTERLEAVE_NONE,
            CU_TENSOR_MAP_SWIZZLE_128B, CU_TENSOR_MAP_L2_PROMOTION_NONE, CU_TENSOR_MAP_FLOAT_OOB_FILL_NONE);
    }
    for (int i = 0; i < 2; i++) {
        cuuint64_t dims[4] = {D_, 4, 8, S_ / 32}, strides[3] = {8 * D_ * 2, D_ * 2, 32 * D_ * 2};
        cuuint32_t box[4] = {16, 4, 8, 4}, es[4] = {1, 1, 1, 1};
        enc(i ? &tm.v : &tm.k, CU_TENSOR_MAP_DATA_TYPE_BFLOAT16, 4, (void*)(i ? A_v : A_k), dims, strides, box, es, CU_TENSOR_MAP_INTERLEAVE_NONE,
            CU_TENSOR_MAP_SWIZZLE_32B, CU_TENSOR_MAP_L2_PROMOTION_NONE, CU_TENSOR_MAP_FLOAT_OOB_FILL_NONE);
    }
    mega_kernel<<<2 * NCL, 384, MEGA_SMEM, cudaStreamPerThread>>>(tm, out, act, w1, w2, w3, A_q, A_k, A_v, A_shk, A_ssk, A_ssD);
}
```

```cpp
#include <cuda_runtime.h>
#include <cuda_bf16.h>
#include <cuda.h>
#include <stdint.h>

typedef __nv_bfloat16 bf16;

constexpr int S_ = 2048;
constexpr int D_ = 1024;
constexpr int F_ = 3584;

constexpr int R_XA = 0, R_X1 = 256, R_H2 = 512, R_Y = 1536, R_H = 16384 + 8, R_HP = S_ + 8, R_END = R_H + 2 * R_HP;
__device__ __align__(1024) bf16 g_act[(size_t)(R_END + 1024) * D_];
__device__ __align__(16) float g_cpart[16 * (F_ + D_)];
__device__ __align__(128) float2 g_stats[3 * S_ * 8];
__device__ __align__(128) uint4 g_halo[2 * 144 * 64];

__device__ __forceinline__ float bfr(float x) { return __bfloat162float(__float2bfloat16_rn(x)); }
__device__ __forceinline__ uint32_t pack2(float lo, float hi) {
    __nv_bfloat162 v = __floats2bfloat162_rn(lo, hi);
    return *reinterpret_cast<uint32_t*>(&v);
}
__device__ __forceinline__ float lo2f(uint32_t v) { return __uint_as_float(v << 16); }
__device__ __forceinline__ float hi2f(uint32_t v) { return __uint_as_float(v & 0xffff0000u); }
__device__ __forceinline__ float frcp(float x) { float r; asm("rcp.approx.f32 %0, %1;" : "=f"(r) : "f"(x)); return r; }
__device__ __forceinline__ float fsqrt(float x) { float r; asm("sqrt.approx.f32 %0, %1;" : "=f"(r) : "f"(x)); return r; }
__device__ __forceinline__ uint32_t smem_u32(const void* p) { return (uint32_t)__cvta_generic_to_shared(p); }

__device__ __forceinline__ void mbar_init(uint32_t bar, uint32_t cnt) {
    asm volatile("mbarrier.init.shared::cta.b64 [%0], %1;" ::"r"(bar), "r"(cnt));
}
__device__ __forceinline__ void mbar_expect_tx(uint32_t bar, uint32_t bytes) {
    asm volatile("mbarrier.arrive.expect_tx.shared::cta.b64 _, [%0], %1;" ::"r"(bar), "r"(bytes) : "memory");
}
__device__ __forceinline__ void mbar_arrive(uint32_t bar) {
    asm volatile("mbarrier.arrive.shared::cta.b64 _, [%0];" ::"r"(bar) : "memory");
}
__device__ __forceinline__ void mbar_wait(uint32_t bar, uint32_t parity) {
    asm volatile(
        "{\n.reg .pred p;\n.reg .u32 n;\n"
        "mbarrier.try_wait.parity.shared::cta.b64 p, [%0], %1;\n"
        "@p bra LD;\n"
        "mov.u32 n, 0;\n"
        "LW:\n"
        "mbarrier.try_wait.parity.shared::cta.b64 p, [%0], %1;\n"
        "@p bra LD;\n"
        "add.u32 n, n, 1;\n"
        "setp.lt.u32 p, n, 0x400000;\n"
        "@p bra LW;\n"
        "LD:\n}\n"
        ::"r"(bar), "r"(parity) : "memory");
}
__device__ __forceinline__ void tma_load_2d(uint32_t dst, const CUtensorMap* tm, uint32_t bar, int c0, int c1) {
    asm volatile(
        "cp.async.bulk.tensor.2d.shared::cluster.global.mbarrier::complete_tx::bytes [%0], [%1, {%3, %4}], [%2];"
        ::"r"(dst), "l"((uint64_t)tm), "r"(bar), "r"(c0), "r"(c1) : "memory");
}
__device__ __forceinline__ void tma_load_2d_mc(uint32_t dst, const CUtensorMap* tm, uint32_t bar, int c0, int c1) {
    asm volatile(
        "cp.async.bulk.tensor.2d.shared::cluster.global.mbarrier::complete_tx::bytes.multicast::cluster [%0], [%1, {%3, %4}], [%2], %5;"
        ::"r"(dst), "l"((uint64_t)tm), "r"(bar), "r"(c0), "r"(c1), "h"((uint16_t)3) : "memory");
}
__device__ __forceinline__ void tma_prefetch_2d(const CUtensorMap* tm, int c0, int c1) {
    asm volatile("cp.async.bulk.prefetch.tensor.2d.L2.global.tile [%0, {%1, %2}];" ::"l"((uint64_t)tm), "r"(c0), "r"(c1) : "memory");
}
__device__ __forceinline__ void tma_store_2d(const CUtensorMap* tm, uint32_t src, int c0, int c1) {
    asm volatile("cp.async.bulk.tensor.2d.global.shared::cta.bulk_group [%0, {%2, %3}], [%1];"
                 ::"l"((uint64_t)tm), "r"(src), "r"(c0), "r"(c1) : "memory");
}
__device__ __forceinline__ void wgmma_fence() { asm volatile("wgmma.fence.sync.aligned;" ::: "memory"); }
__device__ __forceinline__ void wgmma_commit() { asm volatile("wgmma.commit_group.sync.aligned;" ::: "memory"); }
template <int N> __device__ __forceinline__ void wgmma_wait() { asm volatile("wgmma.wait_group.sync.aligned %0;" ::"n"(N) : "memory"); }
__device__ __forceinline__ void named_bar_arrive(int id, int n) { asm volatile("bar.arrive %0, %1;" ::"r"(id), "r"(n) : "memory"); }
__device__ __forceinline__ void named_bar_sync(int id, int n) { asm volatile("bar.sync %0, %1;" ::"r"(id), "r"(n) : "memory"); }

__device__ __forceinline__ uint32_t desc_a(uint32_t addr) { return ((addr & 0x3FFFF) >> 4) | (1u << 16); }
__device__ __forceinline__ uint32_t desc_b(uint32_t addr) { return ((addr & 0x3FFFF) >> 4) | (512u << 16); }

template <int ACC> __device__ __forceinline__ void wgmma_m64n192k16(float (&d)[96], uint32_t descA, uint32_t descB) {
  asm volatile("{\n.reg .pred p;\n.reg .b64 da, db;\nsetp.ne.b32 p, %99, 0;\nmov.b64 da, {%96, %98};\nmov.b64 db, {%97, %98};\n"
    "wgmma.mma_async.sync.aligned.m64n192k16.f32.bf16.bf16 "
    "{%0, %1, %2, %3, %4, %5, %6, %7, %8, %9, %10, %11, %12, %13, %14, %15, %16, %17, %18, %19, %20, %21, %22, %23, %24, %25, %26, %27, %28, %29, %30, %31, %32, %33, %34, %35, %36, %37, %38, %39, %40, %41, %42, %43, %44, %45, %46, %47, %48, %49, %50, %51, %52, %53, %54, %55, %56, %57, %58, %59, %60, %61, %62, %63, %64, %65, %66, %67, %68, %69, %70, %71, %72, %73, %74, %75, %76, %77, %78, %79, %80, %81, %82, %83, %84, %85, %86, %87, %88, %89, %90, %91, %92, %93, %94, %95}, "
    "da, db, p, 1, 1, 0, 1;\n}\n"
    : "+f"(d[0]), "+f"(d[1]), "+f"(d[2]), "+f"(d[3]), "+f"(d[4]), "+f"(d[5]), "+f"(d[6]), "+f"(d[7]), "+f"(d[8]), "+f"(d[9]), "+f"(d[10]), "+f"(d[11]), "+f"(d[12]), "+f"(d[13]), "+f"(d[14]), "+f"(d[15]), "+f"(d[16]), "+f"(d[17]), "+f"(d[18]), "+f"(d[19]), "+f"(d[20]), "+f"(d[21]), "+f"(d[22]), "+f"(d[23]), "+f"(d[24]), "+f"(d[25]), "+f"(d[26]), "+f"(d[27]), "+f"(d[28]), "+f"(d[29]), "+f"(d[30]), "+f"(d[31]), "+f"(d[32]), "+f"(d[33]), "+f"(d[34]), "+f"(d[35]), "+f"(d[36]), "+f"(d[37]), "+f"(d[38]), "+f"(d[39]), "+f"(d[40]), "+f"(d[41]), "+f"(d[42]), "+f"(d[43]), "+f"(d[44]), "+f"(d[45]), "+f"(d[46]), "+f"(d[47]), "+f"(d[48]), "+f"(d[49]), "+f"(d[50]), "+f"(d[51]), "+f"(d[52]), "+f"(d[53]), "+f"(d[54]), "+f"(d[55]), "+f"(d[56]), "+f"(d[57]), "+f"(d[58]), "+f"(d[59]), "+f"(d[60]), "+f"(d[61]), "+f"(d[62]), "+f"(d[63]), "+f"(d[64]), "+f"(d[65]), "+f"(d[66]), "+f"(d[67]), "+f"(d[68]), "+f"(d[69]), "+f"(d[70]), "+f"(d[71]), "+f"(d[72]), "+f"(d[73]), "+f"(d[74]), "+f"(d[75]), "+f"(d[76]), "+f"(d[77]), "+f"(d[78]), "+f"(d[79]), "+f"(d[80]), "+f"(d[81]), "+f"(d[82]), "+f"(d[83]), "+f"(d[84]), "+f"(d[85]), "+f"(d[86]), "+f"(d[87]), "+f"(d[88]), "+f"(d[89]), "+f"(d[90]), "+f"(d[91]), "+f"(d[92]), "+f"(d[93]), "+f"(d[94]), "+f"(d[95])
    : "r"(descA), "r"(descB), "r"(0x40000040u), "n"(ACC));
}

template <int ACC> __device__ __forceinline__ void wgmma_m64n256k16(float (&d)[128], uint32_t descA, uint32_t descB) {
  asm volatile("{\n.reg .pred p;\n.reg .b64 da, db;\nsetp.ne.b32 p, %131, 0;\nmov.b64 da, {%128, %130};\nmov.b64 db, {%129, %130};\n"
    "wgmma.mma_async.sync.aligned.m64n256k16.f32.bf16.bf16 "
    "{%0, %1, %2, %3, %4, %5, %6, %7, %8, %9, %10, %11, %12, %13, %14, %15, %16, %17, %18, %19, %20, %21, %22, %23, %24, %25, %26, %27, %28, %29, %30, %31, %32, %33, %34, %35, %36, %37, %38, %39, %40, %41, %42, %43, %44, %45, %46, %47, %48, %49, %50, %51, %52, %53, %54, %55, %56, %57, %58, %59, %60, %61, %62, %63, %64, %65, %66, %67, %68, %69, %70, %71, %72, %73, %74, %75, %76, %77, %78, %79, %80, %81, %82, %83, %84, %85, %86, %87, %88, %89, %90, %91, %92, %93, %94, %95, %96, %97, %98, %99, %100, %101, %102, %103, %104, %105, %106, %107, %108, %109, %110, %111, %112, %113, %114, %115, %116, %117, %118, %119, %120, %121, %122, %123, %124, %125, %126, %127}, "
    "da, db, p, 1, 1, 0, 1;\n}\n"
    : "+f"(d[0]), "+f"(d[1]), "+f"(d[2]), "+f"(d[3]), "+f"(d[4]), "+f"(d[5]), "+f"(d[6]), "+f"(d[7]), "+f"(d[8]), "+f"(d[9]), "+f"(d[10]), "+f"(d[11]), "+f"(d[12]), "+f"(d[13]), "+f"(d[14]), "+f"(d[15]), "+f"(d[16]), "+f"(d[17]), "+f"(d[18]), "+f"(d[19]), "+f"(d[20]), "+f"(d[21]), "+f"(d[22]), "+f"(d[23]), "+f"(d[24]), "+f"(d[25]), "+f"(d[26]), "+f"(d[27]), "+f"(d[28]), "+f"(d[29]), "+f"(d[30]), "+f"(d[31]), "+f"(d[32]), "+f"(d[33]), "+f"(d[34]), "+f"(d[35]), "+f"(d[36]), "+f"(d[37]), "+f"(d[38]), "+f"(d[39]), "+f"(d[40]), "+f"(d[41]), "+f"(d[42]), "+f"(d[43]), "+f"(d[44]), "+f"(d[45]), "+f"(d[46]), "+f"(d[47]), "+f"(d[48]), "+f"(d[49]), "+f"(d[50]), "+f"(d[51]), "+f"(d[52]), "+f"(d[53]), "+f"(d[54]), "+f"(d[55]), "+f"(d[56]), "+f"(d[57]), "+f"(d[58]), "+f"(d[59]), "+f"(d[60]), "+f"(d[61]), "+f"(d[62]), "+f"(d[63]), "+f"(d[64]), "+f"(d[65]), "+f"(d[66]), "+f"(d[67]), "+f"(d[68]), "+f"(d[69]), "+f"(d[70]), "+f"(d[71]), "+f"(d[72]), "+f"(d[73]), "+f"(d[74]), "+f"(d[75]), "+f"(d[76]), "+f"(d[77]), "+f"(d[78]), "+f"(d[79]), "+f"(d[80]), "+f"(d[81]), "+f"(d[82]), "+f"(d[83]), "+f"(d[84]), "+f"(d[85]), "+f"(d[86]), "+f"(d[87]), "+f"(d[88]), "+f"(d[89]), "+f"(d[90]), "+f"(d[91]), "+f"(d[92]), "+f"(d[93]), "+f"(d[94]), "+f"(d[95]), "+f"(d[96]), "+f"(d[97]), "+f"(d[98]), "+f"(d[99]), "+f"(d[100]), "+f"(d[101]), "+f"(d[102]), "+f"(d[103]), "+f"(d[104]), "+f"(d[105]), "+f"(d[106]), "+f"(d[107]), "+f"(d[108]), "+f"(d[109]), "+f"(d[110]), "+f"(d[111]), "+f"(d[112]), "+f"(d[113]), "+f"(d[114]), "+f"(d[115]), "+f"(d[116]), "+f"(d[117]), "+f"(d[118]), "+f"(d[119]), "+f"(d[120]), "+f"(d[121]), "+f"(d[122]), "+f"(d[123]), "+f"(d[124]), "+f"(d[125]), "+f"(d[126]), "+f"(d[127])
    : "r"(descA), "r"(descB), "r"(0x40000040u), "n"(ACC));
}

template <int ACC> __device__ __forceinline__ void wgmma_m64n128k16(float (&d)[64], uint32_t descA, uint32_t descB) {
  asm volatile("{\n.reg .pred p;\n.reg .b64 da, db;\nsetp.ne.b32 p, %67, 0;\nmov.b64 da, {%64, %66};\nmov.b64 db, {%65, %66};\n"
    "wgmma.mma_async.sync.aligned.m64n128k16.f32.bf16.bf16 "
    "{%0, %1, %2, %3, %4, %5, %6, %7, %8, %9, %10, %11, %12, %13, %14, %15, %16, %17, %18, %19, %20, %21, %22, %23, %24, %25, %26, %27, %28, %29, %30, %31, %32, %33, %34, %35, %36, %37, %38, %39, %40, %41, %42, %43, %44, %45, %46, %47, %48, %49, %50, %51, %52, %53, %54, %55, %56, %57, %58, %59, %60, %61, %62, %63}, "
    "da, db, p, 1, 1, 0, 1;\n}\n"
    : "+f"(d[0]), "+f"(d[1]), "+f"(d[2]), "+f"(d[3]), "+f"(d[4]), "+f"(d[5]), "+f"(d[6]), "+f"(d[7]), "+f"(d[8]), "+f"(d[9]), "+f"(d[10]), "+f"(d[11]), "+f"(d[12]), "+f"(d[13]), "+f"(d[14]), "+f"(d[15]), "+f"(d[16]), "+f"(d[17]), "+f"(d[18]), "+f"(d[19]), "+f"(d[20]), "+f"(d[21]), "+f"(d[22]), "+f"(d[23]), "+f"(d[24]), "+f"(d[25]), "+f"(d[26]), "+f"(d[27]), "+f"(d[28]), "+f"(d[29]), "+f"(d[30]), "+f"(d[31]), "+f"(d[32]), "+f"(d[33]), "+f"(d[34]), "+f"(d[35]), "+f"(d[36]), "+f"(d[37]), "+f"(d[38]), "+f"(d[39]), "+f"(d[40]), "+f"(d[41]), "+f"(d[42]), "+f"(d[43]), "+f"(d[44]), "+f"(d[45]), "+f"(d[46]), "+f"(d[47]), "+f"(d[48]), "+f"(d[49]), "+f"(d[50]), "+f"(d[51]), "+f"(d[52]), "+f"(d[53]), "+f"(d[54]), "+f"(d[55]), "+f"(d[56]), "+f"(d[57]), "+f"(d[58]), "+f"(d[59]), "+f"(d[60]), "+f"(d[61]), "+f"(d[62]), "+f"(d[63])
    : "r"(descA), "r"(descB), "r"(0x40000040u), "n"(ACC));
}

template <int BN> struct WG;
template <> struct WG<128> { template <int ACC> static __device__ __forceinline__ void mma(float (&d)[64], uint32_t a, uint32_t b) { wgmma_m64n128k16<ACC>(d, a, b); } };
template <> struct WG<256> { template <int ACC> static __device__ __forceinline__ void mma(float (&d)[128], uint32_t a, uint32_t b) { wgmma_m64n256k16<ACC>(d, a, b); } };
template <> struct WG<192> { template <int ACC> static __device__ __forceinline__ void mma(float (&d)[96], uint32_t a, uint32_t b) { wgmma_m64n192k16<ACC>(d, a, b); } };

#define DBG_T(i)
__device__ __forceinline__ void fence_async_smem() { asm volatile("fence.proxy.async.shared::cta;" ::: "memory"); }
__device__ __forceinline__ void prefetch_tmap(const CUtensorMap* tm) { asm volatile("prefetch.tensormap [%0];" ::"l"((uint64_t)tm) : "memory"); }
__device__ __forceinline__ uint32_t mapa_u32(uint32_t addr, uint32_t cta) {
    uint32_t r;
    asm volatile("mapa.shared::cluster.u32 %0, %1, %2;" : "=r"(r) : "r"(addr), "r"(cta));
    return r;
}
__device__ __forceinline__ void mbar_arrive_cluster(uint32_t cluster_addr) {
    asm volatile("mbarrier.arrive.shared::cluster.b64 _, [%0];" ::"r"(cluster_addr) : "memory");
}
__device__ __forceinline__ bool elect_one() {
    uint32_t p;
    asm volatile("{\n.reg .pred P;\nelect.sync _|P, 0xffffffff;\nselp.u32 %0, 1, 0, P;\n}\n" : "=r"(p));
    return p != 0;
}
__device__ __forceinline__ void cluster_arrive_relaxed() { asm volatile("barrier.cluster.arrive.relaxed.aligned;" ::: "memory"); }
__device__ __forceinline__ void cluster_wait() { asm volatile("barrier.cluster.wait.acquire.aligned;" ::: "memory"); }

__device__ __forceinline__ uint32_t bsub2(uint32_t a, uint32_t b) {
    __nv_bfloat162 r = __hsub2(*reinterpret_cast<__nv_bfloat162*>(&a), *reinterpret_cast<__nv_bfloat162*>(&b));
    return *reinterpret_cast<uint32_t*>(&r);
}
__device__ __forceinline__ uint32_t bmul2(uint32_t a, uint32_t b) {
    __nv_bfloat162 r = __hmul2(*reinterpret_cast<__nv_bfloat162*>(&a), *reinterpret_cast<__nv_bfloat162*>(&b));
    return *reinterpret_cast<uint32_t*>(&r);
}
__device__ __forceinline__ uint32_t badd2(uint32_t a, uint32_t b) {
    __nv_bfloat162 r = __hadd2(*reinterpret_cast<__nv_bfloat162*>(&a), *reinterpret_cast<__nv_bfloat162*>(&b));
    return *reinterpret_cast<uint32_t*>(&r);
}
constexpr int BM = 128, BK = 64;
constexpr int R5_STAGE = 32768, R5_N = 5;
constexpr int R4_STAGE = 49152, R4_N = 4;
constexpr int R4B_STAGE = 40960;
constexpr int OFF_STG5 = 0, OFF_R = 32768;
constexpr int OFF_EPI = 196608;
constexpr int OFF_BAR = OFF_EPI + 32768;
constexpr int OFF_RS = OFF_BAR + 256;
constexpr int OFF_CS = OFF_RS + 1024;
constexpr int MEGA_SMEM = OFF_CS + 1792;
enum { FL_XA = 0, FL_H = 2, FL_X1 = 4, FL_H2 = 6, FL_CS = 10, FL_KINDS = 11 };
constexpr int FL_PITCH = 64;
constexpr int FL_WORDS = 2 * FL_KINDS * 16 * FL_PITCH;
__device__ unsigned int g_flag[FL_WORDS];
__device__ __align__(8) unsigned int g_ticket[18 * FL_PITCH];
constexpr int NCL = 66;
__device__ __forceinline__ unsigned int* flag_ptr(int layer, int kind, int i) { return g_flag + ((layer * FL_KINDS + kind) * 16 + i) * FL_PITCH; }

__device__ __forceinline__ void wait_flag(const unsigned int* p, unsigned int target) {
    long long t0 = clock64();
    while (true) {
        unsigned int v;
        asm volatile("ld.relaxed.gpu.global.u32 %0, [%1];" : "=r"(v) : "l"(p) : "memory");
        if ((int)(v - target) >= 0) break;
        if (clock64() - t0 > 2000000000LL) break;
    }
    asm volatile("fence.acquire.gpu;" ::: "memory");
}
__device__ __forceinline__ void fence_proxy_async() {
    asm volatile("fence.proxy.async.global;" ::: "memory");
    asm volatile("fence.proxy.async.shared::cta;" ::: "memory");
}
__device__ __forceinline__ void stsm4(uint32_t addr, uint32_t r0, uint32_t r1, uint32_t r2, uint32_t r3) {
    asm volatile("stmatrix.sync.aligned.m8n8.x4.shared.b16 [%0], {%1,%2,%3,%4};" ::"r"(addr), "r"(r0), "r"(r1), "r"(r2), "r"(r3));
}
__device__ __forceinline__ uint4 lds128(uint32_t a) {
    uint4 v;
    asm volatile("ld.shared.v4.b32 {%0,%1,%2,%3}, [%4];" : "=r"(v.x), "=r"(v.y), "=r"(v.z), "=r"(v.w) : "r"(a) : "memory");
    return v;
}
__device__ __forceinline__ void stg128(void* p, uint4 v) {
    asm volatile("st.global.v4.b32 [%0], {%1,%2,%3,%4};" ::"l"(p), "r"(v.x), "r"(v.y), "r"(v.z), "r"(v.w) : "memory");
}
__device__ __forceinline__ float gelu_tanh_h(float hx) {
    float z = hx * fmaf(hx * hx, 8.0f * 0.035677408136300125f, 2.0f * 0.7978845608028654f);
    float t;
    asm("tanh.approx.f32 %0, %1;" : "=f"(t) : "f"(z));
    return fmaf(hx, t, hx);
}
__device__ __forceinline__ uint32_t gelu2h(uint32_t hx) {
    uint32_t r;
    asm("{\n.reg .b32 z;\nmul.rn.bf16x2 z, %1, %1;\nfma.rn.bf16x2 z, z, %2, %3;\nmul.rn.bf16x2 z, z, %1;\ntanh.approx.bf16x2 z, z;\nfma.rn.bf16x2 %0, %1, z, %1;\n}"
        : "=r"(r) : "r"(hx), "r"(0x3e923e92u), "r"(0x3fcc3fccu));
    return r;
}
__device__ __forceinline__ uint4 gelu8h(uint4 v) { return make_uint4(gelu2h(v.x), gelu2h(v.y), gelu2h(v.z), gelu2h(v.w)); }

__device__ __forceinline__ void row_stats(const float2* p, uint32_t tag, float& mean, float& var) {
    float2 v[8];
#pragma unroll 1
    for (int n = 0; n < (1 << 20); n++) {
#pragma unroll
        for (int i = 0; i < 8; i++)
            asm volatile("{\n.reg .b64 t;\nld.relaxed.gpu.global.b64 t, [%2];\nmov.b64 {%0, %1}, t;\n}" : "=f"(v[i].x), "=f"(v[i].y) : "l"(p + 128 * i) : "memory");
        uint32_t old = 0;
#pragma unroll
        for (int i = 0; i < 8; i++) old |= __float_as_uint(v[i].y) ^ tag;
        if ((int)old >= 0) break;
    }
    mean = (((v[0].x + v[1].x) + (v[2].x + v[3].x)) + ((v[4].x + v[5].x) + (v[6].x + v[7].x))) * 0.125f;
    float m2 = 0.f, d2 = 0.f;
#pragma unroll
    for (int i = 0; i < 8; i++) { m2 += fabsf(v[i].y); d2 = fmaf(v[i].x - mean, v[i].x - mean, d2); }
    var = fmaf(128.0f, d2, m2) * (1.0f / D_);
}
struct RingState { uint32_t st, ph; };

#define DT(i)
#define DT_DECL
#define DT_PAR
#define DT_ARG
#define DT_DUMP
#define DP(i)
#define DQ(i)
#define GT(i)
#define TM(i)

template <int BN, int NST, int ACC = 1>
__device__ __forceinline__ void kblock(float (&acc)[BN / 2], uint32_t da, uint32_t db, uint32_t bfull, RingState& rs) {
    mbar_wait(bfull + 8 * rs.st, rs.ph);
    wgmma_fence();
    WG<BN>::template mma<ACC>(acc, da, db);
#pragma unroll
    for (int k = 1; k < 4; k++) WG<BN>::template mma<1>(acc, da + k * 2, db + k * 128);
    wgmma_commit();
    if (++rs.st == NST) { rs.st = 0; rs.ph ^= 1; }
}
#define PA3A 1
#define RLX 1
#define NPRE 12
#define PP3 2
#define NCS 8
template <int V> struct IC { static constexpr int v = V; };
template <int A, int B, class F> __device__ __forceinline__ void static_for(F f) {
    if constexpr (A < B) { f(IC<A>()); static_for<A + 1, B>(f); }
}
#define SPL 21
#define PF4A 22
#define PF4N 1
#define XCS 0
#define PA1 45
#define PA2 33
#define PA4 33
#define LAGX 1
#define PA3B 0
template <int BN, int NST, int STAGE, int PS = 0, int TW = 0, class F>
__device__ __forceinline__ void mainloop(float (&acc)[BN / 2], int KB, uint32_t da0, uint32_t db0, uint32_t bfull, uint32_t rel, bool rel_on,
                                         RingState& rs, int dbg, F pre DT_PAR, int wg = 0) {
    constexpr int SG = PS / 10, PAUSE = PS % 10;
    uint32_t prev = rs.st ? rs.st - 1 : NST - 1;
    const int pause = wg ? KB - PAUSE : -1;
#pragma unroll 1
    for (int kk = 0; kk < KB; kk++) {
        const uint32_t cur = rs.st;
        if (PAUSE && kk == pause) {
            wgmma_wait<0>();
            if (rel_on) mbar_arrive_cluster(rel + 8 * prev);
            named_bar_sync(15, 256);
        }
        kblock<BN, NST>(acc, da0 + cur * (STAGE / 16), db0 + cur * (STAGE / 16), bfull, rs);
        if (PAUSE && SG >= 2 && wg == 0 && kk == KB + 1 - SG) named_bar_arrive(15, 256);
        wgmma_wait<1>();
        if (rel_on && !(PAUSE && kk == pause)) mbar_arrive_cluster(rel + 8 * prev);
        prev = cur;
    }
    if (PAUSE && SG == 0 && wg == 0) named_bar_arrive(15, 256);
    pre();
    wgmma_wait<TW>();
#pragma unroll
    for (int i = 0; i < BN / 2; i++) asm volatile("" : "+f"(acc[i])::"memory");
    if (PAUSE && SG == 1 && wg == 0) named_bar_arrive(15, 256);
    if (rel_on) mbar_arrive_cluster(rel + 8 * prev);
}
__device__ __forceinline__ void hmma(float (&c)[4], uint32_t a0, uint32_t a1, uint32_t a2, uint32_t a3, uint32_t b0, uint32_t b1, bool first) {
    if (first) asm("{\n.reg .f32 z;\nmov.f32 z, 0f00000000;\nmma.sync.aligned.m16n8k16.row.col.f32.bf16.bf16.f32 {%0,%1,%2,%3}, {%4,%5,%6,%7}, {%8,%9}, {z,z,z,z};\n}"
        : "=f"(c[0]), "=f"(c[1]), "=f"(c[2]), "=f"(c[3]) : "r"(a0), "r"(a1), "r"(a2), "r"(a3), "r"(b0), "r"(b1));
    else
    asm("mma.sync.aligned.m16n8k16.row.col.f32.bf16.bf16.f32 {%0,%1,%2,%3}, {%4,%5,%6,%7}, {%8,%9}, {%0,%1,%2,%3};"
        : "+f"(c[0]), "+f"(c[1]), "+f"(c[2]), "+f"(c[3]) : "r"(a0), "r"(a1), "r"(a2), "r"(a3), "r"(b0), "r"(b1));
}
__device__ __forceinline__ void hmma8(float (&c)[4], uint32_t a0, uint32_t a1, uint32_t b0, bool first) {
    if (first) asm("{\n.reg .f32 z;\nmov.f32 z, 0f00000000;\nmma.sync.aligned.m16n8k8.row.col.f32.bf16.bf16.f32 {%0,%1,%2,%3}, {%4,%5}, {%6}, {z,z,z,z};\n}"
        : "=f"(c[0]), "=f"(c[1]), "=f"(c[2]), "=f"(c[3]) : "r"(a0), "r"(a1), "r"(b0));
    else
    asm("mma.sync.aligned.m16n8k8.row.col.f32.bf16.bf16.f32 {%0,%1,%2,%3}, {%4,%5}, {%6}, {%0,%1,%2,%3};"
        : "+f"(c[0]), "+f"(c[1]), "+f"(c[2]), "+f"(c[3]) : "r"(a0), "r"(a1), "r"(b0));
}
template <int N> __device__ __forceinline__ void zero_acc(float (&acc)[N]) {
#pragma unroll
    for (int i = 0; i < N; i++) acc[i] = 0.f;
}
__device__ __forceinline__ void ldsm4(uint32_t& r0, uint32_t& r1, uint32_t& r2, uint32_t& r3, uint32_t addr) {
    asm volatile("ldmatrix.sync.aligned.m8n8.x4.shared.b16 {%0,%1,%2,%3}, [%4];" : "=r"(r0), "=r"(r1), "=r"(r2), "=r"(r3) : "r"(addr));
}

__device__ __forceinline__ void ldsm4t(uint32_t& r0, uint32_t& r1, uint32_t& r2, uint32_t& r3, uint32_t addr) {
    asm volatile("ldmatrix.sync.aligned.m8n8.x4.trans.shared.b16 {%0,%1,%2,%3}, [%4];" : "=r"(r0), "=r"(r1), "=r"(r2), "=r"(r3) : "r"(addr));
}

#define DBG_S(i)
#define DBG_OUT(r, o)
#define DBG_F(i)
#define DBG_W(i)
constexpr int CV_CH = 8;
constexpr int CV_SL = 16384;
constexpr int CV_QG = 128 * 8 + 16;
constexpr int CV_HPL = 2048 + 192;
constexpr int CV_0 = 32768, CV_H = 9 * CV_SL, CV_BAR = OFF_RS - CV_0;

template <int K> __device__ __forceinline__ void cv_mma(float (&d)[64], const uint32_t (&a)[4], uint32_t db, int acc);
template <> __device__ __forceinline__ void cv_mma<0>(float (&d)[64], const uint32_t (&a)[4], uint32_t db, int acc) {
    asm volatile("{\n.reg .pred p;\n.reg .b64 b;\nsetp.ne.b32 p, %70, 0;\nmov.b64 b, {%68, %69};\n"
        "wgmma.mma_async.sync.aligned.m64n128k16.f32.bf16.bf16 {%0,%1,%2,%3,%4,%5,%6,%7,%8,%9,%10,%11,%12,%13,%14,%15,%16,%17,%18,%19,%20,%21,%22,%23,%24,%25,%26,%27,%28,%29,%30,%31,%32,%33,%34,%35,%36,%37,%38,%39,%40,%41,%42,%43,%44,%45,%46,%47,%48,%49,%50,%51,%52,%53,%54,%55,%56,%57,%58,%59,%60,%61,%62,%63}, {%64,%65,%66,%67}, b, p, 1, 1, 0;\n}\n"
        : "+f"(d[0]), "+f"(d[1]), "+f"(d[2]), "+f"(d[3]), "+f"(d[4]), "+f"(d[5]), "+f"(d[6]), "+f"(d[7]), "+f"(d[8]), "+f"(d[9]), "+f"(d[10]), "+f"(d[11]), "+f"(d[12]), "+f"(d[13]), "+f"(d[14]), "+f"(d[15]), "+f"(d[16]), "+f"(d[17]), "+f"(d[18]), "+f"(d[19]), "+f"(d[20]), "+f"(d[21]), "+f"(d[22]), "+f"(d[23]), "+f"(d[24]), "+f"(d[25]), "+f"(d[26]), "+f"(d[27]), "+f"(d[28]), "+f"(d[29]), "+f"(d[30]), "+f"(d[31]), "+f"(d[32]), "+f"(d[33]), "+f"(d[34]), "+f"(d[35]), "+f"(d[36]), "+f"(d[37]), "+f"(d[38]), "+f"(d[39]), "+f"(d[40]), "+f"(d[41]), "+f"(d[42]), "+f"(d[43]), "+f"(d[44]), "+f"(d[45]), "+f"(d[46]), "+f"(d[47]), "+f"(d[48]), "+f"(d[49]), "+f"(d[50]), "+f"(d[51]), "+f"(d[52]), "+f"(d[53]), "+f"(d[54]), "+f"(d[55]), "+f"(d[56]), "+f"(d[57]), "+f"(d[58]), "+f"(d[59]), "+f"(d[60]), "+f"(d[61]), "+f"(d[62]), "+f"(d[63])
        : "r"(a[0]), "r"(a[1]), "r"(a[2]), "r"(a[3]), "r"(db), "r"(8u), "r"(acc));
}
template <> __device__ __forceinline__ void cv_mma<1>(float (&d)[64], const uint32_t (&a)[4], uint32_t db, int acc) {
    asm volatile("{\n.reg .pred p;\n.reg .b64 b;\nsetp.ne.b32 p, %62, 0;\nmov.b64 b, {%60, %61};\n"
        "wgmma.mma_async.sync.aligned.m64n112k16.f32.bf16.bf16 {%0,%1,%2,%3,%4,%5,%6,%7,%8,%9,%10,%11,%12,%13,%14,%15,%16,%17,%18,%19,%20,%21,%22,%23,%24,%25,%26,%27,%28,%29,%30,%31,%32,%33,%34,%35,%36,%37,%38,%39,%40,%41,%42,%43,%44,%45,%46,%47,%48,%49,%50,%51,%52,%53,%54,%55}, {%56,%57,%58,%59}, b, p, 1, 1, 0;\n}\n"
        : "+f"(d[0]), "+f"(d[1]), "+f"(d[2]), "+f"(d[3]), "+f"(d[4]), "+f"(d[5]), "+f"(d[6]), "+f"(d[7]), "+f"(d[8]), "+f"(d[9]), "+f"(d[10]), "+f"(d[11]), "+f"(d[12]), "+f"(d[13]), "+f"(d[14]), "+f"(d[15]), "+f"(d[16]), "+f"(d[17]), "+f"(d[18]), "+f"(d[19]), "+f"(d[20]), "+f"(d[21]), "+f"(d[22]), "+f"(d[23]), "+f"(d[24]), "+f"(d[25]), "+f"(d[26]), "+f"(d[27]), "+f"(d[28]), "+f"(d[29]), "+f"(d[30]), "+f"(d[31]), "+f"(d[32]), "+f"(d[33]), "+f"(d[34]), "+f"(d[35]), "+f"(d[36]), "+f"(d[37]), "+f"(d[38]), "+f"(d[39]), "+f"(d[40]), "+f"(d[41]), "+f"(d[42]), "+f"(d[43]), "+f"(d[44]), "+f"(d[45]), "+f"(d[46]), "+f"(d[47]), "+f"(d[48]), "+f"(d[49]), "+f"(d[50]), "+f"(d[51]), "+f"(d[52]), "+f"(d[53]), "+f"(d[54]), "+f"(d[55])
        : "r"(a[0]), "r"(a[1]), "r"(a[2]), "r"(a[3]), "r"(db), "r"(8u), "r"(acc));
}
template <> __device__ __forceinline__ void cv_mma<2>(float (&d)[64], const uint32_t (&a)[4], uint32_t db, int acc) {
    asm volatile("{\n.reg .pred p;\n.reg .b64 b;\nsetp.ne.b32 p, %54, 0;\nmov.b64 b, {%52, %53};\n"
        "wgmma.mma_async.sync.aligned.m64n96k16.f32.bf16.bf16 {%0,%1,%2,%3,%4,%5,%6,%7,%8,%9,%10,%11,%12,%13,%14,%15,%16,%17,%18,%19,%20,%21,%22,%23,%24,%25,%26,%27,%28,%29,%30,%31,%32,%33,%34,%35,%36,%37,%38,%39,%40,%41,%42,%43,%44,%45,%46,%47}, {%48,%49,%50,%51}, b, p, 1, 1, 0;\n}\n"
        : "+f"(d[0]), "+f"(d[1]), "+f"(d[2]), "+f"(d[3]), "+f"(d[4]), "+f"(d[5]), "+f"(d[6]), "+f"(d[7]), "+f"(d[8]), "+f"(d[9]), "+f"(d[10]), "+f"(d[11]), "+f"(d[12]), "+f"(d[13]), "+f"(d[14]), "+f"(d[15]), "+f"(d[16]), "+f"(d[17]), "+f"(d[18]), "+f"(d[19]), "+f"(d[20]), "+f"(d[21]), "+f"(d[22]), "+f"(d[23]), "+f"(d[24]), "+f"(d[25]), "+f"(d[26]), "+f"(d[27]), "+f"(d[28]), "+f"(d[29]), "+f"(d[30]), "+f"(d[31]), "+f"(d[32]), "+f"(d[33]), "+f"(d[34]), "+f"(d[35]), "+f"(d[36]), "+f"(d[37]), "+f"(d[38]), "+f"(d[39]), "+f"(d[40]), "+f"(d[41]), "+f"(d[42]), "+f"(d[43]), "+f"(d[44]), "+f"(d[45]), "+f"(d[46]), "+f"(d[47])
        : "r"(a[0]), "r"(a[1]), "r"(a[2]), "r"(a[3]), "r"(db), "r"(8u), "r"(acc));
}
template <> __device__ __forceinline__ void cv_mma<3>(float (&d)[64], const uint32_t (&a)[4], uint32_t db, int acc) {
    asm volatile("{\n.reg .pred p;\n.reg .b64 b;\nsetp.ne.b32 p, %46, 0;\nmov.b64 b, {%44, %45};\n"
        "wgmma.mma_async.sync.aligned.m64n80k16.f32.bf16.bf16 {%0,%1,%2,%3,%4,%5,%6,%7,%8,%9,%10,%11,%12,%13,%14,%15,%16,%17,%18,%19,%20,%21,%22,%23,%24,%25,%26,%27,%28,%29,%30,%31,%32,%33,%34,%35,%36,%37,%38,%39}, {%40,%41,%42,%43}, b, p, 1, 1, 0;\n}\n"
        : "+f"(d[0]), "+f"(d[1]), "+f"(d[2]), "+f"(d[3]), "+f"(d[4]), "+f"(d[5]), "+f"(d[6]), "+f"(d[7]), "+f"(d[8]), "+f"(d[9]), "+f"(d[10]), "+f"(d[11]), "+f"(d[12]), "+f"(d[13]), "+f"(d[14]), "+f"(d[15]), "+f"(d[16]), "+f"(d[17]), "+f"(d[18]), "+f"(d[19]), "+f"(d[20]), "+f"(d[21]), "+f"(d[22]), "+f"(d[23]), "+f"(d[24]), "+f"(d[25]), "+f"(d[26]), "+f"(d[27]), "+f"(d[28]), "+f"(d[29]), "+f"(d[30]), "+f"(d[31]), "+f"(d[32]), "+f"(d[33]), "+f"(d[34]), "+f"(d[35]), "+f"(d[36]), "+f"(d[37]), "+f"(d[38]), "+f"(d[39])
        : "r"(a[0]), "r"(a[1]), "r"(a[2]), "r"(a[3]), "r"(db), "r"(8u), "r"(acc));
}
template <> __device__ __forceinline__ void cv_mma<4>(float (&d)[64], const uint32_t (&a)[4], uint32_t db, int acc) {
    asm volatile("{\n.reg .pred p;\n.reg .b64 b;\nsetp.ne.b32 p, %38, 0;\nmov.b64 b, {%36, %37};\n"
        "wgmma.mma_async.sync.aligned.m64n64k16.f32.bf16.bf16 {%0,%1,%2,%3,%4,%5,%6,%7,%8,%9,%10,%11,%12,%13,%14,%15,%16,%17,%18,%19,%20,%21,%22,%23,%24,%25,%26,%27,%28,%29,%30,%31}, {%32,%33,%34,%35}, b, p, 1, 1, 0;\n}\n"
        : "+f"(d[0]), "+f"(d[1]), "+f"(d[2]), "+f"(d[3]), "+f"(d[4]), "+f"(d[5]), "+f"(d[6]), "+f"(d[7]), "+f"(d[8]), "+f"(d[9]), "+f"(d[10]), "+f"(d[11]), "+f"(d[12]), "+f"(d[13]), "+f"(d[14]), "+f"(d[15]), "+f"(d[16]), "+f"(d[17]), "+f"(d[18]), "+f"(d[19]), "+f"(d[20]), "+f"(d[21]), "+f"(d[22]), "+f"(d[23]), "+f"(d[24]), "+f"(d[25]), "+f"(d[26]), "+f"(d[27]), "+f"(d[28]), "+f"(d[29]), "+f"(d[30]), "+f"(d[31])
        : "r"(a[0]), "r"(a[1]), "r"(a[2]), "r"(a[3]), "r"(db), "r"(8u), "r"(acc));
}
template <> __device__ __forceinline__ void cv_mma<5>(float (&d)[64], const uint32_t (&a)[4], uint32_t db, int acc) {
    asm volatile("{\n.reg .pred p;\n.reg .b64 b;\nsetp.ne.b32 p, %30, 0;\nmov.b64 b, {%28, %29};\n"
        "wgmma.mma_async.sync.aligned.m64n48k16.f32.bf16.bf16 {%0,%1,%2,%3,%4,%5,%6,%7,%8,%9,%10,%11,%12,%13,%14,%15,%16,%17,%18,%19,%20,%21,%22,%23}, {%24,%25,%26,%27}, b, p, 1, 1, 0;\n}\n"
        : "+f"(d[0]), "+f"(d[1]), "+f"(d[2]), "+f"(d[3]), "+f"(d[4]), "+f"(d[5]), "+f"(d[6]), "+f"(d[7]), "+f"(d[8]), "+f"(d[9]), "+f"(d[10]), "+f"(d[11]), "+f"(d[12]), "+f"(d[13]), "+f"(d[14]), "+f"(d[15]), "+f"(d[16]), "+f"(d[17]), "+f"(d[18]), "+f"(d[19]), "+f"(d[20]), "+f"(d[21]), "+f"(d[22]), "+f"(d[23])
        : "r"(a[0]), "r"(a[1]), "r"(a[2]), "r"(a[3]), "r"(db), "r"(8u), "r"(acc));
}
template <> __device__ __forceinline__ void cv_mma<6>(float (&d)[64], const uint32_t (&a)[4], uint32_t db, int acc) {
    asm volatile("{\n.reg .pred p;\n.reg .b64 b;\nsetp.ne.b32 p, %22, 0;\nmov.b64 b, {%20, %21};\n"
        "wgmma.mma_async.sync.aligned.m64n32k16.f32.bf16.bf16 {%0,%1,%2,%3,%4,%5,%6,%7,%8,%9,%10,%11,%12,%13,%14,%15}, {%16,%17,%18,%19}, b, p, 1, 1, 0;\n}\n"
        : "+f"(d[0]), "+f"(d[1]), "+f"(d[2]), "+f"(d[3]), "+f"(d[4]), "+f"(d[5]), "+f"(d[6]), "+f"(d[7]), "+f"(d[8]), "+f"(d[9]), "+f"(d[10]), "+f"(d[11]), "+f"(d[12]), "+f"(d[13]), "+f"(d[14]), "+f"(d[15])
        : "r"(a[0]), "r"(a[1]), "r"(a[2]), "r"(a[3]), "r"(db), "r"(8u), "r"(acc));
}
template <> __device__ __forceinline__ void cv_mma<7>(float (&d)[64], const uint32_t (&a)[4], uint32_t db, int acc) {
    asm volatile("{\n.reg .pred p;\n.reg .b64 b;\nsetp.ne.b32 p, %14, 0;\nmov.b64 b, {%12, %13};\n"
        "wgmma.mma_async.sync.aligned.m64n16k16.f32.bf16.bf16 {%0,%1,%2,%3,%4,%5,%6,%7}, {%8,%9,%10,%11}, b, p, 1, 1, 0;\n}\n"
        : "+f"(d[0]), "+f"(d[1]), "+f"(d[2]), "+f"(d[3]), "+f"(d[4]), "+f"(d[5]), "+f"(d[6]), "+f"(d[7])
        : "r"(a[0]), "r"(a[1]), "r"(a[2]), "r"(a[3]), "r"(db), "r"(8u), "r"(acc));
}
__device__ __forceinline__ void stsm4t(uint32_t addr, uint32_t r0, uint32_t r1, uint32_t r2, uint32_t r3) {
    asm volatile("stmatrix.sync.aligned.m8n8.x4.trans.shared.b16 [%0], {%1,%2,%3,%4};" ::"r"(addr), "r"(r0), "r"(r1), "r"(r2), "r"(r3) : "memory");
}
__device__ __forceinline__ void cp16(uint32_t dst, const void* src, int n = 16) {
    asm volatile("cp.async.cg.shared.global.L2::128B [%0], [%1], 16, %2;" ::"r"(dst), "l"(src), "r"(n) : "memory");
}
__device__ __forceinline__ void cp_arrive(uint32_t bar) { asm volatile("cp.async.mbarrier.arrive.noinc.shared::cta.b64 [%0];" ::"r"(bar) : "memory"); }
__device__ __forceinline__ void lds64(uint32_t& x, uint32_t& y, uint32_t a) { asm volatile("ld.shared.v2.b32 {%0,%1}, [%2];" : "=r"(x), "=r"(y) : "r"(a) : "memory"); }
__device__ __forceinline__ void sts128(uint32_t a, uint32_t x, uint32_t y, uint32_t z, uint32_t w) {
    asm volatile("st.shared.v4.b32 [%0], {%1,%2,%3,%4};" ::"r"(a), "r"(x), "r"(y), "r"(z), "r"(w) : "memory");
}
__device__ __forceinline__ uint32_t bfma2(uint32_t a, uint32_t b, uint32_t c) {
    uint32_t r;
    asm("fma.rn.bf16x2 %0, %1, %2, %3;" : "=r"(r) : "r"(a), "r"(b), "r"(c));
    return r;
}
#define CV_NS 4
#define CV_W 1
constexpr int CV_GC = 8 / CV_NS, CV_NA = (CV_W + 2) * CV_NS;
struct CvAddr { uint32_t pa[2], p0[4], db, rdy, xw, xr, bar; bool wrap, neg[2]; };
template <int G> __device__ __forceinline__ void cv_load(uint32_t (&a)[CV_NA][4], const CvAddr& p) {
    if constexpr (G % CV_GC == 0) mbar_wait(p.rdy + 8 * (G / CV_GC), 0);
#pragma unroll
    for (int i = G * CV_NS; i < (G + 1) * CV_NS; i++) {
        const int of = (i / 2 % 2) * CV_QG + (i / 8) * CV_SL + 256 * (i % 2 + (i / 2 & 2));
        if ((i & 5) == 0) {
#pragma unroll
            for (int e = 0; e < 4; e++) asm volatile("ld.shared.b32 %0, [%1];" : "=r"(a[i % CV_NA][e]) : "r"(p.p0[e] + of) : "memory");
            if (i < 8) { if (p.neg[0]) a[i % CV_NA][0] = 0; if (p.neg[1]) a[i % CV_NA][2] = 0; }
        } else {
            lds64(a[i % CV_NA][0], a[i % CV_NA][1], p.pa[0] + of - 256);
            lds64(a[i % CV_NA][2], a[i % CV_NA][3], p.pa[1] + of - 256);
        }
    }
}
__device__ __forceinline__ float vadd(float a, float b) {
    float r;
    asm volatile("add.f32 %0, %1, %2;" : "=f"(r) : "f"(a), "f"(b));
    return r;
}
template <int K> __device__ __forceinline__ uint32_t cv_tail(float (&d)[64], bool wrap) {
    float* z = d + 56 - 8 * K;
    z[4] = vadd(z[4], K > 0 ? z[10] : 0.f);
    if constexpr (K > 0) z[5] = vadd(z[5], z[11]);
    z[0] = vadd(z[0], z[6]);
    z[1] = vadd(z[1], z[7]);
    return pack2(wrap ? (K > 0 ? z[8] : 0.f) : z[4], wrap ? z[4] : z[0]);
}
template <int K> __device__ __forceinline__ uint32_t cv_fin(const float (&d)[64], uint32_t x) { return pack2(d[61 - 8 * K] + lo2f(x), d[57 - 8 * K] + hi2f(x)); }
template <int G>
__device__ __forceinline__ void cv_steps(float (&d)[2][64], uint32_t (&a)[CV_NA][4], uint32_t (&tv)[2][8], const CvAddr& p) {
    constexpr int K = G / CV_GC, GN = 8 * CV_GC;
    constexpr int T = G - CV_W - CV_GC, F = T - 1, TK = T / CV_GC, FK = F / CV_GC;
    if constexpr (G == 0) cv_load<0>(a, p);
    if constexpr (G < GN) {
        wgmma_fence();
#pragma unroll
        for (int i = G * CV_NS; i < (G + 1) * CV_NS; i++)
            cv_mma<K>(d[i / 2 % 2], a[i % CV_NA], p.db + (i / 2 % 2) * (CV_HPL / 8) + 16 * K + 2 * (i % 2 + (i / 2 & 2)), i & ~2 ? 1 : p.bar >> 8);
        wgmma_commit();
    }
    if constexpr (G < GN - 1) cv_load<G + 1>(a, p);
    if constexpr (T >= 0 && T % CV_GC == 0) {
        tv[0][TK] = cv_tail<TK>(d[0], p.wrap);
        tv[1][TK] = cv_tail<TK>(d[1], p.wrap);
        if constexpr (TK & 1) sts128(p.xw + TK / 2 * 512, tv[0][TK - 1], tv[0][TK], tv[1][TK - 1], tv[1][TK]);
    }
    if constexpr (F >= 0 && F % (2 * CV_GC) == CV_GC) {
        const uint4 x = lds128(p.xr + FK / 2 * 512);
        tv[0][FK - 1] = cv_fin<FK - 1>(d[0], x.x); tv[0][FK] = cv_fin<FK>(d[0], x.y);
        tv[1][FK - 1] = cv_fin<FK - 1>(d[1], x.z); tv[1][FK] = cv_fin<FK>(d[1], x.w);
    }
    if constexpr (G < GN - 1) wgmma_wait<CV_W>();
    if constexpr (G == GN - 1) wgmma_wait<0>();
    if constexpr (T >= 0 && T % (2 * CV_GC) == CV_GC) named_bar_sync(p.bar, 128);
    if constexpr (F < GN - CV_GC) cv_steps<G + 1>(d, a, tv, p);
}

#define CV_PF 7
#define Y_FIRST 1
#define Y_HOLD 0
#define PS2_EARLY 1
#define PS1_EARLY 1
#define FMOVE 1
#define SENDC 1
#define HDELAY 0
#define NH16 1
#define GST 23
#define GS2 0
#define H11 0
#define REL 3
#define W3_AT -1
constexpr int SPL2 = SPL & ~GST;
struct MegaMaps {
    CUtensorMap q, act;
    CUtensorMap a64, w1, w2, w3, w4;
    CUtensorMap k, v, y;
};

__global__ void __cluster_dims__(2, 1, 1) __launch_bounds__(384, 1)
mega_kernel(const __grid_constant__ MegaMaps tm, bf16* __restrict__ outp, bf16* act, const bf16* __restrict__ w1p, const bf16* __restrict__ w2p,
            const bf16* __restrict__ w3p, const bf16* __restrict__ xq, const bf16* __restrict__ kp, const bf16* __restrict__ vp,
            const bf16* __restrict__ shk, const bf16* __restrict__ ssk, const bf16* __restrict__ ssD) {
    extern __shared__ __align__(1024) uint8_t sgen[];
    const uint32_t sbase = smem_u32(sgen);
    const int warp = __shfl_sync(0xffffffffu, threadIdx.x >> 5, 0), lane = threadIdx.x & 31;
    const int rank = blockIdx.x & 1;
    const uint32_t s_bar = sbase + OFF_BAR;
    const uint32_t f5 = s_bar, e5 = s_bar + 64, f4 = s_bar + 144, e4 = s_bar + 104;
    const uint32_t b_rfull = s_bar + 176, b_role = s_bar + 184, b_stg = s_bar + 136, b_h2 = s_bar + 32;
    const uint32_t s_epi = sbase + OFF_EPI, s_stg = sbase + OFF_STG5, s_r = sbase + OFF_R;
    uint8_t* sm = sgen + CV_0;
    const uint32_t sb = sbase + CV_0;
    const int tid = threadIdx.x, wg = warp >> 2, w = warp & 3;
    const int d0 = blockIdx.x * CV_CH;
    const bool cv = blockIdx.x < D_ / CV_CH;
    const uint32_t b_full = sb + CV_BAR, b_rdy = b_full + 64, b_h = b_full + 128;
    GT(0);
    if (tid == 0) TM(0);
    auto row_at = [&](int r) { return sb + CV_SL + (r < 0 ? -8192 : 0) + ((r & 127) >> 5) * 1024 + (r & 7) * 128 + ((r >> 3) & 3) * 32 + ((r ^ rank) & 1) * 16; };
    auto load_kv = [&](int c) {
#pragma unroll
        for (int i = 0; i < 2; i++)
            asm volatile("cp.async.bulk.tensor.4d.shared::cluster.global.mbarrier::complete_tx::bytes.multicast::cluster [%0], [%1, {%3, %4, %4, %5}], [%2], %6;"
                         ::"r"(sb + (c + 1) * CV_SL + rank * 8192 + i * 4096), "l"((uint64_t)(i ? &tm.v : &tm.k)), "r"(b_full + 8 * c), "r"(d0 & ~15), "r"(0),
                         "r"(8 * c + 4 * rank), "h"((uint16_t)3) : "memory");
    };
    auto bulk = [&](uint32_t dst, const void* src, uint32_t n, uint32_t bar) {
        asm volatile("cp.async.bulk.shared::cluster.global.mbarrier::complete_tx::bytes [%0], [%1], %2, [%3];" ::"r"(dst), "l"(src), "r"(n), "r"(bar) : "memory");
    };
    auto put_h = [&](int ch) {
        const uint32_t dk = (tid & 127) ? 0 : *reinterpret_cast<const volatile uint32_t*>(sm + CV_BAR + 160 + 16 * wg + 2 * ch);
        uint4 v[4];
#pragma unroll
        for (int i = 0; i < 4; i++) v[i] = lds128(sbase + ch * 4096 + i * 2048 + (tid & 127) * 16);
        v[0].x = pack2(lo2f(v[0].x) + lo2f(dk), hi2f(v[0].x));
        v[2].x = pack2(lo2f(v[2].x) + hi2f(dk), hi2f(v[2].x));
#pragma unroll
        for (int i = 0; i < 4; i++)
            sts128(sb + CV_H + (2 * ch + (i & 2) + (tid & 1)) * CV_HPL + (127 - ((tid & 127) >> 1)) * 16 - (i & 1) * 1024, v[i].x, v[i].y, v[i].z, v[i].w);
    };
    int bi, bj, m0, tb;
    uint32_t ep;
    auto get_role = [&]() {
        mbar_wait(b_role, 0);
        int role;
        asm volatile("ld.shared.v2.b32 {%0,%1}, [%2];" : "=r"(role), "=r"(ep) : "r"(s_bar + 248) : "memory");
        bi = (role >> 3) * 2 + rank; bj = role & 7; m0 = bi * BM; tb = (role >> 3) * 2048 + rank * 128;
        return role < 64;
    };

    if (warp >= 8) {
        asm volatile("setmaxnreg.dec.sync.aligned.u32 88;");
        cluster_arrive_relaxed();
        if (!cv) cluster_wait(); else {
            const int bt = tid - 256, g = lane >> 2, t = lane & 3;
            if (bt < 16) sts128(row_at((bt & 7) - 8) + (bt >> 3) * 4096, 0, 0, 0, 0);
#pragma unroll
            for (int i = 0; i < 4; i++)
                cp16(row_at(bt) + i * 4096, (i & 1 ? vp : kp) + (size_t)(bt + (i >> 1) * 128) * D_ + d0);
            DBG_S(16 + (3));
            uint2 wa;
            asm volatile("ld.global.nc.v2.b32 {%0,%1}, [%2];" : "=r"(wa.x), "=r"(wa.y) : "l"(shk + (d0 + g) * 4));
            const int mi = lane >> 3, r0 = 32 * w + 8 * ((lane >> 1) & 3) - (lane & 1);
            const uint32_t ka0 = row_at(r0 + 2 * mi - 3), ka1 = row_at(r0 + 2 * (mi & 1) + 5) + (mi >> 1) * 8192;
            const uint32_t va0 = row_at(r0 + 2 * mi + 1) + 4096, va1 = row_at(r0 - 1) + 4096 + (mi & 1) * 8192;
            const uint32_t qd = sb + g * CV_QG + (32 * w + 8 * t) * 8, qd0 = qd + (t & 2) * 16, qd1 = qd + (~t & 2) * 16;
            const uint32_t w0 = __byte_perm(wa.x, 0, 0x1010), w1 = __byte_perm(wa.x, 0, 0x3232), w2 = __byte_perm(wa.y, 0, 0x1010), w3 = __byte_perm(wa.y, 0, 0x3232);
            cluster_wait();
            DBG_S(16 + (5));
            asm volatile("cp.async.wait_all;" ::: "memory");
            named_bar_sync(7, 128);
            DBG_S(16 + (1));
            struct KV { uint32_t k[2][6], v[2][5]; };
            auto get = [&](KV& x, uint32_t so) {
                ldsm4t(x.k[0][0], x.k[0][1], x.k[0][2], x.k[0][3], ka0 + so);
                ldsm4t(x.k[0][4], x.k[0][5], x.k[1][4], x.k[1][5], ka1 + so);
                ldsm4t(x.k[1][0], x.k[1][1], x.k[1][2], x.k[1][3], ka0 + so + 8192);
                asm volatile("ldmatrix.sync.aligned.m8n8.x2.trans.shared.b16 {%0,%1}, [%2];" : "=r"(x.v[0][0]), "=r"(x.v[1][0]) : "r"(va1 + so));
                ldsm4t(x.v[0][1], x.v[0][2], x.v[0][3], x.v[0][4], va0 + so);
                ldsm4t(x.v[1][1], x.v[1][2], x.v[1][3], x.v[1][4], va0 + so + 8192);
            };
            auto build = [&](int c, const KV& x, KV& nx) {
                const uint32_t so = c * CV_SL;
                DBG_F(1);
                uint32_t early;
                asm volatile("{\n.reg .pred p;\nmbarrier.test_wait.parity.shared::cta.b64 p, [%1], 0;\nvote.sync.all.pred p, p, -1;\nselp.u32 %0, 1, 0, p;\n}"
                             : "=r"(early) : "r"(b_full + 8 * (c < 7 ? c + 1 : c)) : "memory");
                if (early) get(nx, so + CV_SL);
                DBG_F(2);
                uint32_t p[8][2];
#pragma unroll
                for (int sg = 0; sg < 2; sg++) {
                    uint32_t u[5], ke[6];
#pragma unroll
                    for (int i = 0; i < 6; i++) ke[i] = __byte_perm(x.k[sg][i], x.k[sg][i ? i - 1 : 0], 0x5432);
#pragma unroll
                    for (int i = 0; i < 5; i++) {
                        u[i] = bmul2(bfma2(x.k[sg][i + 1], w0, bfma2(ke[i + 1], w1, bfma2(x.k[sg][i], w2, bmul2(ke[i], w3)))), x.v[sg][i]);
                        if (i) { p[2 * i - 1][sg] = u[i]; p[2 * i - 2][sg] = __byte_perm(u[i], u[i - 1], 0x5432); }
                    }
                }
                DBG_F(3);
#pragma unroll
                for (int j = 0; j < 4; j++) sts128((j & 2 ? qd1 : qd0) + so + 16 * (j & 1), p[2 * j][0], p[2 * j][1], p[2 * j + 1][0], p[2 * j + 1][1]);
                __syncwarp();
                DBG_F(4);
                if (lane == 0) {
                    mbar_arrive(b_rdy + 8 * c);
                    if (c == w) {
                        if (c < 3) load_kv(c + 5);
                        else { bulk(sbase + 16384, ssk + (size_t)(d0 + 4) * S_, 16384, b_h + 16); bulk(b_full + 192, ssD + d0, 16, b_h + 16); }
                    }
                    if (c == w + 4 && (CV_PF >> w & 1)) {
                        const uint32_t n = w == 0 ? 32768 : w == 3 ? 57344 : 16384;
                        const char* src = reinterpret_cast<const char*>(w == 0 ? xq : w == 1 ? w1p : w == 2 ? w2p : w3p) + (size_t)blockIdx.x * n;
                        asm volatile("cp.async.bulk.prefetch.L2.global [%0], %1;" ::"l"(src), "r"(n) : "memory");
                    }
                }
                DBG_F(5);
                named_bar_sync(7, 128);
                DBG_F(6);
                DBG_S(16 + (c == 0 ? 4 : 5 + c));
                if (!early) { mbar_wait(b_full + 8 * c + 8, 0); get(nx, so + CV_SL); }
                DBG_F(7);
            };
            KV x0, x1;
            get(x0, 0);
#pragma unroll 1
            for (int c = 0; c < 8; c += 2) { build(c, x0, x1); build(c + 1, x1, x0); }
            mbar_wait(b_h + 16, 0);
            put_h(4); put_h(6);
            fence_async_smem();
            __syncwarp();
            if (lane == 0) mbar_arrive(b_full);
            named_bar_sync(7, 128);
            DBG_S(16 + (13));
        }
    } else {
        if (elect_one()) {
            mbar_init(b_full + 8 * warp, warp ? 1 : 4);
            mbar_init(b_rdy + 8 * warp, 4);
            if (warp) mbar_expect_tx(b_full + 8 * warp, 16384);
            if (w == 0 && cv) {
                mbar_init(b_h + 8 * wg, 1);
                mbar_expect_tx(b_h + 8 * wg, 8192 + 16);
                fence_async_smem();
                bulk(sbase + wg * 8192, ssk + (size_t)(d0 + 2 * wg) * S_, 8192, b_h + 8 * wg);
                bulk(b_full + 160 + 16 * wg, ssD + d0, 16, b_h + 8 * wg);
            }
            mbar_init(s_bar + 8 * warp, 1);
            mbar_init(s_bar + 64 + 8 * warp, 4);
            mbar_init(s_bar + 128 + 8 * warp, warp < 2 ? 4 << warp : warp == 6 ? 2 : 1);
            if (wg) mbar_init(s_bar + 160 + 8 * warp, 8);
            if (warp == 0) mbar_arrive(f5);
            if (warp == 7) mbar_expect_tx(b_role, 8);
            if (warp == 1) { mbar_init(b_h + 16, 1); mbar_expect_tx(b_h + 16, 16384 + 16); }
            if (w == 2) sts128(s_bar + 224 + 16 * wg, 0, 0, 0, 0);
            asm volatile("fence.mbarrier_init.release.cluster;" ::: "memory");
            if (warp == 2) { prefetch_tmap(&tm.k); prefetch_tmap(&tm.v); }
        }
        __syncwarp();
        DBG_W(1);
        cluster_arrive_relaxed();
        asm volatile("setmaxnreg.inc.sync.aligned.u32 208;");
        DBG_W(2);
        const int zi = (tid & 127) - 32;
        if (zi >= 0 && zi < 48) sts128(sb + CV_H + (4 * wg + (zi / 6 & 3) + (zi / 24) * 8) * CV_HPL + 2048 + (zi % 6) * 16, 0, 0, 0, 0);
        DBG_W(3);
        cluster_wait();
        DBG_W(5);
        if (cv) {
            if (tid == 32) {
#pragma unroll 1
                for (int c = 1; c < 5; c++) load_kv(c);
                prefetch_tmap(&tm.y);
            }
            __syncwarp();
            DBG_W(6);
            const int g = lane >> 2, t = lane & 3;
            const int x0 = 32 + 8 * w + g - 2 * t;
            CvAddr p;
            p.rdy = b_rdy;
            p.bar = 1 + wg;
            p.xr = sbase + (warp ^ 2) * 2048 + lane * 16;
            p.xw = sbase + warp * 2048 + (g * 4 + ((t - (w >> 1)) & 3)) * 16;
            p.wrap = t == 0 && w >= 2;
            mbar_wait(b_h + 8 * wg, 0);
            DBG_W(4);
            put_h(2 * wg);
            fence_async_smem();
            named_bar_sync(1 + wg, 128);
            float acc[2][64];
            zero_acc(acc[0]); zero_acc(acc[1]);
#pragma unroll 1
            for (int round = 0; round < 2; round++) {
                const int ch = round * 4 + 2 * wg;
                uint32_t a[CV_NA][4], tv[2][8];
#pragma unroll
                for (int e = 0; e < 2; e++) {
                    const int x = x0 - 8 * e;
                    p.neg[e] = x < 32;
                    p.pa[e] = sb + ch * CV_QG + 8 * (x ^ (x >> 2 & 4));
                    p.p0[2 * e] = p.pa[e] + (x < 32 ? 768 + 4 - CV_SL : -256);
                    p.p0[2 * e + 1] = p.pa[e] + (x < 32 ? 768 : -256 + 4);
                }
                p.db = (((sb + CV_H + ch * 2 * CV_HPL) & 0x3FFFF) >> 4) | ((CV_HPL / 16) << 16);
                if (round) mbar_wait(b_full, 0);
                DBG_S(7 + 3 * round);
                cv_steps<0>(acc, a, tv, p);
                DBG_S(8 + 3 * round);
                const int r128 = 4 * (lane >> 3) + 2 * (lane & 1) + ((~lane >> 2) & 1);
#pragma unroll
                for (int i = 0; i < 2; i++) {
                    const uint32_t ta = sb + ((ch + i + 1) & 7) * CV_SL + 12288 + r128 * 128 + ((((~lane & 2) * 2 + w) ^ (r128 & 7)) << 4);
                    stsm4t(ta, tv[i][0], tv[i][1], tv[i][2], tv[i][3]);
                    stsm4t(ta + 2048, tv[i][4], tv[i][5], tv[i][6], tv[i][7]);
                }
                if (!(GST & 2)) fence_async_smem();
                named_bar_sync(1 + wg, 128);
                if (GST & 2) {
                    const int l = 4 * w + (lane >> 3);
                    uint4 v[4];
#pragma unroll
                    for (int i = 0; i < 4; i++) v[i] = lds128(sb + ((ch + (i >> 1) + 1) & 7) * CV_SL + 12288 + (i & 1) * 2048 + l * 128 + (((lane ^ l) & 7) << 4));
                    bf16* gy = act + (size_t)(R_Y + w * 2048 + ((d0 + ch) & 255)) * D_ + (d0 & ~255) + lane * 8;
#pragma unroll
                    for (int i = 0; i < 4; i++) stg128(gy + ((i & 1) * 8192 + (i >> 1)) * D_, v[i]);
                } else if ((tid & 127) < 2) {
                    const int d = d0 + ch + (tid & 1);
                    asm volatile("cp.async.bulk.tensor.4d.global.shared::cta.bulk_group [%0, {%2, %3, %4, %2}], [%1];"
                                 ::"l"((uint64_t)&tm.y), "r"(sb + ((ch + (tid & 1) + 1) & 7) * CV_SL + 12288), "r"(0), "r"(4 * (d >> 8)), "r"(d & 255) : "memory");
                    asm volatile("cp.async.bulk.commit_group;" ::: "memory");
                }
                __syncwarp();
                DBG_S(9 + 3 * round);
            }
        }
    }
    int warp2 = warp;
    asm volatile("" : "+r"(warp2));
    if (warp2 >= 8) {
        asm volatile("setmaxnreg.dec.sync.aligned.u32 72;");
        if (warp == 8) { if (elect_one()) {
            if (rank == 0) {
                uint32_t smid;
                asm volatile("mov.u32 %0, %%smid;" : "=r"(smid));
                const int t = smid >> 1;
                int team = t < 32 ? t & 7 : t < 60 ? 1 + (t - 32) % 7 : t < 62 ? t - 54 : 0;
                const unsigned long long arr = atomicAdd(reinterpret_cast<unsigned long long*>(g_ticket + 16 * FL_PITCH), 1ull);
                const uint32_t e1 = (uint32_t)(arr / NCL) + 1;
                unsigned int* tk = g_ticket + (e1 & 1) * 8 * FL_PITCH;
                int slot = atomicAdd(tk + team * FL_PITCH, 1u);
                atomicAdd(g_ticket + 17 * FL_PITCH, 1u);
                if (blockIdx.x < 16) g_ticket[((~e1 & 1) * 8 + (blockIdx.x >> 1)) * FL_PITCH] = 0;
                if (slot >= 8) {
                    const long long t0 = clock64();
                    while ((int)(*(volatile unsigned int*)(g_ticket + 17 * FL_PITCH) - e1 * NCL) < 0 && clock64() - t0 < 100000) {}
                    for (team = 0; team < 8; team++)
                        if ((slot = atomicAdd(tk + team * FL_PITCH, 1u)) < 8) break;
                }
#pragma unroll
                for (int i = 0; i < 2; i++)
                    asm volatile("st.async.weak.shared::cluster.mbarrier::complete_tx::bytes.v2.b32 [%0], {%1, %2}, [%3];"
                                 ::"r"(mapa_u32(s_bar + 248, i)), "r"(team * 8 + slot), "r"(e1), "r"(mapa_u32(b_role, i)) : "memory");
            }
            if (get_role()) {
            TM(2);
            mbar_expect_tx(b_rfull, 32768);
            tma_load_2d(sbase + 16384, &tm.q, b_rfull, bj * 128, m0);
            tma_load_2d(sb + 8 * CV_SL, &tm.q, b_rfull, bj * 128 + 64, m0);
            int s5 = 0, s4 = 0;
            uint32_t p5 = 0, p4 = 1;
            auto putB = [&](const CUtensorMap* tB, int kc, uint32_t bytes) {
                const uint32_t full = f5 + 8 * s5;
                mbar_wait(full + 64, (p5 >> s5) & 1);
                mbar_expect_tx(full, bytes);
                tma_load_2d_mc(s_r + 16384 + rank * 8192 + s5 * R5_STAGE, tB, full, bj * 128 + rank * 64, kc);
                p5 ^= 1u << s5;
            };
            auto putA = [&](int c, int r) {
                tma_load_2d(s_r + s5 * R5_STAGE, &tm.act, f5 + 8 * s5, c, r);
                if (++s5 == R5_N) s5 = 0;
            };
            prefetch_tmap(&tm.act); prefetch_tmap(&tm.w1); prefetch_tmap(&tm.w2); prefetch_tmap(&tm.w3); prefetch_tmap(&tm.w4); prefetch_tmap(&tm.a64);
            auto own_first = [&](int it) {
                const int hf = it >= 9, c = it - 2 - 7 * hf;
                return (it < 2 ? 2 * bj + it : 2 * (c + (c >= bj)) + hf) * BK;
            };
            const unsigned int n8 = 8 * ep, nh = NH16 ? ((bi == 0 || bi == 15) ? 12 * ep : 2 * n8) : (bi == 0 || bi == 15) ? 2 * n8 : 3 * n8;
#pragma unroll 1
            for (int layer = 0; layer < 2; layer++) {
                s5 = 2;
#pragma unroll 1
                for (int kk = -(layer | Y_FIRST); kk < 5 - (layer | Y_FIRST); kk++) {
                    if (kk & 4) {
                        if (layer == 0) { TM(1); wait_flag(flag_ptr(0, FL_CS, 8 + bj), 8 * n8); TM(4); fence_proxy_async(); }
                        mbar_wait(e5 + 8, (p5 >> 1) & 1);
                        mbar_expect_tx(f5 + 8, 32768);
                        tma_load_2d(s_r + R5_STAGE, &tm.act, f5 + 8, (bj >> 1) * 256 + rank * 128, R_Y + (tb & ~255) + (bj & 1) * 128);
                        tma_load_2d(s_r + R5_STAGE + 16384, &tm.act, f5 + 8, (bj >> 1) * 256 + rank * 128 + 64, R_Y + (tb & ~255) + (bj & 1) * 128);
                        p5 ^= 2;
                        if (layer == 0) TM(5);
                    } else {
                        if (kk == Y_HOLD && layer == 0) mbar_wait(f5 + 8, 0);
                        putB(&tm.w1, own_first(kk), kk < 2 ? 16384 : R5_STAGE);
                        if (++s5 == R5_N) s5 = 0;
                    }
                }
                s5 = 4;
#pragma unroll 1
                for (int kk = 2; kk < 16; kk++) {
                    const int kc = own_first(kk);
                    if (kk >= 4) putB(&tm.w1, kc, R5_STAGE);
                    if (kk == 2 || kk == 9) {
                        wait_flag(flag_ptr(layer, FL_XA + (kk & 1), bi), n8);
                        if (layer == 0 && kk == 2) TM(14);
                        DP(8 * (FL_XA + (kk & 1)) + 3);
                        fence_proxy_async();
                        DP(8 * (FL_XA + (kk & 1)) + 4);
                    }
                    putA(kc, R_XA + tb);
                }
                mbar_wait(e5 + 24, (p5 >> 3) & 1);
                mbar_arrive(f5 + 24);
                p5 ^= 8;
                s5 = 4;
#pragma unroll 1
                for (int kk = 0; kk < 5; kk++) { putB(&tm.w2, own_first(kk), kk < 2 ? 16384 : R5_STAGE); if (++s5 == R5_N) s5 = 0; }
                s5 = 1;
#pragma unroll 1
                for (int kk = 2; kk < 16; kk++) {
                    const int kc = own_first(kk);
                    if (kk >= 5) putB(&tm.w2, kc, R5_STAGE);
                    if (kk == 2 || kk == 9) {
                        wait_flag(flag_ptr(layer, FL_H + (kk & 1), bi), nh);
                        DP(8 * (FL_H + (kk & 1)) + 3);
                        fence_proxy_async();
                        DP(8 * (FL_H + (kk & 1)) + 4);
                    }
                    putA(kc, R_H + layer * R_HP + m0 + (int)((0x4031u >> (kc >> 6 & 12)) & 7) - 2);
                }
#pragma unroll 1
                for (int it = 0; it < 32; it++) {
                    const int kc = it >= 16 ? (it - 16) * BK : own_first(it);
                    const int nb = it < 16 ? 4 : 3, n0 = bj * 448 + (it < 16 ? 0 : 256);
                    if (it > 0 && it < 4) {
                        const int i = (it - 1) * 3 >> 1;
                        mbar_wait(e5 + 8 * i, (p5 >> i) & 1);
                        mbar_wait(e5 + 8 * i + 8, (p5 >> (i + 1)) & 1);
                    }
                    mbar_wait(e4 + 8 * s4, p4);
                    if (it >= 16 && it < 19) mbar_wait(e4 + 8 * s4 + 8, p4);
                    uint32_t sa = s_r + s4 * (it < 16 ? R4_STAGE : R4B_STAGE), full = f4 + 8 * s4;
                    mbar_expect_tx(full, (it < 2 ? 0 : 16384) + nb * 8192);
#pragma unroll 1
                    for (int j = (it ^ rank) & 1; j < nb; j += 2) tma_load_2d_mc(sa + (it < 16 ? -32768 : 16384) + j * 8192, &tm.w3, full, n0 + j * 64, kc);
                    if (it == 3 || it == 9) {
                        wait_flag(flag_ptr(layer, FL_X1 + (it >> 3), bi), n8);
                        DP(8 * (FL_X1 + (it >> 3)) + 3);
                        fence_proxy_async();
                        DP(8 * (FL_X1 + (it >> 3)) + 4);
                        if (it == 3) tma_load_2d(s_r + 2 * R4_STAGE, &tm.act, f4 + 16, own_first(2), R_X1 + tb);
                    }
                    if (it >= 3) tma_load_2d(sa, &tm.act, full, kc, R_X1 + tb);
                    if (it >= PF4A && it < PF4A + PF4N && layer == 0) tma_prefetch_2d(&tm.w4, bj * 128 + rank * 64, (7 * (bi >> 1) + it - PF4A) * BK);
                    if (++s4 == R4_N) { s4 = 0; p4 ^= 1; }
                }
                wait_flag(flag_ptr(layer, FL_H2, bi), n8);
                fence_proxy_async();
                s5 = 0;
#pragma unroll 1
                for (int j = 0; j < 7; j++) {
                    if (j > 0 && (j & 1) == 0) {
                        mbar_wait(b_h2 + 4 * j, layer);
                        fence_proxy_async();
                    }
                    const int ra = R_H2 + (j >> 1) * 256 + tb;
#pragma unroll 1
                    for (int b = 0; b < 8; b++) {
                        if (j == 0 && b < R4_N) mbar_wait(e4 + 8 * b, p4);
                        putB(&tm.w4, (7 * b + j) * BK, R5_STAGE);
                        putA(((j & 1) * 8 + b) * BK, ra);
                    }
                }
            }
        } } } else {
            auto colsum = [&](bool is1, int bi, int bj) {
                const int pitch = is1 ? D_ : F_, c = is1 ? bj * 128 + (lane & 15) * 8 : bj * 448 + min((warp & 2) * 128 + lane * 8, 440);
                const bf16* p = (is1 ? w1p : w3p) + ((bi * 64 + (is1 ? (lane >> 4) * 32 : 0)) * pitch + c);
                float a[8];
#pragma unroll
                for (int i = 0; i < 8; i++) a[i] = 0.f;
#pragma unroll 1
                for (int r0 = is1 ? 32 : XCS; r0 < 64; r0 += 8) {
                    uint4 v[8];
#pragma unroll
                    for (int r = 0; r < 8; r++, p += pitch) v[r] = __ldg(reinterpret_cast<const uint4*>(p));
#pragma unroll
                    for (int r = 0; r < 8; r++) {
                        a[0] += lo2f(v[r].x); a[1] += hi2f(v[r].x); a[2] += lo2f(v[r].y); a[3] += hi2f(v[r].y);
                        a[4] += lo2f(v[r].z); a[5] += hi2f(v[r].z); a[6] += lo2f(v[r].w); a[7] += hi2f(v[r].w);
                    }
                }
                if (is1) {
#pragma unroll
                    for (int i = 0; i < 8; i++) a[i] += __shfl_xor_sync(0xffffffffu, a[i], 16);
                }
                float4* dst = reinterpret_cast<float4*>(g_cpart + bi * (F_ + D_) + (is1 ? F_ : 0) + c);
                dst[0] = make_float4(a[0], a[1], a[2], a[3]);
                dst[1] = make_float4(a[4], a[5], a[6], a[7]);
                asm volatile("fence.release.gpu;" ::: "memory");
                __syncwarp();
                if (lane == 0) asm volatile("red.relaxed.gpu.global.add.u32 [%0], 1;" ::"l"(flag_ptr(!is1, FL_CS, bj)) : "memory");
            };
            if (cv && warp == 10) colsum(true, blockIdx.x >> 3, blockIdx.x & 7);
            if ((GST & 2) && cv && warp == 9) {
                named_bar_sync(12, 288);
                if (lane == 0) {
                    asm volatile("fence.release.gpu;" ::: "memory");
                    asm volatile("red.relaxed.gpu.global.add.u32 [%0], 4;" ::"l"(flag_ptr(0, FL_CS, 8 + (blockIdx.x >> 4))) : "memory");
                }
                __syncwarp();
            }
            auto halo = [&](int layer) {
                const int dn = bj & 2 ? 1 : -1;
                const uint4* gh = g_halo + (layer * 144 + 8 + bi * 8 + bj) * 64 + lane;
                uint4 v[2] = {};
#pragma unroll 1
                for (int n = (bi + dn) & 16 ? 1 << 20 : 0; n < (1 << 20); n++) {
#pragma unroll
                    for (int i = 0; i < 2; i++)
                        asm volatile("{\n.reg .b64 u, v;\nld.relaxed.gpu.global.v2.b64 {u, v}, [%4];\nmov.b64 {%0, %1}, u;\nmov.b64 {%2, %3}, v;\n}"
                                     : "=r"(v[i].x), "=r"(v[i].y), "=r"(v[i].z), "=r"(v[i].w) : "l"(gh + 32 * i) : "memory");
                    if (v[0].y == ep && v[0].w == ep && v[1].y == ep && v[1].w == ep) break;
                }
#pragma unroll
                for (int i = 0; i < 2; i++)
                    asm volatile("st.shared.v2.b32 [%0], {%1, %2};" ::"r"(s_stg + 1024 + i * OFF_EPI + (63 + 65 * dn) * 128 + 8 * lane), "r"(v[i].x), "r"(v[i].z) : "memory");
                fence_async_smem();
                __syncwarp();
                DP(8 * FL_H + 5);
                named_bar_arrive(14, 160);
            };
            float4 keep[2];
            const bool on = get_role();
            if (on && warp == 11) {
                uint4* ps = reinterpret_cast<uint4*>(g_stats + (bi * 8 + bj) * 128) + lane;
                ps[0] = ps[32] = make_uint4(0, 0, 0, 0);
                asm volatile("fence.acq_rel.gpu;" ::: "memory");
                __syncwarp();
                if (lane == 0) mbar_arrive(b_rfull);
            }
#pragma unroll 1
            for (int layer = on ? 0 : 2; layer < 2; layer++) {
                if (warp == 10) {
#pragma unroll 1
                    for (int kind = 0; kind < 6; kind += 2) {
                        const uint32_t src = kind == FL_H ? s_stg + 1024 : s_epi, sd = kind == FL_H ? OFF_EPI : 16384;
                        const int dn = bj & 2 ? 1 : -1;
                        const int r = kind == FL_H ? R_H + layer * R_HP + m0 : (kind == FL_XA ? R_XA : R_X1) + tb;
#pragma unroll 1
                        for (int hf = 0; hf < 2; hf++) {
                            const bool sp = hf == 0 && (SPL2 >> kind & 1);
                            const int lw = kind == FL_H && dn < 0 ? 64 : 0;
                            if (sp) {
                                named_bar_sync(7, 160);
                                if (lane == 0) {
                                    fence_async_smem();
                                    tma_store_2d(&tm.a64, src + lw * 128, bj * 128, r + lw);
                                }
                                __syncwarp();
                            }
                            named_bar_sync(5 + hf, sp ? 160 : 288);
                            DQ(0);
                            if (lane == 0 && !((hf ? GS2 : GST) >> kind & 1)) {
                                if (FMOVE) fence_async_smem();
                                tma_store_2d(sp ? &tm.a64 : &tm.act, src + (sp ? (lw ^ 64) * 128 : hf * sd), bj * 128 + hf * 64, sp ? r + (lw ^ 64) : r);
                                asm volatile("cp.async.bulk.commit_group;" ::: "memory");
                            }
                            __syncwarp();
                            if (!H11 && kind + hf == FL_H + 1) halo(layer);
                            if (lane == 0) {
                                asm volatile("cp.async.bulk.wait_group 0;" ::: "memory");
                                DQ(1);
                                if (REL & 1) asm volatile("fence.release.gpu;" ::: "memory");
                                DQ(2);
                                unsigned int* fp = flag_ptr(layer, kind + hf, bi);
                                asm volatile("red.relaxed.gpu.global.add.u32 [%0], 1;" ::"l"(fp) : "memory");
                                if (kind == FL_H) {
                                    if (bi > 0 && (!NH16 || dn > 0)) asm volatile("red.relaxed.gpu.global.add.u32 [%0], 1;" ::"l"(fp - FL_PITCH) : "memory");
                                    if (bi < 15 && (!NH16 || dn < 0)) asm volatile("red.relaxed.gpu.global.add.u32 [%0], 1;" ::"l"(fp + FL_PITCH) : "memory");
                                }
                            }
                            __syncwarp();
                        }
                    }
                } else {
                    uint32_t* rs = reinterpret_cast<uint32_t*>(sgen + OFF_RS);
                    float* cs = reinterpret_cast<float*>(sgen + OFF_CS);
#pragma unroll 1
                    for (int which = 0; which < 2; which++) {
                        if (layer < which) {
                            if (warp == 11 && lane == 0) {
                                if (W3_AT >= 0) wait_flag(flag_ptr(0, FL_XA + (W3_AT & 1), bi), 8 * ep);
                                asm volatile("cp.async.bulk.prefetch.L2.global [%0], %1;" ::"l"(w3p + (bi * 8 + bj) * 28672), "r"(57344) : "memory");
                            }
                            __syncwarp();
                            colsum(false, bi, bj);
                        }
                        if (warp == 11) {
                            if (H11 && which) { named_bar_sync(4, 160); halo(layer); }
                            continue;
                        }
                        if (layer == 0) {
                            if (lane == 0) wait_flag(flag_ptr(which, FL_CS, bj), (16 << which) * ep);
                            __syncwarp();
#pragma unroll 1
                            for (int c = (which ? 384 : 768) + lane * 4; c < 896; c += 128) {
                                const float* cp = g_cpart + (which ? bj * 448 + min(c & 511, 444) : F_ + bj * 128 + lane * 4);
                                float4 a = make_float4(0.f, 0.f, 0.f, 0.f);
#pragma unroll
                                for (int r0 = 0; r0 < 16; r0 += 8) {
                                    float4 v[8];
#pragma unroll
                                    for (int r = 0; r < 8; r++) v[r] = __ldcg(reinterpret_cast<const float4*>(cp + (r0 + r) * (F_ + D_)));
#pragma unroll
                                    for (int r = 0; r < 8; r++) { a.x += v[r].x; a.y += v[r].y; a.z += v[r].z; a.w += v[r].w; }
                                }
                                if (c < 768) *reinterpret_cast<float4*>(cs + min(c & 511, 444)) = a;
                                keep[0] = a;
                            }
                        }
                        if (lane == 0 && (layer | which)) wait_flag(flag_ptr(layer, which == 0 ? FL_XA : FL_X1, bi), 8 * ep);
                        __syncwarp();
                        *reinterpret_cast<float4*>(cs + 256 + lane * 4) = keep[0];
                        { const float4 k0 = keep[0]; keep[0] = keep[1]; keep[1] = k0; }
#pragma unroll 1
                        for (int i = 0; i < 4; i++) {
                            const int r = i * 32 + lane;
                            float mean, var;
                            row_stats(g_stats + (1 + which) * S_ * 8 + bi * 1024 + r, ~layer << 31, mean, var);
                            const uint32_t c0 = pack2(mean, fsqrt(bfr(bfr(var) + 1e-5f)));
                            if (lane < 19 && (layer | which | i) == 0) asm volatile("mbarrier.inval.shared::cta.b64 [%0];" ::"r"(b_full + 8 * lane) : "memory");
                            __syncwarp();
                            rs[r] = c0;
                            const float rd = frcp(hi2f(c0));
                            rs[128 + r] = pack2((mean - lo2f(c0)) * rd, fsqrt(bfr(bfr(var * rd * rd) + 1e-5f)));
                        }
                        __syncwarp();
                        named_bar_arrive(3, 160);
                        named_bar_arrive(11, 160);
                    }
                }
                const uint32_t s_cnt = s_bar + 224;
                auto ticket = [&](uint32_t a) {
                    uint32_t v = 0;
                    if (lane == 0) asm volatile("atom.acq_rel.cta.shared.add.u32 %0, [%1], 1;" : "=r"(v) : "r"(a) : "memory");
                    return v;
                };
                auto next = [&]() {
                    uint32_t v = 0;
                    if (lane == 0) asm volatile("atom.relaxed.cta.shared.add.u32 %0, [%1], 1;" : "=r"(v) : "r"(s_cnt + 16 + 4 * layer) : "memory");
                    return v;
                };
                mbar_wait(b_stg, layer);
                int u = __shfl_sync(0xffffffffu, next(), 0), step = 0;
#pragma unroll 1
                while (true) {
#pragma unroll 1
                    for (; step < 5 && u >= (int)((0x3830201810ull >> (8 * step)) & 255); step++) {
                        if (step == 1) { named_bar_arrive(4, 224); named_bar_arrive(12, 224); continue; }
                        const int part = step ? step - 1 : 0;
                        __syncwarp();
                        if (ticket(s_cnt + 4 * part) == 3 * layer + 2) {
                            asm volatile("fence.release.gpu;" ::: "memory");
                            unsigned int* fp = flag_ptr(layer, FL_H2 + part, bi);
                            asm volatile("red.relaxed.gpu.global.add.u32 [%0], 1;" ::"l"(fp) : "memory");
                            if (part > 0) { wait_flag(fp, 8 * ep); mbar_arrive(b_h2 + 8 * part); }
                        }
                        __syncwarp();
                    }
                    if (u >= 56) break;
                    const uint32_t un = next();
                    const int job = u >> 3, r = (u & 7) * 16 + (lane >> 3);
                    if (job >= 2) mbar_wait(s_bar + 168 + 8 * max(job, 3), layer);
                    const uint32_t sp = sbase + ((job & 2) ? OFF_STG5 : OFF_EPI) + r * 256 + (job & 1) * 128;
                    bf16* gp = act + (size_t)(R_H2 + (job >> 1) * 256 + tb + r) * D_ + ((job & 1) * 8 + bj) * 64 + (lane & 7) * 8;
                    uint4 v[4];
#pragma unroll
                    for (int e = 0; e < 4; e++) v[e] = lds128(sp + e * 1024 + (((lane & 7) ^ ((r + 4 * e) & 7)) << 4));
#pragma unroll
                    for (int e = 0; e < 4; e++) stg128(gp + 4 * e * D_, gelu8h(v[e]));
                    u = __shfl_sync(0xffffffffu, un, 0);
                }
                if (layer == 0 && warp == 11) {
                    const char* ps = reinterpret_cast<const char*>(g_stats + bi * 1024) + lane * 128;
                    const char* py = reinterpret_cast<const char*>(act + (size_t)(R_Y + (tb & ~255) + (bj & 1) * 128 + (lane >> 1)) * D_ + (bj >> 1) * 256 + rank * 128) + (lane & 1) * 128;
#pragma unroll 1
                    for (int i = 0; i < 8; i++) {
                        asm volatile("prefetch.global.L2 [%0];" ::"l"(py + (size_t)i * 16 * D_ * 2) : "memory");
                        if (i >= 6) asm volatile("prefetch.global.L2 [%0];" ::"l"(ps + (i & 1) * 4096) : "memory");
                        __nanosleep(400);
                    }
                }
            }
        }
        __syncwarp();
        asm volatile("barrier.cluster.arrive.relaxed.aligned;\nbarrier.cluster.wait.acquire.aligned; // helpers" ::: "memory");
    } else {
        DT_DECL;
        DT(0);
        auto put_y = [&]() {
            if (GST & 2) { if (cv) named_bar_arrive(12, 288); }
            else if ((tid & 127) < 2 && cv) {
                asm volatile("cp.async.bulk.wait_group 0;" ::: "memory");
                if (REL & 2) asm volatile("fence.release.gpu;" ::: "memory");
                asm volatile("red.relaxed.gpu.global.add.u32 [%0], 1;" ::"l"(flag_ptr(0, FL_CS, 8 + (blockIdx.x >> 4))) : "memory");
            }
            __syncwarp();
        };
        put_y();
        DT(24);
        asm volatile("setmaxnreg.inc.sync.aligned.u32 216;");
        if (get_role()) {
        const bool rel_on = (tid & 95) == 0;
        const uint32_t rel5 = mapa_u32(e5, (warp & 1) ^ rank), rel4 = rel5 + (e4 - e5);
        const uint32_t da0 = desc_a(s_r + wg * 8192), db0 = desc_b(s_r + BM * BK * 2), dae = da0 + (OFF_EPI - OFF_R) / 16, db4 = db0 - 49152 / 16;
        auto skip5 = [&](RingState& rs) {
            if (rel_on) mbar_arrive_cluster(rel5 + 8 * rs.st);
            rs.st++;
        };
        const int t = lane & 3;
        const int row = warp * 16 + (lane >> 2);
        const uint32_t st_w = (uint32_t)((warp * 16 + ((lane >> 3) & 1) * 8 + (lane & 7)) * 256 + (((lane >> 4) ^ (lane & 7)) << 4));
        const uint32_t fr = (uint32_t)((warp * 16 + ((lane >> 3) & 1) * 8 + (lane & 7)) * 128 + (((lane >> 4) ^ (lane & 7)) << 4));
        auto copy_out = [&](bf16* dst, uint32_t src) {
            const int r = warp * 16 + (lane >> 4);
            bf16* ox = dst + (size_t)(m0 + r) * D_ + bj * 128 + (lane & 15) * 8;
            const uint32_t ra = src + ((lane & 15) >> 3) * 16384 + r * 128;
            uint4 v[8];
#pragma unroll
            for (int it = 0; it < 8; it++) v[it] = lds128(ra + it * 256 + (((lane & 7) ^ ((2 * it + (lane >> 4)) & 7)) << 4));
#pragma unroll
            for (int it = 0; it < 8; it++) *reinterpret_cast<uint4*>(ox + (size_t)it * 2 * D_) = v[it];
        };
        auto put_half = [&](uint32_t src, int r0, int hf) {
            const int r = warp * 16 + (lane >> 3);
            bf16* gp = act + (size_t)(r0 + r) * D_ + bj * 128 + hf * 64 + (lane & 7) * 8;
            uint4 v[4];
            __syncwarp();
#pragma unroll
            for (int i = 0; i < 4; i++) v[i] = lds128(src + (r + 4 * i) * 128 + (((lane ^ (r + 4 * i)) & 7) << 4));
#pragma unroll
            for (int i = 0; i < 4; i++) stg128(gp + 4 * i * D_, v[i]);
        };
        auto put_stats = [&](const uint32_t (&w)[32], int which, int layer) {
            float c[6][4];
#pragma unroll
            for (int e = 0; e < 32; e++) {
                hmma8(c[e & 3], w[e & ~1], w[e | 1], w[e], e < 4);
                if ((e & 3) == 0) hmma(c[4 + (e >> 2 & 1)], w[e], w[e + 1], w[e + 2], w[e + 3], 0x3f803f80u, 0x3f803f80u, e < 8);
            }
            if (t == lane >> 3) {
#pragma unroll
                for (int e = 0; e < 2; e++) {
                    const float q1 = lane & 4 ? c[e][2 * e + 1] + c[e + 2][2 * e + 1] : c[e][2 * e] + c[e + 2][2 * e], s1 = c[4][2 * e] + c[5][2 * e], mu = s1 * (1.0f / 128);
                    asm volatile("{\n.reg .b64 t;\nmov.b64 t, {%1, %2};\nst.relaxed.gpu.global.b64 [%0], t;\n}"
                                 ::"l"(g_stats + which * S_ * 8 + (bi * 8 + bj) * 128 + row + 8 * e), "f"(mu), "r"(__float_as_uint(fmaxf(q1 - s1 * mu, 0.f)) | ~layer << 31) : "memory");
                }
            }
        };
        auto split = [](float r) { const float h = bfr(r); return pack2(h, r - h); };
        auto norm2 = [](uint32_t x, uint32_t m, uint32_t r) {
            const uint32_t d = bsub2(x, m);
            return bfma2(d, __byte_perm(r, 0, 0x1010), bmul2(d, __byte_perm(r, 0, 0x3232)));
        };
        const float* csp = reinterpret_cast<const float*>(sgen + OFF_CS) + 2 * t;
        float mrow[2], rrow[2];
        const uint32_t* rsp = reinterpret_cast<const uint32_t*>(sgen + OFF_RS) + row;
        auto row_consts = [&](bool twice) {
#pragma unroll
            for (int e = 0; e < 2; e++) {
                const uint32_t q0 = rsp[8 * e], q1 = rsp[128 + 8 * e];
                mrow[e] = twice ? fmaf(lo2f(q1), hi2f(q0), lo2f(q0)) : lo2f(q0);
                rrow[e] = 0.5f * frcp(twice ? hi2f(q0) * hi2f(q1) : hi2f(q0));
            }
        };
        auto keep_consts = [&](float2 (&cs)[8]) {
#pragma unroll
            for (int e = 0; e < 8; e++) asm volatile("" : "+f"(cs[e].x), "+f"(cs[e].y));
            asm volatile("" : "+f"(mrow[0]), "+f"(mrow[1]), "+f"(rrow[0]), "+f"(rrow[1]));
        };
        RingState r5{1, 0}, r4{0, 0};
        DT(1);
        uint32_t x[32];
        mbar_wait(b_rfull, 0);
#pragma unroll
        for (int jp = 0; jp < 8; jp++) ldsm4(x[4 * jp], x[4 * jp + 1], x[4 * jp + 2], x[4 * jp + 3], sbase + 16384 + (fr ^ ((jp & 3) << 5)) + (jp >> 2) * (16384 + 8 * CV_SL));
#pragma unroll
        for (int e = 0; e < 32; e++) asm volatile("" : "+r"(x[e]));
        named_bar_sync(9 + wg, 128);
        if ((tid & 95) < R5_N) mbar_arrive_cluster(rel5 + 8 * lane);
#pragma unroll 1
        for (int layer = 0; layer < 2; layer++) {
            {
                DT(2 + 24 * layer);
                put_stats(x, 0, layer);
                DT(20 + 24 * layer);
                DT(22 + 24 * layer);
                uint32_t mb[2], rd[2];
                {
                    float mean, var;
                    row_stats(g_stats + bi * 1024 + warp * 16 + (lane & 15), ~layer << 31, mean, var);
                    __syncwarp();
                    const uint32_t r1 = split(frcp(bfr(fsqrt(bfr(bfr(var) + 1e-5f)))));
                    const uint32_t m1 = pack2(mean, mean);
#pragma unroll
                    for (int e = 0; e < 2; e++) { mb[e] = __shfl_sync(0xffffffffu, m1, (lane >> 2) + 8 * e); rd[e] = __shfl_sync(0xffffffffu, r1, (lane >> 2) + 8 * e); }
                }
                DT(21 + 24 * layer);
                mbar_wait(f5 + 8, r5.ph);
                DT(23 + 24 * layer);
                const uint32_t ya = s_r + R5_STAGE + wg * 16384 + ((lane >> 4) * 8 + (lane & 7)) * 128 + ((((warp & 3) * 2 + ((lane >> 3) & 1)) ^ (lane & 7)) << 4);
                uint32_t y[16];
#pragma unroll
                for (int e = 0; e < 32; e++) {
                    if ((e & 15) == 0) {
#pragma unroll
                        for (int jp = 0; jp < 4; jp++) ldsm4t(y[4 * jp], y[4 * jp + 1], y[4 * jp + 2], y[4 * jp + 3], ya + jp * 2048 + e * 512);
                    }
                    x[e] = bfma2(norm2(x[e], mb[e & 1], rd[e & 1]), y[e & 15], x[e]);
                    if ((e & 3) == 3) stsm4(s_epi + (fr ^ (((e >> 2) & 3) << 5)) + (e >> 4) * 16384, x[e - 3], x[e - 2], x[e - 1], x[e]);
                    if ((e & 15) == 15 && ((e > 15 ? GS2 : GST) & 1)) put_half(s_epi + (e >> 4) * 16384, R_XA + tb, e >> 4);
                    if ((e & 15) == 15) { if (e == 15 && (SPL2 & 1)) named_bar_arrive(7 - 2 * wg, 160); else named_bar_arrive(5 + (e >> 4), 288); }
                    if (e == 15) mbar_wait(b_role, 0);
                }
                DT(19 + 24 * layer);
                if (FMOVE) fence_async_smem();
                if (PS1_EARLY) put_stats(x, 1, layer);
                named_bar_sync(9 + wg, 128);
                skip5(r5);
                DT(3 + 24 * layer);
            }
            {
                float acc[64];
                kblock<128, R5_N, 0>(acc, dae, db0 + 2 * (R5_STAGE / 16), f5, r5);
                kblock<128, R5_N>(acc, dae + 1024, db0 + 3 * (R5_STAGE / 16), f5, r5);
                if (!PS1_EARLY) put_stats(x, 1, layer);
                wgmma_wait<1>();
                if (rel_on) mbar_arrive_cluster(rel5 + 16);
                float2 cs[8];
                mainloop<128, R5_N, R5_STAGE, PA1>(acc, 14, da0, db0, f5, rel5, rel_on, r5, 15 + 24 * layer, [&]() {
                    named_bar_sync(3 + 8 * wg, 160);
                    row_consts(true);
#pragma unroll
                    for (int e = 0; e < 8; e++) cs[e] = *reinterpret_cast<const float2*>(csp + 256 + 8 * e);
                    keep_consts(cs);
                } DT_ARG, (wg ^ bj >> 1 ^ LAGX) & 1);
                DT(4 + 24 * layer);
#pragma unroll
                for (int j = 0; j < 16; j += 2) {
                    if (j == 8) {
#pragma unroll
                        for (int e = 0; e < 8; e++) cs[e] = *reinterpret_cast<const float2*>(csp + 256 + 8 * (j + e));
                    }
                    uint32_t w[4];
#pragma unroll
                    for (int e = 0; e < 4; e++) {
                        const float* a = acc + 4 * j + 2 * e;
                        const float2 c = cs[(j & 7) + (e >> 1)];
                        w[e] = gelu2h(pack2(fmaf(-mrow[e & 1], c.x, a[0]) * rrow[e & 1], fmaf(-mrow[e & 1], c.y, a[1]) * rrow[e & 1]));
                    }
                    stsm4(s_stg + 1024 + (fr ^ ((j & 7) << 4)) + (j >> 3) * OFF_EPI, w[0], w[1], w[2], w[3]);
                    if ((j & 7) == 6 && ((j > 7 ? GS2 : GST) & 4)) put_half(s_stg + 1024 + (j >> 3) * OFF_EPI, R_H + layer * R_HP + m0, j >> 3);
                    if ((j & 7) == 6) { if (j == 6 && (SPL2 & 4)) named_bar_arrive(7 - 2 * ((wg ^ bj >> 1 ^ 1) & 1), 160); else named_bar_arrive(5 + (j >> 3), 288); }
                }
                if (SENDC && warp == (bj & 2 ? 0 : 7)) {
                    __syncwarp();
                    uint32_t a[4];
                    lds64(a[0], a[1], s_stg + 1024 + 18 * 128 * warp + 8 * lane);
                    lds64(a[2], a[3], s_epi + 1024 + 18 * 128 * warp + 8 * lane);
                    uint4* gh = g_halo + (layer * 144 + (warp & 2) * 8 + bi * 8 + bj) * 64 + lane;
#pragma unroll
                    for (int i = 0; i < 2; i++)
                        asm volatile("{\n.reg .b64 u, v;\nmov.b64 u, {%1, %3};\nmov.b64 v, {%2, %3};\nst.relaxed.gpu.global.v2.b64 [%0], {u, v};\n}"
                                     ::"l"(gh + i * 32), "r"(a[2 * i]), "r"(a[2 * i + 1]), "r"(ep) : "memory");
                }
                fence_async_smem();
                if (wg == (bj >> 1 & 1)) { if (H11) named_bar_arrive(4, 160); named_bar_arrive(13, 256); }
                DT(5 + 24 * layer);
            }
            {
                float acc[64];
                uint32_t u[32];
                {
                    uint32_t mb[2], rd[2];
#pragma unroll
                    for (int e = 0; e < 2; e++) { const uint32_t q0 = rsp[8 * e]; mb[e] = (q0 & 0xffffu) * 0x10001u; rd[e] = split(frcp(hi2f(q0))); }
#pragma unroll
                    for (int e = 0; e < 32; e++) {
                        u[e] = norm2(x[e], mb[e & 1], rd[e & 1]);
                        asm volatile("" : "+r"(u[e]));
                    }
                }
                if (!(warp & 2)) mbar_wait(f5 + 24, r5.ph);
                skip5(r5);
                {
                    const bool nb = wg == (bj >> 1 & 1);
                    named_bar_sync(nb ? 14 : 13, nb ? 160 : 256);
                }
                const uint32_t dah = da0 - (OFF_R - 1024 + 256) / 16 + ((0x4031u >> (2 * bj & 12)) & 7) * 8;
                kblock<128, R5_N, 0>(acc, dah, db0 + 4 * (R5_STAGE / 16), f5, r5);
                kblock<128, R5_N>(acc, dah + OFF_EPI / 16, db0, f5, r5);
                wgmma_wait<1>();
                if (rel_on) mbar_arrive_cluster(rel5 + 32);
                mainloop<128, R5_N, R5_STAGE, PA2>(acc, 14, da0, db0, f5, rel5, rel_on, r5, 16 + 24 * layer, []() {} DT_ARG, wg);
                DT(6 + 24 * layer);
#pragma unroll
                for (int j = 0; j < 16; j += 2) {
#pragma unroll
                    for (int e = 0; e < 4; e++) u[2 * j + e] = badd2(u[2 * j + e], pack2(acc[4 * j + 2 * e], acc[4 * j + 2 * e + 1]));
                    stsm4(s_epi + (fr ^ ((j & 7) << 4)) + (j >> 3) * 16384, u[2 * j], u[2 * j + 1], u[2 * j + 2], u[2 * j + 3]);
                    if ((j & 7) == 6 && ((j > 7 ? GS2 : GST) & 16)) put_half(s_epi + (j >> 3) * 16384, R_X1 + tb, j >> 3);
                    if ((j & 7) == 6) { if (j == 6 && (SPL2 & 16)) named_bar_arrive(7 - 2 * wg, 160); else named_bar_arrive(5 + (j >> 3), 288); mbar_wait(b_role, 0); }
                }
                if (FMOVE) fence_async_smem();
#pragma unroll
                for (int e = 0; e < 32; e++) x[e] = badd2(x[e], u[e]);
                put_stats(u, 2, layer);
                named_bar_sync(9 + wg, 128);
                DT(7 + 24 * layer);
            }
            {
                float2 cs[NCS];
                auto piece = [&](const float* acc, auto pc) {
                    constexpr int j = 2 * decltype(pc)::v, jl = j & 31;
                    uint32_t w[4];
#pragma unroll
                    for (int e = 0; e < 2; e++) {
                        const float* a = acc + 4 * (jl + e);
                        const float2 cc = cs[(j + e) % NCS];
                        w[2 * e] = pack2(fmaf(-mrow[0], cc.x, a[0]) * rrow[0], fmaf(-mrow[0], cc.y, a[1]) * rrow[0]);
                        w[2 * e + 1] = pack2(fmaf(-mrow[1], cc.x, a[2]) * rrow[1], fmaf(-mrow[1], cc.y, a[3]) * rrow[1]);
                    }
                    stsm4(((jl < 16 ? s_epi : s_stg) + st_w) ^ ((j & 15) << 4), w[0], w[1], w[2], w[3]);
                    if (j + NCS < 56) {
#pragma unroll
                        for (int e = 0; e < 2; e++) { uint32_t u0, u1; lds64(u0, u1, smem_u32(csp + 8 * (j + e + NCS))); cs[(j + e) % NCS] = make_float2(__uint_as_float(u0), __uint_as_float(u1)); }
                    }
                    if (j == 14 || (j >= 30 && (j & 7) == 6)) {
                        __syncwarp();
                        if (lane == 0) mbar_arrive(j == 14 ? b_stg : s_bar + 168 + (j & 56));
                    }
                };
                auto pieces = [&](const float* acc, auto p0, auto p1) {
                    constexpr int a = decltype(p0)::v, b = decltype(p1)::v;
                    static_for<a, b>([&](auto i) { piece(acc, i); });
                };
                float ac3[128];
                kblock<256, R4_N, 0>(ac3, dae, db4, f4, r4);
                kblock<256, R4_N>(ac3, dae + 1024, db4 + R4_STAGE / 16, f4, r4);
                wgmma_wait<1>();
                if (rel_on) mbar_arrive_cluster(rel4);
                mainloop<256, R4_N, R4_STAGE, PA3A>(ac3, 14, da0, db4, f4, rel4, rel_on, r4, 17 + 24 * layer, [&]() {
                    named_bar_sync(3 + 8 * wg, 160);
                    mbar_wait(e4, 1);
                    row_consts(false);
#pragma unroll
                    for (int e = 0; e < NCS; e++) {
                        cs[e] = *reinterpret_cast<const float2*>(csp + 8 * e);
                        asm volatile("" : "+f"(cs[e].x), "+f"(cs[e].y));
                    }
                    asm volatile("" : "+f"(mrow[0]), "+f"(mrow[1]), "+f"(rrow[0]), "+f"(rrow[1]));
                } DT_ARG, wg);
                DT(8 + 24 * layer);
                pieces(ac3, IC<0>(), IC<NPRE>());
                DT(9 + 24 * layer);
                float acc[96];
                constexpr int NS3 = NPRE == 16 ? 1 : (16 - NPRE + PP3 - 1) / PP3;
                static_for<0, NS3>([&](auto cc) {
                    constexpr int c = decltype(cc)::v, q = NPRE + PP3 * c;
                    const uint32_t da = da0 + c * (R4B_STAGE / 16), db = db0 + c * (R4B_STAGE / 16);
                    mbar_wait(f4 + 8 * c, r4.ph);
                    wgmma_fence();
                    static_for<0, 4>([&](auto ic) {
                        constexpr int i = decltype(ic)::v, q0 = q + i * PP3 / 4, q1 = q + (i + 1) * PP3 / 4;
                        WG<192>::mma<(c | i) != 0>(acc, da + 2 * i, db + 128 * i);
                        if (i == 3) {
                            wgmma_commit();
                            if (c) {
                                wgmma_wait<1>();
                                if (rel_on) mbar_arrive_cluster(rel4 + 8 * ((c + 3) & 3));
                            }
                        }
                        pieces(ac3, IC<(q0 < 16 ? q0 : 16)>(), IC<(q1 < 16 ? q1 : 16)>());
                    });
                });
                r4.st = NS3 & 3;
                if (NS3 == 4) r4.ph ^= 1;
                float ac4[64];
                mainloop<192, R4_N, R4B_STAGE, PA3B, 1>(acc, 16 - NS3, da0, db0, f4, rel4, rel_on, r4, -1, [&]() {
#pragma unroll
                    for (int i = 0; i < 32; i++) asm volatile("shl.b32 %0, %2, 16;\nand.b32 %1, %2, 0xffff0000;" : "=f"(ac4[2 * i]), "=f"(ac4[2 * i + 1]) : "r"(x[i]));
                    kblock<128, R5_N>(ac4, da0, db0, f5, r5);
                } DT_ARG, wg);
                DT(10 + 24 * layer);
                named_bar_sync(4 + 8 * wg, 224);
                piece(acc, IC<16>());
                static_for<1, 7>([&](auto cc) {
                    constexpr int c = decltype(cc)::v;
                    const uint32_t da = da0 + (c % 5) * (R5_STAGE / 16), db = db0 + (c % 5) * (R5_STAGE / 16);
                    mbar_wait(f5 + 8 * (c % 5), r5.ph);
                    wgmma_fence();
                    WG<128>::mma<1>(ac4, da, db);
                    WG<128>::mma<1>(ac4, da + 2, db + 128);
                    piece(acc, IC<15 + 2 * c>());
                    WG<128>::mma<1>(ac4, da + 4, db + 256);
                    WG<128>::mma<1>(ac4, da + 6, db + 384);
                    wgmma_commit();
                    if (c % 5 == 4) r5.ph ^= 1;
                    wgmma_wait<1>();
                    if (rel_on) mbar_arrive_cluster(rel5 + 8 * ((c - 1) % 5));
                    if constexpr (c < 6) piece(acc, IC<16 + 2 * c>());
                });
                r5.st = 2;
                DT(11 + 24 * layer);
                DT(18 + 24 * layer);
                mainloop<128, R5_N, R5_STAGE, PA4>(ac4, 49, da0, db0, f5, rel5, rel_on, r5, 62 - 40 * (layer ^ 1), []() {} DT_ARG, wg);
                DT(12 + 24 * layer);
#pragma unroll
                for (int i = 0; i < 32; i++) x[i] = pack2(ac4[2 * i], ac4[2 * i + 1]);
                DT(13 + 24 * layer);
                DT(14 + 24 * layer);
            }
        }
#pragma unroll
        for (int jp = 0; jp < 8; jp++) stsm4(s_epi + (fr ^ ((jp & 3) << 5)) + (jp >> 2) * 16384, x[4 * jp], x[4 * jp + 1], x[4 * jp + 2], x[4 * jp + 3]);
        __syncwarp();
        copy_out(outp, s_epi);
        DT(38);
        DT_DUMP;
        GT(4);
        }
        cluster_arrive_relaxed();
        cluster_wait();
    }
}

typedef CUresult (*PFN_encodeTiled)(CUtensorMap*, CUtensorMapDataType, cuuint32_t, void*, const cuuint64_t*, const cuuint64_t*,
                                    const cuuint32_t*, const cuuint32_t*, CUtensorMapInterleave, CUtensorMapSwizzle,
                                    CUtensorMapL2promotion, CUtensorMapFloatOOBfill);

static CUtensorMap make_map(PFN_encodeTiled enc, const void* ptr, int inner, int outer, int box_inner, int box_outer,
                            CUtensorMapSwizzle swz = CU_TENSOR_MAP_SWIZZLE_128B) {
    CUtensorMap m;
    cuuint64_t dims[2] = {(cuuint64_t)inner, (cuuint64_t)outer};
    cuuint64_t strides[1] = {(cuuint64_t)inner * 2};
    cuuint32_t box[2] = {(cuuint32_t)box_inner, (cuuint32_t)box_outer};
    cuuint32_t es[2] = {1, 1};
    enc(&m, CU_TENSOR_MAP_DATA_TYPE_BFLOAT16, 2, const_cast<void*>(ptr), dims, strides, box, es, CU_TENSOR_MAP_INTERLEAVE_NONE,
        swz, CU_TENSOR_MAP_L2_PROMOTION_L2_256B, CU_TENSOR_MAP_FLOAT_OOB_FILL_NONE);
    return m;
}

extern "C" void kernel_launch(void* const* d_in, const int* in_sizes, int n_in, void* d_out, int out_size) {
    const bf16* A_q = (const bf16*)d_in[0];
    const bf16* A_k = (const bf16*)d_in[1];
    const bf16* A_v = (const bf16*)d_in[2];
    const bf16* A_shk = (const bf16*)d_in[3];
    const bf16* A_ssk = (const bf16*)d_in[4];
    const bf16* A_ssD = (const bf16*)d_in[5];
    const bf16* w1 = (const bf16*)d_in[7];
    const bf16* w2 = (const bf16*)d_in[8];
    const bf16* w3 = (const bf16*)d_in[9];
    const bf16* w4 = (const bf16*)d_in[10];
    bf16* out = (bf16*)d_out;

    static PFN_encodeTiled enc = nullptr;
    static bool attr_done = false;
    if (!enc) {
        void* fn = nullptr;
        cudaDriverEntryPointQueryResult qr;
        cudaGetDriverEntryPoint("cuTensorMapEncodeTiled", &fn, cudaEnableDefault, &qr);
        enc = (PFN_encodeTiled)fn;
    }
    if (!attr_done) {
        cudaFuncSetAttribute(mega_kernel, cudaFuncAttributeMaxDynamicSharedMemorySize, MEGA_SMEM);
        attr_done = true;
    }
    void* p_act;
    cudaGetSymbolAddress(&p_act, g_act);
    bf16* act = (bf16*)(((uintptr_t)p_act + 0x1fffff) & ~(uintptr_t)0x1fffff);

    MegaMaps tm;
    tm.q = make_map(enc, A_q, D_, S_, 64, 128);
    tm.act = make_map(enc, act, D_, R_END, 64, 128);
    tm.a64 = make_map(enc, act, D_, R_END, 64, 64);
    tm.w1 = make_map(enc, w1, D_, D_, 64, 64);
    tm.w2 = make_map(enc, w2, D_, D_, 64, 64);
    tm.w3 = make_map(enc, w3, F_, D_, 64, 64);
    tm.w4 = make_map(enc, w4, D_, F_, 64, 64);
    {
        cuuint64_t dims[4] = {64, 16, 256, 8}, strides[3] = {128, D_ * 2, (cuuint64_t)2048 * D_ * 2};
        cuuint32_t box[4] = {64, 4, 1, 8}, es[4] = {1, 1, 1, 1};
        enc(&tm.y, CU_TENSOR_MAP_DATA_TYPE_BFLOAT16, 4, act + (size_t)R_Y * D_, dims, strides, box, es, CU_TENSOR_MAP_INTERLEAVE_NONE,
            CU_TENSOR_MAP_SWIZZLE_128B, CU_TENSOR_MAP_L2_PROMOTION_NONE, CU_TENSOR_MAP_FLOAT_OOB_FILL_NONE);
    }
    for (int i = 0; i < 2; i++) {
        cuuint64_t dims[4] = {D_, 4, 8, S_ / 32}, strides[3] = {8 * D_ * 2, D_ * 2, 32 * D_ * 2};
        cuuint32_t box[4] = {16, 4, 8, 4}, es[4] = {1, 1, 1, 1};
        enc(i ? &tm.v : &tm.k, CU_TENSOR_MAP_DATA_TYPE_BFLOAT16, 4, (void*)(i ? A_v : A_k), dims, strides, box, es, CU_TENSOR_MAP_INTERLEAVE_NONE,
            CU_TENSOR_MAP_SWIZZLE_32B, CU_TENSOR_MAP_L2_PROMOTION_NONE, CU_TENSOR_MAP_FLOAT_OOB_FILL_NONE);
    }
    mega_kernel<<<2 * NCL, 384, MEGA_SMEM, cudaStreamPerThread>>>(tm, out, act, w1, w2, w3, A_q, A_k, A_v, A_shk, A_ssk, A_ssD);
}
```

```cpp
#include <cuda_runtime.h>
#include <cuda_bf16.h>
#include <cuda.h>
#include <stdint.h>

typedef __nv_bfloat16 bf16;

constexpr int S_ = 2048;
constexpr int D_ = 1024;
constexpr int F_ = 3584;

constexpr int R_XA = 0, R_X1 = 256, R_H2 = 512, R_Y = 1536, R_H = 16384 + 8, R_HP = S_ + 8, R_END = R_H + 2 * R_HP;
__device__ __align__(1024) bf16 g_act[(size_t)(R_END + 1024) * D_];
__device__ __align__(16) float g_cpart[16 * (F_ + D_)];
__device__ __align__(128) float2 g_stats[3 * S_ * 8];
__device__ __align__(128) uint4 g_halo[2 * 144 * 64];

__device__ __forceinline__ float bfr(float x) { return __bfloat162float(__float2bfloat16_rn(x)); }
__device__ __forceinline__ uint32_t pack2(float lo, float hi) {
    __nv_bfloat162 v = __floats2bfloat162_rn(lo, hi);
    return *reinterpret_cast<uint32_t*>(&v);
}
__device__ __forceinline__ float lo2f(uint32_t v) { return __uint_as_float(v << 16); }
__device__ __forceinline__ float hi2f(uint32_t v) { return __uint_as_float(v & 0xffff0000u); }
__device__ __forceinline__ float frcp(float x) { float r; asm("rcp.approx.f32 %0, %1;" : "=f"(r) : "f"(x)); return r; }
__device__ __forceinline__ float fsqrt(float x) { float r; asm("sqrt.approx.f32 %0, %1;" : "=f"(r) : "f"(x)); return r; }
__device__ __forceinline__ uint32_t smem_u32(const void* p) { return (uint32_t)__cvta_generic_to_shared(p); }

__device__ __forceinline__ void mbar_init(uint32_t bar, uint32_t cnt) {
    asm volatile("mbarrier.init.shared::cta.b64 [%0], %1;" ::"r"(bar), "r"(cnt));
}
__device__ __forceinline__ void mbar_expect_tx(uint32_t bar, uint32_t bytes) {
    asm volatile("mbarrier.arrive.expect_tx.shared::cta.b64 _, [%0], %1;" ::"r"(bar), "r"(bytes) : "memory");
}
__device__ __forceinline__ void mbar_arrive(uint32_t bar) {
    asm volatile("mbarrier.arrive.shared::cta.b64 _, [%0];" ::"r"(bar) : "memory");
}
__device__ __forceinline__ void mbar_wait(uint32_t bar, uint32_t parity) {
    asm volatile(
        "{\n.reg .pred p;\n.reg .u32 n;\n"
        "mbarrier.try_wait.parity.shared::cta.b64 p, [%0], %1;\n"
        "@p bra LD;\n"
        "mov.u32 n, 0;\n"
        "LW:\n"
        "mbarrier.try_wait.parity.shared::cta.b64 p, [%0], %1;\n"
        "@p bra LD;\n"
        "add.u32 n, n, 1;\n"
        "setp.lt.u32 p, n, 0x400000;\n"
        "@p bra LW;\n"
        "LD:\n}\n"
        ::"r"(bar), "r"(parity) : "memory");
}
__device__ __forceinline__ void tma_load_2d(uint32_t dst, const CUtensorMap* tm, uint32_t bar, int c0, int c1) {
    asm volatile(
        "cp.async.bulk.tensor.2d.shared::cluster.global.mbarrier::complete_tx::bytes [%0], [%1, {%3, %4}], [%2];"
        ::"r"(dst), "l"((uint64_t)tm), "r"(bar), "r"(c0), "r"(c1) : "memory");
}
__device__ __forceinline__ void tma_load_2d_mc(uint32_t dst, const CUtensorMap* tm, uint32_t bar, int c0, int c1) {
    asm volatile(
        "cp.async.bulk.tensor.2d.shared::cluster.global.mbarrier::complete_tx::bytes.multicast::cluster [%0], [%1, {%3, %4}], [%2], %5;"
        ::"r"(dst), "l"((uint64_t)tm), "r"(bar), "r"(c0), "r"(c1), "h"((uint16_t)3) : "memory");
}
__device__ __forceinline__ void tma_prefetch_2d(const CUtensorMap* tm, int c0, int c1) {
    asm volatile("cp.async.bulk.prefetch.tensor.2d.L2.global.tile [%0, {%1, %2}];" ::"l"((uint64_t)tm), "r"(c0), "r"(c1) : "memory");
}
__device__ __forceinline__ void tma_store_2d(const CUtensorMap* tm, uint32_t src, int c0, int c1) {
    asm volatile("cp.async.bulk.tensor.2d.global.shared::cta.bulk_group [%0, {%2, %3}], [%1];"
                 ::"l"((uint64_t)tm), "r"(src), "r"(c0), "r"(c1) : "memory");
}
__device__ __forceinline__ void wgmma_fence() { asm volatile("wgmma.fence.sync.aligned;" ::: "memory"); }
__device__ __forceinline__ void wgmma_commit() { asm volatile("wgmma.commit_group.sync.aligned;" ::: "memory"); }
template <int N> __device__ __forceinline__ void wgmma_wait() { asm volatile("wgmma.wait_group.sync.aligned %0;" ::"n"(N) : "memory"); }
__device__ __forceinline__ void named_bar_arrive(int id, int n) { asm volatile("bar.arrive %0, %1;" ::"r"(id), "r"(n) : "memory"); }
__device__ __forceinline__ void named_bar_sync(int id, int n) { asm volatile("bar.sync %0, %1;" ::"r"(id), "r"(n) : "memory"); }

__device__ __forceinline__ uint32_t desc_a(uint32_t addr) { return ((addr & 0x3FFFF) >> 4) | (1u << 16); }
__device__ __forceinline__ uint32_t desc_b(uint32_t addr) { return ((addr & 0x3FFFF) >> 4) | (512u << 16); }

template <int ACC> __device__ __forceinline__ void wgmma_m64n192k16(float (&d)[96], uint32_t descA, uint32_t descB) {
  asm volatile("{\n.reg .pred p;\n.reg .b64 da, db;\nsetp.ne.b32 p, %99, 0;\nmov.b64 da, {%96, %98};\nmov.b64 db, {%97, %98};\n"
    "wgmma.mma_async.sync.aligned.m64n192k16.f32.bf16.bf16 "
    "{%0, %1, %2, %3, %4, %5, %6, %7, %8, %9, %10, %11, %12, %13, %14, %15, %16, %17, %18, %19, %20, %21, %22, %23, %24, %25, %26, %27, %28, %29, %30, %31, %32, %33, %34, %35, %36, %37, %38, %39, %40, %41, %42, %43, %44, %45, %46, %47, %48, %49, %50, %51, %52, %53, %54, %55, %56, %57, %58, %59, %60, %61, %62, %63, %64, %65, %66, %67, %68, %69, %70, %71, %72, %73, %74, %75, %76, %77, %78, %79, %80, %81, %82, %83, %84, %85, %86, %87, %88, %89, %90, %91, %92, %93, %94, %95}, "
    "da, db, p, 1, 1, 0, 1;\n}\n"
    : "+f"(d[0]), "+f"(d[1]), "+f"(d[2]), "+f"(d[3]), "+f"(d[4]), "+f"(d[5]), "+f"(d[6]), "+f"(d[7]), "+f"(d[8]), "+f"(d[9]), "+f"(d[10]), "+f"(d[11]), "+f"(d[12]), "+f"(d[13]), "+f"(d[14]), "+f"(d[15]), "+f"(d[16]), "+f"(d[17]), "+f"(d[18]), "+f"(d[19]), "+f"(d[20]), "+f"(d[21]), "+f"(d[22]), "+f"(d[23]), "+f"(d[24]), "+f"(d[25]), "+f"(d[26]), "+f"(d[27]), "+f"(d[28]), "+f"(d[29]), "+f"(d[30]), "+f"(d[31]), "+f"(d[32]), "+f"(d[33]), "+f"(d[34]), "+f"(d[35]), "+f"(d[36]), "+f"(d[37]), "+f"(d[38]), "+f"(d[39]), "+f"(d[40]), "+f"(d[41]), "+f"(d[42]), "+f"(d[43]), "+f"(d[44]), "+f"(d[45]), "+f"(d[46]), "+f"(d[47]), "+f"(d[48]), "+f"(d[49]), "+f"(d[50]), "+f"(d[51]), "+f"(d[52]), "+f"(d[53]), "+f"(d[54]), "+f"(d[55]), "+f"(d[56]), "+f"(d[57]), "+f"(d[58]), "+f"(d[59]), "+f"(d[60]), "+f"(d[61]), "+f"(d[62]), "+f"(d[63]), "+f"(d[64]), "+f"(d[65]), "+f"(d[66]), "+f"(d[67]), "+f"(d[68]), "+f"(d[69]), "+f"(d[70]), "+f"(d[71]), "+f"(d[72]), "+f"(d[73]), "+f"(d[74]), "+f"(d[75]), "+f"(d[76]), "+f"(d[77]), "+f"(d[78]), "+f"(d[79]), "+f"(d[80]), "+f"(d[81]), "+f"(d[82]), "+f"(d[83]), "+f"(d[84]), "+f"(d[85]), "+f"(d[86]), "+f"(d[87]), "+f"(d[88]), "+f"(d[89]), "+f"(d[90]), "+f"(d[91]), "+f"(d[92]), "+f"(d[93]), "+f"(d[94]), "+f"(d[95])
    : "r"(descA), "r"(descB), "r"(0x40000040u), "n"(ACC));
}

template <int ACC> __device__ __forceinline__ void wgmma_m64n256k16(float (&d)[128], uint32_t descA, uint32_t descB) {
  asm volatile("{\n.reg .pred p;\n.reg .b64 da, db;\nsetp.ne.b32 p, %131, 0;\nmov.b64 da, {%128, %130};\nmov.b64 db, {%129, %130};\n"
    "wgmma.mma_async.sync.aligned.m64n256k16.f32.bf16.bf16 "
    "{%0, %1, %2, %3, %4, %5, %6, %7, %8, %9, %10, %11, %12, %13, %14, %15, %16, %17, %18, %19, %20, %21, %22, %23, %24, %25, %26, %27, %28, %29, %30, %31, %32, %33, %34, %35, %36, %37, %38, %39, %40, %41, %42, %43, %44, %45, %46, %47, %48, %49, %50, %51, %52, %53, %54, %55, %56, %57, %58, %59, %60, %61, %62, %63, %64, %65, %66, %67, %68, %69, %70, %71, %72, %73, %74, %75, %76, %77, %78, %79, %80, %81, %82, %83, %84, %85, %86, %87, %88, %89, %90, %91, %92, %93, %94, %95, %96, %97, %98, %99, %100, %101, %102, %103, %104, %105, %106, %107, %108, %109, %110, %111, %112, %113, %114, %115, %116, %117, %118, %119, %120, %121, %122, %123, %124, %125, %126, %127}, "
    "da, db, p, 1, 1, 0, 1;\n}\n"
    : "+f"(d[0]), "+f"(d[1]), "+f"(d[2]), "+f"(d[3]), "+f"(d[4]), "+f"(d[5]), "+f"(d[6]), "+f"(d[7]), "+f"(d[8]), "+f"(d[9]), "+f"(d[10]), "+f"(d[11]), "+f"(d[12]), "+f"(d[13]), "+f"(d[14]), "+f"(d[15]), "+f"(d[16]), "+f"(d[17]), "+f"(d[18]), "+f"(d[19]), "+f"(d[20]), "+f"(d[21]), "+f"(d[22]), "+f"(d[23]), "+f"(d[24]), "+f"(d[25]), "+f"(d[26]), "+f"(d[27]), "+f"(d[28]), "+f"(d[29]), "+f"(d[30]), "+f"(d[31]), "+f"(d[32]), "+f"(d[33]), "+f"(d[34]), "+f"(d[35]), "+f"(d[36]), "+f"(d[37]), "+f"(d[38]), "+f"(d[39]), "+f"(d[40]), "+f"(d[41]), "+f"(d[42]), "+f"(d[43]), "+f"(d[44]), "+f"(d[45]), "+f"(d[46]), "+f"(d[47]), "+f"(d[48]), "+f"(d[49]), "+f"(d[50]), "+f"(d[51]), "+f"(d[52]), "+f"(d[53]), "+f"(d[54]), "+f"(d[55]), "+f"(d[56]), "+f"(d[57]), "+f"(d[58]), "+f"(d[59]), "+f"(d[60]), "+f"(d[61]), "+f"(d[62]), "+f"(d[63]), "+f"(d[64]), "+f"(d[65]), "+f"(d[66]), "+f"(d[67]), "+f"(d[68]), "+f"(d[69]), "+f"(d[70]), "+f"(d[71]), "+f"(d[72]), "+f"(d[73]), "+f"(d[74]), "+f"(d[75]), "+f"(d[76]), "+f"(d[77]), "+f"(d[78]), "+f"(d[79]), "+f"(d[80]), "+f"(d[81]), "+f"(d[82]), "+f"(d[83]), "+f"(d[84]), "+f"(d[85]), "+f"(d[86]), "+f"(d[87]), "+f"(d[88]), "+f"(d[89]), "+f"(d[90]), "+f"(d[91]), "+f"(d[92]), "+f"(d[93]), "+f"(d[94]), "+f"(d[95]), "+f"(d[96]), "+f"(d[97]), "+f"(d[98]), "+f"(d[99]), "+f"(d[100]), "+f"(d[101]), "+f"(d[102]), "+f"(d[103]), "+f"(d[104]), "+f"(d[105]), "+f"(d[106]), "+f"(d[107]), "+f"(d[108]), "+f"(d[109]), "+f"(d[110]), "+f"(d[111]), "+f"(d[112]), "+f"(d[113]), "+f"(d[114]), "+f"(d[115]), "+f"(d[116]), "+f"(d[117]), "+f"(d[118]), "+f"(d[119]), "+f"(d[120]), "+f"(d[121]), "+f"(d[122]), "+f"(d[123]), "+f"(d[124]), "+f"(d[125]), "+f"(d[126]), "+f"(d[127])
    : "r"(descA), "r"(descB), "r"(0x40000040u), "n"(ACC));
}

template <int ACC> __device__ __forceinline__ void wgmma_m64n128k16(float (&d)[64], uint32_t descA, uint32_t descB) {
  asm volatile("{\n.reg .pred p;\n.reg .b64 da, db;\nsetp.ne.b32 p, %67, 0;\nmov.b64 da, {%64, %66};\nmov.b64 db, {%65, %66};\n"
    "wgmma.mma_async.sync.aligned.m64n128k16.f32.bf16.bf16 "
    "{%0, %1, %2, %3, %4, %5, %6, %7, %8, %9, %10, %11, %12, %13, %14, %15, %16, %17, %18, %19, %20, %21, %22, %23, %24, %25, %26, %27, %28, %29, %30, %31, %32, %33, %34, %35, %36, %37, %38, %39, %40, %41, %42, %43, %44, %45, %46, %47, %48, %49, %50, %51, %52, %53, %54, %55, %56, %57, %58, %59, %60, %61, %62, %63}, "
    "da, db, p, 1, 1, 0, 1;\n}\n"
    : "+f"(d[0]), "+f"(d[1]), "+f"(d[2]), "+f"(d[3]), "+f"(d[4]), "+f"(d[5]), "+f"(d[6]), "+f"(d[7]), "+f"(d[8]), "+f"(d[9]), "+f"(d[10]), "+f"(d[11]), "+f"(d[12]), "+f"(d[13]), "+f"(d[14]), "+f"(d[15]), "+f"(d[16]), "+f"(d[17]), "+f"(d[18]), "+f"(d[19]), "+f"(d[20]), "+f"(d[21]), "+f"(d[22]), "+f"(d[23]), "+f"(d[24]), "+f"(d[25]), "+f"(d[26]), "+f"(d[27]), "+f"(d[28]), "+f"(d[29]), "+f"(d[30]), "+f"(d[31]), "+f"(d[32]), "+f"(d[33]), "+f"(d[34]), "+f"(d[35]), "+f"(d[36]), "+f"(d[37]), "+f"(d[38]), "+f"(d[39]), "+f"(d[40]), "+f"(d[41]), "+f"(d[42]), "+f"(d[43]), "+f"(d[44]), "+f"(d[45]), "+f"(d[46]), "+f"(d[47]), "+f"(d[48]), "+f"(d[49]), "+f"(d[50]), "+f"(d[51]), "+f"(d[52]), "+f"(d[53]), "+f"(d[54]), "+f"(d[55]), "+f"(d[56]), "+f"(d[57]), "+f"(d[58]), "+f"(d[59]), "+f"(d[60]), "+f"(d[61]), "+f"(d[62]), "+f"(d[63])
    : "r"(descA), "r"(descB), "r"(0x40000040u), "n"(ACC));
}

template <int BN> struct WG;
template <> struct WG<128> { template <int ACC> static __device__ __forceinline__ void mma(float (&d)[64], uint32_t a, uint32_t b) { wgmma_m64n128k16<ACC>(d, a, b); } };
template <> struct WG<256> { template <int ACC> static __device__ __forceinline__ void mma(float (&d)[128], uint32_t a, uint32_t b) { wgmma_m64n256k16<ACC>(d, a, b); } };
template <> struct WG<192> { template <int ACC> static __device__ __forceinline__ void mma(float (&d)[96], uint32_t a, uint32_t b) { wgmma_m64n192k16<ACC>(d, a, b); } };

#define DBG_T(i)
__device__ __forceinline__ void fence_async_smem() { asm volatile("fence.proxy.async.shared::cta;" ::: "memory"); }
__device__ __forceinline__ void prefetch_tmap(const CUtensorMap* tm) { asm volatile("prefetch.tensormap [%0];" ::"l"((uint64_t)tm) : "memory"); }
__device__ __forceinline__ uint32_t mapa_u32(uint32_t addr, uint32_t cta) {
    uint32_t r;
    asm volatile("mapa.shared::cluster.u32 %0, %1, %2;" : "=r"(r) : "r"(addr), "r"(cta));
    return r;
}
__device__ __forceinline__ void mbar_arrive_cluster(uint32_t cluster_addr) {
    asm volatile("mbarrier.arrive.shared::cluster.b64 _, [%0];" ::"r"(cluster_addr) : "memory");
}
__device__ __forceinline__ bool elect_one() {
    uint32_t p;
    asm volatile("{\n.reg .pred P;\nelect.sync _|P, 0xffffffff;\nselp.u32 %0, 1, 0, P;\n}\n" : "=r"(p));
    return p != 0;
}
__device__ __forceinline__ void cluster_arrive_relaxed() { asm volatile("barrier.cluster.arrive.relaxed.aligned;" ::: "memory"); }
__device__ __forceinline__ void cluster_wait() { asm volatile("barrier.cluster.wait.acquire.aligned;" ::: "memory"); }

__device__ __forceinline__ uint32_t bsub2(uint32_t a, uint32_t b) {
    __nv_bfloat162 r = __hsub2(*reinterpret_cast<__nv_bfloat162*>(&a), *reinterpret_cast<__nv_bfloat162*>(&b));
    return *reinterpret_cast<uint32_t*>(&r);
}
__device__ __forceinline__ uint32_t bmul2(uint32_t a, uint32_t b) {
    __nv_bfloat162 r = __hmul2(*reinterpret_cast<__nv_bfloat162*>(&a), *reinterpret_cast<__nv_bfloat162*>(&b));
    return *reinterpret_cast<uint32_t*>(&r);
}
__device__ __forceinline__ uint32_t badd2(uint32_t a, uint32_t b) {
    __nv_bfloat162 r = __hadd2(*reinterpret_cast<__nv_bfloat162*>(&a), *reinterpret_cast<__nv_bfloat162*>(&b));
    return *reinterpret_cast<uint32_t*>(&r);
}
constexpr int BM = 128, BK = 64;
constexpr int R5_STAGE = 32768, R5_N = 5;
constexpr int R4_STAGE = 49152, R4_N = 4;
constexpr int R4B_STAGE = 40960;
constexpr int OFF_STG5 = 0, OFF_R = 32768;
constexpr int OFF_EPI = 196608;
constexpr int OFF_BAR = OFF_EPI + 32768;
constexpr int OFF_RS = OFF_BAR + 256;
constexpr int OFF_CS = OFF_RS + 1024;
constexpr int MEGA_SMEM = OFF_CS + 1792;
enum { FL_XA = 0, FL_H = 2, FL_X1 = 4, FL_H2 = 6, FL_CS = 10, FL_KINDS = 11 };
constexpr int FL_PITCH = 64;
constexpr int FL_WORDS = 2 * FL_KINDS * 16 * FL_PITCH;
__device__ unsigned int g_flag[FL_WORDS];
__device__ __align__(8) unsigned int g_ticket[18 * FL_PITCH];
constexpr int NCL = 66;
__device__ __forceinline__ unsigned int* flag_ptr(int layer, int kind, int i) { return g_flag + ((layer * FL_KINDS + kind) * 16 + i) * FL_PITCH; }

__device__ __forceinline__ void wait_flag(const unsigned int* p, unsigned int target) {
    long long t0 = clock64();
    while (true) {
        unsigned int v;
        asm volatile("ld.relaxed.gpu.global.u32 %0, [%1];" : "=r"(v) : "l"(p) : "memory");
        if ((int)(v - target) >= 0) break;
        if (clock64() - t0 > 2000000000LL) break;
    }
    asm volatile("fence.acquire.gpu;" ::: "memory");
}
__device__ __forceinline__ void fence_proxy_async() {
    asm volatile("fence.proxy.async.global;" ::: "memory");
    asm volatile("fence.proxy.async.shared::cta;" ::: "memory");
}
__device__ __forceinline__ void stsm4(uint32_t addr, uint32_t r0, uint32_t r1, uint32_t r2, uint32_t r3) {
    asm volatile("stmatrix.sync.aligned.m8n8.x4.shared.b16 [%0], {%1,%2,%3,%4};" ::"r"(addr), "r"(r0), "r"(r1), "r"(r2), "r"(r3));
}
__device__ __forceinline__ uint4 lds128(uint32_t a) {
    uint4 v;
    asm volatile("ld.shared.v4.b32 {%0,%1,%2,%3}, [%4];" : "=r"(v.x), "=r"(v.y), "=r"(v.z), "=r"(v.w) : "r"(a) : "memory");
    return v;
}
__device__ __forceinline__ void stg128(void* p, uint4 v) {
    asm volatile("st.global.v4.b32 [%0], {%1,%2,%3,%4};" ::"l"(p), "r"(v.x), "r"(v.y), "r"(v.z), "r"(v.w) : "memory");
}
__device__ __forceinline__ float gelu_tanh_h(float hx) {
    float z = hx * fmaf(hx * hx, 8.0f * 0.035677408136300125f, 2.0f * 0.7978845608028654f);
    float t;
    asm("tanh.approx.f32 %0, %1;" : "=f"(t) : "f"(z));
    return fmaf(hx, t, hx);
}
__device__ __forceinline__ uint32_t gelu2h(uint32_t hx) {
    uint32_t r;
    asm("{\n.reg .b32 z;\nmul.rn.bf16x2 z, %1, %1;\nfma.rn.bf16x2 z, z, %2, %3;\nmul.rn.bf16x2 z, z, %1;\ntanh.approx.bf16x2 z, z;\nfma.rn.bf16x2 %0, %1, z, %1;\n}"
        : "=r"(r) : "r"(hx), "r"(0x3e923e92u), "r"(0x3fcc3fccu));
    return r;
}
__device__ __forceinline__ uint4 gelu8h(uint4 v) { return make_uint4(gelu2h(v.x), gelu2h(v.y), gelu2h(v.z), gelu2h(v.w)); }

__device__ __forceinline__ void row_stats(const float2* p, uint32_t tag, float& mean, float& var) {
    float2 v[8];
#pragma unroll 1
    for (int n = 0; n < (1 << 20); n++) {
#pragma unroll
        for (int i = 0; i < 8; i++)
            asm volatile("{\n.reg .b64 t;\nld.relaxed.gpu.global.b64 t, [%2];\nmov.b64 {%0, %1}, t;\n}" : "=f"(v[i].x), "=f"(v[i].y) : "l"(p + 128 * i) : "memory");
        uint32_t old = 0;
#pragma unroll
        for (int i = 0; i < 8; i++) old |= __float_as_uint(v[i].y) ^ tag;
        if ((int)old >= 0) break;
    }
    mean = (((v[0].x + v[1].x) + (v[2].x + v[3].x)) + ((v[4].x + v[5].x) + (v[6].x + v[7].x))) * 0.125f;
    float m2 = 0.f, d2 = 0.f;
#pragma unroll
    for (int i = 0; i < 8; i++) { m2 += fabsf(v[i].y); d2 = fmaf(v[i].x - mean, v[i].x - mean, d2); }
    var = fmaf(128.0f, d2, m2) * (1.0f / D_);
}
struct RingState { uint32_t st, ph; };

#define DT(i)
#define DT_DECL
#define DT_PAR
#define DT_ARG
#define DT_DUMP
#define DP(i)
#define DQ(i)
#define GT(i)
#define TM(i)

template <int BN, int NST, int ACC = 1>
__device__ __forceinline__ void kblock(float (&acc)[BN / 2], uint32_t da, uint32_t db, uint32_t bfull, RingState& rs) {
    mbar_wait(bfull + 8 * rs.st, rs.ph);
    wgmma_fence();
    WG<BN>::template mma<ACC>(acc, da, db);
#pragma unroll
    for (int k = 1; k < 4; k++) WG<BN>::template mma<1>(acc, da + k * 2, db + k * 128);
    wgmma_commit();
    if (++rs.st == NST) { rs.st = 0; rs.ph ^= 1; }
}
#define PA3A 1
#define RLX 1
#define NPRE 12
#define PP3 2
#define NCS 8
template <int V> struct IC { static constexpr int v = V; };
template <int A, int B, class F> __device__ __forceinline__ void static_for(F f) {
    if constexpr (A < B) { f(IC<A>()); static_for<A + 1, B>(f); }
}
#define SPL 21
#define PF4A 22
#define PF4N 1
#define XCS 0
#define PA1 45
#define PA2 33
#define PA4 33
#define LAGX 1
#define PA3B 0
template <int BN, int NST, int STAGE, int PS = 0, int TW = 0, class F>
__device__ __forceinline__ void mainloop(float (&acc)[BN / 2], int KB, uint32_t da0, uint32_t db0, uint32_t bfull, uint32_t rel, bool rel_on,
                                         RingState& rs, int dbg, F pre DT_PAR, int wg = 0) {
    constexpr int SG = PS / 10, PAUSE = PS % 10;
    uint32_t prev = rs.st ? rs.st - 1 : NST - 1;
    const int pause = wg ? KB - PAUSE : -1;
#pragma unroll 1
    for (int kk = 0; kk < KB; kk++) {
        const uint32_t cur = rs.st;
        if (PAUSE && kk == pause) {
            wgmma_wait<0>();
            if (rel_on) mbar_arrive_cluster(rel + 8 * prev);
            named_bar_sync(15, 256);
        }
        kblock<BN, NST>(acc, da0 + cur * (STAGE / 16), db0 + cur * (STAGE / 16), bfull, rs);
        if (PAUSE && SG >= 2 && wg == 0 && kk == KB + 1 - SG) named_bar_arrive(15, 256);
        wgmma_wait<1>();
        if (rel_on && !(PAUSE && kk == pause)) mbar_arrive_cluster(rel + 8 * prev);
        prev = cur;
    }
    if (PAUSE && SG == 0 && wg == 0) named_bar_arrive(15, 256);
    pre();
    wgmma_wait<TW>();
#pragma unroll
    for (int i = 0; i < BN / 2; i++) asm volatile("" : "+f"(acc[i])::"memory");
    if (PAUSE && SG == 1 && wg == 0) named_bar_arrive(15, 256);
    if (rel_on) mbar_arrive_cluster(rel + 8 * prev);
}
__device__ __forceinline__ void hmma(float (&c)[4], uint32_t a0, uint32_t a1, uint32_t a2, uint32_t a3, uint32_t b0, uint32_t b1, bool first) {
    if (first) asm("{\n.reg .f32 z;\nmov.f32 z, 0f00000000;\nmma.sync.aligned.m16n8k16.row.col.f32.bf16.bf16.f32 {%0,%1,%2,%3}, {%4,%5,%6,%7}, {%8,%9}, {z,z,z,z};\n}"
        : "=f"(c[0]), "=f"(c[1]), "=f"(c[2]), "=f"(c[3]) : "r"(a0), "r"(a1), "r"(a2), "r"(a3), "r"(b0), "r"(b1));
    else
    asm("mma.sync.aligned.m16n8k16.row.col.f32.bf16.bf16.f32 {%0,%1,%2,%3}, {%4,%5,%6,%7}, {%8,%9}, {%0,%1,%2,%3};"
        : "+f"(c[0]), "+f"(c[1]), "+f"(c[2]), "+f"(c[3]) : "r"(a0), "r"(a1), "r"(a2), "r"(a3), "r"(b0), "r"(b1));
}
__device__ __forceinline__ void hmma8(float (&c)[4], uint32_t a0, uint32_t a1, uint32_t b0, bool first) {
    if (first) asm("{\n.reg .f32 z;\nmov.f32 z, 0f00000000;\nmma.sync.aligned.m16n8k8.row.col.f32.bf16.bf16.f32 {%0,%1,%2,%3}, {%4,%5}, {%6}, {z,z,z,z};\n}"
        : "=f"(c[0]), "=f"(c[1]), "=f"(c[2]), "=f"(c[3]) : "r"(a0), "r"(a1), "r"(b0));
    else
    asm("mma.sync.aligned.m16n8k8.row.col.f32.bf16.bf16.f32 {%0,%1,%2,%3}, {%4,%5}, {%6}, {%0,%1,%2,%3};"
        : "+f"(c[0]), "+f"(c[1]), "+f"(c[2]), "+f"(c[3]) : "r"(a0), "r"(a1), "r"(b0));
}
template <int N> __device__ __forceinline__ void zero_acc(float (&acc)[N]) {
#pragma unroll
    for (int i = 0; i < N; i++) acc[i] = 0.f;
}
__device__ __forceinline__ void ldsm4(uint32_t& r0, uint32_t& r1, uint32_t& r2, uint32_t& r3, uint32_t addr) {
    asm volatile("ldmatrix.sync.aligned.m8n8.x4.shared.b16 {%0,%1,%2,%3}, [%4];" : "=r"(r0), "=r"(r1), "=r"(r2), "=r"(r3) : "r"(addr));
}

__device__ __forceinline__ void ldsm4t(uint32_t& r0, uint32_t& r1, uint32_t& r2, uint32_t& r3, uint32_t addr) {
    asm volatile("ldmatrix.sync.aligned.m8n8.x4.trans.shared.b16 {%0,%1,%2,%3}, [%4];" : "=r"(r0), "=r"(r1), "=r"(r2), "=r"(r3) : "r"(addr));
}

#define DBG_S(i)
#define DBG_OUT(r, o)
#define DBG_F(i)
#define DBG_W(i)
constexpr int CV_CH = 8;
constexpr int CV_SL = 16384;
constexpr int CV_QG = 128 * 8 + 16;
constexpr int CV_HPL = 2048 + 192;
constexpr int CV_0 = 32768, CV_H = 9 * CV_SL, CV_BAR = OFF_RS - CV_0;

template <int K> __device__ __forceinline__ void cv_mma(float (&d)[64], const uint32_t (&a)[4], uint32_t db, int acc);
template <> __device__ __forceinline__ void cv_mma<0>(float (&d)[64], const uint32_t (&a)[4], uint32_t db, int acc) {
    asm volatile("{\n.reg .pred p;\n.reg .b64 b;\nsetp.ne.b32 p, %70, 0;\nmov.b64 b, {%68, %69};\n"
        "wgmma.mma_async.sync.aligned.m64n128k16.f32.bf16.bf16 {%0,%1,%2,%3,%4,%5,%6,%7,%8,%9,%10,%11,%12,%13,%14,%15,%16,%17,%18,%19,%20,%21,%22,%23,%24,%25,%26,%27,%28,%29,%30,%31,%32,%33,%34,%35,%36,%37,%38,%39,%40,%41,%42,%43,%44,%45,%46,%47,%48,%49,%50,%51,%52,%53,%54,%55,%56,%57,%58,%59,%60,%61,%62,%63}, {%64,%65,%66,%67}, b, p, 1, 1, 0;\n}\n"
        : "+f"(d[0]), "+f"(d[1]), "+f"(d[2]), "+f"(d[3]), "+f"(d[4]), "+f"(d[5]), "+f"(d[6]), "+f"(d[7]), "+f"(d[8]), "+f"(d[9]), "+f"(d[10]), "+f"(d[11]), "+f"(d[12]), "+f"(d[13]), "+f"(d[14]), "+f"(d[15]), "+f"(d[16]), "+f"(d[17]), "+f"(d[18]), "+f"(d[19]), "+f"(d[20]), "+f"(d[21]), "+f"(d[22]), "+f"(d[23]), "+f"(d[24]), "+f"(d[25]), "+f"(d[26]), "+f"(d[27]), "+f"(d[28]), "+f"(d[29]), "+f"(d[30]), "+f"(d[31]), "+f"(d[32]), "+f"(d[33]), "+f"(d[34]), "+f"(d[35]), "+f"(d[36]), "+f"(d[37]), "+f"(d[38]), "+f"(d[39]), "+f"(d[40]), "+f"(d[41]), "+f"(d[42]), "+f"(d[43]), "+f"(d[44]), "+f"(d[45]), "+f"(d[46]), "+f"(d[47]), "+f"(d[48]), "+f"(d[49]), "+f"(d[50]), "+f"(d[51]), "+f"(d[52]), "+f"(d[53]), "+f"(d[54]), "+f"(d[55]), "+f"(d[56]), "+f"(d[57]), "+f"(d[58]), "+f"(d[59]), "+f"(d[60]), "+f"(d[61]), "+f"(d[62]), "+f"(d[63])
        : "r"(a[0]), "r"(a[1]), "r"(a[2]), "r"(a[3]), "r"(db), "r"(8u), "r"(acc));
}
template <> __device__ __forceinline__ void cv_mma<1>(float (&d)[64], const uint32_t (&a)[4], uint32_t db, int acc) {
    asm volatile("{\n.reg .pred p;\n.reg .b64 b;\nsetp.ne.b32 p, %62, 0;\nmov.b64 b, {%60, %61};\n"
        "wgmma.mma_async.sync.aligned.m64n112k16.f32.bf16.bf16 {%0,%1,%2,%3,%4,%5,%6,%7,%8,%9,%10,%11,%12,%13,%14,%15,%16,%17,%18,%19,%20,%21,%22,%23,%24,%25,%26,%27,%28,%29,%30,%31,%32,%33,%34,%35,%36,%37,%38,%39,%40,%41,%42,%43,%44,%45,%46,%47,%48,%49,%50,%51,%52,%53,%54,%55}, {%56,%57,%58,%59}, b, p, 1, 1, 0;\n}\n"
        : "+f"(d[0]), "+f"(d[1]), "+f"(d[2]), "+f"(d[3]), "+f"(d[4]), "+f"(d[5]), "+f"(d[6]), "+f"(d[7]), "+f"(d[8]), "+f"(d[9]), "+f"(d[10]), "+f"(d[11]), "+f"(d[12]), "+f"(d[13]), "+f"(d[14]), "+f"(d[15]), "+f"(d[16]), "+f"(d[17]), "+f"(d[18]), "+f"(d[19]), "+f"(d[20]), "+f"(d[21]), "+f"(d[22]), "+f"(d[23]), "+f"(d[24]), "+f"(d[25]), "+f"(d[26]), "+f"(d[27]), "+f"(d[28]), "+f"(d[29]), "+f"(d[30]), "+f"(d[31]), "+f"(d[32]), "+f"(d[33]), "+f"(d[34]), "+f"(d[35]), "+f"(d[36]), "+f"(d[37]), "+f"(d[38]), "+f"(d[39]), "+f"(d[40]), "+f"(d[41]), "+f"(d[42]), "+f"(d[43]), "+f"(d[44]), "+f"(d[45]), "+f"(d[46]), "+f"(d[47]), "+f"(d[48]), "+f"(d[49]), "+f"(d[50]), "+f"(d[51]), "+f"(d[52]), "+f"(d[53]), "+f"(d[54]), "+f"(d[55])
        : "r"(a[0]), "r"(a[1]), "r"(a[2]), "r"(a[3]), "r"(db), "r"(8u), "r"(acc));
}
template <> __device__ __forceinline__ void cv_mma<2>(float (&d)[64], const uint32_t (&a)[4], uint32_t db, int acc) {
    asm volatile("{\n.reg .pred p;\n.reg .b64 b;\nsetp.ne.b32 p, %54, 0;\nmov.b64 b, {%52, %53};\n"
        "wgmma.mma_async.sync.aligned.m64n96k16.f32.bf16.bf16 {%0,%1,%2,%3,%4,%5,%6,%7,%8,%9,%10,%11,%12,%13,%14,%15,%16,%17,%18,%19,%20,%21,%22,%23,%24,%25,%26,%27,%28,%29,%30,%31,%32,%33,%34,%35,%36,%37,%38,%39,%40,%41,%42,%43,%44,%45,%46,%47}, {%48,%49,%50,%51}, b, p, 1, 1, 0;\n}\n"
        : "+f"(d[0]), "+f"(d[1]), "+f"(d[2]), "+f"(d[3]), "+f"(d[4]), "+f"(d[5]), "+f"(d[6]), "+f"(d[7]), "+f"(d[8]), "+f"(d[9]), "+f"(d[10]), "+f"(d[11]), "+f"(d[12]), "+f"(d[13]), "+f"(d[14]), "+f"(d[15]), "+f"(d[16]), "+f"(d[17]), "+f"(d[18]), "+f"(d[19]), "+f"(d[20]), "+f"(d[21]), "+f"(d[22]), "+f"(d[23]), "+f"(d[24]), "+f"(d[25]), "+f"(d[26]), "+f"(d[27]), "+f"(d[28]), "+f"(d[29]), "+f"(d[30]), "+f"(d[31]), "+f"(d[32]), "+f"(d[33]), "+f"(d[34]), "+f"(d[35]), "+f"(d[36]), "+f"(d[37]), "+f"(d[38]), "+f"(d[39]), "+f"(d[40]), "+f"(d[41]), "+f"(d[42]), "+f"(d[43]), "+f"(d[44]), "+f"(d[45]), "+f"(d[46]), "+f"(d[47])
        : "r"(a[0]), "r"(a[1]), "r"(a[2]), "r"(a[3]), "r"(db), "r"(8u), "r"(acc));
}
template <> __device__ __forceinline__ void cv_mma<3>(float (&d)[64], const uint32_t (&a)[4], uint32_t db, int acc) {
    asm volatile("{\n.reg .pred p;\n.reg .b64 b;\nsetp.ne.b32 p, %46, 0;\nmov.b64 b, {%44, %45};\n"
        "wgmma.mma_async.sync.aligned.m64n80k16.f32.bf16.bf16 {%0,%1,%2,%3,%4,%5,%6,%7,%8,%9,%10,%11,%12,%13,%14,%15,%16,%17,%18,%19,%20,%21,%22,%23,%24,%25,%26,%27,%28,%29,%30,%31,%32,%33,%34,%35,%36,%37,%38,%39}, {%40,%41,%42,%43}, b, p, 1, 1, 0;\n}\n"
        : "+f"(d[0]), "+f"(d[1]), "+f"(d[2]), "+f"(d[3]), "+f"(d[4]), "+f"(d[5]), "+f"(d[6]), "+f"(d[7]), "+f"(d[8]), "+f"(d[9]), "+f"(d[10]), "+f"(d[11]), "+f"(d[12]), "+f"(d[13]), "+f"(d[14]), "+f"(d[15]), "+f"(d[16]), "+f"(d[17]), "+f"(d[18]), "+f"(d[19]), "+f"(d[20]), "+f"(d[21]), "+f"(d[22]), "+f"(d[23]), "+f"(d[24]), "+f"(d[25]), "+f"(d[26]), "+f"(d[27]), "+f"(d[28]), "+f"(d[29]), "+f"(d[30]), "+f"(d[31]), "+f"(d[32]), "+f"(d[33]), "+f"(d[34]), "+f"(d[35]), "+f"(d[36]), "+f"(d[37]), "+f"(d[38]), "+f"(d[39])
        : "r"(a[0]), "r"(a[1]), "r"(a[2]), "r"(a[3]), "r"(db), "r"(8u), "r"(acc));
}
template <> __device__ __forceinline__ void cv_mma<4>(float (&d)[64], const uint32_t (&a)[4], uint32_t db, int acc) {
    asm volatile("{\n.reg .pred p;\n.reg .b64 b;\nsetp.ne.b32 p, %38, 0;\nmov.b64 b, {%36, %37};\n"
        "wgmma.mma_async.sync.aligned.m64n64k16.f32.bf16.bf16 {%0,%1,%2,%3,%4,%5,%6,%7,%8,%9,%10,%11,%12,%13,%14,%15,%16,%17,%18,%19,%20,%21,%22,%23,%24,%25,%26,%27,%28,%29,%30,%31}, {%32,%33,%34,%35}, b, p, 1, 1, 0;\n}\n"
        : "+f"(d[0]), "+f"(d[1]), "+f"(d[2]), "+f"(d[3]), "+f"(d[4]), "+f"(d[5]), "+f"(d[6]), "+f"(d[7]), "+f"(d[8]), "+f"(d[9]), "+f"(d[10]), "+f"(d[11]), "+f"(d[12]), "+f"(d[13]), "+f"(d[14]), "+f"(d[15]), "+f"(d[16]), "+f"(d[17]), "+f"(d[18]), "+f"(d[19]), "+f"(d[20]), "+f"(d[21]), "+f"(d[22]), "+f"(d[23]), "+f"(d[24]), "+f"(d[25]), "+f"(d[26]), "+f"(d[27]), "+f"(d[28]), "+f"(d[29]), "+f"(d[30]), "+f"(d[31])
        : "r"(a[0]), "r"(a[1]), "r"(a[2]), "r"(a[3]), "r"(db), "r"(8u), "r"(acc));
}
template <> __device__ __forceinline__ void cv_mma<5>(float (&d)[64], const uint32_t (&a)[4], uint32_t db, int acc) {
    asm volatile("{\n.reg .pred p;\n.reg .b64 b;\nsetp.ne.b32 p, %30, 0;\nmov.b64 b, {%28, %29};\n"
        "wgmma.mma_async.sync.aligned.m64n48k16.f32.bf16.bf16 {%0,%1,%2,%3,%4,%5,%6,%7,%8,%9,%10,%11,%12,%13,%14,%15,%16,%17,%18,%19,%20,%21,%22,%23}, {%24,%25,%26,%27}, b, p, 1, 1, 0;\n}\n"
        : "+f"(d[0]), "+f"(d[1]), "+f"(d[2]), "+f"(d[3]), "+f"(d[4]), "+f"(d[5]), "+f"(d[6]), "+f"(d[7]), "+f"(d[8]), "+f"(d[9]), "+f"(d[10]), "+f"(d[11]), "+f"(d[12]), "+f"(d[13]), "+f"(d[14]), "+f"(d[15]), "+f"(d[16]), "+f"(d[17]), "+f"(d[18]), "+f"(d[19]), "+f"(d[20]), "+f"(d[21]), "+f"(d[22]), "+f"(d[23])
        : "r"(a[0]), "r"(a[1]), "r"(a[2]), "r"(a[3]), "r"(db), "r"(8u), "r"(acc));
}
template <> __device__ __forceinline__ void cv_mma<6>(float (&d)[64], const uint32_t (&a)[4], uint32_t db, int acc) {
    asm volatile("{\n.reg .pred p;\n.reg .b64 b;\nsetp.ne.b32 p, %22, 0;\nmov.b64 b, {%20, %21};\n"
        "wgmma.mma_async.sync.aligned.m64n32k16.f32.bf16.bf16 {%0,%1,%2,%3,%4,%5,%6,%7,%8,%9,%10,%11,%12,%13,%14,%15}, {%16,%17,%18,%19}, b, p, 1, 1, 0;\n}\n"
        : "+f"(d[0]), "+f"(d[1]), "+f"(d[2]), "+f"(d[3]), "+f"(d[4]), "+f"(d[5]), "+f"(d[6]), "+f"(d[7]), "+f"(d[8]), "+f"(d[9]), "+f"(d[10]), "+f"(d[11]), "+f"(d[12]), "+f"(d[13]), "+f"(d[14]), "+f"(d[15])
        : "r"(a[0]), "r"(a[1]), "r"(a[2]), "r"(a[3]), "r"(db), "r"(8u), "r"(acc));
}
template <> __device__ __forceinline__ void cv_mma<7>(float (&d)[64], const uint32_t (&a)[4], uint32_t db, int acc) {
    asm volatile("{\n.reg .pred p;\n.reg .b64 b;\nsetp.ne.b32 p, %14, 0;\nmov.b64 b, {%12, %13};\n"
        "wgmma.mma_async.sync.aligned.m64n16k16.f32.bf16.bf16 {%0,%1,%2,%3,%4,%5,%6,%7}, {%8,%9,%10,%11}, b, p, 1, 1, 0;\n}\n"
        : "+f"(d[0]), "+f"(d[1]), "+f"(d[2]), "+f"(d[3]), "+f"(d[4]), "+f"(d[5]), "+f"(d[6]), "+f"(d[7])
        : "r"(a[0]), "r"(a[1]), "r"(a[2]), "r"(a[3]), "r"(db), "r"(8u), "r"(acc));
}
__device__ __forceinline__ void stsm4t(uint32_t addr, uint32_t r0, uint32_t r1, uint32_t r2, uint32_t r3) {
    asm volatile("stmatrix.sync.aligned.m8n8.x4.trans.shared.b16 [%0], {%1,%2,%3,%4};" ::"r"(addr), "r"(r0), "r"(r1), "r"(r2), "r"(r3) : "memory");
}
__device__ __forceinline__ void cp16(uint32_t dst, const void* src, int n = 16) {
    asm volatile("cp.async.cg.shared.global.L2::128B [%0], [%1], 16, %2;" ::"r"(dst), "l"(src), "r"(n) : "memory");
}
__device__ __forceinline__ void cp_arrive(uint32_t bar) { asm volatile("cp.async.mbarrier.arrive.noinc.shared::cta.b64 [%0];" ::"r"(bar) : "memory"); }
__device__ __forceinline__ void lds64(uint32_t& x, uint32_t& y, uint32_t a) { asm volatile("ld.shared.v2.b32 {%0,%1}, [%2];" : "=r"(x), "=r"(y) : "r"(a) : "memory"); }
__device__ __forceinline__ void sts128(uint32_t a, uint32_t x, uint32_t y, uint32_t z, uint32_t w) {
    asm volatile("st.shared.v4.b32 [%0], {%1,%2,%3,%4};" ::"r"(a), "r"(x), "r"(y), "r"(z), "r"(w) : "memory");
}
__device__ __forceinline__ uint32_t bfma2(uint32_t a, uint32_t b, uint32_t c) {
    uint32_t r;
    asm("fma.rn.bf16x2 %0, %1, %2, %3;" : "=r"(r) : "r"(a), "r"(b), "r"(c));
    return r;
}
#define CV_NS 4
#define CV_W 1
constexpr int CV_GC = 8 / CV_NS, CV_NA = (CV_W + 2) * CV_NS;
struct CvAddr { uint32_t pa[2], p0[4], db, rdy, xw, xr, bar; bool wrap, neg[2]; };
template <int G> __device__ __forceinline__ void cv_load(uint32_t (&a)[CV_NA][4], const CvAddr& p) {
    if constexpr (G % CV_GC == 0) mbar_wait(p.rdy + 8 * (G / CV_GC), 0);
#pragma unroll
    for (int i = G * CV_NS; i < (G + 1) * CV_NS; i++) {
        const int of = (i / 2 % 2) * CV_QG + (i / 8) * CV_SL + 256 * (i % 2 + (i / 2 & 2));
        if ((i & 5) == 0) {
#pragma unroll
            for (int e = 0; e < 4; e++) asm volatile("ld.shared.b32 %0, [%1];" : "=r"(a[i % CV_NA][e]) : "r"(p.p0[e] + of) : "memory");
            if (i < 8) { if (p.neg[0]) a[i % CV_NA][0] = 0; if (p.neg[1]) a[i % CV_NA][2] = 0; }
        } else {
            lds64(a[i % CV_NA][0], a[i % CV_NA][1], p.pa[0] + of - 256);
            lds64(a[i % CV_NA][2], a[i % CV_NA][3], p.pa[1] + of - 256);
        }
    }
}
__device__ __forceinline__ float vadd(float a, float b) {
    float r;
    asm volatile("add.f32 %0, %1, %2;" : "=f"(r) : "f"(a), "f"(b));
    return r;
}
template <int K> __device__ __forceinline__ uint32_t cv_tail(float (&d)[64], bool wrap) {
    float* z = d + 56 - 8 * K;
    z[4] = vadd(z[4], K > 0 ? z[10] : 0.f);
    if constexpr (K > 0) z[5] = vadd(z[5], z[11]);
    z[0] = vadd(z[0], z[6]);
    z[1] = vadd(z[1], z[7]);
    return pack2(wrap ? (K > 0 ? z[8] : 0.f) : z[4], wrap ? z[4] : z[0]);
}
template <int K> __device__ __forceinline__ uint32_t cv_fin(const float (&d)[64], uint32_t x) { return pack2(d[61 - 8 * K] + lo2f(x), d[57 - 8 * K] + hi2f(x)); }
template <int G>
__device__ __forceinline__ void cv_steps(float (&d)[2][64], uint32_t (&a)[CV_NA][4], uint32_t (&tv)[2][8], const CvAddr& p) {
    constexpr int K = G / CV_GC, GN = 8 * CV_GC;
    constexpr int T = G - CV_W - CV_GC, F = T - 1, TK = T / CV_GC, FK = F / CV_GC;
    if constexpr (G == 0) cv_load<0>(a, p);
    if constexpr (G < GN) {
        wgmma_fence();
#pragma unroll
        for (int i = G * CV_NS; i < (G + 1) * CV_NS; i++)
            cv_mma<K>(d[i / 2 % 2], a[i % CV_NA], p.db + (i / 2 % 2) * (CV_HPL / 8) + 16 * K + 2 * (i % 2 + (i / 2 & 2)), i & ~2 ? 1 : p.bar >> 8);
        wgmma_commit();
    }
    if constexpr (G < GN - 1) cv_load<G + 1>(a, p);
    if constexpr (T >= 0 && T % CV_GC == 0) {
        tv[0][TK] = cv_tail<TK>(d[0], p.wrap);
        tv[1][TK] = cv_tail<TK>(d[1], p.wrap);
        if constexpr (TK & 1) sts128(p.xw + TK / 2 * 512, tv[0][TK - 1], tv[0][TK], tv[1][TK - 1], tv[1][TK]);
    }
    if constexpr (F >= 0 && F % (2 * CV_GC) == CV_GC) {
        const uint4 x = lds128(p.xr + FK / 2 * 512);
        tv[0][FK - 1] = cv_fin<FK - 1>(d[0], x.x); tv[0][FK] = cv_fin<FK>(d[0], x.y);
        tv[1][FK - 1] = cv_fin<FK - 1>(d[1], x.z); tv[1][FK] = cv_fin<FK>(d[1], x.w);
    }
    if constexpr (G < GN - 1) wgmma_wait<CV_W>();
    if constexpr (G == GN - 1) wgmma_wait<0>();
    if constexpr (T >= 0 && T % (2 * CV_GC) == CV_GC) named_bar_sync(p.bar, 128);
    if constexpr (F < GN - CV_GC) cv_steps<G + 1>(d, a, tv, p);
}

#define CV_PF 7
#define Y_FIRST 1
#define Y_HOLD 0
#define PS2_EARLY 1
#define PS1_EARLY 1
#define FMOVE 1
#define SENDC 1
#define HDELAY 0
#define NH16 1
#define GST 23
#define GS2 1
#define H11 0
#define X1AT 2
#define X1B 0
#define NOF 0
#define FD 0
#define FD3 FD
#define SD3 0
#define REL 3
#define W3_AT -1
constexpr int SPL2 = SPL & ~GST;
struct MegaMaps {
    CUtensorMap q, act;
    CUtensorMap a64, w1, w2, w3, w4;
    CUtensorMap k, v, y;
};

__global__ void __cluster_dims__(2, 1, 1) __launch_bounds__(384, 1)
mega_kernel(const __grid_constant__ MegaMaps tm, bf16* __restrict__ outp, bf16* act, const bf16* __restrict__ w1p, const bf16* __restrict__ w2p,
            const bf16* __restrict__ w3p, const bf16* __restrict__ xq, const bf16* __restrict__ kp, const bf16* __restrict__ vp,
            const bf16* __restrict__ shk, const bf16* __restrict__ ssk, const bf16* __restrict__ ssD) {
    extern __shared__ __align__(1024) uint8_t sgen[];
    const uint32_t sbase = smem_u32(sgen);
    const int warp = __shfl_sync(0xffffffffu, threadIdx.x >> 5, 0), lane = threadIdx.x & 31;
    const int rank = blockIdx.x & 1;
    const uint32_t s_bar = sbase + OFF_BAR;
    const uint32_t f5 = s_bar, e5 = s_bar + 64, f4 = s_bar + 144, e4 = s_bar + 104;
    const uint32_t b_rfull = s_bar + 176, b_role = s_bar + 184, b_stg = s_bar + 136, b_h2 = s_bar + 32;
    const uint32_t s_epi = sbase + OFF_EPI, s_stg = sbase + OFF_STG5, s_r = sbase + OFF_R;
    uint8_t* sm = sgen + CV_0;
    const uint32_t sb = sbase + CV_0;
    const int tid = threadIdx.x, wg = warp >> 2, w = warp & 3;
    const int d0 = blockIdx.x * CV_CH;
    const bool cv = blockIdx.x < D_ / CV_CH;
    const uint32_t b_full = sb + CV_BAR, b_rdy = b_full + 64, b_h = b_full + 128;
    GT(0);
    if (tid == 0) TM(0);
    auto row_at = [&](int r) { return sb + CV_SL + (r < 0 ? -8192 : 0) + ((r & 127) >> 5) * 1024 + (r & 7) * 128 + ((r >> 3) & 3) * 32 + ((r ^ rank) & 1) * 16; };
    auto load_kv = [&](int c) {
#pragma unroll
        for (int i = 0; i < 2; i++)
            asm volatile("cp.async.bulk.tensor.4d.shared::cluster.global.mbarrier::complete_tx::bytes.multicast::cluster [%0], [%1, {%3, %4, %4, %5}], [%2], %6;"
                         ::"r"(sb + (c + 1) * CV_SL + rank * 8192 + i * 4096), "l"((uint64_t)(i ? &tm.v : &tm.k)), "r"(b_full + 8 * c), "r"(d0 & ~15), "r"(0),
                         "r"(8 * c + 4 * rank), "h"((uint16_t)3) : "memory");
    };
    auto bulk = [&](uint32_t dst, const void* src, uint32_t n, uint32_t bar) {
        asm volatile("cp.async.bulk.shared::cluster.global.mbarrier::complete_tx::bytes [%0], [%1], %2, [%3];" ::"r"(dst), "l"(src), "r"(n), "r"(bar) : "memory");
    };
    auto put_h = [&](int ch) {
        const uint32_t dk = (tid & 127) ? 0 : *reinterpret_cast<const volatile uint32_t*>(sm + CV_BAR + 160 + 16 * wg + 2 * ch);
        uint4 v[4];
#pragma unroll
        for (int i = 0; i < 4; i++) v[i] = lds128(sbase + ch * 4096 + i * 2048 + (tid & 127) * 16);
        v[0].x = pack2(lo2f(v[0].x) + lo2f(dk), hi2f(v[0].x));
        v[2].x = pack2(lo2f(v[2].x) + hi2f(dk), hi2f(v[2].x));
#pragma unroll
        for (int i = 0; i < 4; i++)
            sts128(sb + CV_H + (2 * ch + (i & 2) + (tid & 1)) * CV_HPL + (127 - ((tid & 127) >> 1)) * 16 - (i & 1) * 1024, v[i].x, v[i].y, v[i].z, v[i].w);
    };
    int bi, bj, m0, tb;
    uint32_t ep;
    auto get_role = [&]() {
        mbar_wait(b_role, 0);
        int role;
        asm volatile("ld.shared.v2.b32 {%0,%1}, [%2];" : "=r"(role), "=r"(ep) : "r"(s_bar + 248) : "memory");
        bi = (role >> 3) * 2 + rank; bj = role & 7; m0 = bi * BM; tb = (role >> 3) * 2048 + rank * 128;
        return role < 64;
    };

    if (warp >= 8) {
        asm volatile("setmaxnreg.dec.sync.aligned.u32 88;");
        cluster_arrive_relaxed();
        if (!cv) cluster_wait(); else {
            const int bt = tid - 256, g = lane >> 2, t = lane & 3;
            if (bt < 16) sts128(row_at((bt & 7) - 8) + (bt >> 3) * 4096, 0, 0, 0, 0);
#pragma unroll
            for (int i = 0; i < 4; i++)
                cp16(row_at(bt) + i * 4096, (i & 1 ? vp : kp) + (size_t)(bt + (i >> 1) * 128) * D_ + d0);
            DBG_S(16 + (3));
            uint2 wa;
            asm volatile("ld.global.nc.v2.b32 {%0,%1}, [%2];" : "=r"(wa.x), "=r"(wa.y) : "l"(shk + (d0 + g) * 4));
            const int mi = lane >> 3, r0 = 32 * w + 8 * ((lane >> 1) & 3) - (lane & 1);
            const uint32_t ka0 = row_at(r0 + 2 * mi - 3), ka1 = row_at(r0 + 2 * (mi & 1) + 5) + (mi >> 1) * 8192;
            const uint32_t va0 = row_at(r0 + 2 * mi + 1) + 4096, va1 = row_at(r0 - 1) + 4096 + (mi & 1) * 8192;
            const uint32_t qd = sb + g * CV_QG + (32 * w + 8 * t) * 8, qd0 = qd + (t & 2) * 16, qd1 = qd + (~t & 2) * 16;
            const uint32_t w0 = __byte_perm(wa.x, 0, 0x1010), w1 = __byte_perm(wa.x, 0, 0x3232), w2 = __byte_perm(wa.y, 0, 0x1010), w3 = __byte_perm(wa.y, 0, 0x3232);
            cluster_wait();
            DBG_S(16 + (5));
            asm volatile("cp.async.wait_all;" ::: "memory");
            named_bar_sync(7, 128);
            DBG_S(16 + (1));
            struct KV { uint32_t k[2][6], v[2][5]; };
            auto get = [&](KV& x, uint32_t so) {
                ldsm4t(x.k[0][0], x.k[0][1], x.k[0][2], x.k[0][3], ka0 + so);
                ldsm4t(x.k[0][4], x.k[0][5], x.k[1][4], x.k[1][5], ka1 + so);
                ldsm4t(x.k[1][0], x.k[1][1], x.k[1][2], x.k[1][3], ka0 + so + 8192);
                asm volatile("ldmatrix.sync.aligned.m8n8.x2.trans.shared.b16 {%0,%1}, [%2];" : "=r"(x.v[0][0]), "=r"(x.v[1][0]) : "r"(va1 + so));
                ldsm4t(x.v[0][1], x.v[0][2], x.v[0][3], x.v[0][4], va0 + so);
                ldsm4t(x.v[1][1], x.v[1][2], x.v[1][3], x.v[1][4], va0 + so + 8192);
            };
            auto build = [&](int c, const KV& x, KV& nx) {
                const uint32_t so = c * CV_SL;
                DBG_F(1);
                uint32_t early;
                asm volatile("{\n.reg .pred p;\nmbarrier.test_wait.parity.shared::cta.b64 p, [%1], 0;\nvote.sync.all.pred p, p, -1;\nselp.u32 %0, 1, 0, p;\n}"
                             : "=r"(early) : "r"(b_full + 8 * (c < 7 ? c + 1 : c)) : "memory");
                if (early) get(nx, so + CV_SL);
                DBG_F(2);
                uint32_t p[8][2];
#pragma unroll
                for (int sg = 0; sg < 2; sg++) {
                    uint32_t u[5], ke[6];
#pragma unroll
                    for (int i = 0; i < 6; i++) ke[i] = __byte_perm(x.k[sg][i], x.k[sg][i ? i - 1 : 0], 0x5432);
#pragma unroll
                    for (int i = 0; i < 5; i++) {
                        u[i] = bmul2(bfma2(x.k[sg][i + 1], w0, bfma2(ke[i + 1], w1, bfma2(x.k[sg][i], w2, bmul2(ke[i], w3)))), x.v[sg][i]);
                        if (i) { p[2 * i - 1][sg] = u[i]; p[2 * i - 2][sg] = __byte_perm(u[i], u[i - 1], 0x5432); }
                    }
                }
                DBG_F(3);
#pragma unroll
                for (int j = 0; j < 4; j++) sts128((j & 2 ? qd1 : qd0) + so + 16 * (j & 1), p[2 * j][0], p[2 * j][1], p[2 * j + 1][0], p[2 * j + 1][1]);
                __syncwarp();
                DBG_F(4);
                if (lane == 0) {
                    mbar_arrive(b_rdy + 8 * c);
                    if (c == w) {
                        if (c < 3) load_kv(c + 5);
                        else { bulk(sbase + 16384, ssk + (size_t)(d0 + 4) * S_, 16384, b_h + 16); bulk(b_full + 192, ssD + d0, 16, b_h + 16); }
                    }
                    if (c == w + 4 && (CV_PF >> w & 1)) {
                        const uint32_t n = w == 0 ? 32768 : w == 3 ? 57344 : 16384;
                        const char* src = reinterpret_cast<const char*>(w == 0 ? xq : w == 1 ? w1p : w == 2 ? w2p : w3p) + (size_t)blockIdx.x * n;
                        asm volatile("cp.async.bulk.prefetch.L2.global [%0], %1;" ::"l"(src), "r"(n) : "memory");
                    }
                }
                DBG_F(5);
                named_bar_sync(7, 128);
                DBG_F(6);
                DBG_S(16 + (c == 0 ? 4 : 5 + c));
                if (!early) { mbar_wait(b_full + 8 * c + 8, 0); get(nx, so + CV_SL); }
                DBG_F(7);
            };
            KV x0, x1;
            get(x0, 0);
#pragma unroll 1
            for (int c = 0; c < 8; c += 2) { build(c, x0, x1); build(c + 1, x1, x0); }
            mbar_wait(b_h + 16, 0);
            put_h(4); put_h(6);
            fence_async_smem();
            __syncwarp();
            if (lane == 0) mbar_arrive(b_full);
            named_bar_sync(7, 128);
            DBG_S(16 + (13));
        }
    } else {
        if (elect_one()) {
            mbar_init(b_full + 8 * warp, warp ? 1 : 4);
            mbar_init(b_rdy + 8 * warp, 4);
            if (warp) mbar_expect_tx(b_full + 8 * warp, 16384);
            if (w == 0 && cv) {
                mbar_init(b_h + 8 * wg, 1);
                mbar_expect_tx(b_h + 8 * wg, 8192 + 16);
                fence_async_smem();
                bulk(sbase + wg * 8192, ssk + (size_t)(d0 + 2 * wg) * S_, 8192, b_h + 8 * wg);
                bulk(b_full + 160 + 16 * wg, ssD + d0, 16, b_h + 8 * wg);
            }
            mbar_init(s_bar + 8 * warp, 1);
            mbar_init(s_bar + 64 + 8 * warp, 4);
            mbar_init(s_bar + 128 + 8 * warp, warp < 2 ? 4 << warp : warp == 6 ? 2 : 1);
            if (wg) mbar_init(s_bar + 160 + 8 * warp, 8);
            if (warp == 0) mbar_arrive(f5);
            if (warp == 7) mbar_expect_tx(b_role, 8);
            if (warp == 1) { mbar_init(b_h + 16, 1); mbar_expect_tx(b_h + 16, 16384 + 16); }
            if (w == 2) sts128(s_bar + 224 + 16 * wg, 0, 0, 0, 0);
            asm volatile("fence.mbarrier_init.release.cluster;" ::: "memory");
            if (warp == 2) { prefetch_tmap(&tm.k); prefetch_tmap(&tm.v); }
        }
        __syncwarp();
        DBG_W(1);
        cluster_arrive_relaxed();
        asm volatile("setmaxnreg.inc.sync.aligned.u32 208;");
        DBG_W(2);
        const int zi = (tid & 127) - 32;
        if (zi >= 0 && zi < 48) sts128(sb + CV_H + (4 * wg + (zi / 6 & 3) + (zi / 24) * 8) * CV_HPL + 2048 + (zi % 6) * 16, 0, 0, 0, 0);
        DBG_W(3);
        cluster_wait();
        DBG_W(5);
        if (cv) {
            if (tid == 32) {
#pragma unroll 1
                for (int c = 1; c < 5; c++) load_kv(c);
                prefetch_tmap(&tm.y);
            }
            __syncwarp();
            DBG_W(6);
            const int g = lane >> 2, t = lane & 3;
            const int x0 = 32 + 8 * w + g - 2 * t;
            CvAddr p;
            p.rdy = b_rdy;
            p.bar = 1 + wg;
            p.xr = sbase + (warp ^ 2) * 2048 + lane * 16;
            p.xw = sbase + warp * 2048 + (g * 4 + ((t - (w >> 1)) & 3)) * 16;
            p.wrap = t == 0 && w >= 2;
            mbar_wait(b_h + 8 * wg, 0);
            DBG_W(4);
            put_h(2 * wg);
            fence_async_smem();
            named_bar_sync(1 + wg, 128);
            float acc[2][64];
            zero_acc(acc[0]); zero_acc(acc[1]);
#pragma unroll 1
            for (int round = 0; round < 2; round++) {
                const int ch = round * 4 + 2 * wg;
                uint32_t a[CV_NA][4], tv[2][8];
#pragma unroll
                for (int e = 0; e < 2; e++) {
                    const int x = x0 - 8 * e;
                    p.neg[e] = x < 32;
                    p.pa[e] = sb + ch * CV_QG + 8 * (x ^ (x >> 2 & 4));
                    p.p0[2 * e] = p.pa[e] + (x < 32 ? 768 + 4 - CV_SL : -256);
                    p.p0[2 * e + 1] = p.pa[e] + (x < 32 ? 768 : -256 + 4);
                }
                p.db = (((sb + CV_H + ch * 2 * CV_HPL) & 0x3FFFF) >> 4) | ((CV_HPL / 16) << 16);
                if (round) mbar_wait(b_full, 0);
                DBG_S(7 + 3 * round);
                cv_steps<0>(acc, a, tv, p);
                DBG_S(8 + 3 * round);
                const int r128 = 4 * (lane >> 3) + 2 * (lane & 1) + ((~lane >> 2) & 1);
#pragma unroll
                for (int i = 0; i < 2; i++) {
                    const uint32_t ta = sb + ((ch + i + 1) & 7) * CV_SL + 12288 + r128 * 128 + ((((~lane & 2) * 2 + w) ^ (r128 & 7)) << 4);
                    stsm4t(ta, tv[i][0], tv[i][1], tv[i][2], tv[i][3]);
                    stsm4t(ta + 2048, tv[i][4], tv[i][5], tv[i][6], tv[i][7]);
                }
                if (!(GST & 2)) fence_async_smem();
                named_bar_sync(1 + wg, 128);
                if (GST & 2) {
                    const int l = 4 * w + (lane >> 3);
                    uint4 v[4];
#pragma unroll
                    for (int i = 0; i < 4; i++) v[i] = lds128(sb + ((ch + (i >> 1) + 1) & 7) * CV_SL + 12288 + (i & 1) * 2048 + l * 128 + (((lane ^ l) & 7) << 4));
                    bf16* gy = act + (size_t)(R_Y + w * 2048 + ((d0 + ch) & 255)) * D_ + (d0 & ~255) + lane * 8;
#pragma unroll
                    for (int i = 0; i < 4; i++) stg128(gy + ((i & 1) * 8192 + (i >> 1)) * D_, v[i]);
                } else if ((tid & 127) < 2) {
                    const int d = d0 + ch + (tid & 1);
                    asm volatile("cp.async.bulk.tensor.4d.global.shared::cta.bulk_group [%0, {%2, %3, %4, %2}], [%1];"
                                 ::"l"((uint64_t)&tm.y), "r"(sb + ((ch + (tid & 1) + 1) & 7) * CV_SL + 12288), "r"(0), "r"(4 * (d >> 8)), "r"(d & 255) : "memory");
                    asm volatile("cp.async.bulk.commit_group;" ::: "memory");
                }
                __syncwarp();
                DBG_S(9 + 3 * round);
            }
        }
    }
    int warp2 = warp;
    asm volatile("" : "+r"(warp2));
    if (warp2 >= 8) {
        asm volatile("setmaxnreg.dec.sync.aligned.u32 72;");
        if (warp == 8) { if (elect_one()) {
            if (rank == 0) {
                uint32_t smid;
                asm volatile("mov.u32 %0, %%smid;" : "=r"(smid));
                const int t = smid >> 1;
                int team = t < 32 ? t & 7 : t < 60 ? 1 + (t - 32) % 7 : t < 62 ? t - 54 : 0;
                const unsigned long long arr = atomicAdd(reinterpret_cast<unsigned long long*>(g_ticket + 16 * FL_PITCH), 1ull);
                const uint32_t e1 = (uint32_t)(arr / NCL) + 1;
                unsigned int* tk = g_ticket + (e1 & 1) * 8 * FL_PITCH;
                int slot = atomicAdd(tk + team * FL_PITCH, 1u);
                atomicAdd(g_ticket + 17 * FL_PITCH, 1u);
                if (blockIdx.x < 16) g_ticket[((~e1 & 1) * 8 + (blockIdx.x >> 1)) * FL_PITCH] = 0;
                if (slot >= 8) {
                    const long long t0 = clock64();
                    while ((int)(*(volatile unsigned int*)(g_ticket + 17 * FL_PITCH) - e1 * NCL) < 0 && clock64() - t0 < 100000) {}
                    for (team = 0; team < 8; team++)
                        if ((slot = atomicAdd(tk + team * FL_PITCH, 1u)) < 8) break;
                }
#pragma unroll
                for (int i = 0; i < 2; i++)
                    asm volatile("st.async.weak.shared::cluster.mbarrier::complete_tx::bytes.v2.b32 [%0], {%1, %2}, [%3];"
                                 ::"r"(mapa_u32(s_bar + 248, i)), "r"(team * 8 + slot), "r"(e1), "r"(mapa_u32(b_role, i)) : "memory");
            }
            if (get_role()) {
            TM(2);
            mbar_expect_tx(b_rfull, 32768);
            tma_load_2d(sbase + 16384, &tm.q, b_rfull, bj * 128, m0);
            tma_load_2d(sb + 8 * CV_SL, &tm.q, b_rfull, bj * 128 + 64, m0);
            int s5 = 0, s4 = 0;
            uint32_t p5 = 0, p4 = 1;
            auto putB = [&](const CUtensorMap* tB, int kc, uint32_t bytes) {
                const uint32_t full = f5 + 8 * s5;
                mbar_wait(full + 64, (p5 >> s5) & 1);
                mbar_expect_tx(full, bytes);
                tma_load_2d_mc(s_r + 16384 + rank * 8192 + s5 * R5_STAGE, tB, full, bj * 128 + rank * 64, kc);
                p5 ^= 1u << s5;
            };
            auto putA = [&](int c, int r) {
                tma_load_2d(s_r + s5 * R5_STAGE, &tm.act, f5 + 8 * s5, c, r);
                if (++s5 == R5_N) s5 = 0;
            };
            prefetch_tmap(&tm.act); prefetch_tmap(&tm.w1); prefetch_tmap(&tm.w2); prefetch_tmap(&tm.w3); prefetch_tmap(&tm.w4); prefetch_tmap(&tm.a64);
            auto own_first = [&](int it) {
                const int hf = it >= 9, c = it - 2 - 7 * hf;
                return (it < 2 ? 2 * bj + it : 2 * (c + (c >= bj)) + hf) * BK;
            };
            const unsigned int n8 = 8 * ep, nh = NH16 ? ((bi == 0 || bi == 15) ? 12 * ep : 2 * n8) : (bi == 0 || bi == 15) ? 2 * n8 : 3 * n8;
#pragma unroll 1
            for (int layer = 0; layer < 2; layer++) {
                s5 = 2;
#pragma unroll 1
                for (int kk = -(layer | Y_FIRST); kk < 5 - (layer | Y_FIRST); kk++) {
                    if (kk & 4) {
                        if (layer == 0) { TM(1); wait_flag(flag_ptr(0, FL_CS, 8 + bj), 8 * n8); TM(4); fence_proxy_async(); }
                        mbar_wait(e5 + 8, (p5 >> 1) & 1);
                        mbar_expect_tx(f5 + 8, 32768);
                        tma_load_2d(s_r + R5_STAGE, &tm.act, f5 + 8, (bj >> 1) * 256 + rank * 128, R_Y + (tb & ~255) + (bj & 1) * 128);
                        tma_load_2d(s_r + R5_STAGE + 16384, &tm.act, f5 + 8, (bj >> 1) * 256 + rank * 128 + 64, R_Y + (tb & ~255) + (bj & 1) * 128);
                        p5 ^= 2;
                        if (layer == 0) TM(5);
                    } else {
                        if (kk == Y_HOLD && layer == 0) mbar_wait(f5 + 8, 0);
                        putB(&tm.w1, own_first(kk), kk < 2 ? 16384 : R5_STAGE);
                        if (++s5 == R5_N) s5 = 0;
                    }
                }
                s5 = 4;
#pragma unroll 1
                for (int kk = 2; kk < 16; kk++) {
                    const int kc = own_first(kk);
                    if (kk >= 4) putB(&tm.w1, kc, R5_STAGE);
                    if (kk == 2 || kk == 9) {
                        wait_flag(flag_ptr(layer, FL_XA + (kk & 1), bi), n8);
                        if (layer == 0 && kk == 2) TM(14);
                        DP(8 * (FL_XA + (kk & 1)) + 3);
                        fence_proxy_async();
                        DP(8 * (FL_XA + (kk & 1)) + 4);
                    }
                    putA(kc, R_XA + tb);
                }
                mbar_wait(e5 + 24, (p5 >> 3) & 1);
                mbar_arrive(f5 + 24);
                p5 ^= 8;
                s5 = 4;
#pragma unroll 1
                for (int kk = 0; kk < 5; kk++) { putB(&tm.w2, own_first(kk), kk < 2 ? 16384 : R5_STAGE); if (++s5 == R5_N) s5 = 0; }
                s5 = 1;
#pragma unroll 1
                for (int kk = 2; kk < 16; kk++) {
                    const int kc = own_first(kk);
                    if (kk >= 5) putB(&tm.w2, kc, R5_STAGE);
                    if (kk == 2 || kk == 9) {
                        wait_flag(flag_ptr(layer, FL_H + (kk & 1), bi), nh);
                        DP(8 * (FL_H + (kk & 1)) + 3);
                        fence_proxy_async();
                        DP(8 * (FL_H + (kk & 1)) + 4);
                    }
                    putA(kc, R_H + layer * R_HP + m0 + (int)((0x4031u >> (kc >> 6 & 12)) & 7) - 2);
                }
#pragma unroll 1
                for (int it = 0; it < 32; it++) {
                    const int kc = it >= 16 ? (it - 16) * BK : own_first(it);
                    const int nb = it < 16 ? 4 : 3, n0 = bj * 448 + (it < 16 ? 0 : 256);
                    if (it > 0 && it < 4) {
                        const int i = (it - 1) * 3 >> 1;
                        mbar_wait(e5 + 8 * i, (p5 >> i) & 1);
                        mbar_wait(e5 + 8 * i + 8, (p5 >> (i + 1)) & 1);
                    }
                    mbar_wait(e4 + 8 * s4, p4);
                    if (it >= 16 && it < 19) mbar_wait(e4 + 8 * s4 + 8, p4);
                    uint32_t sa = s_r + s4 * (it < 16 ? R4_STAGE : R4B_STAGE), full = f4 + 8 * s4;
                    mbar_expect_tx(full, (it < 2 ? 0 : 16384) + nb * 8192);
                    if (X1B && it == 2) wait_flag(flag_ptr(layer, FL_X1, bi), X1B == 1 ? n8 : n8 - 8 + X1B);
#pragma unroll 1
                    for (int j = (it ^ rank) & 1; j < nb; j += 2) tma_load_2d_mc(sa + (it < 16 ? -32768 : 16384) + j * 8192, &tm.w3, full, n0 + j * 64, kc);
                    if (it == X1AT || it == 9) {
                        wait_flag(flag_ptr(layer, FL_X1 + (it >> 3), bi), n8);
                        DP(8 * (FL_X1 + (it >> 3)) + 3);
                        fence_proxy_async();
                        DP(8 * (FL_X1 + (it >> 3)) + 4);
                        if (X1AT == 3 && it == 3) tma_load_2d(s_r + 2 * R4_STAGE, &tm.act, f4 + 16, own_first(2), R_X1 + tb);
                    }
                    if (it >= X1AT) tma_load_2d(sa, &tm.act, full, kc, R_X1 + tb);
                    if (it >= PF4A && it < PF4A + PF4N && layer == 0) tma_prefetch_2d(&tm.w4, bj * 128 + rank * 64, (7 * (bi >> 1) + it - PF4A) * BK);
                    if (++s4 == R4_N) { s4 = 0; p4 ^= 1; }
                }
                wait_flag(flag_ptr(layer, FL_H2, bi), n8);
                fence_proxy_async();
                s5 = 0;
#pragma unroll 1
                for (int j = 0; j < 7; j++) {
                    if (j > 0 && (j & 1) == 0) {
                        mbar_wait(b_h2 + 4 * j, layer);
                        fence_proxy_async();
                    }
                    const int ra = R_H2 + (j >> 1) * 256 + tb;
#pragma unroll 1
                    for (int b = 0; b < 8; b++) {
                        if (j == 0 && b < R4_N) mbar_wait(e4 + 8 * b, p4);
                        putB(&tm.w4, (7 * b + j) * BK, R5_STAGE);
                        putA(((j & 1) * 8 + b) * BK, ra);
                    }
                }
            }
        } } } else {
            auto colsum = [&](bool is1, int bi, int bj) {
                const int pitch = is1 ? D_ : F_, c = is1 ? bj * 128 + (lane & 15) * 8 : bj * 448 + min((warp & 2) * 128 + lane * 8, 440);
                const bf16* p = (is1 ? w1p : w3p) + ((bi * 64 + (is1 ? (lane >> 4) * 32 : 0)) * pitch + c);
                float a[8];
#pragma unroll
                for (int i = 0; i < 8; i++) a[i] = 0.f;
#pragma unroll 1
                for (int r0 = is1 ? 32 : XCS; r0 < 64; r0 += 8) {
                    uint4 v[8];
#pragma unroll
                    for (int r = 0; r < 8; r++, p += pitch) v[r] = __ldg(reinterpret_cast<const uint4*>(p));
#pragma unroll
                    for (int r = 0; r < 8; r++) {
                        a[0] += lo2f(v[r].x); a[1] += hi2f(v[r].x); a[2] += lo2f(v[r].y); a[3] += hi2f(v[r].y);
                        a[4] += lo2f(v[r].z); a[5] += hi2f(v[r].z); a[6] += lo2f(v[r].w); a[7] += hi2f(v[r].w);
                    }
                }
                if (is1) {
#pragma unroll
                    for (int i = 0; i < 8; i++) a[i] += __shfl_xor_sync(0xffffffffu, a[i], 16);
                }
                float4* dst = reinterpret_cast<float4*>(g_cpart + bi * (F_ + D_) + (is1 ? F_ : 0) + c);
                dst[0] = make_float4(a[0], a[1], a[2], a[3]);
                dst[1] = make_float4(a[4], a[5], a[6], a[7]);
                asm volatile("fence.release.gpu;" ::: "memory");
                __syncwarp();
                if (lane == 0) asm volatile("red.relaxed.gpu.global.add.u32 [%0], 1;" ::"l"(flag_ptr(!is1, FL_CS, bj)) : "memory");
            };
            if (cv && warp == 10) colsum(true, blockIdx.x >> 3, blockIdx.x & 7);
            if ((GST & 2) && cv && warp == 9) {
                named_bar_sync(12, 288);
                if (lane == 0) {
                    if (!(NOF & 2)) asm volatile("fence.release.gpu;" ::: "memory");
                    asm volatile("red.relaxed.gpu.global.add.u32 [%0], 4;" ::"l"(flag_ptr(0, FL_CS, 8 + (blockIdx.x >> 4))) : "memory");
                }
                __syncwarp();
            }
            auto halo = [&](int layer) {
                const int dn = bj & 2 ? 1 : -1;
                const uint4* gh = g_halo + (layer * 144 + 8 + bi * 8 + bj) * 64 + lane;
                uint4 v[2] = {};
#pragma unroll 1
                for (int n = (bi + dn) & 16 ? 1 << 20 : 0; n < (1 << 20); n++) {
#pragma unroll
                    for (int i = 0; i < 2; i++)
                        asm volatile("{\n.reg .b64 u, v;\nld.relaxed.gpu.global.v2.b64 {u, v}, [%4];\nmov.b64 {%0, %1}, u;\nmov.b64 {%2, %3}, v;\n}"
                                     : "=r"(v[i].x), "=r"(v[i].y), "=r"(v[i].z), "=r"(v[i].w) : "l"(gh + 32 * i) : "memory");
                    if (v[0].y == ep && v[0].w == ep && v[1].y == ep && v[1].w == ep) break;
                }
#pragma unroll
                for (int i = 0; i < 2; i++)
                    asm volatile("st.shared.v2.b32 [%0], {%1, %2};" ::"r"(s_stg + 1024 + i * OFF_EPI + (63 + 65 * dn) * 128 + 8 * lane), "r"(v[i].x), "r"(v[i].z) : "memory");
                fence_async_smem();
                __syncwarp();
                DP(8 * FL_H + 5);
                named_bar_arrive(14, 160);
            };
            float4 keep[2];
            const bool on = get_role();
            if (on && warp == 11) {
                uint4* ps = reinterpret_cast<uint4*>(g_stats + (bi * 8 + bj) * 128) + lane;
                ps[0] = ps[32] = make_uint4(0, 0, 0, 0);
                asm volatile("fence.acq_rel.gpu;" ::: "memory");
                __syncwarp();
                if (lane == 0) mbar_arrive(b_rfull);
            }
#pragma unroll 1
            for (int layer = on ? 0 : 2; layer < 2; layer++) {
                if (warp == 10) {
#pragma unroll 1
                    for (int kind = 0; kind < 6; kind += 2) {
                        const uint32_t src = kind == FL_H ? s_stg + 1024 : s_epi, sd = kind == FL_H ? OFF_EPI : 16384;
                        const int dn = bj & 2 ? 1 : -1;
                        const int r = kind == FL_H ? R_H + layer * R_HP + m0 : (kind == FL_XA ? R_XA : R_X1) + tb;
#pragma unroll 1
                        for (int hf = 0; hf < 2; hf++) {
                            const bool sp = hf == 0 && (SPL2 >> kind & 1);
                            const int lw = kind == FL_H && dn < 0 ? 64 : 0;
                            if (sp) {
                                named_bar_sync(7, 160);
                                if (lane == 0) {
                                    fence_async_smem();
                                    tma_store_2d(&tm.a64, src + lw * 128, bj * 128, r + lw);
                                }
                                __syncwarp();
                            }
                            named_bar_sync(5 + hf, sp ? 160 : 288);
                            DQ(0);
                            if (lane == 0 && !((hf ? GS2 : GST) >> kind & 1)) {
                                if (FMOVE) fence_async_smem();
                                if (SD3 && kind == FL_X1) __nanosleep(SD3);
                                tma_store_2d(sp ? &tm.a64 : &tm.act, src + (sp ? (lw ^ 64) * 128 : hf * sd), bj * 128 + hf * 64, sp ? r + (lw ^ 64) : r);
                                asm volatile("cp.async.bulk.commit_group;" ::: "memory");
                            }
                            __syncwarp();
                            if (!H11 && kind + hf == FL_H + 1) halo(layer);
                            if (lane == 0) {
                                asm volatile("cp.async.bulk.wait_group 0;" ::: "memory");
                                if (FD && hf) __nanosleep(kind == FL_X1 ? FD3 : FD);
                                DQ(1);
                                if (!(NOF >> (hf ? 3 : kind) & 1)) asm volatile("fence.release.gpu;" ::: "memory");
                                DQ(2);
                                unsigned int* fp = flag_ptr(layer, kind + hf, bi);
                                asm volatile("red.relaxed.gpu.global.add.u32 [%0], 1;" ::"l"(fp) : "memory");
                                if (kind == FL_H) {
                                    if (bi > 0 && (!NH16 || dn > 0)) asm volatile("red.relaxed.gpu.global.add.u32 [%0], 1;" ::"l"(fp - FL_PITCH) : "memory");
                                    if (bi < 15 && (!NH16 || dn < 0)) asm volatile("red.relaxed.gpu.global.add.u32 [%0], 1;" ::"l"(fp + FL_PITCH) : "memory");
                                }
                            }
                            __syncwarp();
                        }
                    }
                } else {
                    uint32_t* rs = reinterpret_cast<uint32_t*>(sgen + OFF_RS);
                    float* cs = reinterpret_cast<float*>(sgen + OFF_CS);
#pragma unroll 1
                    for (int which = 0; which < 2; which++) {
                        if (layer < which) {
                            if (warp == 11 && lane == 0) {
                                if (W3_AT == 0 || W3_AT == 1) wait_flag(flag_ptr(0, FL_XA + (W3_AT & 1), bi), 8 * ep);
                                if (W3_AT == 5) mbar_wait(f5 + 8, 0);
                                asm volatile("cp.async.bulk.prefetch.L2.global [%0], %1;" ::"l"(w3p + (bi * 8 + bj) * 28672), "r"(57344) : "memory");
                                if (W3_AT == 2 || W3_AT == 3) wait_flag(flag_ptr(0, FL_XA + (W3_AT & 1), bi), 8 * ep);
                                if (W3_AT == 4) mbar_wait(f5 + 8, 0);
                            }
                            __syncwarp();
                            colsum(false, bi, bj);
                        }
                        if (warp == 11) {
                            if (H11 && which) { named_bar_sync(4, 160); halo(layer); }
                            continue;
                        }
                        if (layer == 0) {
                            if (lane == 0) wait_flag(flag_ptr(which, FL_CS, bj), (16 << which) * ep);
                            __syncwarp();
#pragma unroll 1
                            for (int c = (which ? 384 : 768) + lane * 4; c < 896; c += 128) {
                                const float* cp = g_cpart + (which ? bj * 448 + min(c & 511, 444) : F_ + bj * 128 + lane * 4);
                                float4 a = make_float4(0.f, 0.f, 0.f, 0.f);
#pragma unroll
                                for (int r0 = 0; r0 < 16; r0 += 8) {
                                    float4 v[8];
#pragma unroll
                                    for (int r = 0; r < 8; r++) v[r] = __ldcg(reinterpret_cast<const float4*>(cp + (r0 + r) * (F_ + D_)));
#pragma unroll
                                    for (int r = 0; r < 8; r++) { a.x += v[r].x; a.y += v[r].y; a.z += v[r].z; a.w += v[r].w; }
                                }
                                if (c < 768) *reinterpret_cast<float4*>(cs + min(c & 511, 444)) = a;
                                keep[0] = a;
                            }
                        }
                        if (lane == 0 && (layer | which)) wait_flag(flag_ptr(layer, which == 0 ? FL_XA : FL_X1, bi), 8 * ep);
                        __syncwarp();
                        *reinterpret_cast<float4*>(cs + 256 + lane * 4) = keep[0];
                        { const float4 k0 = keep[0]; keep[0] = keep[1]; keep[1] = k0; }
#pragma unroll 1
                        for (int i = 0; i < 4; i++) {
                            const int r = i * 32 + lane;
                            float mean, var;
                            row_stats(g_stats + (1 + which) * S_ * 8 + bi * 1024 + r, ~layer << 31, mean, var);
                            const uint32_t c0 = pack2(mean, fsqrt(bfr(bfr(var) + 1e-5f)));
                            if (lane < 19 && (layer | which | i) == 0) asm volatile("mbarrier.inval.shared::cta.b64 [%0];" ::"r"(b_full + 8 * lane) : "memory");
                            __syncwarp();
                            rs[r] = c0;
                            const float rd = frcp(hi2f(c0));
                            rs[128 + r] = pack2((mean - lo2f(c0)) * rd, fsqrt(bfr(bfr(var * rd * rd) + 1e-5f)));
                        }
                        __syncwarp();
                        named_bar_arrive(3, 160);
                        named_bar_arrive(11, 160);
                    }
                }
                const uint32_t s_cnt = s_bar + 224;
                auto ticket = [&](uint32_t a) {
                    uint32_t v = 0;
                    if (lane == 0) asm volatile("atom.acq_rel.cta.shared.add.u32 %0, [%1], 1;" : "=r"(v) : "r"(a) : "memory");
                    return v;
                };
                auto next = [&]() {
                    uint32_t v = 0;
                    if (lane == 0) asm volatile("atom.relaxed.cta.shared.add.u32 %0, [%1], 1;" : "=r"(v) : "r"(s_cnt + 16 + 4 * layer) : "memory");
                    return v;
                };
                mbar_wait(b_stg, layer);
                int u = __shfl_sync(0xffffffffu, next(), 0), step = 0;
#pragma unroll 1
                while (true) {
#pragma unroll 1
                    for (; step < 5 && u >= (int)((0x3830201810ull >> (8 * step)) & 255); step++) {
                        if (step == 1) { named_bar_arrive(4, 224); named_bar_arrive(12, 224); continue; }
                        const int part = step ? step - 1 : 0;
                        __syncwarp();
                        if (ticket(s_cnt + 4 * part) == 3 * layer + 2) {
                            asm volatile("fence.release.gpu;" ::: "memory");
                            unsigned int* fp = flag_ptr(layer, FL_H2 + part, bi);
                            asm volatile("red.relaxed.gpu.global.add.u32 [%0], 1;" ::"l"(fp) : "memory");
                            if (part > 0) { wait_flag(fp, 8 * ep); mbar_arrive(b_h2 + 8 * part); }
                        }
                        __syncwarp();
                    }
                    if (u >= 56) break;
                    const uint32_t un = next();
                    const int job = u >> 3, r = (u & 7) * 16 + (lane >> 3);
                    if (job >= 2) mbar_wait(s_bar + 168 + 8 * max(job, 3), layer);
                    const uint32_t sp = sbase + ((job & 2) ? OFF_STG5 : OFF_EPI) + r * 256 + (job & 1) * 128;
                    bf16* gp = act + (size_t)(R_H2 + (job >> 1) * 256 + tb + r) * D_ + ((job & 1) * 8 + bj) * 64 + (lane & 7) * 8;
                    uint4 v[4];
#pragma unroll
                    for (int e = 0; e < 4; e++) v[e] = lds128(sp + e * 1024 + (((lane & 7) ^ ((r + 4 * e) & 7)) << 4));
#pragma unroll
                    for (int e = 0; e < 4; e++) stg128(gp + 4 * e * D_, gelu8h(v[e]));
                    u = __shfl_sync(0xffffffffu, un, 0);
                }
                if (layer == 0 && warp == 11) {
                    const char* ps = reinterpret_cast<const char*>(g_stats + bi * 1024) + lane * 128;
                    const char* py = reinterpret_cast<const char*>(act + (size_t)(R_Y + (tb & ~255) + (bj & 1) * 128 + (lane >> 1)) * D_ + (bj >> 1) * 256 + rank * 128) + (lane & 1) * 128;
#pragma unroll 1
                    for (int i = 0; i < 8; i++) {
                        asm volatile("prefetch.global.L2 [%0];" ::"l"(py + (size_t)i * 16 * D_ * 2) : "memory");
                        if (i >= 6) asm volatile("prefetch.global.L2 [%0];" ::"l"(ps + (i & 1) * 4096) : "memory");
                        __nanosleep(400);
                    }
                }
            }
        }
        __syncwarp();
        asm volatile("barrier.cluster.arrive.relaxed.aligned;\nbarrier.cluster.wait.acquire.aligned; // helpers" ::: "memory");
    } else {
        DT_DECL;
        DT(0);
        auto put_y = [&]() {
            if (GST & 2) { if (cv) named_bar_arrive(12, 288); }
            else if ((tid & 127) < 2 && cv) {
                asm volatile("cp.async.bulk.wait_group 0;" ::: "memory");
                if (REL & 2) asm volatile("fence.release.gpu;" ::: "memory");
                asm volatile("red.relaxed.gpu.global.add.u32 [%0], 1;" ::"l"(flag_ptr(0, FL_CS, 8 + (blockIdx.x >> 4))) : "memory");
            }
            __syncwarp();
        };
        put_y();
        DT(24);
        asm volatile("setmaxnreg.inc.sync.aligned.u32 216;");
        if (get_role()) {
        const bool rel_on = (tid & 95) == 0;
        const uint32_t rel5 = mapa_u32(e5, (warp & 1) ^ rank), rel4 = rel5 + (e4 - e5);
        const uint32_t da0 = desc_a(s_r + wg * 8192), db0 = desc_b(s_r + BM * BK * 2), dae = da0 + (OFF_EPI - OFF_R) / 16, db4 = db0 - 49152 / 16;
        auto skip5 = [&](RingState& rs) {
            if (rel_on) mbar_arrive_cluster(rel5 + 8 * rs.st);
            rs.st++;
        };
        const int t = lane & 3;
        const int row = warp * 16 + (lane >> 2);
        const uint32_t st_w = (uint32_t)((warp * 16 + ((lane >> 3) & 1) * 8 + (lane & 7)) * 256 + (((lane >> 4) ^ (lane & 7)) << 4));
        const uint32_t fr = (uint32_t)((warp * 16 + ((lane >> 3) & 1) * 8 + (lane & 7)) * 128 + (((lane >> 4) ^ (lane & 7)) << 4));
        auto copy_out = [&](bf16* dst, uint32_t src) {
            const int r = warp * 16 + (lane >> 4);
            bf16* ox = dst + (size_t)(m0 + r) * D_ + bj * 128 + (lane & 15) * 8;
            const uint32_t ra = src + ((lane & 15) >> 3) * 16384 + r * 128;
            uint4 v[8];
#pragma unroll
            for (int it = 0; it < 8; it++) v[it] = lds128(ra + it * 256 + (((lane & 7) ^ ((2 * it + (lane >> 4)) & 7)) << 4));
#pragma unroll
            for (int it = 0; it < 8; it++) *reinterpret_cast<uint4*>(ox + (size_t)it * 2 * D_) = v[it];
        };
        auto put_half = [&](uint32_t src, int r0, int hf) {
            const int r = warp * 16 + (lane >> 3);
            bf16* gp = act + (size_t)(r0 + r) * D_ + bj * 128 + hf * 64 + (lane & 7) * 8;
            uint4 v[4];
            __syncwarp();
#pragma unroll
            for (int i = 0; i < 4; i++) v[i] = lds128(src + (r + 4 * i) * 128 + (((lane ^ (r + 4 * i)) & 7) << 4));
#pragma unroll
            for (int i = 0; i < 4; i++) stg128(gp + 4 * i * D_, v[i]);
        };
        auto put_stats = [&](const uint32_t (&w)[32], int which, int layer) {
            float c[6][4];
#pragma unroll
            for (int e = 0; e < 32; e++) {
                hmma8(c[e & 3], w[e & ~1], w[e | 1], w[e], e < 4);
                if ((e & 3) == 0) hmma(c[4 + (e >> 2 & 1)], w[e], w[e + 1], w[e + 2], w[e + 3], 0x3f803f80u, 0x3f803f80u, e < 8);
            }
            if (t == lane >> 3) {
#pragma unroll
                for (int e = 0; e < 2; e++) {
                    const float q1 = lane & 4 ? c[e][2 * e + 1] + c[e + 2][2 * e + 1] : c[e][2 * e] + c[e + 2][2 * e], s1 = c[4][2 * e] + c[5][2 * e], mu = s1 * (1.0f / 128);
                    asm volatile("{\n.reg .b64 t;\nmov.b64 t, {%1, %2};\nst.relaxed.gpu.global.b64 [%0], t;\n}"
                                 ::"l"(g_stats + which * S_ * 8 + (bi * 8 + bj) * 128 + row + 8 * e), "f"(mu), "r"(__float_as_uint(fmaxf(q1 - s1 * mu, 0.f)) | ~layer << 31) : "memory");
                }
            }
        };
        auto split = [](float r) { const float h = bfr(r); return pack2(h, r - h); };
        auto norm2 = [](uint32_t x, uint32_t m, uint32_t r) {
            const uint32_t d = bsub2(x, m);
            return bfma2(d, __byte_perm(r, 0, 0x1010), bmul2(d, __byte_perm(r, 0, 0x3232)));
        };
        const float* csp = reinterpret_cast<const float*>(sgen + OFF_CS) + 2 * t;
        float mrow[2], rrow[2];
        const uint32_t* rsp = reinterpret_cast<const uint32_t*>(sgen + OFF_RS) + row;
        auto row_consts = [&](bool twice) {
#pragma unroll
            for (int e = 0; e < 2; e++) {
                const uint32_t q0 = rsp[8 * e], q1 = rsp[128 + 8 * e];
                mrow[e] = twice ? fmaf(lo2f(q1), hi2f(q0), lo2f(q0)) : lo2f(q0);
                rrow[e] = 0.5f * frcp(twice ? hi2f(q0) * hi2f(q1) : hi2f(q0));
            }
        };
        auto keep_consts = [&](float2 (&cs)[8]) {
#pragma unroll
            for (int e = 0; e < 8; e++) asm volatile("" : "+f"(cs[e].x), "+f"(cs[e].y));
            asm volatile("" : "+f"(mrow[0]), "+f"(mrow[1]), "+f"(rrow[0]), "+f"(rrow[1]));
        };
        RingState r5{1, 0}, r4{0, 0};
        DT(1);
        uint32_t x[32];
        mbar_wait(b_rfull, 0);
#pragma unroll
        for (int jp = 0; jp < 8; jp++) ldsm4(x[4 * jp], x[4 * jp + 1], x[4 * jp + 2], x[4 * jp + 3], sbase + 16384 + (fr ^ ((jp & 3) << 5)) + (jp >> 2) * (16384 + 8 * CV_SL));
#pragma unroll
        for (int e = 0; e < 32; e++) asm volatile("" : "+r"(x[e]));
        named_bar_sync(9 + wg, 128);
        if ((tid & 95) < R5_N) mbar_arrive_cluster(rel5 + 8 * lane);
#pragma unroll 1
        for (int layer = 0; layer < 2; layer++) {
            {
                DT(2 + 24 * layer);
                put_stats(x, 0, layer);
                DT(20 + 24 * layer);
                DT(22 + 24 * layer);
                uint32_t mb[2], rd[2];
                {
                    float mean, var;
                    row_stats(g_stats + bi * 1024 + warp * 16 + (lane & 15), ~layer << 31, mean, var);
                    __syncwarp();
                    const uint32_t r1 = split(frcp(bfr(fsqrt(bfr(bfr(var) + 1e-5f)))));
                    const uint32_t m1 = pack2(mean, mean);
#pragma unroll
                    for (int e = 0; e < 2; e++) { mb[e] = __shfl_sync(0xffffffffu, m1, (lane >> 2) + 8 * e); rd[e] = __shfl_sync(0xffffffffu, r1, (lane >> 2) + 8 * e); }
                }
                DT(21 + 24 * layer);
                mbar_wait(f5 + 8, r5.ph);
                DT(23 + 24 * layer);
                const uint32_t ya = s_r + R5_STAGE + wg * 16384 + ((lane >> 4) * 8 + (lane & 7)) * 128 + ((((warp & 3) * 2 + ((lane >> 3) & 1)) ^ (lane & 7)) << 4);
                uint32_t y[16];
#pragma unroll
                for (int e = 0; e < 32; e++) {
                    if ((e & 15) == 0) {
#pragma unroll
                        for (int jp = 0; jp < 4; jp++) ldsm4t(y[4 * jp], y[4 * jp + 1], y[4 * jp + 2], y[4 * jp + 3], ya + jp * 2048 + e * 512);
                    }
                    x[e] = bfma2(norm2(x[e], mb[e & 1], rd[e & 1]), y[e & 15], x[e]);
                    if ((e & 3) == 3) stsm4(s_epi + (fr ^ (((e >> 2) & 3) << 5)) + (e >> 4) * 16384, x[e - 3], x[e - 2], x[e - 1], x[e]);
                    if ((e & 15) == 15 && ((e > 15 ? GS2 : GST) & 1)) put_half(s_epi + (e >> 4) * 16384, R_XA + tb, e >> 4);
                    if ((e & 15) == 15) { if (e == 15 && (SPL2 & 1)) named_bar_arrive(7 - 2 * wg, 160); else named_bar_arrive(5 + (e >> 4), 288); }
                    if (e == 15) mbar_wait(b_role, 0);
                }
                DT(19 + 24 * layer);
                if (FMOVE) fence_async_smem();
                if (PS1_EARLY) put_stats(x, 1, layer);
                named_bar_sync(9 + wg, 128);
                skip5(r5);
                DT(3 + 24 * layer);
            }
            {
                float acc[64];
                kblock<128, R5_N, 0>(acc, dae, db0 + 2 * (R5_STAGE / 16), f5, r5);
                kblock<128, R5_N>(acc, dae + 1024, db0 + 3 * (R5_STAGE / 16), f5, r5);
                if (!PS1_EARLY) put_stats(x, 1, layer);
                wgmma_wait<1>();
                if (rel_on) mbar_arrive_cluster(rel5 + 16);
                float2 cs[8];
                mainloop<128, R5_N, R5_STAGE, PA1>(acc, 14, da0, db0, f5, rel5, rel_on, r5, 15 + 24 * layer, [&]() {
                    named_bar_sync(3 + 8 * wg, 160);
                    row_consts(true);
#pragma unroll
                    for (int e = 0; e < 8; e++) cs[e] = *reinterpret_cast<const float2*>(csp + 256 + 8 * e);
                    keep_consts(cs);
                } DT_ARG, (wg ^ bj >> 1 ^ LAGX) & 1);
                DT(4 + 24 * layer);
#pragma unroll
                for (int j = 0; j < 16; j += 2) {
                    if (j == 8) {
#pragma unroll
                        for (int e = 0; e < 8; e++) cs[e] = *reinterpret_cast<const float2*>(csp + 256 + 8 * (j + e));
                    }
                    uint32_t w[4];
#pragma unroll
                    for (int e = 0; e < 4; e++) {
                        const float* a = acc + 4 * j + 2 * e;
                        const float2 c = cs[(j & 7) + (e >> 1)];
                        w[e] = gelu2h(pack2(fmaf(-mrow[e & 1], c.x, a[0]) * rrow[e & 1], fmaf(-mrow[e & 1], c.y, a[1]) * rrow[e & 1]));
                    }
                    stsm4(s_stg + 1024 + (fr ^ ((j & 7) << 4)) + (j >> 3) * OFF_EPI, w[0], w[1], w[2], w[3]);
                    if ((j & 7) == 6 && ((j > 7 ? GS2 : GST) & 4)) put_half(s_stg + 1024 + (j >> 3) * OFF_EPI, R_H + layer * R_HP + m0, j >> 3);
                    if ((j & 7) == 6) { if (j == 6 && (SPL2 & 4)) named_bar_arrive(7 - 2 * ((wg ^ bj >> 1 ^ 1) & 1), 160); else named_bar_arrive(5 + (j >> 3), 288); }
                }
                if (SENDC && warp == (bj & 2 ? 0 : 7)) {
                    __syncwarp();
                    uint32_t a[4];
                    lds64(a[0], a[1], s_stg + 1024 + 18 * 128 * warp + 8 * lane);
                    lds64(a[2], a[3], s_epi + 1024 + 18 * 128 * warp + 8 * lane);
                    uint4* gh = g_halo + (layer * 144 + (warp & 2) * 8 + bi * 8 + bj) * 64 + lane;
#pragma unroll
                    for (int i = 0; i < 2; i++)
                        asm volatile("{\n.reg .b64 u, v;\nmov.b64 u, {%1, %3};\nmov.b64 v, {%2, %3};\nst.relaxed.gpu.global.v2.b64 [%0], {u, v};\n}"
                                     ::"l"(gh + i * 32), "r"(a[2 * i]), "r"(a[2 * i + 1]), "r"(ep) : "memory");
                }
                fence_async_smem();
                if (wg == (bj >> 1 & 1)) { if (H11) named_bar_arrive(4, 160); named_bar_arrive(13, 256); }
                DT(5 + 24 * layer);
            }
            {
                float acc[64];
                uint32_t u[32];
                {
                    uint32_t mb[2], rd[2];
#pragma unroll
                    for (int e = 0; e < 2; e++) { const uint32_t q0 = rsp[8 * e]; mb[e] = (q0 & 0xffffu) * 0x10001u; rd[e] = split(frcp(hi2f(q0))); }
#pragma unroll
                    for (int e = 0; e < 32; e++) {
                        u[e] = norm2(x[e], mb[e & 1], rd[e & 1]);
                        asm volatile("" : "+r"(u[e]));
                    }
                }
                if (!(warp & 2)) mbar_wait(f5 + 24, r5.ph);
                skip5(r5);
                {
                    const bool nb = wg == (bj >> 1 & 1);
                    named_bar_sync(nb ? 14 : 13, nb ? 160 : 256);
                }
                const uint32_t dah = da0 - (OFF_R - 1024 + 256) / 16 + ((0x4031u >> (2 * bj & 12)) & 7) * 8;
                kblock<128, R5_N, 0>(acc, dah, db0 + 4 * (R5_STAGE / 16), f5, r5);
                kblock<128, R5_N>(acc, dah + OFF_EPI / 16, db0, f5, r5);
                wgmma_wait<1>();
                if (rel_on) mbar_arrive_cluster(rel5 + 32);
                mainloop<128, R5_N, R5_STAGE, PA2>(acc, 14, da0, db0, f5, rel5, rel_on, r5, 16 + 24 * layer, []() {} DT_ARG, wg);
                DT(6 + 24 * layer);
#pragma unroll
                for (int j = 0; j < 16; j += 2) {
#pragma unroll
                    for (int e = 0; e < 4; e++) u[2 * j + e] = badd2(u[2 * j + e], pack2(acc[4 * j + 2 * e], acc[4 * j + 2 * e + 1]));
                    stsm4(s_epi + (fr ^ ((j & 7) << 4)) + (j >> 3) * 16384, u[2 * j], u[2 * j + 1], u[2 * j + 2], u[2 * j + 3]);
                    if ((j & 7) == 6 && ((j > 7 ? GS2 : GST) & 16)) put_half(s_epi + (j >> 3) * 16384, R_X1 + tb, j >> 3);
                    if ((j & 7) == 6) { if (j == 6 && (SPL2 & 16)) named_bar_arrive(7 - 2 * wg, 160); else named_bar_arrive(5 + (j >> 3), 288); mbar_wait(b_role, 0); }
                }
                if (FMOVE) fence_async_smem();
#pragma unroll
                for (int e = 0; e < 32; e++) x[e] = badd2(x[e], u[e]);
                put_stats(u, 2, layer);
                named_bar_sync(9 + wg, 128);
                DT(7 + 24 * layer);
            }
            {
                float2 cs[NCS];
                auto piece = [&](const float* acc, auto pc) {
                    constexpr int j = 2 * decltype(pc)::v, jl = j & 31;
                    uint32_t w[4];
#pragma unroll
                    for (int e = 0; e < 2; e++) {
                        const float* a = acc + 4 * (jl + e);
                        const float2 cc = cs[(j + e) % NCS];
                        w[2 * e] = pack2(fmaf(-mrow[0], cc.x, a[0]) * rrow[0], fmaf(-mrow[0], cc.y, a[1]) * rrow[0]);
                        w[2 * e + 1] = pack2(fmaf(-mrow[1], cc.x, a[2]) * rrow[1], fmaf(-mrow[1], cc.y, a[3]) * rrow[1]);
                    }
                    stsm4(((jl < 16 ? s_epi : s_stg) + st_w) ^ ((j & 15) << 4), w[0], w[1], w[2], w[3]);
                    if (j + NCS < 56) {
#pragma unroll
                        for (int e = 0; e < 2; e++) { uint32_t u0, u1; lds64(u0, u1, smem_u32(csp + 8 * (j + e + NCS))); cs[(j + e) % NCS] = make_float2(__uint_as_float(u0), __uint_as_float(u1)); }
                    }
                    if (j == 14 || (j >= 30 && (j & 7) == 6)) {
                        __syncwarp();
                        if (lane == 0) mbar_arrive(j == 14 ? b_stg : s_bar + 168 + (j & 56));
                    }
                };
                auto pieces = [&](const float* acc, auto p0, auto p1) {
                    constexpr int a = decltype(p0)::v, b = decltype(p1)::v;
                    static_for<a, b>([&](auto i) { piece(acc, i); });
                };
                float ac3[128];
                kblock<256, R4_N, 0>(ac3, dae, db4, f4, r4);
                kblock<256, R4_N>(ac3, dae + 1024, db4 + R4_STAGE / 16, f4, r4);
                wgmma_wait<1>();
                if (rel_on) mbar_arrive_cluster(rel4);
                mainloop<256, R4_N, R4_STAGE, PA3A>(ac3, 14, da0, db4, f4, rel4, rel_on, r4, 17 + 24 * layer, [&]() {
                    named_bar_sync(3 + 8 * wg, 160);
                    mbar_wait(e4, 1);
                    row_consts(false);
#pragma unroll
                    for (int e = 0; e < NCS; e++) {
                        cs[e] = *reinterpret_cast<const float2*>(csp + 8 * e);
                        asm volatile("" : "+f"(cs[e].x), "+f"(cs[e].y));
                    }
                    asm volatile("" : "+f"(mrow[0]), "+f"(mrow[1]), "+f"(rrow[0]), "+f"(rrow[1]));
                } DT_ARG, wg);
                DT(8 + 24 * layer);
                pieces(ac3, IC<0>(), IC<NPRE>());
                DT(9 + 24 * layer);
                float acc[96];
                constexpr int NS3 = NPRE == 16 ? 1 : (16 - NPRE + PP3 - 1) / PP3;
                static_for<0, NS3>([&](auto cc) {
                    constexpr int c = decltype(cc)::v, q = NPRE + PP3 * c;
                    const uint32_t da = da0 + c * (R4B_STAGE / 16), db = db0 + c * (R4B_STAGE / 16);
                    mbar_wait(f4 + 8 * c, r4.ph);
                    wgmma_fence();
                    static_for<0, 4>([&](auto ic) {
                        constexpr int i = decltype(ic)::v, q0 = q + i * PP3 / 4, q1 = q + (i + 1) * PP3 / 4;
                        WG<192>::mma<(c | i) != 0>(acc, da + 2 * i, db + 128 * i);
                        if (i == 3) {
                            wgmma_commit();
                            if (c) {
                                wgmma_wait<1>();
                                if (rel_on) mbar_arrive_cluster(rel4 + 8 * ((c + 3) & 3));
                            }
                        }
                        pieces(ac3, IC<(q0 < 16 ? q0 : 16)>(), IC<(q1 < 16 ? q1 : 16)>());
                    });
                });
                r4.st = NS3 & 3;
                if (NS3 == 4) r4.ph ^= 1;
                float ac4[64];
                mainloop<192, R4_N, R4B_STAGE, PA3B, 1>(acc, 16 - NS3, da0, db0, f4, rel4, rel_on, r4, -1, [&]() {
#pragma unroll
                    for (int i = 0; i < 32; i++) asm volatile("shl.b32 %0, %2, 16;\nand.b32 %1, %2, 0xffff0000;" : "=f"(ac4[2 * i]), "=f"(ac4[2 * i + 1]) : "r"(x[i]));
                    kblock<128, R5_N>(ac4, da0, db0, f5, r5);
                } DT_ARG, wg);
                DT(10 + 24 * layer);
                named_bar_sync(4 + 8 * wg, 224);
                piece(acc, IC<16>());
                static_for<1, 7>([&](auto cc) {
                    constexpr int c = decltype(cc)::v;
                    const uint32_t da = da0 + (c % 5) * (R5_STAGE / 16), db = db0 + (c % 5) * (R5_STAGE / 16);
                    mbar_wait(f5 + 8 * (c % 5), r5.ph);
                    wgmma_fence();
                    WG<128>::mma<1>(ac4, da, db);
                    WG<128>::mma<1>(ac4, da + 2, db + 128);
                    piece(acc, IC<15 + 2 * c>());
                    WG<128>::mma<1>(ac4, da + 4, db + 256);
                    WG<128>::mma<1>(ac4, da + 6, db + 384);
                    wgmma_commit();
                    if (c % 5 == 4) r5.ph ^= 1;
                    wgmma_wait<1>();
                    if (rel_on) mbar_arrive_cluster(rel5 + 8 * ((c - 1) % 5));
                    if constexpr (c < 6) piece(acc, IC<16 + 2 * c>());
                });
                r5.st = 2;
                DT(11 + 24 * layer);
                DT(18 + 24 * layer);
                mainloop<128, R5_N, R5_STAGE, PA4>(ac4, 49, da0, db0, f5, rel5, rel_on, r5, 62 - 40 * (layer ^ 1), []() {} DT_ARG, wg);
                DT(12 + 24 * layer);
#pragma unroll
                for (int i = 0; i < 32; i++) x[i] = pack2(ac4[2 * i], ac4[2 * i + 1]);
                DT(13 + 24 * layer);
                DT(14 + 24 * layer);
            }
        }
#pragma unroll
        for (int jp = 0; jp < 8; jp++) stsm4(s_epi + (fr ^ ((jp & 3) << 5)) + (jp >> 2) * 16384, x[4 * jp], x[4 * jp + 1], x[4 * jp + 2], x[4 * jp + 3]);
        __syncwarp();
        copy_out(outp, s_epi);
        DT(38);
        DT_DUMP;
        GT(4);
        }
        cluster_arrive_relaxed();
        cluster_wait();
    }
}

typedef CUresult (*PFN_encodeTiled)(CUtensorMap*, CUtensorMapDataType, cuuint32_t, void*, const cuuint64_t*, const cuuint64_t*,
                                    const cuuint32_t*, const cuuint32_t*, CUtensorMapInterleave, CUtensorMapSwizzle,
                                    CUtensorMapL2promotion, CUtensorMapFloatOOBfill);

static CUtensorMap make_map(PFN_encodeTiled enc, const void* ptr, int inner, int outer, int box_inner, int box_outer,
                            CUtensorMapSwizzle swz = CU_TENSOR_MAP_SWIZZLE_128B) {
    CUtensorMap m;
    cuuint64_t dims[2] = {(cuuint64_t)inner, (cuuint64_t)outer};
    cuuint64_t strides[1] = {(cuuint64_t)inner * 2};
    cuuint32_t box[2] = {(cuuint32_t)box_inner, (cuuint32_t)box_outer};
    cuuint32_t es[2] = {1, 1};
    enc(&m, CU_TENSOR_MAP_DATA_TYPE_BFLOAT16, 2, const_cast<void*>(ptr), dims, strides, box, es, CU_TENSOR_MAP_INTERLEAVE_NONE,
        swz, CU_TENSOR_MAP_L2_PROMOTION_L2_256B, CU_TENSOR_MAP_FLOAT_OOB_FILL_NONE);
    return m;
}

extern "C" void kernel_launch(void* const* d_in, const int* in_sizes, int n_in, void* d_out, int out_size) {
    const bf16* A_q = (const bf16*)d_in[0];
    const bf16* A_k = (const bf16*)d_in[1];
    const bf16* A_v = (const bf16*)d_in[2];
    const bf16* A_shk = (const bf16*)d_in[3];
    const bf16* A_ssk = (const bf16*)d_in[4];
    const bf16* A_ssD = (const bf16*)d_in[5];
    const bf16* w1 = (const bf16*)d_in[7];
    const bf16* w2 = (const bf16*)d_in[8];
    const bf16* w3 = (const bf16*)d_in[9];
    const bf16* w4 = (const bf16*)d_in[10];
    bf16* out = (bf16*)d_out;

    static PFN_encodeTiled enc = nullptr;
    static bool attr_done = false;
    if (!enc) {
        void* fn = nullptr;
        cudaDriverEntryPointQueryResult qr;
        cudaGetDriverEntryPoint("cuTensorMapEncodeTiled", &fn, cudaEnableDefault, &qr);
        enc = (PFN_encodeTiled)fn;
    }
    if (!attr_done) {
        cudaFuncSetAttribute(mega_kernel, cudaFuncAttributeMaxDynamicSharedMemorySize, MEGA_SMEM);
        attr_done = true;
    }
    void* p_act;
    cudaGetSymbolAddress(&p_act, g_act);
    bf16* act = (bf16*)(((uintptr_t)p_act + 0x1fffff) & ~(uintptr_t)0x1fffff);

    MegaMaps tm;
    tm.q = make_map(enc, A_q, D_, S_, 64, 128);
    tm.act = make_map(enc, act, D_, R_END, 64, 128);
    tm.a64 = make_map(enc, act, D_, R_END, 64, 64);
    tm.w1 = make_map(enc, w1, D_, D_, 64, 64);
    tm.w2 = make_map(enc, w2, D_, D_, 64, 64);
    tm.w3 = make_map(enc, w3, F_, D_, 64, 64);
    tm.w4 = make_map(enc, w4, D_, F_, 64, 64);
    {
        cuuint64_t dims[4] = {64, 16, 256, 8}, strides[3] = {128, D_ * 2, (cuuint64_t)2048 * D_ * 2};
        cuuint32_t box[4] = {64, 4, 1, 8}, es[4] = {1, 1, 1, 1};
        enc(&tm.y, CU_TENSOR_MAP_DATA_TYPE_BFLOAT16, 4, act + (size_t)R_Y * D_, dims, strides, box, es, CU_TENSOR_MAP_INTERLEAVE_NONE,
            CU_TENSOR_MAP_SWIZZLE_128B, CU_TENSOR_MAP_L2_PROMOTION_NONE, CU_TENSOR_MAP_FLOAT_OOB_FILL_NONE);
    }
    for (int i = 0; i < 2; i++) {
        cuuint64_t dims[4] = {D_, 4, 8, S_ / 32}, strides[3] = {8 * D_ * 2, D_ * 2, 32 * D_ * 2};
        cuuint32_t box[4] = {16, 4, 8, 4}, es[4] = {1, 1, 1, 1};
        enc(i ? &tm.v : &tm.k, CU_TENSOR_MAP_DATA_TYPE_BFLOAT16, 4, (void*)(i ? A_v : A_k), dims, strides, box, es, CU_TENSOR_MAP_INTERLEAVE_NONE,
            CU_TENSOR_MAP_SWIZZLE_32B, CU_TENSOR_MAP_L2_PROMOTION_NONE, CU_TENSOR_MAP_FLOAT_OOB_FILL_NONE);
    }
    mega_kernel<<<2 * NCL, 384, MEGA_SMEM, cudaStreamPerThread>>>(tm, out, act, w1, w2, w3, A_q, A_k, A_v, A_shk, A_ssk, A_ssD);
}
```

```cpp
#include <cuda_runtime.h>
#include <cuda_bf16.h>
#include <cuda.h>
#include <stdint.h>

typedef __nv_bfloat16 bf16;

constexpr int S_ = 2048;
constexpr int D_ = 1024;
constexpr int F_ = 3584;

constexpr int R_XA = 0, R_X1 = 256, R_H2 = 512, R_Y = 1536, R_H = 16384 + 8, R_HP = S_ + 8, R_END = R_H + 2 * R_HP;
__device__ __align__(1024) bf16 g_act[(size_t)(R_END + 1024) * D_];
__device__ __align__(16) float g_cpart[16 * (F_ + D_)];
__device__ __align__(128) float2 g_stats[3 * S_ * 8];
__device__ __align__(128) uint4 g_halo[2 * 144 * 64];

__device__ __forceinline__ float bfr(float x) { return __bfloat162float(__float2bfloat16_rn(x)); }
__device__ __forceinline__ uint32_t pack2(float lo, float hi) {
    __nv_bfloat162 v = __floats2bfloat162_rn(lo, hi);
    return *reinterpret_cast<uint32_t*>(&v);
}
__device__ __forceinline__ float lo2f(uint32_t v) { return __uint_as_float(v << 16); }
__device__ __forceinline__ float hi2f(uint32_t v) { return __uint_as_float(v & 0xffff0000u); }
__device__ __forceinline__ float frcp(float x) { float r; asm("rcp.approx.f32 %0, %1;" : "=f"(r) : "f"(x)); return r; }
__device__ __forceinline__ float fsqrt(float x) { float r; asm("sqrt.approx.f32 %0, %1;" : "=f"(r) : "f"(x)); return r; }
__device__ __forceinline__ uint32_t smem_u32(const void* p) { return (uint32_t)__cvta_generic_to_shared(p); }

__device__ __forceinline__ void mbar_init(uint32_t bar, uint32_t cnt) {
    asm volatile("mbarrier.init.shared::cta.b64 [%0], %1;" ::"r"(bar), "r"(cnt));
}
__device__ __forceinline__ void mbar_expect_tx(uint32_t bar, uint32_t bytes) {
    asm volatile("mbarrier.arrive.expect_tx.shared::cta.b64 _, [%0], %1;" ::"r"(bar), "r"(bytes) : "memory");
}
__device__ __forceinline__ void mbar_arrive(uint32_t bar) {
    asm volatile("mbarrier.arrive.shared::cta.b64 _, [%0];" ::"r"(bar) : "memory");
}
__device__ __forceinline__ void mbar_wait(uint32_t bar, uint32_t parity) {
    asm volatile(
        "{\n.reg .pred p;\n.reg .u32 n;\n"
        "mbarrier.try_wait.parity.shared::cta.b64 p, [%0], %1;\n"
        "@p bra LD;\n"
        "mov.u32 n, 0;\n"
        "LW:\n"
        "mbarrier.try_wait.parity.shared::cta.b64 p, [%0], %1;\n"
        "@p bra LD;\n"
        "add.u32 n, n, 1;\n"
        "setp.lt.u32 p, n, 0x400000;\n"
        "@p bra LW;\n"
        "LD:\n}\n"
        ::"r"(bar), "r"(parity) : "memory");
}
__device__ __forceinline__ void tma_load_2d(uint32_t dst, const CUtensorMap* tm, uint32_t bar, int c0, int c1) {
    asm volatile(
        "cp.async.bulk.tensor.2d.shared::cluster.global.mbarrier::complete_tx::bytes [%0], [%1, {%3, %4}], [%2];"
        ::"r"(dst), "l"((uint64_t)tm), "r"(bar), "r"(c0), "r"(c1) : "memory");
}
__device__ __forceinline__ void tma_load_2d_mc(uint32_t dst, const CUtensorMap* tm, uint32_t bar, int c0, int c1) {
    asm volatile(
        "cp.async.bulk.tensor.2d.shared::cluster.global.mbarrier::complete_tx::bytes.multicast::cluster [%0], [%1, {%3, %4}], [%2], %5;"
        ::"r"(dst), "l"((uint64_t)tm), "r"(bar), "r"(c0), "r"(c1), "h"((uint16_t)3) : "memory");
}
__device__ __forceinline__ void tma_prefetch_2d(const CUtensorMap* tm, int c0, int c1) {
    asm volatile("cp.async.bulk.prefetch.tensor.2d.L2.global.tile [%0, {%1, %2}];" ::"l"((uint64_t)tm), "r"(c0), "r"(c1) : "memory");
}
__device__ __forceinline__ void tma_store_2d(const CUtensorMap* tm, uint32_t src, int c0, int c1) {
    asm volatile("cp.async.bulk.tensor.2d.global.shared::cta.bulk_group [%0, {%2, %3}], [%1];"
                 ::"l"((uint64_t)tm), "r"(src), "r"(c0), "r"(c1) : "memory");
}
__device__ __forceinline__ void wgmma_fence() { asm volatile("wgmma.fence.sync.aligned;" ::: "memory"); }
__device__ __forceinline__ void wgmma_commit() { asm volatile("wgmma.commit_group.sync.aligned;" ::: "memory"); }
template <int N> __device__ __forceinline__ void wgmma_wait() { asm volatile("wgmma.wait_group.sync.aligned %0;" ::"n"(N) : "memory"); }
__device__ __forceinline__ void named_bar_arrive(int id, int n) { asm volatile("bar.arrive %0, %1;" ::"r"(id), "r"(n) : "memory"); }
__device__ __forceinline__ void named_bar_sync(int id, int n) { asm volatile("bar.sync %0, %1;" ::"r"(id), "r"(n) : "memory"); }

__device__ __forceinline__ uint32_t desc_a(uint32_t addr) { return ((addr & 0x3FFFF) >> 4) | (1u << 16); }
__device__ __forceinline__ uint32_t desc_b(uint32_t addr) { return ((addr & 0x3FFFF) >> 4) | (512u << 16); }

template <int ACC> __device__ __forceinline__ void wgmma_m64n192k16(float (&d)[96], uint32_t descA, uint32_t descB) {
  asm volatile("{\n.reg .pred p;\n.reg .b64 da, db;\nsetp.ne.b32 p, %99, 0;\nmov.b64 da, {%96, %98};\nmov.b64 db, {%97, %98};\n"
    "wgmma.mma_async.sync.aligned.m64n192k16.f32.bf16.bf16 "
    "{%0, %1, %2, %3, %4, %5, %6, %7, %8, %9, %10, %11, %12, %13, %14, %15, %16, %17, %18, %19, %20, %21, %22, %23, %24, %25, %26, %27, %28, %29, %30, %31, %32, %33, %34, %35, %36, %37, %38, %39, %40, %41, %42, %43, %44, %45, %46, %47, %48, %49, %50, %51, %52, %53, %54, %55, %56, %57, %58, %59, %60, %61, %62, %63, %64, %65, %66, %67, %68, %69, %70, %71, %72, %73, %74, %75, %76, %77, %78, %79, %80, %81, %82, %83, %84, %85, %86, %87, %88, %89, %90, %91, %92, %93, %94, %95}, "
    "da, db, p, 1, 1, 0, 1;\n}\n"
    : "+f"(d[0]), "+f"(d[1]), "+f"(d[2]), "+f"(d[3]), "+f"(d[4]), "+f"(d[5]), "+f"(d[6]), "+f"(d[7]), "+f"(d[8]), "+f"(d[9]), "+f"(d[10]), "+f"(d[11]), "+f"(d[12]), "+f"(d[13]), "+f"(d[14]), "+f"(d[15]), "+f"(d[16]), "+f"(d[17]), "+f"(d[18]), "+f"(d[19]), "+f"(d[20]), "+f"(d[21]), "+f"(d[22]), "+f"(d[23]), "+f"(d[24]), "+f"(d[25]), "+f"(d[26]), "+f"(d[27]), "+f"(d[28]), "+f"(d[29]), "+f"(d[30]), "+f"(d[31]), "+f"(d[32]), "+f"(d[33]), "+f"(d[34]), "+f"(d[35]), "+f"(d[36]), "+f"(d[37]), "+f"(d[38]), "+f"(d[39]), "+f"(d[40]), "+f"(d[41]), "+f"(d[42]), "+f"(d[43]), "+f"(d[44]), "+f"(d[45]), "+f"(d[46]), "+f"(d[47]), "+f"(d[48]), "+f"(d[49]), "+f"(d[50]), "+f"(d[51]), "+f"(d[52]), "+f"(d[53]), "+f"(d[54]), "+f"(d[55]), "+f"(d[56]), "+f"(d[57]), "+f"(d[58]), "+f"(d[59]), "+f"(d[60]), "+f"(d[61]), "+f"(d[62]), "+f"(d[63]), "+f"(d[64]), "+f"(d[65]), "+f"(d[66]), "+f"(d[67]), "+f"(d[68]), "+f"(d[69]), "+f"(d[70]), "+f"(d[71]), "+f"(d[72]), "+f"(d[73]), "+f"(d[74]), "+f"(d[75]), "+f"(d[76]), "+f"(d[77]), "+f"(d[78]), "+f"(d[79]), "+f"(d[80]), "+f"(d[81]), "+f"(d[82]), "+f"(d[83]), "+f"(d[84]), "+f"(d[85]), "+f"(d[86]), "+f"(d[87]), "+f"(d[88]), "+f"(d[89]), "+f"(d[90]), "+f"(d[91]), "+f"(d[92]), "+f"(d[93]), "+f"(d[94]), "+f"(d[95])
    : "r"(descA), "r"(descB), "r"(0x40000040u), "n"(ACC));
}

template <int ACC> __device__ __forceinline__ void wgmma_m64n256k16(float (&d)[128], uint32_t descA, uint32_t descB) {
  asm volatile("{\n.reg .pred p;\n.reg .b64 da, db;\nsetp.ne.b32 p, %131, 0;\nmov.b64 da, {%128, %130};\nmov.b64 db, {%129, %130};\n"
    "wgmma.mma_async.sync.aligned.m64n256k16.f32.bf16.bf16 "
    "{%0, %1, %2, %3, %4, %5, %6, %7, %8, %9, %10, %11, %12, %13, %14, %15, %16, %17, %18, %19, %20, %21, %22, %23, %24, %25, %26, %27, %28, %29, %30, %31, %32, %33, %34, %35, %36, %37, %38, %39, %40, %41, %42, %43, %44, %45, %46, %47, %48, %49, %50, %51, %52, %53, %54, %55, %56, %57, %58, %59, %60, %61, %62, %63, %64, %65, %66, %67, %68, %69, %70, %71, %72, %73, %74, %75, %76, %77, %78, %79, %80, %81, %82, %83, %84, %85, %86, %87, %88, %89, %90, %91, %92, %93, %94, %95, %96, %97, %98, %99, %100, %101, %102, %103, %104, %105, %106, %107, %108, %109, %110, %111, %112, %113, %114, %115, %116, %117, %118, %119, %120, %121, %122, %123, %124, %125, %126, %127}, "
    "da, db, p, 1, 1, 0, 1;\n}\n"
    : "+f"(d[0]), "+f"(d[1]), "+f"(d[2]), "+f"(d[3]), "+f"(d[4]), "+f"(d[5]), "+f"(d[6]), "+f"(d[7]), "+f"(d[8]), "+f"(d[9]), "+f"(d[10]), "+f"(d[11]), "+f"(d[12]), "+f"(d[13]), "+f"(d[14]), "+f"(d[15]), "+f"(d[16]), "+f"(d[17]), "+f"(d[18]), "+f"(d[19]), "+f"(d[20]), "+f"(d[21]), "+f"(d[22]), "+f"(d[23]), "+f"(d[24]), "+f"(d[25]), "+f"(d[26]), "+f"(d[27]), "+f"(d[28]), "+f"(d[29]), "+f"(d[30]), "+f"(d[31]), "+f"(d[32]), "+f"(d[33]), "+f"(d[34]), "+f"(d[35]), "+f"(d[36]), "+f"(d[37]), "+f"(d[38]), "+f"(d[39]), "+f"(d[40]), "+f"(d[41]), "+f"(d[42]), "+f"(d[43]), "+f"(d[44]), "+f"(d[45]), "+f"(d[46]), "+f"(d[47]), "+f"(d[48]), "+f"(d[49]), "+f"(d[50]), "+f"(d[51]), "+f"(d[52]), "+f"(d[53]), "+f"(d[54]), "+f"(d[55]), "+f"(d[56]), "+f"(d[57]), "+f"(d[58]), "+f"(d[59]), "+f"(d[60]), "+f"(d[61]), "+f"(d[62]), "+f"(d[63]), "+f"(d[64]), "+f"(d[65]), "+f"(d[66]), "+f"(d[67]), "+f"(d[68]), "+f"(d[69]), "+f"(d[70]), "+f"(d[71]), "+f"(d[72]), "+f"(d[73]), "+f"(d[74]), "+f"(d[75]), "+f"(d[76]), "+f"(d[77]), "+f"(d[78]), "+f"(d[79]), "+f"(d[80]), "+f"(d[81]), "+f"(d[82]), "+f"(d[83]), "+f"(d[84]), "+f"(d[85]), "+f"(d[86]), "+f"(d[87]), "+f"(d[88]), "+f"(d[89]), "+f"(d[90]), "+f"(d[91]), "+f"(d[92]), "+f"(d[93]), "+f"(d[94]), "+f"(d[95]), "+f"(d[96]), "+f"(d[97]), "+f"(d[98]), "+f"(d[99]), "+f"(d[100]), "+f"(d[101]), "+f"(d[102]), "+f"(d[103]), "+f"(d[104]), "+f"(d[105]), "+f"(d[106]), "+f"(d[107]), "+f"(d[108]), "+f"(d[109]), "+f"(d[110]), "+f"(d[111]), "+f"(d[112]), "+f"(d[113]), "+f"(d[114]), "+f"(d[115]), "+f"(d[116]), "+f"(d[117]), "+f"(d[118]), "+f"(d[119]), "+f"(d[120]), "+f"(d[121]), "+f"(d[122]), "+f"(d[123]), "+f"(d[124]), "+f"(d[125]), "+f"(d[126]), "+f"(d[127])
    : "r"(descA), "r"(descB), "r"(0x40000040u), "n"(ACC));
}

template <int ACC> __device__ __forceinline__ void wgmma_m64n128k16(float (&d)[64], uint32_t descA, uint32_t descB) {
  asm volatile("{\n.reg .pred p;\n.reg .b64 da, db;\nsetp.ne.b32 p, %67, 0;\nmov.b64 da, {%64, %66};\nmov.b64 db, {%65, %66};\n"
    "wgmma.mma_async.sync.aligned.m64n128k16.f32.bf16.bf16 "
    "{%0, %1, %2, %3, %4, %5, %6, %7, %8, %9, %10, %11, %12, %13, %14, %15, %16, %17, %18, %19, %20, %21, %22, %23, %24, %25, %26, %27, %28, %29, %30, %31, %32, %33, %34, %35, %36, %37, %38, %39, %40, %41, %42, %43, %44, %45, %46, %47, %48, %49, %50, %51, %52, %53, %54, %55, %56, %57, %58, %59, %60, %61, %62, %63}, "
    "da, db, p, 1, 1, 0, 1;\n}\n"
    : "+f"(d[0]), "+f"(d[1]), "+f"(d[2]), "+f"(d[3]), "+f"(d[4]), "+f"(d[5]), "+f"(d[6]), "+f"(d[7]), "+f"(d[8]), "+f"(d[9]), "+f"(d[10]), "+f"(d[11]), "+f"(d[12]), "+f"(d[13]), "+f"(d[14]), "+f"(d[15]), "+f"(d[16]), "+f"(d[17]), "+f"(d[18]), "+f"(d[19]), "+f"(d[20]), "+f"(d[21]), "+f"(d[22]), "+f"(d[23]), "+f"(d[24]), "+f"(d[25]), "+f"(d[26]), "+f"(d[27]), "+f"(d[28]), "+f"(d[29]), "+f"(d[30]), "+f"(d[31]), "+f"(d[32]), "+f"(d[33]), "+f"(d[34]), "+f"(d[35]), "+f"(d[36]), "+f"(d[37]), "+f"(d[38]), "+f"(d[39]), "+f"(d[40]), "+f"(d[41]), "+f"(d[42]), "+f"(d[43]), "+f"(d[44]), "+f"(d[45]), "+f"(d[46]), "+f"(d[47]), "+f"(d[48]), "+f"(d[49]), "+f"(d[50]), "+f"(d[51]), "+f"(d[52]), "+f"(d[53]), "+f"(d[54]), "+f"(d[55]), "+f"(d[56]), "+f"(d[57]), "+f"(d[58]), "+f"(d[59]), "+f"(d[60]), "+f"(d[61]), "+f"(d[62]), "+f"(d[63])
    : "r"(descA), "r"(descB), "r"(0x40000040u), "n"(ACC));
}

template <int BN> struct WG;
template <> struct WG<128> { template <int ACC> static __device__ __forceinline__ void mma(float (&d)[64], uint32_t a, uint32_t b) { wgmma_m64n128k16<ACC>(d, a, b); } };
template <> struct WG<256> { template <int ACC> static __device__ __forceinline__ void mma(float (&d)[128], uint32_t a, uint32_t b) { wgmma_m64n256k16<ACC>(d, a, b); } };
template <> struct WG<192> { template <int ACC> static __device__ __forceinline__ void mma(float (&d)[96], uint32_t a, uint32_t b) { wgmma_m64n192k16<ACC>(d, a, b); } };

#define DBG_T(i)
__device__ __forceinline__ void fence_async_smem() { asm volatile("fence.proxy.async.shared::cta;" ::: "memory"); }
__device__ __forceinline__ void prefetch_tmap(const CUtensorMap* tm) { asm volatile("prefetch.tensormap [%0];" ::"l"((uint64_t)tm) : "memory"); }
__device__ __forceinline__ uint32_t mapa_u32(uint32_t addr, uint32_t cta) {
    uint32_t r;
    asm volatile("mapa.shared::cluster.u32 %0, %1, %2;" : "=r"(r) : "r"(addr), "r"(cta));
    return r;
}
__device__ __forceinline__ void mbar_arrive_cluster(uint32_t cluster_addr) {
    asm volatile("mbarrier.arrive.shared::cluster.b64 _, [%0];" ::"r"(cluster_addr) : "memory");
}
__device__ __forceinline__ bool elect_one() {
    uint32_t p;
    asm volatile("{\n.reg .pred P;\nelect.sync _|P, 0xffffffff;\nselp.u32 %0, 1, 0, P;\n}\n" : "=r"(p));
    return p != 0;
}
__device__ __forceinline__ void cluster_arrive_relaxed() { asm volatile("barrier.cluster.arrive.relaxed.aligned;" ::: "memory"); }
__device__ __forceinline__ void cluster_wait() { asm volatile("barrier.cluster.wait.acquire.aligned;" ::: "memory"); }

__device__ __forceinline__ uint32_t bsub2(uint32_t a, uint32_t b) {
    __nv_bfloat162 r = __hsub2(*reinterpret_cast<__nv_bfloat162*>(&a), *reinterpret_cast<__nv_bfloat162*>(&b));
    return *reinterpret_cast<uint32_t*>(&r);
}
__device__ __forceinline__ uint32_t bmul2(uint32_t a, uint32_t b) {
    __nv_bfloat162 r = __hmul2(*reinterpret_cast<__nv_bfloat162*>(&a), *reinterpret_cast<__nv_bfloat162*>(&b));
    return *reinterpret_cast<uint32_t*>(&r);
}
__device__ __forceinline__ uint32_t badd2(uint32_t a, uint32_t b) {
    __nv_bfloat162 r = __hadd2(*reinterpret_cast<__nv_bfloat162*>(&a), *reinterpret_cast<__nv_bfloat162*>(&b));
    return *reinterpret_cast<uint32_t*>(&r);
}
constexpr int BM = 128, BK = 64;
constexpr int R5_STAGE = 32768, R5_N = 5;
constexpr int R4_STAGE = 49152, R4_N = 4;
constexpr int R4B_STAGE = 40960;
constexpr int OFF_STG5 = 0, OFF_R = 32768;
constexpr int OFF_EPI = 196608;
constexpr int OFF_BAR = OFF_EPI + 32768;
constexpr int OFF_RS = OFF_BAR + 256;
constexpr int OFF_CS = OFF_RS + 1024;
constexpr int MEGA_SMEM = OFF_CS + 1792;
enum { FL_XA = 0, FL_H = 2, FL_X1 = 4, FL_H2 = 6, FL_CS = 10, FL_KINDS = 11 };
constexpr int FL_PITCH = 64;
constexpr int FL_WORDS = 2 * FL_KINDS * 16 * FL_PITCH;
__device__ unsigned int g_flag[FL_WORDS];
__device__ __align__(8) unsigned int g_ticket[18 * FL_PITCH];
constexpr int NCL = 66;
__device__ __forceinline__ unsigned int* flag_ptr(int layer, int kind, int i) { return g_flag + ((layer * FL_KINDS + kind) * 16 + i) * FL_PITCH; }

__device__ __forceinline__ void wait_flag(const unsigned int* p, unsigned int target) {
    long long t0 = clock64();
    while (true) {
        unsigned int v;
        asm volatile("ld.relaxed.gpu.global.u32 %0, [%1];" : "=r"(v) : "l"(p) : "memory");
        if ((int)(v - target) >= 0) break;
        if (clock64() - t0 > 2000000000LL) break;
    }
    asm volatile("fence.acquire.gpu;" ::: "memory");
}
__device__ __forceinline__ void fence_proxy_async() {
    asm volatile("fence.proxy.async.global;" ::: "memory");
    asm volatile("fence.proxy.async.shared::cta;" ::: "memory");
}
__device__ __forceinline__ void stsm4(uint32_t addr, uint32_t r0, uint32_t r1, uint32_t r2, uint32_t r3) {
    asm volatile("stmatrix.sync.aligned.m8n8.x4.shared.b16 [%0], {%1,%2,%3,%4};" ::"r"(addr), "r"(r0), "r"(r1), "r"(r2), "r"(r3));
}
__device__ __forceinline__ uint4 lds128(uint32_t a) {
    uint4 v;
    asm volatile("ld.shared.v4.b32 {%0,%1,%2,%3}, [%4];" : "=r"(v.x), "=r"(v.y), "=r"(v.z), "=r"(v.w) : "r"(a) : "memory");
    return v;
}
__device__ __forceinline__ void stg128(void* p, uint4 v) {
    asm volatile("st.global.v4.b32 [%0], {%1,%2,%3,%4};" ::"l"(p), "r"(v.x), "r"(v.y), "r"(v.z), "r"(v.w) : "memory");
}
__device__ __forceinline__ float gelu_tanh_h(float hx) {
    float z = hx * fmaf(hx * hx, 8.0f * 0.035677408136300125f, 2.0f * 0.7978845608028654f);
    float t;
    asm("tanh.approx.f32 %0, %1;" : "=f"(t) : "f"(z));
    return fmaf(hx, t, hx);
}
__device__ __forceinline__ uint32_t gelu2h(uint32_t hx) {
    uint32_t r;
    asm("{\n.reg .b32 z;\nmul.rn.bf16x2 z, %1, %1;\nfma.rn.bf16x2 z, z, %2, %3;\nmul.rn.bf16x2 z, z, %1;\ntanh.approx.bf16x2 z, z;\nfma.rn.bf16x2 %0, %1, z, %1;\n}"
        : "=r"(r) : "r"(hx), "r"(0x3e923e92u), "r"(0x3fcc3fccu));
    return r;
}
__device__ __forceinline__ uint4 gelu8h(uint4 v) { return make_uint4(gelu2h(v.x), gelu2h(v.y), gelu2h(v.z), gelu2h(v.w)); }

__device__ __forceinline__ void row_stats(const float2* p, uint32_t tag, float& mean, float& var) {
    float2 v[8];
#pragma unroll 1
    for (int n = 0; n < (1 << 20); n++) {
#pragma unroll
        for (int i = 0; i < 8; i++)
            asm volatile("{\n.reg .b64 t;\nld.relaxed.gpu.global.b64 t, [%2];\nmov.b64 {%0, %1}, t;\n}" : "=f"(v[i].x), "=f"(v[i].y) : "l"(p + 128 * i) : "memory");
        uint32_t old = 0;
#pragma unroll
        for (int i = 0; i < 8; i++) old |= __float_as_uint(v[i].y) ^ tag;
        if ((int)old >= 0) break;
    }
    mean = (((v[0].x + v[1].x) + (v[2].x + v[3].x)) + ((v[4].x + v[5].x) + (v[6].x + v[7].x))) * 0.125f;
    float m2 = 0.f, d2 = 0.f;
#pragma unroll
    for (int i = 0; i < 8; i++) { m2 += fabsf(v[i].y); d2 = fmaf(v[i].x - mean, v[i].x - mean, d2); }
    var = fmaf(128.0f, d2, m2) * (1.0f / D_);
}
struct RingState { uint32_t st, ph; };

#define DT(i)
#define DT_DECL
#define DT_PAR
#define DT_ARG
#define DT_DUMP
#define DP(i)
#define DQ(i)
#define GT(i)
#define TM(i)

template <int BN, int NST, int ACC = 1>
__device__ __forceinline__ void kblock(float (&acc)[BN / 2], uint32_t da, uint32_t db, uint32_t bfull, RingState& rs) {
    mbar_wait(bfull + 8 * rs.st, rs.ph);
    wgmma_fence();
    WG<BN>::template mma<ACC>(acc, da, db);
#pragma unroll
    for (int k = 1; k < 4; k++) WG<BN>::template mma<1>(acc, da + k * 2, db + k * 128);
    wgmma_commit();
    if (++rs.st == NST) { rs.st = 0; rs.ph ^= 1; }
}
#define PA3A 1
#define RLX 1
#define NPRE 12
#define PP3 2
#define NCS 8
template <int V> struct IC { static constexpr int v = V; };
template <int A, int B, class F> __device__ __forceinline__ void static_for(F f) {
    if constexpr (A < B) { f(IC<A>()); static_for<A + 1, B>(f); }
}
#define SPL 21
#define PF4A 22
#define PF4N 1
#define XCS 0
#define PA1 45
#define PA2 33
#define PA4 33
#define LAGX 1
#define PA3B 0
template <int BN, int NST, int STAGE, int PS = 0, int TW = 0, class F>
__device__ __forceinline__ void mainloop(float (&acc)[BN / 2], int KB, uint32_t da0, uint32_t db0, uint32_t bfull, uint32_t rel, bool rel_on,
                                         RingState& rs, int dbg, F pre DT_PAR, int wg = 0) {
    constexpr int SG = PS / 10, PAUSE = PS % 10;
    uint32_t prev = rs.st ? rs.st - 1 : NST - 1;
    const int pause = wg ? KB - PAUSE : -1;
#pragma unroll 1
    for (int kk = 0; kk < KB; kk++) {
        const uint32_t cur = rs.st;
        if (PAUSE && kk == pause) {
            wgmma_wait<0>();
            if (rel_on) mbar_arrive_cluster(rel + 8 * prev);
            named_bar_sync(15, 256);
        }
        kblock<BN, NST>(acc, da0 + cur * (STAGE / 16), db0 + cur * (STAGE / 16), bfull, rs);
        if (PAUSE && SG >= 2 && wg == 0 && kk == KB + 1 - SG) named_bar_arrive(15, 256);
        wgmma_wait<1>();
        if (rel_on && !(PAUSE && kk == pause)) mbar_arrive_cluster(rel + 8 * prev);
        prev = cur;
    }
    if (PAUSE && SG == 0 && wg == 0) named_bar_arrive(15, 256);
    pre();
    wgmma_wait<TW>();
#pragma unroll
    for (int i = 0; i < BN / 2; i++) asm volatile("" : "+f"(acc[i])::"memory");
    if (PAUSE && SG == 1 && wg == 0) named_bar_arrive(15, 256);
    if (rel_on) mbar_arrive_cluster(rel + 8 * prev);
}
__device__ __forceinline__ void hmma(float (&c)[4], uint32_t a0, uint32_t a1, uint32_t a2, uint32_t a3, uint32_t b0, uint32_t b1, bool first) {
    if (first) asm("{\n.reg .f32 z;\nmov.f32 z, 0f00000000;\nmma.sync.aligned.m16n8k16.row.col.f32.bf16.bf16.f32 {%0,%1,%2,%3}, {%4,%5,%6,%7}, {%8,%9}, {z,z,z,z};\n}"
        : "=f"(c[0]), "=f"(c[1]), "=f"(c[2]), "=f"(c[3]) : "r"(a0), "r"(a1), "r"(a2), "r"(a3), "r"(b0), "r"(b1));
    else
    asm("mma.sync.aligned.m16n8k16.row.col.f32.bf16.bf16.f32 {%0,%1,%2,%3}, {%4,%5,%6,%7}, {%8,%9}, {%0,%1,%2,%3};"
        : "+f"(c[0]), "+f"(c[1]), "+f"(c[2]), "+f"(c[3]) : "r"(a0), "r"(a1), "r"(a2), "r"(a3), "r"(b0), "r"(b1));
}
__device__ __forceinline__ void hmma8(float (&c)[4], uint32_t a0, uint32_t a1, uint32_t b0, bool first) {
    if (first) asm("{\n.reg .f32 z;\nmov.f32 z, 0f00000000;\nmma.sync.aligned.m16n8k8.row.col.f32.bf16.bf16.f32 {%0,%1,%2,%3}, {%4,%5}, {%6}, {z,z,z,z};\n}"
        : "=f"(c[0]), "=f"(c[1]), "=f"(c[2]), "=f"(c[3]) : "r"(a0), "r"(a1), "r"(b0));
    else
    asm("mma.sync.aligned.m16n8k8.row.col.f32.bf16.bf16.f32 {%0,%1,%2,%3}, {%4,%5}, {%6}, {%0,%1,%2,%3};"
        : "+f"(c[0]), "+f"(c[1]), "+f"(c[2]), "+f"(c[3]) : "r"(a0), "r"(a1), "r"(b0));
}
template <int N> __device__ __forceinline__ void zero_acc(float (&acc)[N]) {
#pragma unroll
    for (int i = 0; i < N; i++) acc[i] = 0.f;
}
__device__ __forceinline__ void ldsm4(uint32_t& r0, uint32_t& r1, uint32_t& r2, uint32_t& r3, uint32_t addr) {
    asm volatile("ldmatrix.sync.aligned.m8n8.x4.shared.b16 {%0,%1,%2,%3}, [%4];" : "=r"(r0), "=r"(r1), "=r"(r2), "=r"(r3) : "r"(addr));
}

__device__ __forceinline__ void ldsm4t(uint32_t& r0, uint32_t& r1, uint32_t& r2, uint32_t& r3, uint32_t addr) {
    asm volatile("ldmatrix.sync.aligned.m8n8.x4.trans.shared.b16 {%0,%1,%2,%3}, [%4];" : "=r"(r0), "=r"(r1), "=r"(r2), "=r"(r3) : "r"(addr));
}

#define DBG_S(i)
#define DBG_OUT(r, o)
#define DBG_F(i)
#define DBG_W(i)
constexpr int CV_CH = 8;
constexpr int CV_SL = 16384;
constexpr int CV_QG = 128 * 8 + 16;
constexpr int CV_HPL = 2048 + 192;
constexpr int CV_0 = 32768, CV_H = 9 * CV_SL, CV_BAR = OFF_RS - CV_0;

template <int K> __device__ __forceinline__ void cv_mma(float (&d)[64], const uint32_t (&a)[4], uint32_t db, int acc);
template <> __device__ __forceinline__ void cv_mma<0>(float (&d)[64], const uint32_t (&a)[4], uint32_t db, int acc) {
    asm volatile("{\n.reg .pred p;\n.reg .b64 b;\nsetp.ne.b32 p, %70, 0;\nmov.b64 b, {%68, %69};\n"
        "wgmma.mma_async.sync.aligned.m64n128k16.f32.bf16.bf16 {%0,%1,%2,%3,%4,%5,%6,%7,%8,%9,%10,%11,%12,%13,%14,%15,%16,%17,%18,%19,%20,%21,%22,%23,%24,%25,%26,%27,%28,%29,%30,%31,%32,%33,%34,%35,%36,%37,%38,%39,%40,%41,%42,%43,%44,%45,%46,%47,%48,%49,%50,%51,%52,%53,%54,%55,%56,%57,%58,%59,%60,%61,%62,%63}, {%64,%65,%66,%67}, b, p, 1, 1, 0;\n}\n"
        : "+f"(d[0]), "+f"(d[1]), "+f"(d[2]), "+f"(d[3]), "+f"(d[4]), "+f"(d[5]), "+f"(d[6]), "+f"(d[7]), "+f"(d[8]), "+f"(d[9]), "+f"(d[10]), "+f"(d[11]), "+f"(d[12]), "+f"(d[13]), "+f"(d[14]), "+f"(d[15]), "+f"(d[16]), "+f"(d[17]), "+f"(d[18]), "+f"(d[19]), "+f"(d[20]), "+f"(d[21]), "+f"(d[22]), "+f"(d[23]), "+f"(d[24]), "+f"(d[25]), "+f"(d[26]), "+f"(d[27]), "+f"(d[28]), "+f"(d[29]), "+f"(d[30]), "+f"(d[31]), "+f"(d[32]), "+f"(d[33]), "+f"(d[34]), "+f"(d[35]), "+f"(d[36]), "+f"(d[37]), "+f"(d[38]), "+f"(d[39]), "+f"(d[40]), "+f"(d[41]), "+f"(d[42]), "+f"(d[43]), "+f"(d[44]), "+f"(d[45]), "+f"(d[46]), "+f"(d[47]), "+f"(d[48]), "+f"(d[49]), "+f"(d[50]), "+f"(d[51]), "+f"(d[52]), "+f"(d[53]), "+f"(d[54]), "+f"(d[55]), "+f"(d[56]), "+f"(d[57]), "+f"(d[58]), "+f"(d[59]), "+f"(d[60]), "+f"(d[61]), "+f"(d[62]), "+f"(d[63])
        : "r"(a[0]), "r"(a[1]), "r"(a[2]), "r"(a[3]), "r"(db), "r"(8u), "r"(acc));
}
template <> __device__ __forceinline__ void cv_mma<1>(float (&d)[64], const uint32_t (&a)[4], uint32_t db, int acc) {
    asm volatile("{\n.reg .pred p;\n.reg .b64 b;\nsetp.ne.b32 p, %62, 0;\nmov.b64 b, {%60, %61};\n"
        "wgmma.mma_async.sync.aligned.m64n112k16.f32.bf16.bf16 {%0,%1,%2,%3,%4,%5,%6,%7,%8,%9,%10,%11,%12,%13,%14,%15,%16,%17,%18,%19,%20,%21,%22,%23,%24,%25,%26,%27,%28,%29,%30,%31,%32,%33,%34,%35,%36,%37,%38,%39,%40,%41,%42,%43,%44,%45,%46,%47,%48,%49,%50,%51,%52,%53,%54,%55}, {%56,%57,%58,%59}, b, p, 1, 1, 0;\n}\n"
        : "+f"(d[0]), "+f"(d[1]), "+f"(d[2]), "+f"(d[3]), "+f"(d[4]), "+f"(d[5]), "+f"(d[6]), "+f"(d[7]), "+f"(d[8]), "+f"(d[9]), "+f"(d[10]), "+f"(d[11]), "+f"(d[12]), "+f"(d[13]), "+f"(d[14]), "+f"(d[15]), "+f"(d[16]), "+f"(d[17]), "+f"(d[18]), "+f"(d[19]), "+f"(d[20]), "+f"(d[21]), "+f"(d[22]), "+f"(d[23]), "+f"(d[24]), "+f"(d[25]), "+f"(d[26]), "+f"(d[27]), "+f"(d[28]), "+f"(d[29]), "+f"(d[30]), "+f"(d[31]), "+f"(d[32]), "+f"(d[33]), "+f"(d[34]), "+f"(d[35]), "+f"(d[36]), "+f"(d[37]), "+f"(d[38]), "+f"(d[39]), "+f"(d[40]), "+f"(d[41]), "+f"(d[42]), "+f"(d[43]), "+f"(d[44]), "+f"(d[45]), "+f"(d[46]), "+f"(d[47]), "+f"(d[48]), "+f"(d[49]), "+f"(d[50]), "+f"(d[51]), "+f"(d[52]), "+f"(d[53]), "+f"(d[54]), "+f"(d[55])
        : "r"(a[0]), "r"(a[1]), "r"(a[2]), "r"(a[3]), "r"(db), "r"(8u), "r"(acc));
}
template <> __device__ __forceinline__ void cv_mma<2>(float (&d)[64], const uint32_t (&a)[4], uint32_t db, int acc) {
    asm volatile("{\n.reg .pred p;\n.reg .b64 b;\nsetp.ne.b32 p, %54, 0;\nmov.b64 b, {%52, %53};\n"
        "wgmma.mma_async.sync.aligned.m64n96k16.f32.bf16.bf16 {%0,%1,%2,%3,%4,%5,%6,%7,%8,%9,%10,%11,%12,%13,%14,%15,%16,%17,%18,%19,%20,%21,%22,%23,%24,%25,%26,%27,%28,%29,%30,%31,%32,%33,%34,%35,%36,%37,%38,%39,%40,%41,%42,%43,%44,%45,%46,%47}, {%48,%49,%50,%51}, b, p, 1, 1, 0;\n}\n"
        : "+f"(d[0]), "+f"(d[1]), "+f"(d[2]), "+f"(d[3]), "+f"(d[4]), "+f"(d[5]), "+f"(d[6]), "+f"(d[7]), "+f"(d[8]), "+f"(d[9]), "+f"(d[10]), "+f"(d[11]), "+f"(d[12]), "+f"(d[13]), "+f"(d[14]), "+f"(d[15]), "+f"(d[16]), "+f"(d[17]), "+f"(d[18]), "+f"(d[19]), "+f"(d[20]), "+f"(d[21]), "+f"(d[22]), "+f"(d[23]), "+f"(d[24]), "+f"(d[25]), "+f"(d[26]), "+f"(d[27]), "+f"(d[28]), "+f"(d[29]), "+f"(d[30]), "+f"(d[31]), "+f"(d[32]), "+f"(d[33]), "+f"(d[34]), "+f"(d[35]), "+f"(d[36]), "+f"(d[37]), "+f"(d[38]), "+f"(d[39]), "+f"(d[40]), "+f"(d[41]), "+f"(d[42]), "+f"(d[43]), "+f"(d[44]), "+f"(d[45]), "+f"(d[46]), "+f"(d[47])
        : "r"(a[0]), "r"(a[1]), "r"(a[2]), "r"(a[3]), "r"(db), "r"(8u), "r"(acc));
}
template <> __device__ __forceinline__ void cv_mma<3>(float (&d)[64], const uint32_t (&a)[4], uint32_t db, int acc) {
    asm volatile("{\n.reg .pred p;\n.reg .b64 b;\nsetp.ne.b32 p, %46, 0;\nmov.b64 b, {%44, %45};\n"
        "wgmma.mma_async.sync.aligned.m64n80k16.f32.bf16.bf16 {%0,%1,%2,%3,%4,%5,%6,%7,%8,%9,%10,%11,%12,%13,%14,%15,%16,%17,%18,%19,%20,%21,%22,%23,%24,%25,%26,%27,%28,%29,%30,%31,%32,%33,%34,%35,%36,%37,%38,%39}, {%40,%41,%42,%43}, b, p, 1, 1, 0;\n}\n"
        : "+f"(d[0]), "+f"(d[1]), "+f"(d[2]), "+f"(d[3]), "+f"(d[4]), "+f"(d[5]), "+f"(d[6]), "+f"(d[7]), "+f"(d[8]), "+f"(d[9]), "+f"(d[10]), "+f"(d[11]), "+f"(d[12]), "+f"(d[13]), "+f"(d[14]), "+f"(d[15]), "+f"(d[16]), "+f"(d[17]), "+f"(d[18]), "+f"(d[19]), "+f"(d[20]), "+f"(d[21]), "+f"(d[22]), "+f"(d[23]), "+f"(d[24]), "+f"(d[25]), "+f"(d[26]), "+f"(d[27]), "+f"(d[28]), "+f"(d[29]), "+f"(d[30]), "+f"(d[31]), "+f"(d[32]), "+f"(d[33]), "+f"(d[34]), "+f"(d[35]), "+f"(d[36]), "+f"(d[37]), "+f"(d[38]), "+f"(d[39])
        : "r"(a[0]), "r"(a[1]), "r"(a[2]), "r"(a[3]), "r"(db), "r"(8u), "r"(acc));
}
template <> __device__ __forceinline__ void cv_mma<4>(float (&d)[64], const uint32_t (&a)[4], uint32_t db, int acc) {
    asm volatile("{\n.reg .pred p;\n.reg .b64 b;\nsetp.ne.b32 p, %38, 0;\nmov.b64 b, {%36, %37};\n"
        "wgmma.mma_async.sync.aligned.m64n64k16.f32.bf16.bf16 {%0,%1,%2,%3,%4,%5,%6,%7,%8,%9,%10,%11,%12,%13,%14,%15,%16,%17,%18,%19,%20,%21,%22,%23,%24,%25,%26,%27,%28,%29,%30,%31}, {%32,%33,%34,%35}, b, p, 1, 1, 0;\n}\n"
        : "+f"(d[0]), "+f"(d[1]), "+f"(d[2]), "+f"(d[3]), "+f"(d[4]), "+f"(d[5]), "+f"(d[6]), "+f"(d[7]), "+f"(d[8]), "+f"(d[9]), "+f"(d[10]), "+f"(d[11]), "+f"(d[12]), "+f"(d[13]), "+f"(d[14]), "+f"(d[15]), "+f"(d[16]), "+f"(d[17]), "+f"(d[18]), "+f"(d[19]), "+f"(d[20]), "+f"(d[21]), "+f"(d[22]), "+f"(d[23]), "+f"(d[24]), "+f"(d[25]), "+f"(d[26]), "+f"(d[27]), "+f"(d[28]), "+f"(d[29]), "+f"(d[30]), "+f"(d[31])
        : "r"(a[0]), "r"(a[1]), "r"(a[2]), "r"(a[3]), "r"(db), "r"(8u), "r"(acc));
}
template <> __device__ __forceinline__ void cv_mma<5>(float (&d)[64], const uint32_t (&a)[4], uint32_t db, int acc) {
    asm volatile("{\n.reg .pred p;\n.reg .b64 b;\nsetp.ne.b32 p, %30, 0;\nmov.b64 b, {%28, %29};\n"
        "wgmma.mma_async.sync.aligned.m64n48k16.f32.bf16.bf16 {%0,%1,%2,%3,%4,%5,%6,%7,%8,%9,%10,%11,%12,%13,%14,%15,%16,%17,%18,%19,%20,%21,%22,%23}, {%24,%25,%26,%27}, b, p, 1, 1, 0;\n}\n"
        : "+f"(d[0]), "+f"(d[1]), "+f"(d[2]), "+f"(d[3]), "+f"(d[4]), "+f"(d[5]), "+f"(d[6]), "+f"(d[7]), "+f"(d[8]), "+f"(d[9]), "+f"(d[10]), "+f"(d[11]), "+f"(d[12]), "+f"(d[13]), "+f"(d[14]), "+f"(d[15]), "+f"(d[16]), "+f"(d[17]), "+f"(d[18]), "+f"(d[19]), "+f"(d[20]), "+f"(d[21]), "+f"(d[22]), "+f"(d[23])
        : "r"(a[0]), "r"(a[1]), "r"(a[2]), "r"(a[3]), "r"(db), "r"(8u), "r"(acc));
}
template <> __device__ __forceinline__ void cv_mma<6>(float (&d)[64], const uint32_t (&a)[4], uint32_t db, int acc) {
    asm volatile("{\n.reg .pred p;\n.reg .b64 b;\nsetp.ne.b32 p, %22, 0;\nmov.b64 b, {%20, %21};\n"
        "wgmma.mma_async.sync.aligned.m64n32k16.f32.bf16.bf16 {%0,%1,%2,%3,%4,%5,%6,%7,%8,%9,%10,%11,%12,%13,%14,%15}, {%16,%17,%18,%19}, b, p, 1, 1, 0;\n}\n"
        : "+f"(d[0]), "+f"(d[1]), "+f"(d[2]), "+f"(d[3]), "+f"(d[4]), "+f"(d[5]), "+f"(d[6]), "+f"(d[7]), "+f"(d[8]), "+f"(d[9]), "+f"(d[10]), "+f"(d[11]), "+f"(d[12]), "+f"(d[13]), "+f"(d[14]), "+f"(d[15])
        : "r"(a[0]), "r"(a[1]), "r"(a[2]), "r"(a[3]), "r"(db), "r"(8u), "r"(acc));
}
template <> __device__ __forceinline__ void cv_mma<7>(float (&d)[64], const uint32_t (&a)[4], uint32_t db, int acc) {
    asm volatile("{\n.reg .pred p;\n.reg .b64 b;\nsetp.ne.b32 p, %14, 0;\nmov.b64 b, {%12, %13};\n"
        "wgmma.mma_async.sync.aligned.m64n16k16.f32.bf16.bf16 {%0,%1,%2,%3,%4,%5,%6,%7}, {%8,%9,%10,%11}, b, p, 1, 1, 0;\n}\n"
        : "+f"(d[0]), "+f"(d[1]), "+f"(d[2]), "+f"(d[3]), "+f"(d[4]), "+f"(d[5]), "+f"(d[6]), "+f"(d[7])
        : "r"(a[0]), "r"(a[1]), "r"(a[2]), "r"(a[3]), "r"(db), "r"(8u), "r"(acc));
}
__device__ __forceinline__ void stsm4t(uint32_t addr, uint32_t r0, uint32_t r1, uint32_t r2, uint32_t r3) {
    asm volatile("stmatrix.sync.aligned.m8n8.x4.trans.shared.b16 [%0], {%1,%2,%3,%4};" ::"r"(addr), "r"(r0), "r"(r1), "r"(r2), "r"(r3) : "memory");
}
__device__ __forceinline__ void cp16(uint32_t dst, const void* src, int n = 16) {
    asm volatile("cp.async.cg.shared.global.L2::128B [%0], [%1], 16, %2;" ::"r"(dst), "l"(src), "r"(n) : "memory");
}
__device__ __forceinline__ void cp_arrive(uint32_t bar) { asm volatile("cp.async.mbarrier.arrive.noinc.shared::cta.b64 [%0];" ::"r"(bar) : "memory"); }
__device__ __forceinline__ void lds64(uint32_t& x, uint32_t& y, uint32_t a) { asm volatile("ld.shared.v2.b32 {%0,%1}, [%2];" : "=r"(x), "=r"(y) : "r"(a) : "memory"); }
__device__ __forceinline__ void sts128(uint32_t a, uint32_t x, uint32_t y, uint32_t z, uint32_t w) {
    asm volatile("st.shared.v4.b32 [%0], {%1,%2,%3,%4};" ::"r"(a), "r"(x), "r"(y), "r"(z), "r"(w) : "memory");
}
__device__ __forceinline__ uint32_t bfma2(uint32_t a, uint32_t b, uint32_t c) {
    uint32_t r;
    asm("fma.rn.bf16x2 %0, %1, %2, %3;" : "=r"(r) : "r"(a), "r"(b), "r"(c));
    return r;
}
#define CV_NS 4
#define CV_W 1
constexpr int CV_GC = 8 / CV_NS, CV_NA = (CV_W + 2) * CV_NS;
struct CvAddr { uint32_t pa[2], p0[4], db, rdy, xw, xr, bar; bool wrap, neg[2]; };
template <int G> __device__ __forceinline__ void cv_load(uint32_t (&a)[CV_NA][4], const CvAddr& p) {
    if constexpr (G % CV_GC == 0) mbar_wait(p.rdy + 8 * (G / CV_GC), 0);
#pragma unroll
    for (int i = G * CV_NS; i < (G + 1) * CV_NS; i++) {
        const int of = (i / 2 % 2) * CV_QG + (i / 8) * CV_SL + 256 * (i % 2 + (i / 2 & 2));
        if ((i & 5) == 0) {
#pragma unroll
            for (int e = 0; e < 4; e++) asm volatile("ld.shared.b32 %0, [%1];" : "=r"(a[i % CV_NA][e]) : "r"(p.p0[e] + of) : "memory");
            if (i < 8) { if (p.neg[0]) a[i % CV_NA][0] = 0; if (p.neg[1]) a[i % CV_NA][2] = 0; }
        } else {
            lds64(a[i % CV_NA][0], a[i % CV_NA][1], p.pa[0] + of - 256);
            lds64(a[i % CV_NA][2], a[i % CV_NA][3], p.pa[1] + of - 256);
        }
    }
}
__device__ __forceinline__ float vadd(float a, float b) {
    float r;
    asm volatile("add.f32 %0, %1, %2;" : "=f"(r) : "f"(a), "f"(b));
    return r;
}
template <int K> __device__ __forceinline__ uint32_t cv_tail(float (&d)[64], bool wrap) {
    float* z = d + 56 - 8 * K;
    z[4] = vadd(z[4], K > 0 ? z[10] : 0.f);
    if constexpr (K > 0) z[5] = vadd(z[5], z[11]);
    z[0] = vadd(z[0], z[6]);
    z[1] = vadd(z[1], z[7]);
    return pack2(wrap ? (K > 0 ? z[8] : 0.f) : z[4], wrap ? z[4] : z[0]);
}
template <int K> __device__ __forceinline__ uint32_t cv_fin(const float (&d)[64], uint32_t x) { return pack2(d[61 - 8 * K] + lo2f(x), d[57 - 8 * K] + hi2f(x)); }
template <int G>
__device__ __forceinline__ void cv_steps(float (&d)[2][64], uint32_t (&a)[CV_NA][4], uint32_t (&tv)[2][8], const CvAddr& p) {
    constexpr int K = G / CV_GC, GN = 8 * CV_GC;
    constexpr int T = G - CV_W - CV_GC, F = T - 1, TK = T / CV_GC, FK = F / CV_GC;
    if constexpr (G == 0) cv_load<0>(a, p);
    if constexpr (G < GN) {
        wgmma_fence();
#pragma unroll
        for (int i = G * CV_NS; i < (G + 1) * CV_NS; i++)
            cv_mma<K>(d[i / 2 % 2], a[i % CV_NA], p.db + (i / 2 % 2) * (CV_HPL / 8) + 16 * K + 2 * (i % 2 + (i / 2 & 2)), i & ~2 ? 1 : p.bar >> 8);
        wgmma_commit();
    }
    if constexpr (G < GN - 1) cv_load<G + 1>(a, p);
    if constexpr (T >= 0 && T % CV_GC == 0) {
        tv[0][TK] = cv_tail<TK>(d[0], p.wrap);
        tv[1][TK] = cv_tail<TK>(d[1], p.wrap);
        if constexpr (TK & 1) sts128(p.xw + TK / 2 * 512, tv[0][TK - 1], tv[0][TK], tv[1][TK - 1], tv[1][TK]);
    }
    if constexpr (F >= 0 && F % (2 * CV_GC) == CV_GC) {
        const uint4 x = lds128(p.xr + FK / 2 * 512);
        tv[0][FK - 1] = cv_fin<FK - 1>(d[0], x.x); tv[0][FK] = cv_fin<FK>(d[0], x.y);
        tv[1][FK - 1] = cv_fin<FK - 1>(d[1], x.z); tv[1][FK] = cv_fin<FK>(d[1], x.w);
    }
    if constexpr (G < GN - 1) wgmma_wait<CV_W>();
    if constexpr (G == GN - 1) wgmma_wait<0>();
    if constexpr (T >= 0 && T % (2 * CV_GC) == CV_GC) named_bar_sync(p.bar, 128);
    if constexpr (F < GN - CV_GC) cv_steps<G + 1>(d, a, tv, p);
}

#define CV_PF 7
#define Y_FIRST 1
#define Y_HOLD 0
#define PS2_EARLY 1
#define PS1_EARLY 1
#define FMOVE 1
#define SENDC 1
#define HDELAY 0
#define NH16 1
#define GST 23
#define GS2 1
#define H11 0
#define X1AT 2
#define X1B 0
#define NOF 0
#define FD 0
#define FD3 FD
#define SD3 0
#define NXP 0
#define YE 1
#define REL 3
#define W3_AT -1
constexpr int SPL2 = SPL & ~GST;
struct MegaMaps {
    CUtensorMap q, act;
    CUtensorMap a64, w1, w2, w3, w4;
    CUtensorMap k, v, y;
};

__global__ void __cluster_dims__(2, 1, 1) __launch_bounds__(384, 1)
mega_kernel(const __grid_constant__ MegaMaps tm, bf16* __restrict__ outp, bf16* act, const bf16* __restrict__ w1p, const bf16* __restrict__ w2p,
            const bf16* __restrict__ w3p, const bf16* __restrict__ xq, const bf16* __restrict__ kp, const bf16* __restrict__ vp,
            const bf16* __restrict__ shk, const bf16* __restrict__ ssk, const bf16* __restrict__ ssD) {
    extern __shared__ __align__(1024) uint8_t sgen[];
    const uint32_t sbase = smem_u32(sgen);
    const int warp = __shfl_sync(0xffffffffu, threadIdx.x >> 5, 0), lane = threadIdx.x & 31;
    const int rank = blockIdx.x & 1;
    const uint32_t s_bar = sbase + OFF_BAR;
    const uint32_t f5 = s_bar, e5 = s_bar + 64, f4 = s_bar + 144, e4 = s_bar + 104;
    const uint32_t b_rfull = s_bar + 176, b_role = s_bar + 184, b_stg = s_bar + 136, b_h2 = s_bar + 32;
    const uint32_t s_epi = sbase + OFF_EPI, s_stg = sbase + OFF_STG5, s_r = sbase + OFF_R;
    uint8_t* sm = sgen + CV_0;
    const uint32_t sb = sbase + CV_0;
    const int tid = threadIdx.x, wg = warp >> 2, w = warp & 3;
    const int d0 = blockIdx.x * CV_CH;
    const bool cv = blockIdx.x < D_ / CV_CH;
    const uint32_t b_full = sb + CV_BAR, b_rdy = b_full + 64, b_h = b_full + 128;
    GT(0);
    if (tid == 0) TM(0);
    auto row_at = [&](int r) { return sb + CV_SL + (r < 0 ? -8192 : 0) + ((r & 127) >> 5) * 1024 + (r & 7) * 128 + ((r >> 3) & 3) * 32 + ((r ^ rank) & 1) * 16; };
    auto load_kv = [&](int c) {
#pragma unroll
        for (int i = 0; i < 2; i++)
            asm volatile("cp.async.bulk.tensor.4d.shared::cluster.global.mbarrier::complete_tx::bytes.multicast::cluster [%0], [%1, {%3, %4, %4, %5}], [%2], %6;"
                         ::"r"(sb + (c + 1) * CV_SL + rank * 8192 + i * 4096), "l"((uint64_t)(i ? &tm.v : &tm.k)), "r"(b_full + 8 * c), "r"(d0 & ~15), "r"(0),
                         "r"(8 * c + 4 * rank), "h"((uint16_t)3) : "memory");
    };
    auto bulk = [&](uint32_t dst, const void* src, uint32_t n, uint32_t bar) {
        asm volatile("cp.async.bulk.shared::cluster.global.mbarrier::complete_tx::bytes [%0], [%1], %2, [%3];" ::"r"(dst), "l"(src), "r"(n), "r"(bar) : "memory");
    };
    auto put_h = [&](int ch) {
        const uint32_t dk = (tid & 127) ? 0 : *reinterpret_cast<const volatile uint32_t*>(sm + CV_BAR + 160 + 16 * wg + 2 * ch);
        uint4 v[4];
#pragma unroll
        for (int i = 0; i < 4; i++) v[i] = lds128(sbase + ch * 4096 + i * 2048 + (tid & 127) * 16);
        v[0].x = pack2(lo2f(v[0].x) + lo2f(dk), hi2f(v[0].x));
        v[2].x = pack2(lo2f(v[2].x) + hi2f(dk), hi2f(v[2].x));
#pragma unroll
        for (int i = 0; i < 4; i++)
            sts128(sb + CV_H + (2 * ch + (i & 2) + (tid & 1)) * CV_HPL + (127 - ((tid & 127) >> 1)) * 16 - (i & 1) * 1024, v[i].x, v[i].y, v[i].z, v[i].w);
    };
    int bi, bj, m0, tb;
    uint32_t ep;
    auto get_role = [&]() {
        mbar_wait(b_role, 0);
        int role;
        asm volatile("ld.shared.v2.b32 {%0,%1}, [%2];" : "=r"(role), "=r"(ep) : "r"(s_bar + 248) : "memory");
        bi = (role >> 3) * 2 + rank; bj = role & 7; m0 = bi * BM; tb = (role >> 3) * 2048 + rank * 128;
        return role < 64;
    };

    if (warp >= 8) {
        asm volatile("setmaxnreg.dec.sync.aligned.u32 88;");
        cluster_arrive_relaxed();
        if (!cv) cluster_wait(); else {
            const int bt = tid - 256, g = lane >> 2, t = lane & 3;
            if (bt < 16) sts128(row_at((bt & 7) - 8) + (bt >> 3) * 4096, 0, 0, 0, 0);
#pragma unroll
            for (int i = 0; i < 4; i++)
                cp16(row_at(bt) + i * 4096, (i & 1 ? vp : kp) + (size_t)(bt + (i >> 1) * 128) * D_ + d0);
            DBG_S(16 + (3));
            uint2 wa;
            asm volatile("ld.global.nc.v2.b32 {%0,%1}, [%2];" : "=r"(wa.x), "=r"(wa.y) : "l"(shk + (d0 + g) * 4));
            const int mi = lane >> 3, r0 = 32 * w + 8 * ((lane >> 1) & 3) - (lane & 1);
            const uint32_t ka0 = row_at(r0 + 2 * mi - 3), ka1 = row_at(r0 + 2 * (mi & 1) + 5) + (mi >> 1) * 8192;
            const uint32_t va0 = row_at(r0 + 2 * mi + 1) + 4096, va1 = row_at(r0 - 1) + 4096 + (mi & 1) * 8192;
            const uint32_t qd = sb + g * CV_QG + (32 * w + 8 * t) * 8, qd0 = qd + (t & 2) * 16, qd1 = qd + (~t & 2) * 16;
            const uint32_t w0 = __byte_perm(wa.x, 0, 0x1010), w1 = __byte_perm(wa.x, 0, 0x3232), w2 = __byte_perm(wa.y, 0, 0x1010), w3 = __byte_perm(wa.y, 0, 0x3232);
            cluster_wait();
            DBG_S(16 + (5));
            asm volatile("cp.async.wait_all;" ::: "memory");
            named_bar_sync(7, 128);
            DBG_S(16 + (1));
            struct KV { uint32_t k[2][6], v[2][5]; };
            auto get = [&](KV& x, uint32_t so) {
                ldsm4t(x.k[0][0], x.k[0][1], x.k[0][2], x.k[0][3], ka0 + so);
                ldsm4t(x.k[0][4], x.k[0][5], x.k[1][4], x.k[1][5], ka1 + so);
                ldsm4t(x.k[1][0], x.k[1][1], x.k[1][2], x.k[1][3], ka0 + so + 8192);
                asm volatile("ldmatrix.sync.aligned.m8n8.x2.trans.shared.b16 {%0,%1}, [%2];" : "=r"(x.v[0][0]), "=r"(x.v[1][0]) : "r"(va1 + so));
                ldsm4t(x.v[0][1], x.v[0][2], x.v[0][3], x.v[0][4], va0 + so);
                ldsm4t(x.v[1][1], x.v[1][2], x.v[1][3], x.v[1][4], va0 + so + 8192);
            };
            auto build = [&](int c, const KV& x, KV& nx) {
                const uint32_t so = c * CV_SL;
                DBG_F(1);
                uint32_t early;
                asm volatile("{\n.reg .pred p;\nmbarrier.test_wait.parity.shared::cta.b64 p, [%1], 0;\nvote.sync.all.pred p, p, -1;\nselp.u32 %0, 1, 0, p;\n}"
                             : "=r"(early) : "r"(b_full + 8 * (c < 7 ? c + 1 : c)) : "memory");
                if (early) get(nx, so + CV_SL);
                DBG_F(2);
                uint32_t p[8][2];
#pragma unroll
                for (int sg = 0; sg < 2; sg++) {
                    uint32_t u[5], ke[6];
#pragma unroll
                    for (int i = 0; i < 6; i++) ke[i] = __byte_perm(x.k[sg][i], x.k[sg][i ? i - 1 : 0], 0x5432);
#pragma unroll
                    for (int i = 0; i < 5; i++) {
                        u[i] = bmul2(bfma2(x.k[sg][i + 1], w0, bfma2(ke[i + 1], w1, bfma2(x.k[sg][i], w2, bmul2(ke[i], w3)))), x.v[sg][i]);
                        if (i) { p[2 * i - 1][sg] = u[i]; p[2 * i - 2][sg] = __byte_perm(u[i], u[i - 1], 0x5432); }
                    }
                }
                DBG_F(3);
#pragma unroll
                for (int j = 0; j < 4; j++) sts128((j & 2 ? qd1 : qd0) + so + 16 * (j & 1), p[2 * j][0], p[2 * j][1], p[2 * j + 1][0], p[2 * j + 1][1]);
                __syncwarp();
                DBG_F(4);
                if (lane == 0) {
                    mbar_arrive(b_rdy + 8 * c);
                    if (c == w) {
                        if (c < 3) load_kv(c + 5);
                        else { bulk(sbase + 16384, ssk + (size_t)(d0 + 4) * S_, 16384, b_h + 16); bulk(b_full + 192, ssD + d0, 16, b_h + 16); }
                    }
                    if (c == w + 4 && (CV_PF >> w & 1)) {
                        const uint32_t n = w == 0 ? 32768 : w == 3 ? 57344 : 16384;
                        const char* src = reinterpret_cast<const char*>(w == 0 ? xq : w == 1 ? w1p : w == 2 ? w2p : w3p) + (size_t)blockIdx.x * n;
                        asm volatile("cp.async.bulk.prefetch.L2.global [%0], %1;" ::"l"(src), "r"(n) : "memory");
                    }
                }
                DBG_F(5);
                named_bar_sync(7, 128);
                DBG_F(6);
                DBG_S(16 + (c == 0 ? 4 : 5 + c));
                if (!early) { mbar_wait(b_full + 8 * c + 8, 0); get(nx, so + CV_SL); }
                DBG_F(7);
            };
            KV x0, x1;
            get(x0, 0);
#pragma unroll 1
            for (int c = 0; c < 8; c += 2) { build(c, x0, x1); build(c + 1, x1, x0); }
            mbar_wait(b_h + 16, 0);
            put_h(4); put_h(6);
            fence_async_smem();
            __syncwarp();
            if (lane == 0) mbar_arrive(b_full);
            named_bar_sync(7, 128);
            DBG_S(16 + (13));
        }
    } else {
        if (elect_one()) {
            mbar_init(b_full + 8 * warp, warp ? 1 : 4);
            mbar_init(b_rdy + 8 * warp, 4);
            if (warp) mbar_expect_tx(b_full + 8 * warp, 16384);
            if (w == 0 && cv) {
                mbar_init(b_h + 8 * wg, 1);
                mbar_expect_tx(b_h + 8 * wg, 8192 + 16);
                fence_async_smem();
                bulk(sbase + wg * 8192, ssk + (size_t)(d0 + 2 * wg) * S_, 8192, b_h + 8 * wg);
                bulk(b_full + 160 + 16 * wg, ssD + d0, 16, b_h + 8 * wg);
            }
            mbar_init(s_bar + 8 * warp, 1);
            mbar_init(s_bar + 64 + 8 * warp, 4);
            mbar_init(s_bar + 128 + 8 * warp, warp < 2 ? 4 << warp : warp == 6 ? 2 : 1);
            if (wg) mbar_init(s_bar + 160 + 8 * warp, 8);
            if (warp == 0) mbar_arrive(f5);
            if (warp == 7) mbar_expect_tx(b_role, 8);
            if (warp == 1) { mbar_init(b_h + 16, 1); mbar_expect_tx(b_h + 16, 16384 + 16); }
            if (w == 2) sts128(s_bar + 224 + 16 * wg, 0, 0, 0, 0);
            asm volatile("fence.mbarrier_init.release.cluster;" ::: "memory");
            if (warp == 2) { prefetch_tmap(&tm.k); prefetch_tmap(&tm.v); }
        }
        __syncwarp();
        DBG_W(1);
        cluster_arrive_relaxed();
        asm volatile("setmaxnreg.inc.sync.aligned.u32 208;");
        DBG_W(2);
        const int zi = (tid & 127) - 32;
        if (zi >= 0 && zi < 48) sts128(sb + CV_H + (4 * wg + (zi / 6 & 3) + (zi / 24) * 8) * CV_HPL + 2048 + (zi % 6) * 16, 0, 0, 0, 0);
        DBG_W(3);
        cluster_wait();
        DBG_W(5);
        if (cv) {
            if (tid == 32) {
#pragma unroll 1
                for (int c = 1; c < 5; c++) load_kv(c);
                prefetch_tmap(&tm.y);
            }
            __syncwarp();
            DBG_W(6);
            const int g = lane >> 2, t = lane & 3;
            const int x0 = 32 + 8 * w + g - 2 * t;
            CvAddr p;
            p.rdy = b_rdy;
            p.bar = 1 + wg;
            p.xr = sbase + (warp ^ 2) * 2048 + lane * 16;
            p.xw = sbase + warp * 2048 + (g * 4 + ((t - (w >> 1)) & 3)) * 16;
            p.wrap = t == 0 && w >= 2;
            mbar_wait(b_h + 8 * wg, 0);
            DBG_W(4);
            put_h(2 * wg);
            fence_async_smem();
            named_bar_sync(1 + wg, 128);
            float acc[2][64];
            zero_acc(acc[0]); zero_acc(acc[1]);
#pragma unroll 1
            for (int round = 0; round < 2; round++) {
                const int ch = round * 4 + 2 * wg;
                uint32_t a[CV_NA][4], tv[2][8];
#pragma unroll
                for (int e = 0; e < 2; e++) {
                    const int x = x0 - 8 * e;
                    p.neg[e] = x < 32;
                    p.pa[e] = sb + ch * CV_QG + 8 * (x ^ (x >> 2 & 4));
                    p.p0[2 * e] = p.pa[e] + (x < 32 ? 768 + 4 - CV_SL : -256);
                    p.p0[2 * e + 1] = p.pa[e] + (x < 32 ? 768 : -256 + 4);
                }
                p.db = (((sb + CV_H + ch * 2 * CV_HPL) & 0x3FFFF) >> 4) | ((CV_HPL / 16) << 16);
                if (round) mbar_wait(b_full, 0);
                DBG_S(7 + 3 * round);
                cv_steps<0>(acc, a, tv, p);
                DBG_S(8 + 3 * round);
                const int r128 = 4 * (lane >> 3) + 2 * (lane & 1) + ((~lane >> 2) & 1);
#pragma unroll
                for (int i = 0; i < 2; i++) {
                    const uint32_t ta = sb + ((ch + i + 1) & 7) * CV_SL + 12288 + r128 * 128 + ((((~lane & 2) * 2 + w) ^ (r128 & 7)) << 4);
                    stsm4t(ta, tv[i][0], tv[i][1], tv[i][2], tv[i][3]);
                    stsm4t(ta + 2048, tv[i][4], tv[i][5], tv[i][6], tv[i][7]);
                }
                if (!(GST & 2)) fence_async_smem();
                named_bar_sync(1 + wg, 128);
                if (GST & 2) {
                    const int l = 4 * w + (lane >> 3);
                    uint4 v[4];
#pragma unroll
                    for (int i = 0; i < 4; i++) v[i] = lds128(sb + ((ch + (i >> 1) + 1) & 7) * CV_SL + 12288 + (i & 1) * 2048 + l * 128 + (((lane ^ l) & 7) << 4));
                    const int yr = YE ? (d0 & 128) + round * 68 + ((d0 >> 1 & 60) ^ 2 * wg) - (d0 & 8) * round : (d0 + ch) & 255;
                    bf16* gy = act + (size_t)(R_Y + w * 2048 + yr) * D_ + (d0 & ~255) + lane * 8;
#pragma unroll
                    for (int i = 0; i < 4; i++) stg128(gy + ((i & 1) * 8192 + (i >> 1)) * D_, v[i]);
                    if (YE) named_bar_arrive(4 + 8 * round, 288);
                } else if ((tid & 127) < 2) {
                    const int d = d0 + ch + (tid & 1);
                    asm volatile("cp.async.bulk.tensor.4d.global.shared::cta.bulk_group [%0, {%2, %3, %4, %2}], [%1];"
                                 ::"l"((uint64_t)&tm.y), "r"(sb + ((ch + (tid & 1) + 1) & 7) * CV_SL + 12288), "r"(0), "r"(4 * (d >> 8)), "r"(d & 255) : "memory");
                    asm volatile("cp.async.bulk.commit_group;" ::: "memory");
                }
                __syncwarp();
                DBG_S(9 + 3 * round);
            }
        }
    }
    int warp2 = warp;
    asm volatile("" : "+r"(warp2));
    if (warp2 >= 8) {
        asm volatile("setmaxnreg.dec.sync.aligned.u32 72;");
        if (warp == 8) { if (elect_one()) {
            if (rank == 0) {
                uint32_t smid;
                asm volatile("mov.u32 %0, %%smid;" : "=r"(smid));
                const int t = smid >> 1;
                int team = t < 32 ? t & 7 : t < 60 ? 1 + (t - 32) % 7 : t < 62 ? t - 54 : 0;
                const unsigned long long arr = atomicAdd(reinterpret_cast<unsigned long long*>(g_ticket + 16 * FL_PITCH), 1ull);
                const uint32_t e1 = (uint32_t)(arr / NCL) + 1;
                unsigned int* tk = g_ticket + (e1 & 1) * 8 * FL_PITCH;
                int slot = atomicAdd(tk + team * FL_PITCH, 1u);
                atomicAdd(g_ticket + 17 * FL_PITCH, 1u);
                if (blockIdx.x < 16) g_ticket[((~e1 & 1) * 8 + (blockIdx.x >> 1)) * FL_PITCH] = 0;
                if (slot >= 8) {
                    const long long t0 = clock64();
                    while ((int)(*(volatile unsigned int*)(g_ticket + 17 * FL_PITCH) - e1 * NCL) < 0 && clock64() - t0 < 100000) {}
                    for (team = 0; team < 8; team++)
                        if ((slot = atomicAdd(tk + team * FL_PITCH, 1u)) < 8) break;
                }
#pragma unroll
                for (int i = 0; i < 2; i++)
                    asm volatile("st.async.weak.shared::cluster.mbarrier::complete_tx::bytes.v2.b32 [%0], {%1, %2}, [%3];"
                                 ::"r"(mapa_u32(s_bar + 248, i)), "r"(team * 8 + slot), "r"(e1), "r"(mapa_u32(b_role, i)) : "memory");
            }
            if (get_role()) {
            TM(2);
            mbar_expect_tx(b_rfull, 32768);
            tma_load_2d(sbase + 16384, &tm.q, b_rfull, bj * 128, m0);
            tma_load_2d(sb + 8 * CV_SL, &tm.q, b_rfull, bj * 128 + 64, m0);
            int s5 = 0, s4 = 0;
            uint32_t p5 = 0, p4 = 1;
            auto putB = [&](const CUtensorMap* tB, int kc, uint32_t bytes) {
                const uint32_t full = f5 + 8 * s5;
                mbar_wait(full + 64, (p5 >> s5) & 1);
                mbar_expect_tx(full, bytes);
                tma_load_2d_mc(s_r + 16384 + rank * 8192 + s5 * R5_STAGE, tB, full, bj * 128 + rank * 64, kc);
                p5 ^= 1u << s5;
            };
            auto putA = [&](int c, int r) {
                tma_load_2d(s_r + s5 * R5_STAGE, &tm.act, f5 + 8 * s5, c, r);
                if (++s5 == R5_N) s5 = 0;
            };
            prefetch_tmap(&tm.act); prefetch_tmap(&tm.w1); prefetch_tmap(&tm.w2); prefetch_tmap(&tm.w3); prefetch_tmap(&tm.w4); prefetch_tmap(&tm.a64);
            auto own_first = [&](int it) {
                const int hf = it >= 9, c = it - 2 - 7 * hf;
                return (it < 2 ? 2 * bj + it : 2 * (c + (c >= bj)) + hf) * BK;
            };
            const unsigned int n8 = 8 * ep, nh = NH16 ? ((bi == 0 || bi == 15) ? 12 * ep : 2 * n8) : (bi == 0 || bi == 15) ? 2 * n8 : 3 * n8;
#pragma unroll 1
            for (int layer = 0; layer < 2; layer++) {
                s5 = 2;
#pragma unroll 1
                for (int kk = -(layer | Y_FIRST); kk < 5 - (layer | Y_FIRST); kk++) {
                    if (kk & 4) {
                        mbar_wait(e5 + 8, (p5 >> 1) & 1);
                        mbar_expect_tx(f5 + 8, 32768);
#pragma unroll 1
                        for (int i = 0; i < 4; i++) {
                            if (layer == 0 && !(i & 1)) { wait_flag(flag_ptr(1 - (i >> 1), FL_CS, 8 + bj), 8 * n8); TM(4); fence_proxy_async(); }
                            tma_load_2d(s_r + R5_STAGE + (i & 1) * 16384 + (i >> 1) * 8192, &tm.a64, f5 + 8, (bj >> 1) * 256 + rank * 128 + (i & 1) * 64,
                                        R_Y + (tb & ~255) + (bj & 1) * 128 + (i >> 1) * 64);
                        }
                        p5 ^= 2;
                        if (layer == 0) TM(5);
                    } else {
                        if (kk == Y_HOLD && layer == 0) mbar_wait(f5 + 8, 0);
                        putB(&tm.w1, own_first(kk), kk < 2 ? 16384 : R5_STAGE);
                        if (++s5 == R5_N) s5 = 0;
                    }
                }
                s5 = 4;
#pragma unroll 1
                for (int kk = 2; kk < 16; kk++) {
                    const int kc = own_first(kk);
                    if (kk >= 4) putB(&tm.w1, kc, R5_STAGE);
                    if (kk == 2 || kk == 9) {
                        wait_flag(flag_ptr(layer, FL_XA + (kk & 1), bi), n8);
                        if (layer == 0 && kk == 2) TM(14);
                        DP(8 * (FL_XA + (kk & 1)) + 3);
                        fence_proxy_async();
                        DP(8 * (FL_XA + (kk & 1)) + 4);
                    }
                    putA(kc, R_XA + tb);
                }
                mbar_wait(e5 + 24, (p5 >> 3) & 1);
                mbar_arrive(f5 + 24);
                p5 ^= 8;
                s5 = 4;
#pragma unroll 1
                for (int kk = 0; kk < 5; kk++) { putB(&tm.w2, own_first(kk), kk < 2 ? 16384 : R5_STAGE); if (++s5 == R5_N) s5 = 0; }
                s5 = 1;
#pragma unroll 1
                for (int kk = 2; kk < 16; kk++) {
                    const int kc = own_first(kk);
                    if (kk >= 5) putB(&tm.w2, kc, R5_STAGE);
                    if (kk == 2 || kk == 9) {
                        wait_flag(flag_ptr(layer, FL_H + (kk & 1), bi), nh);
                        DP(8 * (FL_H + (kk & 1)) + 3);
                        fence_proxy_async();
                        DP(8 * (FL_H + (kk & 1)) + 4);
                    }
                    putA(kc, R_H + layer * R_HP + m0 + (int)((0x4031u >> (kc >> 6 & 12)) & 7) - 2);
                }
#pragma unroll 1
                for (int it = 0; it < 32; it++) {
                    const int kc = it >= 16 ? (it - 16) * BK : own_first(it);
                    const int nb = it < 16 ? 4 : 3, n0 = bj * 448 + (it < 16 ? 0 : 256);
                    if (it > 0 && it < 4) {
                        const int i = (it - 1) * 3 >> 1;
                        mbar_wait(e5 + 8 * i, (p5 >> i) & 1);
                        mbar_wait(e5 + 8 * i + 8, (p5 >> (i + 1)) & 1);
                    }
                    mbar_wait(e4 + 8 * s4, p4);
                    if (it >= 16 && it < 19) mbar_wait(e4 + 8 * s4 + 8, p4);
                    uint32_t sa = s_r + s4 * (it < 16 ? R4_STAGE : R4B_STAGE), full = f4 + 8 * s4;
                    mbar_expect_tx(full, (it < 2 ? 0 : 16384) + nb * 8192);
                    if (X1B && it == 2) wait_flag(flag_ptr(layer, FL_X1, bi), X1B == 1 ? n8 : n8 - 8 + X1B);
#pragma unroll 1
                    for (int j = (it ^ rank) & 1; j < nb; j += 2) tma_load_2d_mc(sa + (it < 16 ? -32768 : 16384) + j * 8192, &tm.w3, full, n0 + j * 64, kc);
                    if (it == X1AT || it == 9) {
                        wait_flag(flag_ptr(layer, FL_X1 + (it >> 3), bi), n8);
                        DP(8 * (FL_X1 + (it >> 3)) + 3);
                        fence_proxy_async();
                        DP(8 * (FL_X1 + (it >> 3)) + 4);
                        if (X1AT == 3 && it == 3) tma_load_2d(s_r + 2 * R4_STAGE, &tm.act, f4 + 16, own_first(2), R_X1 + tb);
                    }
                    if (it >= X1AT) tma_load_2d(sa, &tm.act, full, kc, R_X1 + tb);
                    if (it >= PF4A && it < PF4A + PF4N && layer == 0) tma_prefetch_2d(&tm.w4, bj * 128 + rank * 64, (7 * (bi >> 1) + it - PF4A) * BK);
                    if (++s4 == R4_N) { s4 = 0; p4 ^= 1; }
                }
                wait_flag(flag_ptr(layer, FL_H2, bi), n8);
                fence_proxy_async();
                s5 = 0;
#pragma unroll 1
                for (int j = 0; j < 7; j++) {
                    if (j > 0 && (j & 1) == 0) {
                        mbar_wait(b_h2 + 4 * j, layer);
                        fence_proxy_async();
                    }
                    const int ra = R_H2 + (j >> 1) * 256 + tb;
#pragma unroll 1
                    for (int b = 0; b < 8; b++) {
                        if (j == 0 && b < R4_N) mbar_wait(e4 + 8 * b, p4);
                        putB(&tm.w4, (7 * b + j) * BK, R5_STAGE);
                        putA(((j & 1) * 8 + b) * BK, ra);
                    }
                }
            }
        } } } else {
            auto colsum = [&](bool is1, int bi, int bj) {
                const int pitch = is1 ? D_ : F_, c = is1 ? bj * 128 + (lane & 15) * 8 : bj * 448 + min((warp & 2) * 128 + lane * 8, 440);
                const bf16* p = (is1 ? w1p : w3p) + ((bi * 64 + (is1 ? (lane >> 4) * 32 : 0)) * pitch + c);
                float a[8];
#pragma unroll
                for (int i = 0; i < 8; i++) a[i] = 0.f;
#pragma unroll 1
                for (int r0 = is1 ? 32 : XCS; r0 < 64; r0 += 8) {
                    uint4 v[8];
#pragma unroll
                    for (int r = 0; r < 8; r++, p += pitch) v[r] = __ldg(reinterpret_cast<const uint4*>(p));
#pragma unroll
                    for (int r = 0; r < 8; r++) {
                        a[0] += lo2f(v[r].x); a[1] += hi2f(v[r].x); a[2] += lo2f(v[r].y); a[3] += hi2f(v[r].y);
                        a[4] += lo2f(v[r].z); a[5] += hi2f(v[r].z); a[6] += lo2f(v[r].w); a[7] += hi2f(v[r].w);
                    }
                }
                if (is1) {
#pragma unroll
                    for (int i = 0; i < 8; i++) a[i] += __shfl_xor_sync(0xffffffffu, a[i], 16);
                }
                float4* dst = reinterpret_cast<float4*>(g_cpart + bi * (F_ + D_) + (is1 ? F_ : 0) + c);
                dst[0] = make_float4(a[0], a[1], a[2], a[3]);
                dst[1] = make_float4(a[4], a[5], a[6], a[7]);
                asm volatile("fence.release.gpu;" ::: "memory");
                __syncwarp();
                if (lane == 0) asm volatile("red.relaxed.gpu.global.add.u32 [%0], 1;" ::"l"(flag_ptr(!is1, FL_CS, bj)) : "memory");
            };
            if (cv && warp == 10) colsum(true, blockIdx.x >> 3, blockIdx.x & 7);
            if ((GST & 2) && cv && warp == 9) {
#pragma unroll 1
                for (int round = !YE; round < 2; round++) {
                    named_bar_sync(4 + 8 * round, 288);
                    if (lane == 0) {
                        if (!(NOF & 2)) asm volatile("fence.release.gpu;" ::: "memory");
                        asm volatile("red.relaxed.gpu.global.add.u32 [%0], 4;" ::"l"(flag_ptr(round ^ 1, FL_CS, 8 + (blockIdx.x >> 4))) : "memory");
                    }
                    __syncwarp();
                }
            }
            auto halo = [&](int layer) {
                const int dn = bj & 2 ? 1 : -1;
                const uint4* gh = g_halo + (layer * 144 + 8 + bi * 8 + bj) * 64 + lane;
                uint4 v[2] = {};
#pragma unroll 1
                for (int n = (bi + dn) & 16 ? 1 << 20 : 0; n < (1 << 20); n++) {
#pragma unroll
                    for (int i = 0; i < 2; i++)
                        asm volatile("{\n.reg .b64 u, v;\nld.relaxed.gpu.global.v2.b64 {u, v}, [%4];\nmov.b64 {%0, %1}, u;\nmov.b64 {%2, %3}, v;\n}"
                                     : "=r"(v[i].x), "=r"(v[i].y), "=r"(v[i].z), "=r"(v[i].w) : "l"(gh + 32 * i) : "memory");
                    if (v[0].y == ep && v[0].w == ep && v[1].y == ep && v[1].w == ep) break;
                }
#pragma unroll
                for (int i = 0; i < 2; i++)
                    asm volatile("st.shared.v2.b32 [%0], {%1, %2};" ::"r"(s_stg + 1024 + i * OFF_EPI + (63 + 65 * dn) * 128 + 8 * lane), "r"(v[i].x), "r"(v[i].z) : "memory");
                fence_async_smem();
                __syncwarp();
                DP(8 * FL_H + 5);
                named_bar_arrive(14, 160);
            };
            float4 keep[2];
            const bool on = get_role();
            if (on && warp == 11) {
                uint4* ps = reinterpret_cast<uint4*>(g_stats + (bi * 8 + bj) * 128) + lane;
                ps[0] = ps[32] = make_uint4(0, 0, 0, 0);
                asm volatile("fence.acq_rel.gpu;" ::: "memory");
                __syncwarp();
                if (lane == 0) mbar_arrive(b_rfull);
            }
#pragma unroll 1
            for (int layer = on ? 0 : 2; layer < 2; layer++) {
                if (warp == 10) {
#pragma unroll 1
                    for (int kind = 0; kind < 6; kind += 2) {
                        const uint32_t src = kind == FL_H ? s_stg + 1024 : s_epi, sd = kind == FL_H ? OFF_EPI : 16384;
                        const int dn = bj & 2 ? 1 : -1;
                        const int r = kind == FL_H ? R_H + layer * R_HP + m0 : (kind == FL_XA ? R_XA : R_X1) + tb;
#pragma unroll 1
                        for (int hf = 0; hf < 2; hf++) {
                            const bool sp = hf == 0 && (SPL2 >> kind & 1);
                            const int lw = kind == FL_H && dn < 0 ? 64 : 0;
                            if (sp) {
                                named_bar_sync(7, 160);
                                if (lane == 0) {
                                    fence_async_smem();
                                    tma_store_2d(&tm.a64, src + lw * 128, bj * 128, r + lw);
                                }
                                __syncwarp();
                            }
                            named_bar_sync(5 + hf, sp ? 160 : 288);
                            DQ(0);
                            if (lane == 0 && !((hf ? GS2 : GST) >> kind & 1)) {
                                if (FMOVE) fence_async_smem();
                                if (SD3 && kind == FL_X1) __nanosleep(SD3);
                                tma_store_2d(sp ? &tm.a64 : &tm.act, src + (sp ? (lw ^ 64) * 128 : hf * sd), bj * 128 + hf * 64, sp ? r + (lw ^ 64) : r);
                                asm volatile("cp.async.bulk.commit_group;" ::: "memory");
                            }
                            __syncwarp();
                            if (!H11 && kind + hf == FL_H + 1) halo(layer);
                            if (lane == 0) {
                                asm volatile("cp.async.bulk.wait_group 0;" ::: "memory");
                                if (FD && hf) __nanosleep(kind == FL_X1 ? FD3 : FD);
                                DQ(1);
                                if (!(NOF >> (hf ? 3 : kind) & 1)) asm volatile("fence.release.gpu;" ::: "memory");
                                DQ(2);
                                unsigned int* fp = flag_ptr(layer, kind + hf, bi);
                                asm volatile("red.relaxed.gpu.global.add.u32 [%0], 1;" ::"l"(fp) : "memory");
                                if (kind == FL_H) {
                                    if (bi > 0 && (!NH16 || dn > 0)) asm volatile("red.relaxed.gpu.global.add.u32 [%0], 1;" ::"l"(fp - FL_PITCH) : "memory");
                                    if (bi < 15 && (!NH16 || dn < 0)) asm volatile("red.relaxed.gpu.global.add.u32 [%0], 1;" ::"l"(fp + FL_PITCH) : "memory");
                                }
                            }
                            __syncwarp();
                        }
                    }
                } else {
                    uint32_t* rs = reinterpret_cast<uint32_t*>(sgen + OFF_RS);
                    float* cs = reinterpret_cast<float*>(sgen + OFF_CS);
#pragma unroll 1
                    for (int which = 0; which < 2; which++) {
                        if (layer < which) {
                            if (warp == 11 && lane == 0) {
                                if (W3_AT == 0 || W3_AT == 1) wait_flag(flag_ptr(0, FL_XA + (W3_AT & 1), bi), 8 * ep);
                                if (W3_AT == 5) mbar_wait(f5 + 8, 0);
                                asm volatile("cp.async.bulk.prefetch.L2.global [%0], %1;" ::"l"(w3p + (bi * 8 + bj) * 28672), "r"(57344) : "memory");
                                if (W3_AT == 2 || W3_AT == 3) wait_flag(flag_ptr(0, FL_XA + (W3_AT & 1), bi), 8 * ep);
                                if (W3_AT == 4) mbar_wait(f5 + 8, 0);
                            }
                            __syncwarp();
                            colsum(false, bi, bj);
                        }
                        if (warp == 11) {
                            if (H11 && which) { named_bar_sync(4, 160); halo(layer); }
                            continue;
                        }
                        if (layer == 0) {
                            if (lane == 0) wait_flag(flag_ptr(which, FL_CS, bj), (16 << which) * ep);
                            __syncwarp();
#pragma unroll 1
                            for (int c = (which ? 384 : 768) + lane * 4; c < 896; c += 128) {
                                const float* cp = g_cpart + (which ? bj * 448 + min(c & 511, 444) : F_ + bj * 128 + lane * 4);
                                float4 a = make_float4(0.f, 0.f, 0.f, 0.f);
#pragma unroll
                                for (int r0 = 0; r0 < 16; r0 += 8) {
                                    float4 v[8];
#pragma unroll
                                    for (int r = 0; r < 8; r++) v[r] = __ldcg(reinterpret_cast<const float4*>(cp + (r0 + r) * (F_ + D_)));
#pragma unroll
                                    for (int r = 0; r < 8; r++) { a.x += v[r].x; a.y += v[r].y; a.z += v[r].z; a.w += v[r].w; }
                                }
                                if (c < 768) *reinterpret_cast<float4*>(cs + min(c & 511, 444)) = a;
                                keep[0] = a;
                            }
                        }
                        if (lane == 0 && (layer | which)) wait_flag(flag_ptr(layer, which == 0 ? FL_XA : FL_X1, bi), 8 * ep);
                        __syncwarp();
                        *reinterpret_cast<float4*>(cs + 256 + lane * 4) = keep[0];
                        { const float4 k0 = keep[0]; keep[0] = keep[1]; keep[1] = k0; }
#pragma unroll 1
                        for (int i = 0; i < 4; i++) {
                            const int r = i * 32 + lane;
                            float mean, var;
                            row_stats(g_stats + (1 + which) * S_ * 8 + bi * 1024 + r, ~layer << 31, mean, var);
                            const uint32_t c0 = pack2(mean, fsqrt(bfr(bfr(var) + 1e-5f)));
                            if (lane < 19 && (layer | which | i) == 0) asm volatile("mbarrier.inval.shared::cta.b64 [%0];" ::"r"(b_full + 8 * lane) : "memory");
                            __syncwarp();
                            rs[r] = c0;
                            const float rd = frcp(hi2f(c0));
                            rs[128 + r] = pack2((mean - lo2f(c0)) * rd, fsqrt(bfr(bfr(var * rd * rd) + 1e-5f)));
                        }
                        __syncwarp();
                        named_bar_arrive(3, 160);
                        named_bar_arrive(11, 160);
                    }
                }
                const uint32_t s_cnt = s_bar + 224;
                auto ticket = [&](uint32_t a) {
                    uint32_t v = 0;
                    if (lane == 0) asm volatile("atom.acq_rel.cta.shared.add.u32 %0, [%1], 1;" : "=r"(v) : "r"(a) : "memory");
                    return v;
                };
                auto next = [&]() {
                    uint32_t v = 0;
                    if (lane == 0) asm volatile("atom.relaxed.cta.shared.add.u32 %0, [%1], 1;" : "=r"(v) : "r"(s_cnt + 16 + 4 * layer) : "memory");
                    return v;
                };
                mbar_wait(b_stg, layer);
                int u = __shfl_sync(0xffffffffu, next(), 0), step = 0;
#pragma unroll 1
                while (true) {
#pragma unroll 1
                    for (; step < 5 && u >= (int)((0x3830201810ull >> (8 * step)) & 255); step++) {
                        if (step == 1) { named_bar_arrive(4, 224); named_bar_arrive(12, 224); continue; }
                        const int part = step ? step - 1 : 0;
                        __syncwarp();
                        if (ticket(s_cnt + 4 * part) == 3 * layer + 2) {
                            asm volatile("fence.release.gpu;" ::: "memory");
                            unsigned int* fp = flag_ptr(layer, FL_H2 + part, bi);
                            asm volatile("red.relaxed.gpu.global.add.u32 [%0], 1;" ::"l"(fp) : "memory");
                            if (part > 0) { wait_flag(fp, 8 * ep); mbar_arrive(b_h2 + 8 * part); }
                        }
                        __syncwarp();
                    }
                    if (u >= 56) break;
                    const uint32_t un = next();
                    const int job = u >> 3, r = (u & 7) * 16 + (lane >> 3);
                    if (job >= 2) mbar_wait(s_bar + 168 + 8 * max(job, 3), layer);
                    const uint32_t sp = sbase + ((job & 2) ? OFF_STG5 : OFF_EPI) + r * 256 + (job & 1) * 128;
                    bf16* gp = act + (size_t)(R_H2 + (job >> 1) * 256 + tb + r) * D_ + ((job & 1) * 8 + bj) * 64 + (lane & 7) * 8;
                    uint4 v[4];
#pragma unroll
                    for (int e = 0; e < 4; e++) v[e] = lds128(sp + e * 1024 + (((lane & 7) ^ ((r + 4 * e) & 7)) << 4));
#pragma unroll
                    for (int e = 0; e < 4; e++) stg128(gp + 4 * e * D_, gelu8h(v[e]));
                    u = __shfl_sync(0xffffffffu, un, 0);
                }
                if (layer == 0 && warp == 11) {
                    const char* ps = reinterpret_cast<const char*>(g_stats + bi * 1024) + lane * 128;
                    const char* py = reinterpret_cast<const char*>(act + (size_t)(R_Y + (tb & ~255) + (bj & 1) * 128 + (lane >> 1)) * D_ + (bj >> 1) * 256 + rank * 128) + (lane & 1) * 128;
#pragma unroll 1
                    for (int i = 0; i < 8; i++) {
                        asm volatile("prefetch.global.L2 [%0];" ::"l"(py + (size_t)i * 16 * D_ * 2) : "memory");
                        if (i >= 6) asm volatile("prefetch.global.L2 [%0];" ::"l"(ps + (i & 1) * 4096) : "memory");
                        __nanosleep(400);
                    }
                }
            }
        }
        __syncwarp();
        asm volatile("barrier.cluster.arrive.relaxed.aligned;\nbarrier.cluster.wait.acquire.aligned; // helpers" ::: "memory");
    } else {
        DT_DECL;
        DT(0);
        auto put_y = [&]() {
            if (GST & 2) { if (cv && !YE) named_bar_arrive(12, 288); }
            else if ((tid & 127) < 2 && cv) {
                asm volatile("cp.async.bulk.wait_group 0;" ::: "memory");
                if (REL & 2) asm volatile("fence.release.gpu;" ::: "memory");
                asm volatile("red.relaxed.gpu.global.add.u32 [%0], 1;" ::"l"(flag_ptr(0, FL_CS, 8 + (blockIdx.x >> 4))) : "memory");
            }
            __syncwarp();
        };
        put_y();
        DT(24);
        asm volatile("setmaxnreg.inc.sync.aligned.u32 216;");
        if (get_role()) {
        const bool rel_on = (tid & 95) == 0;
        const uint32_t rel5 = mapa_u32(e5, (warp & 1) ^ rank), rel4 = rel5 + (e4 - e5);
        const uint32_t da0 = desc_a(s_r + wg * 8192), db0 = desc_b(s_r + BM * BK * 2), dae = da0 + (OFF_EPI - OFF_R) / 16, db4 = db0 - 49152 / 16;
        auto skip5 = [&](RingState& rs) {
            if (rel_on) mbar_arrive_cluster(rel5 + 8 * rs.st);
            rs.st++;
        };
        const int t = lane & 3;
        const int row = warp * 16 + (lane >> 2);
        const uint32_t st_w = (uint32_t)((warp * 16 + ((lane >> 3) & 1) * 8 + (lane & 7)) * 256 + (((lane >> 4) ^ (lane & 7)) << 4));
        const uint32_t fr = (uint32_t)((warp * 16 + ((lane >> 3) & 1) * 8 + (lane & 7)) * 128 + (((lane >> 4) ^ (lane & 7)) << 4));
        auto copy_out = [&](bf16* dst, uint32_t src) {
            const int r = warp * 16 + (lane >> 4);
            bf16* ox = dst + (size_t)(m0 + r) * D_ + bj * 128 + (lane & 15) * 8;
            const uint32_t ra = src + ((lane & 15) >> 3) * 16384 + r * 128;
            uint4 v[8];
#pragma unroll
            for (int it = 0; it < 8; it++) v[it] = lds128(ra + it * 256 + (((lane & 7) ^ ((2 * it + (lane >> 4)) & 7)) << 4));
#pragma unroll
            for (int it = 0; it < 8; it++) *reinterpret_cast<uint4*>(ox + (size_t)it * 2 * D_) = v[it];
        };
        auto put_half = [&](uint32_t src, int r0, int hf) {
            const int r = warp * 16 + (lane >> 3);
            bf16* gp = act + (size_t)(r0 + r) * D_ + bj * 128 + hf * 64 + (lane & 7) * 8;
            uint4 v[4];
            __syncwarp();
#pragma unroll
            for (int i = 0; i < 4; i++) v[i] = lds128(src + (r + 4 * i) * 128 + (((lane ^ (r + 4 * i)) & 7) << 4));
#pragma unroll
            for (int i = 0; i < 4; i++) stg128(gp + 4 * i * D_, v[i]);
        };
        auto put_stats = [&](const uint32_t (&w)[32], int which, int layer) {
            float c[6][4];
#pragma unroll
            for (int e = 0; e < 32; e++) {
                hmma8(c[e & 3], w[e & ~1], w[e | 1], w[e], e < 4);
                if ((e & 3) == 0) hmma(c[4 + (e >> 2 & 1)], w[e], w[e + 1], w[e + 2], w[e + 3], 0x3f803f80u, 0x3f803f80u, e < 8);
            }
            if (t == lane >> 3) {
#pragma unroll
                for (int e = 0; e < 2; e++) {
                    const float q1 = lane & 4 ? c[e][2 * e + 1] + c[e + 2][2 * e + 1] : c[e][2 * e] + c[e + 2][2 * e], s1 = c[4][2 * e] + c[5][2 * e], mu = s1 * (1.0f / 128);
                    asm volatile("{\n.reg .b64 t;\nmov.b64 t, {%1, %2};\nst.relaxed.gpu.global.b64 [%0], t;\n}"
                                 ::"l"(g_stats + which * S_ * 8 + (bi * 8 + bj) * 128 + row + 8 * e), "f"(mu), "r"(__float_as_uint(fmaxf(q1 - s1 * mu, 0.f)) | ~layer << 31) : "memory");
                }
            }
        };
        auto split = [](float r) { const float h = bfr(r); return pack2(h, r - h); };
        auto norm2 = [](uint32_t x, uint32_t m, uint32_t r) {
            const uint32_t d = bsub2(x, m);
            return bfma2(d, __byte_perm(r, 0, 0x1010), bmul2(d, __byte_perm(r, 0, 0x3232)));
        };
        const float* csp = reinterpret_cast<const float*>(sgen + OFF_CS) + 2 * t;
        float mrow[2], rrow[2];
        const uint32_t* rsp = reinterpret_cast<const uint32_t*>(sgen + OFF_RS) + row;
        auto row_consts = [&](bool twice) {
#pragma unroll
            for (int e = 0; e < 2; e++) {
                const uint32_t q0 = rsp[8 * e], q1 = rsp[128 + 8 * e];
                mrow[e] = twice ? fmaf(lo2f(q1), hi2f(q0), lo2f(q0)) : lo2f(q0);
                rrow[e] = 0.5f * frcp(twice ? hi2f(q0) * hi2f(q1) : hi2f(q0));
            }
        };
        auto keep_consts = [&](float2 (&cs)[8]) {
#pragma unroll
            for (int e = 0; e < 8; e++) asm volatile("" : "+f"(cs[e].x), "+f"(cs[e].y));
            asm volatile("" : "+f"(mrow[0]), "+f"(mrow[1]), "+f"(rrow[0]), "+f"(rrow[1]));
        };
        RingState r5{1, 0}, r4{0, 0};
        DT(1);
        uint32_t x[32];
        mbar_wait(b_rfull, 0);
#pragma unroll
        for (int jp = 0; jp < 8; jp++) ldsm4(x[4 * jp], x[4 * jp + 1], x[4 * jp + 2], x[4 * jp + 3], sbase + 16384 + (fr ^ ((jp & 3) << 5)) + (jp >> 2) * (16384 + 8 * CV_SL));
#pragma unroll
        for (int e = 0; e < 32; e++) asm volatile("" : "+r"(x[e]));
        named_bar_sync(9 + wg, 128);
        if ((tid & 95) < R5_N) mbar_arrive_cluster(rel5 + 8 * lane);
#pragma unroll 1
        for (int layer = 0; layer < 2; layer++) {
            {
                DT(2 + 24 * layer);
                put_stats(x, 0, layer);
                DT(20 + 24 * layer);
                DT(22 + 24 * layer);
                uint32_t mb[2], rd[2];
                {
                    float mean, var;
                    row_stats(g_stats + bi * 1024 + warp * 16 + (lane & 15), ~layer << 31, mean, var);
                    __syncwarp();
                    const uint32_t r1 = split(frcp(bfr(fsqrt(bfr(bfr(var) + 1e-5f)))));
                    const uint32_t m1 = pack2(mean, mean);
#pragma unroll
                    for (int e = 0; e < 2; e++) { mb[e] = __shfl_sync(0xffffffffu, m1, (lane >> 2) + 8 * e); rd[e] = __shfl_sync(0xffffffffu, r1, (lane >> 2) + 8 * e); }
                }
                DT(21 + 24 * layer);
                uint32_t nx[NXP + 1];
#pragma unroll
                for (int e = 0; e < NXP; e++) { nx[e] = norm2(x[e], mb[e & 1], rd[e & 1]); asm volatile("" : "+r"(nx[e])); }
                mbar_wait(f5 + 8, r5.ph);
                DT(23 + 24 * layer);
                const int yl = YE ? ((lane >> 2 & 4) ^ (lane & 7)) + (lane & 4) * 16 : (lane >> 4) * 8 + (lane & 7);
                const uint32_t ya = s_r + R5_STAGE + wg * 16384 + yl * 128 + ((((warp & 3) * 2 + ((lane >> 3) & 1)) ^ (yl & 7)) << 4);
                uint32_t y[16];
#pragma unroll
                for (int e = 0; e < 32; e++) {
                    if ((e & 15) == 0) {
#pragma unroll
                        for (int jp = 0; jp < 4; jp++) ldsm4t(y[4 * jp], y[4 * jp + 1], y[4 * jp + 2], y[4 * jp + 3], ya + ((jp * 2048 + e * 512) >> YE));
                    }
                    x[e] = bfma2(e < NXP ? nx[e < NXP ? e : 0] : norm2(x[e], mb[e & 1], rd[e & 1]), y[e & 15], x[e]);
                    if ((e & 3) == 3) stsm4(s_epi + (fr ^ (((e >> 2) & 3) << 5)) + (e >> 4) * 16384, x[e - 3], x[e - 2], x[e - 1], x[e]);
                    if ((e & 15) == 15 && ((e > 15 ? GS2 : GST) & 1)) put_half(s_epi + (e >> 4) * 16384, R_XA + tb, e >> 4);
                    if ((e & 15) == 15) { if (e == 15 && (SPL2 & 1)) named_bar_arrive(7 - 2 * wg, 160); else named_bar_arrive(5 + (e >> 4), 288); }
                    if (e == 15) mbar_wait(b_role, 0);
                }
                DT(19 + 24 * layer);
                if (FMOVE) fence_async_smem();
                if (PS1_EARLY) put_stats(x, 1, layer);
                named_bar_sync(9 + wg, 128);
                skip5(r5);
                DT(3 + 24 * layer);
            }
            {
                float acc[64];
                kblock<128, R5_N, 0>(acc, dae, db0 + 2 * (R5_STAGE / 16), f5, r5);
                kblock<128, R5_N>(acc, dae + 1024, db0 + 3 * (R5_STAGE / 16), f5, r5);
                if (!PS1_EARLY) put_stats(x, 1, layer);
                wgmma_wait<1>();
                if (rel_on) mbar_arrive_cluster(rel5 + 16);
                float2 cs[8];
                mainloop<128, R5_N, R5_STAGE, PA1>(acc, 14, da0, db0, f5, rel5, rel_on, r5, 15 + 24 * layer, [&]() {
                    named_bar_sync(3 + 8 * wg, 160);
                    row_consts(true);
#pragma unroll
                    for (int e = 0; e < 8; e++) cs[e] = *reinterpret_cast<const float2*>(csp + 256 + 8 * e);
                    keep_consts(cs);
                } DT_ARG, (wg ^ bj >> 1 ^ LAGX) & 1);
                DT(4 + 24 * layer);
#pragma unroll
                for (int j = 0; j < 16; j += 2) {
                    if (j == 8) {
#pragma unroll
                        for (int e = 0; e < 8; e++) cs[e] = *reinterpret_cast<const float2*>(csp + 256 + 8 * (j + e));
                    }
                    uint32_t w[4];
#pragma unroll
                    for (int e = 0; e < 4; e++) {
                        const float* a = acc + 4 * j + 2 * e;
                        const float2 c = cs[(j & 7) + (e >> 1)];
                        w[e] = gelu2h(pack2(fmaf(-mrow[e & 1], c.x, a[0]) * rrow[e & 1], fmaf(-mrow[e & 1], c.y, a[1]) * rrow[e & 1]));
                    }
                    stsm4(s_stg + 1024 + (fr ^ ((j & 7) << 4)) + (j >> 3) * OFF_EPI, w[0], w[1], w[2], w[3]);
                    if ((j & 7) == 6 && ((j > 7 ? GS2 : GST) & 4)) put_half(s_stg + 1024 + (j >> 3) * OFF_EPI, R_H + layer * R_HP + m0, j >> 3);
                    if ((j & 7) == 6) { if (j == 6 && (SPL2 & 4)) named_bar_arrive(7 - 2 * ((wg ^ bj >> 1 ^ 1) & 1), 160); else named_bar_arrive(5 + (j >> 3), 288); }
                }
                if (SENDC && warp == (bj & 2 ? 0 : 7)) {
                    __syncwarp();
                    uint32_t a[4];
                    lds64(a[0], a[1], s_stg + 1024 + 18 * 128 * warp + 8 * lane);
                    lds64(a[2], a[3], s_epi + 1024 + 18 * 128 * warp + 8 * lane);
                    uint4* gh = g_halo + (layer * 144 + (warp & 2) * 8 + bi * 8 + bj) * 64 + lane;
#pragma unroll
                    for (int i = 0; i < 2; i++)
                        asm volatile("{\n.reg .b64 u, v;\nmov.b64 u, {%1, %3};\nmov.b64 v, {%2, %3};\nst.relaxed.gpu.global.v2.b64 [%0], {u, v};\n}"
                                     ::"l"(gh + i * 32), "r"(a[2 * i]), "r"(a[2 * i + 1]), "r"(ep) : "memory");
                }
                fence_async_smem();
                if (wg == (bj >> 1 & 1)) { if (H11) named_bar_arrive(4, 160); named_bar_arrive(13, 256); }
                DT(5 + 24 * layer);
            }
            {
                float acc[64];
                uint32_t u[32];
                {
                    uint32_t mb[2], rd[2];
#pragma unroll
                    for (int e = 0; e < 2; e++) { const uint32_t q0 = rsp[8 * e]; mb[e] = (q0 & 0xffffu) * 0x10001u; rd[e] = split(frcp(hi2f(q0))); }
#pragma unroll
                    for (int e = 0; e < 32; e++) {
                        u[e] = norm2(x[e], mb[e & 1], rd[e & 1]);
                        asm volatile("" : "+r"(u[e]));
                    }
                }
                if (!(warp & 2)) mbar_wait(f5 + 24, r5.ph);
                skip5(r5);
                {
                    const bool nb = wg == (bj >> 1 & 1);
                    named_bar_sync(nb ? 14 : 13, nb ? 160 : 256);
                }
                const uint32_t dah = da0 - (OFF_R - 1024 + 256) / 16 + ((0x4031u >> (2 * bj & 12)) & 7) * 8;
                kblock<128, R5_N, 0>(acc, dah, db0 + 4 * (R5_STAGE / 16), f5, r5);
                kblock<128, R5_N>(acc, dah + OFF_EPI / 16, db0, f5, r5);
                wgmma_wait<1>();
                if (rel_on) mbar_arrive_cluster(rel5 + 32);
                mainloop<128, R5_N, R5_STAGE, PA2>(acc, 14, da0, db0, f5, rel5, rel_on, r5, 16 + 24 * layer, []() {} DT_ARG, wg);
                DT(6 + 24 * layer);
#pragma unroll
                for (int j = 0; j < 16; j += 2) {
#pragma unroll
                    for (int e = 0; e < 4; e++) u[2 * j + e] = badd2(u[2 * j + e], pack2(acc[4 * j + 2 * e], acc[4 * j + 2 * e + 1]));
                    stsm4(s_epi + (fr ^ ((j & 7) << 4)) + (j >> 3) * 16384, u[2 * j], u[2 * j + 1], u[2 * j + 2], u[2 * j + 3]);
                    if ((j & 7) == 6 && ((j > 7 ? GS2 : GST) & 16)) put_half(s_epi + (j >> 3) * 16384, R_X1 + tb, j >> 3);
                    if ((j & 7) == 6) { if (j == 6 && (SPL2 & 16)) named_bar_arrive(7 - 2 * wg, 160); else named_bar_arrive(5 + (j >> 3), 288); mbar_wait(b_role, 0); }
                }
                if (FMOVE) fence_async_smem();
#pragma unroll
                for (int e = 0; e < 32; e++) x[e] = badd2(x[e], u[e]);
                put_stats(u, 2, layer);
                named_bar_sync(9 + wg, 128);
                DT(7 + 24 * layer);
            }
            {
                float2 cs[NCS];
                auto piece = [&](const float* acc, auto pc) {
                    constexpr int j = 2 * decltype(pc)::v, jl = j & 31;
                    uint32_t w[4];
#pragma unroll
                    for (int e = 0; e < 2; e++) {
                        const float* a = acc + 4 * (jl + e);
                        const float2 cc = cs[(j + e) % NCS];
                        w[2 * e] = pack2(fmaf(-mrow[0], cc.x, a[0]) * rrow[0], fmaf(-mrow[0], cc.y, a[1]) * rrow[0]);
                        w[2 * e + 1] = pack2(fmaf(-mrow[1], cc.x, a[2]) * rrow[1], fmaf(-mrow[1], cc.y, a[3]) * rrow[1]);
                    }
                    stsm4(((jl < 16 ? s_epi : s_stg) + st_w) ^ ((j & 15) << 4), w[0], w[1], w[2], w[3]);
                    if (j + NCS < 56) {
#pragma unroll
                        for (int e = 0; e < 2; e++) { uint32_t u0, u1; lds64(u0, u1, smem_u32(csp + 8 * (j + e + NCS))); cs[(j + e) % NCS] = make_float2(__uint_as_float(u0), __uint_as_float(u1)); }
                    }
                    if (j == 14 || (j >= 30 && (j & 7) == 6)) {
                        __syncwarp();
                        if (lane == 0) mbar_arrive(j == 14 ? b_stg : s_bar + 168 + (j & 56));
                    }
                };
                auto pieces = [&](const float* acc, auto p0, auto p1) {
                    constexpr int a = decltype(p0)::v, b = decltype(p1)::v;
                    static_for<a, b>([&](auto i) { piece(acc, i); });
                };
                float ac3[128];
                kblock<256, R4_N, 0>(ac3, dae, db4, f4, r4);
                kblock<256, R4_N>(ac3, dae + 1024, db4 + R4_STAGE / 16, f4, r4);
                wgmma_wait<1>();
                if (rel_on) mbar_arrive_cluster(rel4);
                mainloop<256, R4_N, R4_STAGE, PA3A>(ac3, 14, da0, db4, f4, rel4, rel_on, r4, 17 + 24 * layer, [&]() {
                    named_bar_sync(3 + 8 * wg, 160);
                    mbar_wait(e4, 1);
                    row_consts(false);
#pragma unroll
                    for (int e = 0; e < NCS; e++) {
                        cs[e] = *reinterpret_cast<const float2*>(csp + 8 * e);
                        asm volatile("" : "+f"(cs[e].x), "+f"(cs[e].y));
                    }
                    asm volatile("" : "+f"(mrow[0]), "+f"(mrow[1]), "+f"(rrow[0]), "+f"(rrow[1]));
                } DT_ARG, wg);
                DT(8 + 24 * layer);
                pieces(ac3, IC<0>(), IC<NPRE>());
                DT(9 + 24 * layer);
                float acc[96];
                constexpr int NS3 = NPRE == 16 ? 1 : (16 - NPRE + PP3 - 1) / PP3;
                static_for<0, NS3>([&](auto cc) {
                    constexpr int c = decltype(cc)::v, q = NPRE + PP3 * c;
                    const uint32_t da = da0 + c * (R4B_STAGE / 16), db = db0 + c * (R4B_STAGE / 16);
                    mbar_wait(f4 + 8 * c, r4.ph);
                    wgmma_fence();
                    static_for<0, 4>([&](auto ic) {
                        constexpr int i = decltype(ic)::v, q0 = q + i * PP3 / 4, q1 = q + (i + 1) * PP3 / 4;
                        WG<192>::mma<(c | i) != 0>(acc, da + 2 * i, db + 128 * i);
                        if (i == 3) {
                            wgmma_commit();
                            if (c) {
                                wgmma_wait<1>();
                                if (rel_on) mbar_arrive_cluster(rel4 + 8 * ((c + 3) & 3));
                            }
                        }
                        pieces(ac3, IC<(q0 < 16 ? q0 : 16)>(), IC<(q1 < 16 ? q1 : 16)>());
                    });
                });
                r4.st = NS3 & 3;
                if (NS3 == 4) r4.ph ^= 1;
                float ac4[64];
                mainloop<192, R4_N, R4B_STAGE, PA3B, 1>(acc, 16 - NS3, da0, db0, f4, rel4, rel_on, r4, -1, [&]() {
#pragma unroll
                    for (int i = 0; i < 32; i++) asm volatile("shl.b32 %0, %2, 16;\nand.b32 %1, %2, 0xffff0000;" : "=f"(ac4[2 * i]), "=f"(ac4[2 * i + 1]) : "r"(x[i]));
                    kblock<128, R5_N>(ac4, da0, db0, f5, r5);
                } DT_ARG, wg);
                DT(10 + 24 * layer);
                named_bar_sync(4 + 8 * wg, 224);
                piece(acc, IC<16>());
                static_for<1, 7>([&](auto cc) {
                    constexpr int c = decltype(cc)::v;
                    const uint32_t da = da0 + (c % 5) * (R5_STAGE / 16), db = db0 + (c % 5) * (R5_STAGE / 16);
                    mbar_wait(f5 + 8 * (c % 5), r5.ph);
                    wgmma_fence();
                    WG<128>::mma<1>(ac4, da, db);
                    WG<128>::mma<1>(ac4, da + 2, db + 128);
                    piece(acc, IC<15 + 2 * c>());
                    WG<128>::mma<1>(ac4, da + 4, db + 256);
                    WG<128>::mma<1>(ac4, da + 6, db + 384);
                    wgmma_commit();
                    if (c % 5 == 4) r5.ph ^= 1;
                    wgmma_wait<1>();
                    if (rel_on) mbar_arrive_cluster(rel5 + 8 * ((c - 1) % 5));
                    if constexpr (c < 6) piece(acc, IC<16 + 2 * c>());
                });
                r5.st = 2;
                DT(11 + 24 * layer);
                DT(18 + 24 * layer);
                mainloop<128, R5_N, R5_STAGE, PA4>(ac4, 49, da0, db0, f5, rel5, rel_on, r5, 62 - 40 * (layer ^ 1), []() {} DT_ARG, wg);
                DT(12 + 24 * layer);
#pragma unroll
                for (int i = 0; i < 32; i++) x[i] = pack2(ac4[2 * i], ac4[2 * i + 1]);
                DT(13 + 24 * layer);
                DT(14 + 24 * layer);
            }
        }
#pragma unroll
        for (int jp = 0; jp < 8; jp++) stsm4(s_epi + (fr ^ ((jp & 3) << 5)) + (jp >> 2) * 16384, x[4 * jp], x[4 * jp + 1], x[4 * jp + 2], x[4 * jp + 3]);
        __syncwarp();
        copy_out(outp, s_epi);
        DT(38);
        DT_DUMP;
        GT(4);
        }
        cluster_arrive_relaxed();
        cluster_wait();
    }
}

typedef CUresult (*PFN_encodeTiled)(CUtensorMap*, CUtensorMapDataType, cuuint32_t, void*, const cuuint64_t*, const cuuint64_t*,
                                    const cuuint32_t*, const cuuint32_t*, CUtensorMapInterleave, CUtensorMapSwizzle,
                                    CUtensorMapL2promotion, CUtensorMapFloatOOBfill);

static CUtensorMap make_map(PFN_encodeTiled enc, const void* ptr, int inner, int outer, int box_inner, int box_outer,
                            CUtensorMapSwizzle swz = CU_TENSOR_MAP_SWIZZLE_128B) {
    CUtensorMap m;
    cuuint64_t dims[2] = {(cuuint64_t)inner, (cuuint64_t)outer};
    cuuint64_t strides[1] = {(cuuint64_t)inner * 2};
    cuuint32_t box[2] = {(cuuint32_t)box_inner, (cuuint32_t)box_outer};
    cuuint32_t es[2] = {1, 1};
    enc(&m, CU_TENSOR_MAP_DATA_TYPE_BFLOAT16, 2, const_cast<void*>(ptr), dims, strides, box, es, CU_TENSOR_MAP_INTERLEAVE_NONE,
        swz, CU_TENSOR_MAP_L2_PROMOTION_L2_256B, CU_TENSOR_MAP_FLOAT_OOB_FILL_NONE);
    return m;
}

extern "C" void kernel_launch(void* const* d_in, const int* in_sizes, int n_in, void* d_out, int out_size) {
    const bf16* A_q = (const bf16*)d_in[0];
    const bf16* A_k = (const bf16*)d_in[1];
    const bf16* A_v = (const bf16*)d_in[2];
    const bf16* A_shk = (const bf16*)d_in[3];
    const bf16* A_ssk = (const bf16*)d_in[4];
    const bf16* A_ssD = (const bf16*)d_in[5];
    const bf16* w1 = (const bf16*)d_in[7];
    const bf16* w2 = (const bf16*)d_in[8];
    const bf16* w3 = (const bf16*)d_in[9];
    const bf16* w4 = (const bf16*)d_in[10];
    bf16* out = (bf16*)d_out;

    static PFN_encodeTiled enc = nullptr;
    static bool attr_done = false;
    if (!enc) {
        void* fn = nullptr;
        cudaDriverEntryPointQueryResult qr;
        cudaGetDriverEntryPoint("cuTensorMapEncodeTiled", &fn, cudaEnableDefault, &qr);
        enc = (PFN_encodeTiled)fn;
    }
    if (!attr_done) {
        cudaFuncSetAttribute(mega_kernel, cudaFuncAttributeMaxDynamicSharedMemorySize, MEGA_SMEM);
        attr_done = true;
    }
    void* p_act;
    cudaGetSymbolAddress(&p_act, g_act);
    bf16* act = (bf16*)(((uintptr_t)p_act + 0x1fffff) & ~(uintptr_t)0x1fffff);

    MegaMaps tm;
    tm.q = make_map(enc, A_q, D_, S_, 64, 128);
    tm.act = make_map(enc, act, D_, R_END, 64, 128);
    tm.a64 = make_map(enc, act, D_, R_END, 64, 64);
    tm.w1 = make_map(enc, w1, D_, D_, 64, 64);
    tm.w2 = make_map(enc, w2, D_, D_, 64, 64);
    tm.w3 = make_map(enc, w3, F_, D_, 64, 64);
    tm.w4 = make_map(enc, w4, D_, F_, 64, 64);
    {
        cuuint64_t dims[4] = {64, 16, 256, 8}, strides[3] = {128, D_ * 2, (cuuint64_t)2048 * D_ * 2};
        cuuint32_t box[4] = {64, 4, 1, 8}, es[4] = {1, 1, 1, 1};
        enc(&tm.y, CU_TENSOR_MAP_DATA_TYPE_BFLOAT16, 4, act + (size_t)R_Y * D_, dims, strides, box, es, CU_TENSOR_MAP_INTERLEAVE_NONE,
            CU_TENSOR_MAP_SWIZZLE_128B, CU_TENSOR_MAP_L2_PROMOTION_NONE, CU_TENSOR_MAP_FLOAT_OOB_FILL_NONE);
    }
    for (int i = 0; i < 2; i++) {
        cuuint64_t dims[4] = {D_, 4, 8, S_ / 32}, strides[3] = {8 * D_ * 2, D_ * 2, 32 * D_ * 2};
        cuuint32_t box[4] = {16, 4, 8, 4}, es[4] = {1, 1, 1, 1};
        enc(i ? &tm.v : &tm.k, CU_TENSOR_MAP_DATA_TYPE_BFLOAT16, 4, (void*)(i ? A_v : A_k), dims, strides, box, es, CU_TENSOR_MAP_INTERLEAVE_NONE,
            CU_TENSOR_MAP_SWIZZLE_32B, CU_TENSOR_MAP_L2_PROMOTION_NONE, CU_TENSOR_MAP_FLOAT_OOB_FILL_NONE);
    }
    mega_kernel<<<2 * NCL, 384, MEGA_SMEM, cudaStreamPerThread>>>(tm, out, act, w1, w2, w3, A_q, A_k, A_v, A_shk, A_ssk, A_ssD);
}
```

```cpp
#include <cuda_runtime.h>
#include <cuda_bf16.h>
#include <cuda.h>
#include <stdint.h>

typedef __nv_bfloat16 bf16;

constexpr int S_ = 2048;
constexpr int D_ = 1024;
constexpr int F_ = 3584;

constexpr int R_XA = 0, R_X1 = 256, R_H2 = 512, R_Y = 1536, R_H = 16384 + 8, R_HP = S_ + 8, R_END = R_H + 2 * R_HP;
__device__ __align__(1024) bf16 g_act[(size_t)(R_END + 1024) * D_];
__device__ __align__(16) float g_cpart[16 * (F_ + D_)];
__device__ __align__(128) float2 g_stats[3 * S_ * 8];
__device__ __align__(128) uint4 g_halo[2 * 144 * 64];

__device__ __forceinline__ float bfr(float x) { return __bfloat162float(__float2bfloat16_rn(x)); }
__device__ __forceinline__ uint32_t pack2(float lo, float hi) {
    __nv_bfloat162 v = __floats2bfloat162_rn(lo, hi);
    return *reinterpret_cast<uint32_t*>(&v);
}
__device__ __forceinline__ float lo2f(uint32_t v) { return __uint_as_float(v << 16); }
__device__ __forceinline__ float hi2f(uint32_t v) { return __uint_as_float(v & 0xffff0000u); }
__device__ __forceinline__ float frcp(float x) { float r; asm("rcp.approx.f32 %0, %1;" : "=f"(r) : "f"(x)); return r; }
__device__ __forceinline__ float fsqrt(float x) { float r; asm("sqrt.approx.f32 %0, %1;" : "=f"(r) : "f"(x)); return r; }
__device__ __forceinline__ uint32_t smem_u32(const void* p) { return (uint32_t)__cvta_generic_to_shared(p); }

__device__ __forceinline__ void mbar_init(uint32_t bar, uint32_t cnt) {
    asm volatile("mbarrier.init.shared::cta.b64 [%0], %1;" ::"r"(bar), "r"(cnt));
}
__device__ __forceinline__ void mbar_expect_tx(uint32_t bar, uint32_t bytes) {
    asm volatile("mbarrier.arrive.expect_tx.shared::cta.b64 _, [%0], %1;" ::"r"(bar), "r"(bytes) : "memory");
}
__device__ __forceinline__ void mbar_arrive(uint32_t bar) {
    asm volatile("mbarrier.arrive.shared::cta.b64 _, [%0];" ::"r"(bar) : "memory");
}
__device__ __forceinline__ void mbar_wait(uint32_t bar, uint32_t parity) {
    asm volatile(
        "{\n.reg .pred p;\n.reg .u32 n;\n"
        "mbarrier.try_wait.parity.shared::cta.b64 p, [%0], %1;\n"
        "@p bra LD;\n"
        "mov.u32 n, 0;\n"
        "LW:\n"
        "mbarrier.try_wait.parity.shared::cta.b64 p, [%0], %1;\n"
        "@p bra LD;\n"
        "add.u32 n, n, 1;\n"
        "setp.lt.u32 p, n, 0x400000;\n"
        "@p bra LW;\n"
        "LD:\n}\n"
        ::"r"(bar), "r"(parity) : "memory");
}
__device__ __forceinline__ void tma_load_2d(uint32_t dst, const CUtensorMap* tm, uint32_t bar, int c0, int c1) {
    asm volatile(
        "cp.async.bulk.tensor.2d.shared::cluster.global.mbarrier::complete_tx::bytes [%0], [%1, {%3, %4}], [%2];"
        ::"r"(dst), "l"((uint64_t)tm), "r"(bar), "r"(c0), "r"(c1) : "memory");
}
__device__ __forceinline__ void tma_load_2d_mc(uint32_t dst, const CUtensorMap* tm, uint32_t bar, int c0, int c1) {
    asm volatile(
        "cp.async.bulk.tensor.2d.shared::cluster.global.mbarrier::complete_tx::bytes.multicast::cluster [%0], [%1, {%3, %4}], [%2], %5;"
        ::"r"(dst), "l"((uint64_t)tm), "r"(bar), "r"(c0), "r"(c1), "h"((uint16_t)3) : "memory");
}
__device__ __forceinline__ void tma_prefetch_2d(const CUtensorMap* tm, int c0, int c1) {
    asm volatile("cp.async.bulk.prefetch.tensor.2d.L2.global.tile [%0, {%1, %2}];" ::"l"((uint64_t)tm), "r"(c0), "r"(c1) : "memory");
}
__device__ __forceinline__ void tma_store_2d(const CUtensorMap* tm, uint32_t src, int c0, int c1) {
    asm volatile("cp.async.bulk.tensor.2d.global.shared::cta.bulk_group [%0, {%2, %3}], [%1];"
                 ::"l"((uint64_t)tm), "r"(src), "r"(c0), "r"(c1) : "memory");
}
__device__ __forceinline__ void wgmma_fence() { asm volatile("wgmma.fence.sync.aligned;" ::: "memory"); }
__device__ __forceinline__ void wgmma_commit() { asm volatile("wgmma.commit_group.sync.aligned;" ::: "memory"); }
template <int N> __device__ __forceinline__ void wgmma_wait() { asm volatile("wgmma.wait_group.sync.aligned %0;" ::"n"(N) : "memory"); }
__device__ __forceinline__ void named_bar_arrive(int id, int n) { asm volatile("bar.arrive %0, %1;" ::"r"(id), "r"(n) : "memory"); }
__device__ __forceinline__ void named_bar_sync(int id, int n) { asm volatile("bar.sync %0, %1;" ::"r"(id), "r"(n) : "memory"); }

__device__ __forceinline__ uint32_t desc_a(uint32_t addr) { return ((addr & 0x3FFFF) >> 4) | (1u << 16); }
__device__ __forceinline__ uint32_t desc_b(uint32_t addr) { return ((addr & 0x3FFFF) >> 4) | (512u << 16); }

template <int ACC> __device__ __forceinline__ void wgmma_m64n192k16(float (&d)[96], uint32_t descA, uint32_t descB) {
  asm volatile("{\n.reg .pred p;\n.reg .b64 da, db;\nsetp.ne.b32 p, %99, 0;\nmov.b64 da, {%96, %98};\nmov.b64 db, {%97, %98};\n"
    "wgmma.mma_async.sync.aligned.m64n192k16.f32.bf16.bf16 "
    "{%0, %1, %2, %3, %4, %5, %6, %7, %8, %9, %10, %11, %12, %13, %14, %15, %16, %17, %18, %19, %20, %21, %22, %23, %24, %25, %26, %27, %28, %29, %30, %31, %32, %33, %34, %35, %36, %37, %38, %39, %40, %41, %42, %43, %44, %45, %46, %47, %48, %49, %50, %51, %52, %53, %54, %55, %56, %57, %58, %59, %60, %61, %62, %63, %64, %65, %66, %67, %68, %69, %70, %71, %72, %73, %74, %75, %76, %77, %78, %79, %80, %81, %82, %83, %84, %85, %86, %87, %88, %89, %90, %91, %92, %93, %94, %95}, "
    "da, db, p, 1, 1, 0, 1;\n}\n"
    : "+f"(d[0]), "+f"(d[1]), "+f"(d[2]), "+f"(d[3]), "+f"(d[4]), "+f"(d[5]), "+f"(d[6]), "+f"(d[7]), "+f"(d[8]), "+f"(d[9]), "+f"(d[10]), "+f"(d[11]), "+f"(d[12]), "+f"(d[13]), "+f"(d[14]), "+f"(d[15]), "+f"(d[16]), "+f"(d[17]), "+f"(d[18]), "+f"(d[19]), "+f"(d[20]), "+f"(d[21]), "+f"(d[22]), "+f"(d[23]), "+f"(d[24]), "+f"(d[25]), "+f"(d[26]), "+f"(d[27]), "+f"(d[28]), "+f"(d[29]), "+f"(d[30]), "+f"(d[31]), "+f"(d[32]), "+f"(d[33]), "+f"(d[34]), "+f"(d[35]), "+f"(d[36]), "+f"(d[37]), "+f"(d[38]), "+f"(d[39]), "+f"(d[40]), "+f"(d[41]), "+f"(d[42]), "+f"(d[43]), "+f"(d[44]), "+f"(d[45]), "+f"(d[46]), "+f"(d[47]), "+f"(d[48]), "+f"(d[49]), "+f"(d[50]), "+f"(d[51]), "+f"(d[52]), "+f"(d[53]), "+f"(d[54]), "+f"(d[55]), "+f"(d[56]), "+f"(d[57]), "+f"(d[58]), "+f"(d[59]), "+f"(d[60]), "+f"(d[61]), "+f"(d[62]), "+f"(d[63]), "+f"(d[64]), "+f"(d[65]), "+f"(d[66]), "+f"(d[67]), "+f"(d[68]), "+f"(d[69]), "+f"(d[70]), "+f"(d[71]), "+f"(d[72]), "+f"(d[73]), "+f"(d[74]), "+f"(d[75]), "+f"(d[76]), "+f"(d[77]), "+f"(d[78]), "+f"(d[79]), "+f"(d[80]), "+f"(d[81]), "+f"(d[82]), "+f"(d[83]), "+f"(d[84]), "+f"(d[85]), "+f"(d[86]), "+f"(d[87]), "+f"(d[88]), "+f"(d[89]), "+f"(d[90]), "+f"(d[91]), "+f"(d[92]), "+f"(d[93]), "+f"(d[94]), "+f"(d[95])
    : "r"(descA), "r"(descB), "r"(0x40000040u), "n"(ACC));
}

template <int ACC> __device__ __forceinline__ void wgmma_m64n256k16(float (&d)[128], uint32_t descA, uint32_t descB) {
  asm volatile("{\n.reg .pred p;\n.reg .b64 da, db;\nsetp.ne.b32 p, %131, 0;\nmov.b64 da, {%128, %130};\nmov.b64 db, {%129, %130};\n"
    "wgmma.mma_async.sync.aligned.m64n256k16.f32.bf16.bf16 "
    "{%0, %1, %2, %3, %4, %5, %6, %7, %8, %9, %10, %11, %12, %13, %14, %15, %16, %17, %18, %19, %20, %21, %22, %23, %24, %25, %26, %27, %28, %29, %30, %31, %32, %33, %34, %35, %36, %37, %38, %39, %40, %41, %42, %43, %44, %45, %46, %47, %48, %49, %50, %51, %52, %53, %54, %55, %56, %57, %58, %59, %60, %61, %62, %63, %64, %65, %66, %67, %68, %69, %70, %71, %72, %73, %74, %75, %76, %77, %78, %79, %80, %81, %82, %83, %84, %85, %86, %87, %88, %89, %90, %91, %92, %93, %94, %95, %96, %97, %98, %99, %100, %101, %102, %103, %104, %105, %106, %107, %108, %109, %110, %111, %112, %113, %114, %115, %116, %117, %118, %119, %120, %121, %122, %123, %124, %125, %126, %127}, "
    "da, db, p, 1, 1, 0, 1;\n}\n"
    : "+f"(d[0]), "+f"(d[1]), "+f"(d[2]), "+f"(d[3]), "+f"(d[4]), "+f"(d[5]), "+f"(d[6]), "+f"(d[7]), "+f"(d[8]), "+f"(d[9]), "+f"(d[10]), "+f"(d[11]), "+f"(d[12]), "+f"(d[13]), "+f"(d[14]), "+f"(d[15]), "+f"(d[16]), "+f"(d[17]), "+f"(d[18]), "+f"(d[19]), "+f"(d[20]), "+f"(d[21]), "+f"(d[22]), "+f"(d[23]), "+f"(d[24]), "+f"(d[25]), "+f"(d[26]), "+f"(d[27]), "+f"(d[28]), "+f"(d[29]), "+f"(d[30]), "+f"(d[31]), "+f"(d[32]), "+f"(d[33]), "+f"(d[34]), "+f"(d[35]), "+f"(d[36]), "+f"(d[37]), "+f"(d[38]), "+f"(d[39]), "+f"(d[40]), "+f"(d[41]), "+f"(d[42]), "+f"(d[43]), "+f"(d[44]), "+f"(d[45]), "+f"(d[46]), "+f"(d[47]), "+f"(d[48]), "+f"(d[49]), "+f"(d[50]), "+f"(d[51]), "+f"(d[52]), "+f"(d[53]), "+f"(d[54]), "+f"(d[55]), "+f"(d[56]), "+f"(d[57]), "+f"(d[58]), "+f"(d[59]), "+f"(d[60]), "+f"(d[61]), "+f"(d[62]), "+f"(d[63]), "+f"(d[64]), "+f"(d[65]), "+f"(d[66]), "+f"(d[67]), "+f"(d[68]), "+f"(d[69]), "+f"(d[70]), "+f"(d[71]), "+f"(d[72]), "+f"(d[73]), "+f"(d[74]), "+f"(d[75]), "+f"(d[76]), "+f"(d[77]), "+f"(d[78]), "+f"(d[79]), "+f"(d[80]), "+f"(d[81]), "+f"(d[82]), "+f"(d[83]), "+f"(d[84]), "+f"(d[85]), "+f"(d[86]), "+f"(d[87]), "+f"(d[88]), "+f"(d[89]), "+f"(d[90]), "+f"(d[91]), "+f"(d[92]), "+f"(d[93]), "+f"(d[94]), "+f"(d[95]), "+f"(d[96]), "+f"(d[97]), "+f"(d[98]), "+f"(d[99]), "+f"(d[100]), "+f"(d[101]), "+f"(d[102]), "+f"(d[103]), "+f"(d[104]), "+f"(d[105]), "+f"(d[106]), "+f"(d[107]), "+f"(d[108]), "+f"(d[109]), "+f"(d[110]), "+f"(d[111]), "+f"(d[112]), "+f"(d[113]), "+f"(d[114]), "+f"(d[115]), "+f"(d[116]), "+f"(d[117]), "+f"(d[118]), "+f"(d[119]), "+f"(d[120]), "+f"(d[121]), "+f"(d[122]), "+f"(d[123]), "+f"(d[124]), "+f"(d[125]), "+f"(d[126]), "+f"(d[127])
    : "r"(descA), "r"(descB), "r"(0x40000040u), "n"(ACC));
}

template <int ACC> __device__ __forceinline__ void wgmma_m64n128k16(float (&d)[64], uint32_t descA, uint32_t descB) {
  asm volatile("{\n.reg .pred p;\n.reg .b64 da, db;\nsetp.ne.b32 p, %67, 0;\nmov.b64 da, {%64, %66};\nmov.b64 db, {%65, %66};\n"
    "wgmma.mma_async.sync.aligned.m64n128k16.f32.bf16.bf16 "
    "{%0, %1, %2, %3, %4, %5, %6, %7, %8, %9, %10, %11, %12, %13, %14, %15, %16, %17, %18, %19, %20, %21, %22, %23, %24, %25, %26, %27, %28, %29, %30, %31, %32, %33, %34, %35, %36, %37, %38, %39, %40, %41, %42, %43, %44, %45, %46, %47, %48, %49, %50, %51, %52, %53, %54, %55, %56, %57, %58, %59, %60, %61, %62, %63}, "
    "da, db, p, 1, 1, 0, 1;\n}\n"
    : "+f"(d[0]), "+f"(d[1]), "+f"(d[2]), "+f"(d[3]), "+f"(d[4]), "+f"(d[5]), "+f"(d[6]), "+f"(d[7]), "+f"(d[8]), "+f"(d[9]), "+f"(d[10]), "+f"(d[11]), "+f"(d[12]), "+f"(d[13]), "+f"(d[14]), "+f"(d[15]), "+f"(d[16]), "+f"(d[17]), "+f"(d[18]), "+f"(d[19]), "+f"(d[20]), "+f"(d[21]), "+f"(d[22]), "+f"(d[23]), "+f"(d[24]), "+f"(d[25]), "+f"(d[26]), "+f"(d[27]), "+f"(d[28]), "+f"(d[29]), "+f"(d[30]), "+f"(d[31]), "+f"(d[32]), "+f"(d[33]), "+f"(d[34]), "+f"(d[35]), "+f"(d[36]), "+f"(d[37]), "+f"(d[38]), "+f"(d[39]), "+f"(d[40]), "+f"(d[41]), "+f"(d[42]), "+f"(d[43]), "+f"(d[44]), "+f"(d[45]), "+f"(d[46]), "+f"(d[47]), "+f"(d[48]), "+f"(d[49]), "+f"(d[50]), "+f"(d[51]), "+f"(d[52]), "+f"(d[53]), "+f"(d[54]), "+f"(d[55]), "+f"(d[56]), "+f"(d[57]), "+f"(d[58]), "+f"(d[59]), "+f"(d[60]), "+f"(d[61]), "+f"(d[62]), "+f"(d[63])
    : "r"(descA), "r"(descB), "r"(0x40000040u), "n"(ACC));
}

template <int BN> struct WG;
template <> struct WG<128> { template <int ACC> static __device__ __forceinline__ void mma(float (&d)[64], uint32_t a, uint32_t b) { wgmma_m64n128k16<ACC>(d, a, b); } };
template <> struct WG<256> { template <int ACC> static __device__ __forceinline__ void mma(float (&d)[128], uint32_t a, uint32_t b) { wgmma_m64n256k16<ACC>(d, a, b); } };
template <> struct WG<192> { template <int ACC> static __device__ __forceinline__ void mma(float (&d)[96], uint32_t a, uint32_t b) { wgmma_m64n192k16<ACC>(d, a, b); } };

#define DBG_T(i)
__device__ __forceinline__ void fence_async_smem() { asm volatile("fence.proxy.async.shared::cta;" ::: "memory"); }
__device__ __forceinline__ void prefetch_tmap(const CUtensorMap* tm) { asm volatile("prefetch.tensormap [%0];" ::"l"((uint64_t)tm) : "memory"); }
__device__ __forceinline__ uint32_t mapa_u32(uint32_t addr, uint32_t cta) {
    uint32_t r;
    asm volatile("mapa.shared::cluster.u32 %0, %1, %2;" : "=r"(r) : "r"(addr), "r"(cta));
    return r;
}
__device__ __forceinline__ void mbar_arrive_cluster(uint32_t cluster_addr) {
    asm volatile("mbarrier.arrive.shared::cluster.b64 _, [%0];" ::"r"(cluster_addr) : "memory");
}
__device__ __forceinline__ bool elect_one() {
    uint32_t p;
    asm volatile("{\n.reg .pred P;\nelect.sync _|P, 0xffffffff;\nselp.u32 %0, 1, 0, P;\n}\n" : "=r"(p));
    return p != 0;
}
__device__ __forceinline__ void cluster_arrive_relaxed() { asm volatile("barrier.cluster.arrive.relaxed.aligned;" ::: "memory"); }
__device__ __forceinline__ void cluster_wait() { asm volatile("barrier.cluster.wait.acquire.aligned;" ::: "memory"); }

__device__ __forceinline__ uint32_t bsub2(uint32_t a, uint32_t b) {
    __nv_bfloat162 r = __hsub2(*reinterpret_cast<__nv_bfloat162*>(&a), *reinterpret_cast<__nv_bfloat162*>(&b));
    return *reinterpret_cast<uint32_t*>(&r);
}
__device__ __forceinline__ uint32_t bmul2(uint32_t a, uint32_t b) {
    __nv_bfloat162 r = __hmul2(*reinterpret_cast<__nv_bfloat162*>(&a), *reinterpret_cast<__nv_bfloat162*>(&b));
    return *reinterpret_cast<uint32_t*>(&r);
}
__device__ __forceinline__ uint32_t badd2(uint32_t a, uint32_t b) {
    __nv_bfloat162 r = __hadd2(*reinterpret_cast<__nv_bfloat162*>(&a), *reinterpret_cast<__nv_bfloat162*>(&b));
    return *reinterpret_cast<uint32_t*>(&r);
}
constexpr int BM = 128, BK = 64;
constexpr int R5_STAGE = 32768, R5_N = 5;
constexpr int R4_STAGE = 49152, R4_N = 4;
constexpr int R4B_STAGE = 40960;
constexpr int OFF_STG5 = 0, OFF_R = 32768;
constexpr int OFF_EPI = 196608;
constexpr int OFF_BAR = OFF_EPI + 32768;
constexpr int OFF_RS = OFF_BAR + 256;
constexpr int OFF_CS = OFF_RS + 1024;
constexpr int MEGA_SMEM = OFF_CS + 1792;
enum { FL_XA = 0, FL_H = 2, FL_X1 = 4, FL_H2 = 6, FL_CS = 10, FL_KINDS = 11 };
constexpr int FL_PITCH = 64;
constexpr int FL_WORDS = 2 * FL_KINDS * 16 * FL_PITCH;
__device__ unsigned int g_flag[FL_WORDS];
__device__ __align__(8) unsigned int g_ticket[18 * FL_PITCH];
constexpr int NCL = 66;
__device__ __forceinline__ unsigned int* flag_ptr(int layer, int kind, int i) { return g_flag + ((layer * FL_KINDS + kind) * 16 + i) * FL_PITCH; }

__device__ __forceinline__ void wait_flag(const unsigned int* p, unsigned int target) {
    long long t0 = clock64();
    while (true) {
        unsigned int v;
        asm volatile("ld.relaxed.gpu.global.u32 %0, [%1];" : "=r"(v) : "l"(p) : "memory");
        if ((int)(v - target) >= 0) break;
        if (clock64() - t0 > 2000000000LL) break;
    }
    asm volatile("fence.acquire.gpu;" ::: "memory");
}
__device__ __forceinline__ void fence_proxy_async() {
    asm volatile("fence.proxy.async.global;" ::: "memory");
    asm volatile("fence.proxy.async.shared::cta;" ::: "memory");
}
__device__ __forceinline__ void stsm4(uint32_t addr, uint32_t r0, uint32_t r1, uint32_t r2, uint32_t r3) {
    asm volatile("stmatrix.sync.aligned.m8n8.x4.shared.b16 [%0], {%1,%2,%3,%4};" ::"r"(addr), "r"(r0), "r"(r1), "r"(r2), "r"(r3));
}
__device__ __forceinline__ uint4 lds128(uint32_t a) {
    uint4 v;
    asm volatile("ld.shared.v4.b32 {%0,%1,%2,%3}, [%4];" : "=r"(v.x), "=r"(v.y), "=r"(v.z), "=r"(v.w) : "r"(a) : "memory");
    return v;
}
__device__ __forceinline__ void stg128(void* p, uint4 v) {
    asm volatile("st.global.v4.b32 [%0], {%1,%2,%3,%4};" ::"l"(p), "r"(v.x), "r"(v.y), "r"(v.z), "r"(v.w) : "memory");
}
__device__ __forceinline__ float gelu_tanh_h(float hx) {
    float z = hx * fmaf(hx * hx, 8.0f * 0.035677408136300125f, 2.0f * 0.7978845608028654f);
    float t;
    asm("tanh.approx.f32 %0, %1;" : "=f"(t) : "f"(z));
    return fmaf(hx, t, hx);
}
__device__ __forceinline__ uint32_t gelu2h(uint32_t hx) {
    uint32_t r;
    asm("{\n.reg .b32 z;\nmul.rn.bf16x2 z, %1, %1;\nfma.rn.bf16x2 z, z, %2, %3;\nmul.rn.bf16x2 z, z, %1;\ntanh.approx.bf16x2 z, z;\nfma.rn.bf16x2 %0, %1, z, %1;\n}"
        : "=r"(r) : "r"(hx), "r"(0x3e923e92u), "r"(0x3fcc3fccu));
    return r;
}
__device__ __forceinline__ uint4 gelu8h(uint4 v) { return make_uint4(gelu2h(v.x), gelu2h(v.y), gelu2h(v.z), gelu2h(v.w)); }

__device__ __forceinline__ void row_stats(const float2* p, uint32_t tag, float& mean, float& var) {
    float2 v[8];
#pragma unroll 1
    for (int n = 0; n < (1 << 20); n++) {
#pragma unroll
        for (int i = 0; i < 8; i++)
            asm volatile("{\n.reg .b64 t;\nld.relaxed.gpu.global.b64 t, [%2];\nmov.b64 {%0, %1}, t;\n}" : "=f"(v[i].x), "=f"(v[i].y) : "l"(p + 128 * i) : "memory");
        uint32_t old = 0;
#pragma unroll
        for (int i = 0; i < 8; i++) old |= __float_as_uint(v[i].y) ^ tag;
        if ((int)old >= 0) break;
    }
    mean = (((v[0].x + v[1].x) + (v[2].x + v[3].x)) + ((v[4].x + v[5].x) + (v[6].x + v[7].x))) * 0.125f;
    float m2 = 0.f, d2 = 0.f;
#pragma unroll
    for (int i = 0; i < 8; i++) { m2 += fabsf(v[i].y); d2 = fmaf(v[i].x - mean, v[i].x - mean, d2); }
    var = fmaf(128.0f, d2, m2) * (1.0f / D_);
}
struct RingState { uint32_t st, ph; };

#define DT(i)
#define DT_DECL
#define DT_PAR
#define DT_ARG
#define DT_DUMP
#define DP(i)
#define DQ(i)
#define GT(i)
#define TM(i)

template <int BN, int NST, int ACC = 1>
__device__ __forceinline__ void kblock(float (&acc)[BN / 2], uint32_t da, uint32_t db, uint32_t bfull, RingState& rs) {
    mbar_wait(bfull + 8 * rs.st, rs.ph);
    wgmma_fence();
    WG<BN>::template mma<ACC>(acc, da, db);
#pragma unroll
    for (int k = 1; k < 4; k++) WG<BN>::template mma<1>(acc, da + k * 2, db + k * 128);
    wgmma_commit();
    if (++rs.st == NST) { rs.st = 0; rs.ph ^= 1; }
}
#define PA3A 1
#define RLX 1
#define NPRE 12
#define PP3 2
#define NCS 8
template <int V> struct IC { static constexpr int v = V; };
template <int A, int B, class F> __device__ __forceinline__ void static_for(F f) {
    if constexpr (A < B) { f(IC<A>()); static_for<A + 1, B>(f); }
}
#define PF4A 22
#define PF4N 1
#define PA1 44
#define PA2 44
#define PA4 33
#define LAGX 1
#define PA3B 0
template <int BN, int NST, int STAGE, int PS = 0, int TW = 0, class F>
__device__ __forceinline__ void mainloop(float (&acc)[BN / 2], int KB, uint32_t da0, uint32_t db0, uint32_t bfull, uint32_t rel, bool rel_on,
                                         RingState& rs, int dbg, F pre DT_PAR, int wg = 0) {
    constexpr int SG = PS / 10, PAUSE = PS % 10;
    uint32_t prev = rs.st ? rs.st - 1 : NST - 1;
    const int pause = wg ? KB - PAUSE : -1;
#pragma unroll 1
    for (int kk = 0; kk < KB; kk++) {
        const uint32_t cur = rs.st;
        if (PAUSE && kk == pause) {
            wgmma_wait<0>();
            if (rel_on) mbar_arrive_cluster(rel + 8 * prev);
            named_bar_sync(15, 256);
        }
        kblock<BN, NST>(acc, da0 + cur * (STAGE / 16), db0 + cur * (STAGE / 16), bfull, rs);
        if (PAUSE && SG >= 2 && wg == 0 && kk == KB + 1 - SG) named_bar_arrive(15, 256);
        wgmma_wait<1>();
        if (rel_on && !(PAUSE && kk == pause)) mbar_arrive_cluster(rel + 8 * prev);
        prev = cur;
    }
    if (PAUSE && SG == 0 && wg == 0) named_bar_arrive(15, 256);
    pre();
    wgmma_wait<TW>();
#pragma unroll
    for (int i = 0; i < BN / 2; i++) asm volatile("" : "+f"(acc[i])::"memory");
    if (PAUSE && SG == 1 && wg == 0) named_bar_arrive(15, 256);
    if (rel_on) mbar_arrive_cluster(rel + 8 * prev);
}
__device__ __forceinline__ void hmma(float (&c)[4], uint32_t a0, uint32_t a1, uint32_t a2, uint32_t a3, uint32_t b0, uint32_t b1, bool first) {
    if (first) asm("{\n.reg .f32 z;\nmov.f32 z, 0f00000000;\nmma.sync.aligned.m16n8k16.row.col.f32.bf16.bf16.f32 {%0,%1,%2,%3}, {%4,%5,%6,%7}, {%8,%9}, {z,z,z,z};\n}"
        : "=f"(c[0]), "=f"(c[1]), "=f"(c[2]), "=f"(c[3]) : "r"(a0), "r"(a1), "r"(a2), "r"(a3), "r"(b0), "r"(b1));
    else
    asm("mma.sync.aligned.m16n8k16.row.col.f32.bf16.bf16.f32 {%0,%1,%2,%3}, {%4,%5,%6,%7}, {%8,%9}, {%0,%1,%2,%3};"
        : "+f"(c[0]), "+f"(c[1]), "+f"(c[2]), "+f"(c[3]) : "r"(a0), "r"(a1), "r"(a2), "r"(a3), "r"(b0), "r"(b1));
}
__device__ __forceinline__ void hmma8(float (&c)[4], uint32_t a0, uint32_t a1, uint32_t b0, bool first) {
    if (first) asm("{\n.reg .f32 z;\nmov.f32 z, 0f00000000;\nmma.sync.aligned.m16n8k8.row.col.f32.bf16.bf16.f32 {%0,%1,%2,%3}, {%4,%5}, {%6}, {z,z,z,z};\n}"
        : "=f"(c[0]), "=f"(c[1]), "=f"(c[2]), "=f"(c[3]) : "r"(a0), "r"(a1), "r"(b0));
    else
    asm("mma.sync.aligned.m16n8k8.row.col.f32.bf16.bf16.f32 {%0,%1,%2,%3}, {%4,%5}, {%6}, {%0,%1,%2,%3};"
        : "+f"(c[0]), "+f"(c[1]), "+f"(c[2]), "+f"(c[3]) : "r"(a0), "r"(a1), "r"(b0));
}
template <int N> __device__ __forceinline__ void zero_acc(float (&acc)[N]) {
#pragma unroll
    for (int i = 0; i < N; i++) acc[i] = 0.f;
}
__device__ __forceinline__ void ldsm4(uint32_t& r0, uint32_t& r1, uint32_t& r2, uint32_t& r3, uint32_t addr) {
    asm volatile("ldmatrix.sync.aligned.m8n8.x4.shared.b16 {%0,%1,%2,%3}, [%4];" : "=r"(r0), "=r"(r1), "=r"(r2), "=r"(r3) : "r"(addr));
}

__device__ __forceinline__ void ldsm4t(uint32_t& r0, uint32_t& r1, uint32_t& r2, uint32_t& r3, uint32_t addr) {
    asm volatile("ldmatrix.sync.aligned.m8n8.x4.trans.shared.b16 {%0,%1,%2,%3}, [%4];" : "=r"(r0), "=r"(r1), "=r"(r2), "=r"(r3) : "r"(addr));
}

#define DBG_S(i)
#define DBG_OUT(r, o)
#define DBG_F(i)
#define DBG_W(i)
constexpr int CV_CH = 8;
constexpr int CV_SL = 16384;
constexpr int CV_QG = 128 * 8 + 16;
constexpr int CV_HPL = 2048 + 192;
constexpr int CV_0 = 32768, CV_H = 9 * CV_SL, CV_BAR = OFF_RS - CV_0;

template <int K> __device__ __forceinline__ void cv_mma(float (&d)[64], const uint32_t (&a)[4], uint32_t db, int acc);
template <> __device__ __forceinline__ void cv_mma<0>(float (&d)[64], const uint32_t (&a)[4], uint32_t db, int acc) {
    asm volatile("{\n.reg .pred p;\n.reg .b64 b;\nsetp.ne.b32 p, %70, 0;\nmov.b64 b, {%68, %69};\n"
        "wgmma.mma_async.sync.aligned.m64n128k16.f32.bf16.bf16 {%0,%1,%2,%3,%4,%5,%6,%7,%8,%9,%10,%11,%12,%13,%14,%15,%16,%17,%18,%19,%20,%21,%22,%23,%24,%25,%26,%27,%28,%29,%30,%31,%32,%33,%34,%35,%36,%37,%38,%39,%40,%41,%42,%43,%44,%45,%46,%47,%48,%49,%50,%51,%52,%53,%54,%55,%56,%57,%58,%59,%60,%61,%62,%63}, {%64,%65,%66,%67}, b, p, 1, 1, 0;\n}\n"
        : "+f"(d[0]), "+f"(d[1]), "+f"(d[2]), "+f"(d[3]), "+f"(d[4]), "+f"(d[5]), "+f"(d[6]), "+f"(d[7]), "+f"(d[8]), "+f"(d[9]), "+f"(d[10]), "+f"(d[11]), "+f"(d[12]), "+f"(d[13]), "+f"(d[14]), "+f"(d[15]), "+f"(d[16]), "+f"(d[17]), "+f"(d[18]), "+f"(d[19]), "+f"(d[20]), "+f"(d[21]), "+f"(d[22]), "+f"(d[23]), "+f"(d[24]), "+f"(d[25]), "+f"(d[26]), "+f"(d[27]), "+f"(d[28]), "+f"(d[29]), "+f"(d[30]), "+f"(d[31]), "+f"(d[32]), "+f"(d[33]), "+f"(d[34]), "+f"(d[35]), "+f"(d[36]), "+f"(d[37]), "+f"(d[38]), "+f"(d[39]), "+f"(d[40]), "+f"(d[41]), "+f"(d[42]), "+f"(d[43]), "+f"(d[44]), "+f"(d[45]), "+f"(d[46]), "+f"(d[47]), "+f"(d[48]), "+f"(d[49]), "+f"(d[50]), "+f"(d[51]), "+f"(d[52]), "+f"(d[53]), "+f"(d[54]), "+f"(d[55]), "+f"(d[56]), "+f"(d[57]), "+f"(d[58]), "+f"(d[59]), "+f"(d[60]), "+f"(d[61]), "+f"(d[62]), "+f"(d[63])
        : "r"(a[0]), "r"(a[1]), "r"(a[2]), "r"(a[3]), "r"(db), "r"(8u), "r"(acc));
}
template <> __device__ __forceinline__ void cv_mma<1>(float (&d)[64], const uint32_t (&a)[4], uint32_t db, int acc) {
    asm volatile("{\n.reg .pred p;\n.reg .b64 b;\nsetp.ne.b32 p, %62, 0;\nmov.b64 b, {%60, %61};\n"
        "wgmma.mma_async.sync.aligned.m64n112k16.f32.bf16.bf16 {%0,%1,%2,%3,%4,%5,%6,%7,%8,%9,%10,%11,%12,%13,%14,%15,%16,%17,%18,%19,%20,%21,%22,%23,%24,%25,%26,%27,%28,%29,%30,%31,%32,%33,%34,%35,%36,%37,%38,%39,%40,%41,%42,%43,%44,%45,%46,%47,%48,%49,%50,%51,%52,%53,%54,%55}, {%56,%57,%58,%59}, b, p, 1, 1, 0;\n}\n"
        : "+f"(d[0]), "+f"(d[1]), "+f"(d[2]), "+f"(d[3]), "+f"(d[4]), "+f"(d[5]), "+f"(d[6]), "+f"(d[7]), "+f"(d[8]), "+f"(d[9]), "+f"(d[10]), "+f"(d[11]), "+f"(d[12]), "+f"(d[13]), "+f"(d[14]), "+f"(d[15]), "+f"(d[16]), "+f"(d[17]), "+f"(d[18]), "+f"(d[19]), "+f"(d[20]), "+f"(d[21]), "+f"(d[22]), "+f"(d[23]), "+f"(d[24]), "+f"(d[25]), "+f"(d[26]), "+f"(d[27]), "+f"(d[28]), "+f"(d[29]), "+f"(d[30]), "+f"(d[31]), "+f"(d[32]), "+f"(d[33]), "+f"(d[34]), "+f"(d[35]), "+f"(d[36]), "+f"(d[37]), "+f"(d[38]), "+f"(d[39]), "+f"(d[40]), "+f"(d[41]), "+f"(d[42]), "+f"(d[43]), "+f"(d[44]), "+f"(d[45]), "+f"(d[46]), "+f"(d[47]), "+f"(d[48]), "+f"(d[49]), "+f"(d[50]), "+f"(d[51]), "+f"(d[52]), "+f"(d[53]), "+f"(d[54]), "+f"(d[55])
        : "r"(a[0]), "r"(a[1]), "r"(a[2]), "r"(a[3]), "r"(db), "r"(8u), "r"(acc));
}
template <> __device__ __forceinline__ void cv_mma<2>(float (&d)[64], const uint32_t (&a)[4], uint32_t db, int acc) {
    asm volatile("{\n.reg .pred p;\n.reg .b64 b;\nsetp.ne.b32 p, %54, 0;\nmov.b64 b, {%52, %53};\n"
        "wgmma.mma_async.sync.aligned.m64n96k16.f32.bf16.bf16 {%0,%1,%2,%3,%4,%5,%6,%7,%8,%9,%10,%11,%12,%13,%14,%15,%16,%17,%18,%19,%20,%21,%22,%23,%24,%25,%26,%27,%28,%29,%30,%31,%32,%33,%34,%35,%36,%37,%38,%39,%40,%41,%42,%43,%44,%45,%46,%47}, {%48,%49,%50,%51}, b, p, 1, 1, 0;\n}\n"
        : "+f"(d[0]), "+f"(d[1]), "+f"(d[2]), "+f"(d[3]), "+f"(d[4]), "+f"(d[5]), "+f"(d[6]), "+f"(d[7]), "+f"(d[8]), "+f"(d[9]), "+f"(d[10]), "+f"(d[11]), "+f"(d[12]), "+f"(d[13]), "+f"(d[14]), "+f"(d[15]), "+f"(d[16]), "+f"(d[17]), "+f"(d[18]), "+f"(d[19]), "+f"(d[20]), "+f"(d[21]), "+f"(d[22]), "+f"(d[23]), "+f"(d[24]), "+f"(d[25]), "+f"(d[26]), "+f"(d[27]), "+f"(d[28]), "+f"(d[29]), "+f"(d[30]), "+f"(d[31]), "+f"(d[32]), "+f"(d[33]), "+f"(d[34]), "+f"(d[35]), "+f"(d[36]), "+f"(d[37]), "+f"(d[38]), "+f"(d[39]), "+f"(d[40]), "+f"(d[41]), "+f"(d[42]), "+f"(d[43]), "+f"(d[44]), "+f"(d[45]), "+f"(d[46]), "+f"(d[47])
        : "r"(a[0]), "r"(a[1]), "r"(a[2]), "r"(a[3]), "r"(db), "r"(8u), "r"(acc));
}
template <> __device__ __forceinline__ void cv_mma<3>(float (&d)[64], const uint32_t (&a)[4], uint32_t db, int acc) {
    asm volatile("{\n.reg .pred p;\n.reg .b64 b;\nsetp.ne.b32 p, %46, 0;\nmov.b64 b, {%44, %45};\n"
        "wgmma.mma_async.sync.aligned.m64n80k16.f32.bf16.bf16 {%0,%1,%2,%3,%4,%5,%6,%7,%8,%9,%10,%11,%12,%13,%14,%15,%16,%17,%18,%19,%20,%21,%22,%23,%24,%25,%26,%27,%28,%29,%30,%31,%32,%33,%34,%35,%36,%37,%38,%39}, {%40,%41,%42,%43}, b, p, 1, 1, 0;\n}\n"
        : "+f"(d[0]), "+f"(d[1]), "+f"(d[2]), "+f"(d[3]), "+f"(d[4]), "+f"(d[5]), "+f"(d[6]), "+f"(d[7]), "+f"(d[8]), "+f"(d[9]), "+f"(d[10]), "+f"(d[11]), "+f"(d[12]), "+f"(d[13]), "+f"(d[14]), "+f"(d[15]), "+f"(d[16]), "+f"(d[17]), "+f"(d[18]), "+f"(d[19]), "+f"(d[20]), "+f"(d[21]), "+f"(d[22]), "+f"(d[23]), "+f"(d[24]), "+f"(d[25]), "+f"(d[26]), "+f"(d[27]), "+f"(d[28]), "+f"(d[29]), "+f"(d[30]), "+f"(d[31]), "+f"(d[32]), "+f"(d[33]), "+f"(d[34]), "+f"(d[35]), "+f"(d[36]), "+f"(d[37]), "+f"(d[38]), "+f"(d[39])
        : "r"(a[0]), "r"(a[1]), "r"(a[2]), "r"(a[3]), "r"(db), "r"(8u), "r"(acc));
}
template <> __device__ __forceinline__ void cv_mma<4>(float (&d)[64], const uint32_t (&a)[4], uint32_t db, int acc) {
    asm volatile("{\n.reg .pred p;\n.reg .b64 b;\nsetp.ne.b32 p, %38, 0;\nmov.b64 b, {%36, %37};\n"
        "wgmma.mma_async.sync.aligned.m64n64k16.f32.bf16.bf16 {%0,%1,%2,%3,%4,%5,%6,%7,%8,%9,%10,%11,%12,%13,%14,%15,%16,%17,%18,%19,%20,%21,%22,%23,%24,%25,%26,%27,%28,%29,%30,%31}, {%32,%33,%34,%35}, b, p, 1, 1, 0;\n}\n"
        : "+f"(d[0]), "+f"(d[1]), "+f"(d[2]), "+f"(d[3]), "+f"(d[4]), "+f"(d[5]), "+f"(d[6]), "+f"(d[7]), "+f"(d[8]), "+f"(d[9]), "+f"(d[10]), "+f"(d[11]), "+f"(d[12]), "+f"(d[13]), "+f"(d[14]), "+f"(d[15]), "+f"(d[16]), "+f"(d[17]), "+f"(d[18]), "+f"(d[19]), "+f"(d[20]), "+f"(d[21]), "+f"(d[22]), "+f"(d[23]), "+f"(d[24]), "+f"(d[25]), "+f"(d[26]), "+f"(d[27]), "+f"(d[28]), "+f"(d[29]), "+f"(d[30]), "+f"(d[31])
        : "r"(a[0]), "r"(a[1]), "r"(a[2]), "r"(a[3]), "r"(db), "r"(8u), "r"(acc));
}
template <> __device__ __forceinline__ void cv_mma<5>(float (&d)[64], const uint32_t (&a)[4], uint32_t db, int acc) {
    asm volatile("{\n.reg .pred p;\n.reg .b64 b;\nsetp.ne.b32 p, %30, 0;\nmov.b64 b, {%28, %29};\n"
        "wgmma.mma_async.sync.aligned.m64n48k16.f32.bf16.bf16 {%0,%1,%2,%3,%4,%5,%6,%7,%8,%9,%10,%11,%12,%13,%14,%15,%16,%17,%18,%19,%20,%21,%22,%23}, {%24,%25,%26,%27}, b, p, 1, 1, 0;\n}\n"
        : "+f"(d[0]), "+f"(d[1]), "+f"(d[2]), "+f"(d[3]), "+f"(d[4]), "+f"(d[5]), "+f"(d[6]), "+f"(d[7]), "+f"(d[8]), "+f"(d[9]), "+f"(d[10]), "+f"(d[11]), "+f"(d[12]), "+f"(d[13]), "+f"(d[14]), "+f"(d[15]), "+f"(d[16]), "+f"(d[17]), "+f"(d[18]), "+f"(d[19]), "+f"(d[20]), "+f"(d[21]), "+f"(d[22]), "+f"(d[23])
        : "r"(a[0]), "r"(a[1]), "r"(a[2]), "r"(a[3]), "r"(db), "r"(8u), "r"(acc));
}
template <> __device__ __forceinline__ void cv_mma<6>(float (&d)[64], const uint32_t (&a)[4], uint32_t db, int acc) {
    asm volatile("{\n.reg .pred p;\n.reg .b64 b;\nsetp.ne.b32 p, %22, 0;\nmov.b64 b, {%20, %21};\n"
        "wgmma.mma_async.sync.aligned.m64n32k16.f32.bf16.bf16 {%0,%1,%2,%3,%4,%5,%6,%7,%8,%9,%10,%11,%12,%13,%14,%15}, {%16,%17,%18,%19}, b, p, 1, 1, 0;\n}\n"
        : "+f"(d[0]), "+f"(d[1]), "+f"(d[2]), "+f"(d[3]), "+f"(d[4]), "+f"(d[5]), "+f"(d[6]), "+f"(d[7]), "+f"(d[8]), "+f"(d[9]), "+f"(d[10]), "+f"(d[11]), "+f"(d[12]), "+f"(d[13]), "+f"(d[14]), "+f"(d[15])
        : "r"(a[0]), "r"(a[1]), "r"(a[2]), "r"(a[3]), "r"(db), "r"(8u), "r"(acc));
}
template <> __device__ __forceinline__ void cv_mma<7>(float (&d)[64], const uint32_t (&a)[4], uint32_t db, int acc) {
    asm volatile("{\n.reg .pred p;\n.reg .b64 b;\nsetp.ne.b32 p, %14, 0;\nmov.b64 b, {%12, %13};\n"
        "wgmma.mma_async.sync.aligned.m64n16k16.f32.bf16.bf16 {%0,%1,%2,%3,%4,%5,%6,%7}, {%8,%9,%10,%11}, b, p, 1, 1, 0;\n}\n"
        : "+f"(d[0]), "+f"(d[1]), "+f"(d[2]), "+f"(d[3]), "+f"(d[4]), "+f"(d[5]), "+f"(d[6]), "+f"(d[7])
        : "r"(a[0]), "r"(a[1]), "r"(a[2]), "r"(a[3]), "r"(db), "r"(8u), "r"(acc));
}
__device__ __forceinline__ void stsm4t(uint32_t addr, uint32_t r0, uint32_t r1, uint32_t r2, uint32_t r3) {
    asm volatile("stmatrix.sync.aligned.m8n8.x4.trans.shared.b16 [%0], {%1,%2,%3,%4};" ::"r"(addr), "r"(r0), "r"(r1), "r"(r2), "r"(r3) : "memory");
}
__device__ __forceinline__ void cp16(uint32_t dst, const void* src, int n = 16) {
    asm volatile("cp.async.cg.shared.global.L2::128B [%0], [%1], 16, %2;" ::"r"(dst), "l"(src), "r"(n) : "memory");
}
__device__ __forceinline__ void cp_arrive(uint32_t bar) { asm volatile("cp.async.mbarrier.arrive.noinc.shared::cta.b64 [%0];" ::"r"(bar) : "memory"); }
__device__ __forceinline__ void lds64(uint32_t& x, uint32_t& y, uint32_t a) { asm volatile("ld.shared.v2.b32 {%0,%1}, [%2];" : "=r"(x), "=r"(y) : "r"(a) : "memory"); }
__device__ __forceinline__ void sts128(uint32_t a, uint32_t x, uint32_t y, uint32_t z, uint32_t w) {
    asm volatile("st.shared.v4.b32 [%0], {%1,%2,%3,%4};" ::"r"(a), "r"(x), "r"(y), "r"(z), "r"(w) : "memory");
}
__device__ __forceinline__ uint32_t bfma2(uint32_t a, uint32_t b, uint32_t c) {
    uint32_t r;
    asm("fma.rn.bf16x2 %0, %1, %2, %3;" : "=r"(r) : "r"(a), "r"(b), "r"(c));
    return r;
}
#define CV_NS 4
#define CV_W 1
constexpr int CV_GC = 8 / CV_NS, CV_NA = (CV_W + 2) * CV_NS;
struct CvAddr { uint32_t pa[2], p0[4], db, rdy, xw, xr, bar; bool wrap, neg[2]; };
template <int G> __device__ __forceinline__ void cv_load(uint32_t (&a)[CV_NA][4], const CvAddr& p) {
    if constexpr (G % CV_GC == 0) mbar_wait(p.rdy + 8 * (G / CV_GC), 0);
#pragma unroll
    for (int i = G * CV_NS; i < (G + 1) * CV_NS; i++) {
        const int of = (i / 2 % 2) * CV_QG + (i / 8) * CV_SL + 256 * (i % 2 + (i / 2 & 2));
        if ((i & 5) == 0) {
#pragma unroll
            for (int e = 0; e < 4; e++) asm volatile("ld.shared.b32 %0, [%1];" : "=r"(a[i % CV_NA][e]) : "r"(p.p0[e] + of) : "memory");
            if (i < 8) { if (p.neg[0]) a[i % CV_NA][0] = 0; if (p.neg[1]) a[i % CV_NA][2] = 0; }
        } else {
            lds64(a[i % CV_NA][0], a[i % CV_NA][1], p.pa[0] + of - 256);
            lds64(a[i % CV_NA][2], a[i % CV_NA][3], p.pa[1] + of - 256);
        }
    }
}
__device__ __forceinline__ float vadd(float a, float b) {
    float r;
    asm volatile("add.f32 %0, %1, %2;" : "=f"(r) : "f"(a), "f"(b));
    return r;
}
template <int K> __device__ __forceinline__ uint32_t cv_tail(float (&d)[64], bool wrap) {
    float* z = d + 56 - 8 * K;
    z[4] = vadd(z[4], K > 0 ? z[10] : 0.f);
    if constexpr (K > 0) z[5] = vadd(z[5], z[11]);
    z[0] = vadd(z[0], z[6]);
    z[1] = vadd(z[1], z[7]);
    return pack2(wrap ? (K > 0 ? z[8] : 0.f) : z[4], wrap ? z[4] : z[0]);
}
template <int K> __device__ __forceinline__ uint32_t cv_fin(const float (&d)[64], uint32_t x) { return pack2(d[61 - 8 * K] + lo2f(x), d[57 - 8 * K] + hi2f(x)); }
template <int G>
__device__ __forceinline__ void cv_steps(float (&d)[2][64], uint32_t (&a)[CV_NA][4], uint32_t (&tv)[2][8], const CvAddr& p) {
    constexpr int K = G / CV_GC, GN = 8 * CV_GC;
    constexpr int T = G - CV_W - CV_GC, F = T - 1, TK = T / CV_GC, FK = F / CV_GC;
    if constexpr (G == 0) cv_load<0>(a, p);
    if constexpr (G < GN) {
        wgmma_fence();
#pragma unroll
        for (int i = G * CV_NS; i < (G + 1) * CV_NS; i++)
            cv_mma<K>(d[i / 2 % 2], a[i % CV_NA], p.db + (i / 2 % 2) * (CV_HPL / 8) + 16 * K + 2 * (i % 2 + (i / 2 & 2)), i & ~2 ? 1 : p.bar >> 8);
        wgmma_commit();
    }
    if constexpr (G < GN - 1) cv_load<G + 1>(a, p);
    if constexpr (T >= 0 && T % CV_GC == 0) {
        tv[0][TK] = cv_tail<TK>(d[0], p.wrap);
        tv[1][TK] = cv_tail<TK>(d[1], p.wrap);
        if constexpr (TK & 1) sts128(p.xw + TK / 2 * 512, tv[0][TK - 1], tv[0][TK], tv[1][TK - 1], tv[1][TK]);
    }
    if constexpr (F >= 0 && F % (2 * CV_GC) == CV_GC) {
        const uint4 x = lds128(p.xr + FK / 2 * 512);
        tv[0][FK - 1] = cv_fin<FK - 1>(d[0], x.x); tv[0][FK] = cv_fin<FK>(d[0], x.y);
        tv[1][FK - 1] = cv_fin<FK - 1>(d[1], x.z); tv[1][FK] = cv_fin<FK>(d[1], x.w);
    }
    if constexpr (G < GN - 1) wgmma_wait<CV_W>();
    if constexpr (G == GN - 1) wgmma_wait<0>();
    if constexpr (T >= 0 && T % (2 * CV_GC) == CV_GC) named_bar_sync(p.bar, 128);
    if constexpr (F < GN - CV_GC) cv_steps<G + 1>(d, a, tv, p);
}

#define CV_PF 7
#define Y_FIRST 1
#define Y_HOLD 0
#define PS2_EARLY 1
#define PS1_EARLY 1
struct MegaMaps {
    CUtensorMap q, act;
    CUtensorMap a64, w1, w2, w3, w4;
    CUtensorMap k, v;
};

__global__ void __cluster_dims__(2, 1, 1) __launch_bounds__(384, 1)
mega_kernel(const __grid_constant__ MegaMaps tm, bf16* __restrict__ outp, bf16* act, const bf16* __restrict__ w1p, const bf16* __restrict__ w2p,
            const bf16* __restrict__ w3p, const bf16* __restrict__ xq, const bf16* __restrict__ kp, const bf16* __restrict__ vp,
            const bf16* __restrict__ shk, const bf16* __restrict__ ssk, const bf16* __restrict__ ssD) {
    extern __shared__ __align__(1024) uint8_t sgen[];
    const uint32_t sbase = smem_u32(sgen);
    const int warp = __shfl_sync(0xffffffffu, threadIdx.x >> 5, 0), lane = threadIdx.x & 31;
    const int rank = blockIdx.x & 1;
    const uint32_t s_bar = sbase + OFF_BAR;
    const uint32_t f5 = s_bar, e5 = s_bar + 64, f4 = s_bar + 144, e4 = s_bar + 104;
    const uint32_t b_rfull = s_bar + 176, b_role = s_bar + 184, b_stg = s_bar + 136, b_h2 = s_bar + 32;
    const uint32_t s_epi = sbase + OFF_EPI, s_stg = sbase + OFF_STG5, s_r = sbase + OFF_R;
    uint8_t* sm = sgen + CV_0;
    const uint32_t sb = sbase + CV_0;
    const int tid = threadIdx.x, wg = warp >> 2, w = warp & 3;
    const int d0 = blockIdx.x * CV_CH;
    const bool cv = blockIdx.x < D_ / CV_CH;
    const uint32_t b_full = sb + CV_BAR, b_rdy = b_full + 64, b_h = b_full + 128;
    GT(0);
    if (tid == 0) TM(0);
    auto row_at = [&](int r) { return sb + CV_SL + (r < 0 ? -8192 : 0) + ((r & 127) >> 5) * 1024 + (r & 7) * 128 + ((r >> 3) & 3) * 32 + ((r ^ rank) & 1) * 16; };
    auto load_kv = [&](int c) {
#pragma unroll
        for (int i = 0; i < 2; i++)
            asm volatile("cp.async.bulk.tensor.4d.shared::cluster.global.mbarrier::complete_tx::bytes.multicast::cluster [%0], [%1, {%3, %4, %4, %5}], [%2], %6;"
                         ::"r"(sb + (c + 1) * CV_SL + rank * 8192 + i * 4096), "l"((uint64_t)(i ? &tm.v : &tm.k)), "r"(b_full + 8 * c), "r"(d0 & ~15), "r"(0),
                         "r"(8 * c + 4 * rank), "h"((uint16_t)3) : "memory");
    };
    auto bulk = [&](uint32_t dst, const void* src, uint32_t n, uint32_t bar) {
        asm volatile("cp.async.bulk.shared::cluster.global.mbarrier::complete_tx::bytes [%0], [%1], %2, [%3];" ::"r"(dst), "l"(src), "r"(n), "r"(bar) : "memory");
    };
    auto put_h = [&](int ch) {
        const uint32_t dk = (tid & 127) ? 0 : *reinterpret_cast<const volatile uint32_t*>(sm + CV_BAR + 160 + 16 * wg + 2 * ch);
        uint4 v[4];
#pragma unroll
        for (int i = 0; i < 4; i++) v[i] = lds128(sbase + ch * 4096 + i * 2048 + (tid & 127) * 16);
        v[0].x = pack2(lo2f(v[0].x) + lo2f(dk), hi2f(v[0].x));
        v[2].x = pack2(lo2f(v[2].x) + hi2f(dk), hi2f(v[2].x));
#pragma unroll
        for (int i = 0; i < 4; i++)
            sts128(sb + CV_H + (2 * ch + (i & 2) + (tid & 1)) * CV_HPL + (127 - ((tid & 127) >> 1)) * 16 - (i & 1) * 1024, v[i].x, v[i].y, v[i].z, v[i].w);
    };
    int bi, bj, m0, tb;
    uint32_t ep;
    auto get_role = [&]() {
        mbar_wait(b_role, 0);
        int role;
        asm volatile("ld.shared.v2.b32 {%0,%1}, [%2];" : "=r"(role), "=r"(ep) : "r"(s_bar + 248) : "memory");
        bi = (role >> 3) * 2 + rank; bj = role & 7; m0 = bi * BM; tb = (role >> 3) * 2048 + rank * 128;
        return role < 64;
    };

    if (warp >= 8) {
        asm volatile("setmaxnreg.dec.sync.aligned.u32 88;");
        cluster_arrive_relaxed();
        if (!cv) cluster_wait(); else {
            const int bt = tid - 256, g = lane >> 2, t = lane & 3;
            if (bt < 16) sts128(row_at((bt & 7) - 8) + (bt >> 3) * 4096, 0, 0, 0, 0);
#pragma unroll
            for (int i = 0; i < 4; i++)
                cp16(row_at(bt) + i * 4096, (i & 1 ? vp : kp) + (size_t)(bt + (i >> 1) * 128) * D_ + d0);
            DBG_S(16 + (3));
            uint2 wa;
            asm volatile("ld.global.nc.v2.b32 {%0,%1}, [%2];" : "=r"(wa.x), "=r"(wa.y) : "l"(shk + (d0 + g) * 4));
            const int mi = lane >> 3, r0 = 32 * w + 8 * ((lane >> 1) & 3) - (lane & 1);
            const uint32_t ka0 = row_at(r0 + 2 * mi - 3), ka1 = row_at(r0 + 2 * (mi & 1) + 5) + (mi >> 1) * 8192;
            const uint32_t va0 = row_at(r0 + 2 * mi + 1) + 4096, va1 = row_at(r0 - 1) + 4096 + (mi & 1) * 8192;
            const uint32_t qd = sb + g * CV_QG + (32 * w + 8 * t) * 8, qd0 = qd + (t & 2) * 16, qd1 = qd + (~t & 2) * 16;
            const uint32_t w0 = __byte_perm(wa.x, 0, 0x1010), w1 = __byte_perm(wa.x, 0, 0x3232), w2 = __byte_perm(wa.y, 0, 0x1010), w3 = __byte_perm(wa.y, 0, 0x3232);
            cluster_wait();
            DBG_S(16 + (5));
            asm volatile("cp.async.wait_all;" ::: "memory");
            named_bar_sync(7, 128);
            DBG_S(16 + (1));
            struct KV { uint32_t k[2][6], v[2][5]; };
            auto get = [&](KV& x, uint32_t so) {
                ldsm4t(x.k[0][0], x.k[0][1], x.k[0][2], x.k[0][3], ka0 + so);
                ldsm4t(x.k[0][4], x.k[0][5], x.k[1][4], x.k[1][5], ka1 + so);
                ldsm4t(x.k[1][0], x.k[1][1], x.k[1][2], x.k[1][3], ka0 + so + 8192);
                asm volatile("ldmatrix.sync.aligned.m8n8.x2.trans.shared.b16 {%0,%1}, [%2];" : "=r"(x.v[0][0]), "=r"(x.v[1][0]) : "r"(va1 + so));
                ldsm4t(x.v[0][1], x.v[0][2], x.v[0][3], x.v[0][4], va0 + so);
                ldsm4t(x.v[1][1], x.v[1][2], x.v[1][3], x.v[1][4], va0 + so + 8192);
            };
            auto build = [&](int c, const KV& x, KV& nx) {
                const uint32_t so = c * CV_SL;
                DBG_F(1);
                uint32_t early;
                asm volatile("{\n.reg .pred p;\nmbarrier.test_wait.parity.shared::cta.b64 p, [%1], 0;\nvote.sync.all.pred p, p, -1;\nselp.u32 %0, 1, 0, p;\n}"
                             : "=r"(early) : "r"(b_full + 8 * (c < 7 ? c + 1 : c)) : "memory");
                if (early) get(nx, so + CV_SL);
                DBG_F(2);
                uint32_t p[8][2];
#pragma unroll
                for (int sg = 0; sg < 2; sg++) {
                    uint32_t u[5], ke[6];
#pragma unroll
                    for (int i = 0; i < 6; i++) ke[i] = __byte_perm(x.k[sg][i], x.k[sg][i ? i - 1 : 0], 0x5432);
#pragma unroll
                    for (int i = 0; i < 5; i++) {
                        u[i] = bmul2(bfma2(x.k[sg][i + 1], w0, bfma2(ke[i + 1], w1, bfma2(x.k[sg][i], w2, bmul2(ke[i], w3)))), x.v[sg][i]);
                        if (i) { p[2 * i - 1][sg] = u[i]; p[2 * i - 2][sg] = __byte_perm(u[i], u[i - 1], 0x5432); }
                    }
                }
                DBG_F(3);
#pragma unroll
                for (int j = 0; j < 4; j++) sts128((j & 2 ? qd1 : qd0) + so + 16 * (j & 1), p[2 * j][0], p[2 * j][1], p[2 * j + 1][0], p[2 * j + 1][1]);
                __syncwarp();
                DBG_F(4);
                if (lane == 0) {
                    mbar_arrive(b_rdy + 8 * c);
                    if (c == w) {
                        if (c < 3) load_kv(c + 5);
                        else { bulk(sbase + 16384, ssk + (size_t)(d0 + 4) * S_, 16384, b_h + 16); bulk(b_full + 192, ssD + d0, 16, b_h + 16); }
                    }
                    if (c == w + 4 && (CV_PF >> w & 1)) {
                        const uint32_t n = w == 0 ? 32768 : w == 3 ? 57344 : 16384;
                        const char* src = reinterpret_cast<const char*>(w == 0 ? xq : w == 1 ? w1p : w == 2 ? w2p : w3p) + (size_t)blockIdx.x * n;
                        asm volatile("cp.async.bulk.prefetch.L2.global [%0], %1;" ::"l"(src), "r"(n) : "memory");
                    }
                }
                DBG_F(5);
                named_bar_sync(7, 128);
                DBG_F(6);
                DBG_S(16 + (c == 0 ? 4 : 5 + c));
                if (!early) { mbar_wait(b_full + 8 * c + 8, 0); get(nx, so + CV_SL); }
                DBG_F(7);
            };
            KV x0, x1;
            get(x0, 0);
#pragma unroll 1
            for (int c = 0; c < 8; c += 2) { build(c, x0, x1); build(c + 1, x1, x0); }
            mbar_wait(b_h + 16, 0);
            put_h(4); put_h(6);
            fence_async_smem();
            __syncwarp();
            if (lane == 0) mbar_arrive(b_full);
            named_bar_sync(7, 128);
            DBG_S(16 + (13));
        }
    } else {
        if (elect_one()) {
            mbar_init(b_full + 8 * warp, warp ? 1 : 4);
            mbar_init(b_rdy + 8 * warp, 4);
            if (warp) mbar_expect_tx(b_full + 8 * warp, 16384);
            if (w == 0 && cv) {
                mbar_init(b_h + 8 * wg, 1);
                mbar_expect_tx(b_h + 8 * wg, 8192 + 16);
                fence_async_smem();
                bulk(sbase + wg * 8192, ssk + (size_t)(d0 + 2 * wg) * S_, 8192, b_h + 8 * wg);
                bulk(b_full + 160 + 16 * wg, ssD + d0, 16, b_h + 8 * wg);
            }
            mbar_init(s_bar + 8 * warp, 1);
            mbar_init(s_bar + 64 + 8 * warp, 4);
            mbar_init(s_bar + 128 + 8 * warp, warp < 2 ? 4 << warp : warp == 6 ? 2 : 1);
            if (wg) mbar_init(s_bar + 160 + 8 * warp, 8);
            if (warp == 0) mbar_arrive(f5);
            if (warp == 7) mbar_expect_tx(b_role, 8);
            if (warp == 1) { mbar_init(b_h + 16, 1); mbar_expect_tx(b_h + 16, 16384 + 16); }
            if (w == 2) sts128(s_bar + 224 + 16 * wg, 0, 0, 0, 0);
            asm volatile("fence.mbarrier_init.release.cluster;" ::: "memory");
            if (warp == 2) { prefetch_tmap(&tm.k); prefetch_tmap(&tm.v); }
        }
        __syncwarp();
        DBG_W(1);
        cluster_arrive_relaxed();
        asm volatile("setmaxnreg.inc.sync.aligned.u32 208;");
        DBG_W(2);
        const int zi = (tid & 127) - 32;
        if (zi >= 0 && zi < 48) sts128(sb + CV_H + (4 * wg + (zi / 6 & 3) + (zi / 24) * 8) * CV_HPL + 2048 + (zi % 6) * 16, 0, 0, 0, 0);
        DBG_W(3);
        cluster_wait();
        DBG_W(5);
        if (cv) {
            if (tid == 32) {
#pragma unroll 1
                for (int c = 1; c < 5; c++) load_kv(c);
            }
            __syncwarp();
            DBG_W(6);
            const int g = lane >> 2, t = lane & 3;
            const int x0 = 32 + 8 * w + g - 2 * t;
            CvAddr p;
            p.rdy = b_rdy;
            p.bar = 1 + wg;
            p.xr = sbase + (warp ^ 2) * 2048 + lane * 16;
            p.xw = sbase + warp * 2048 + (g * 4 + ((t - (w >> 1)) & 3)) * 16;
            p.wrap = t == 0 && w >= 2;
            mbar_wait(b_h + 8 * wg, 0);
            DBG_W(4);
            put_h(2 * wg);
            fence_async_smem();
            named_bar_sync(1 + wg, 128);
            float acc[2][64];
            zero_acc(acc[0]); zero_acc(acc[1]);
#pragma unroll 1
            for (int round = 0; round < 2; round++) {
                const int ch = round * 4 + 2 * wg;
                uint32_t a[CV_NA][4], tv[2][8];
#pragma unroll
                for (int e = 0; e < 2; e++) {
                    const int x = x0 - 8 * e;
                    p.neg[e] = x < 32;
                    p.pa[e] = sb + ch * CV_QG + 8 * (x ^ (x >> 2 & 4));
                    p.p0[2 * e] = p.pa[e] + (x < 32 ? 768 + 4 - CV_SL : -256);
                    p.p0[2 * e + 1] = p.pa[e] + (x < 32 ? 768 : -256 + 4);
                }
                p.db = (((sb + CV_H + ch * 2 * CV_HPL) & 0x3FFFF) >> 4) | ((CV_HPL / 16) << 16);
                if (round) mbar_wait(b_full, 0);
                DBG_S(7 + 3 * round);
                cv_steps<0>(acc, a, tv, p);
                DBG_S(8 + 3 * round);
                const int r128 = 4 * (lane >> 3) + 2 * (lane & 1) + ((~lane >> 2) & 1);
#pragma unroll
                for (int i = 0; i < 2; i++) {
                    const uint32_t ta = sb + ((ch + i + 1) & 7) * CV_SL + 12288 + r128 * 128 + ((((~lane & 2) * 2 + w) ^ (r128 & 7)) << 4);
                    stsm4t(ta, tv[i][0], tv[i][1], tv[i][2], tv[i][3]);
                    stsm4t(ta + 2048, tv[i][4], tv[i][5], tv[i][6], tv[i][7]);
                }
                named_bar_sync(1 + wg, 128);
                {
                    const int l = 4 * w + (lane >> 3);
                    uint4 v[4];
#pragma unroll
                    for (int i = 0; i < 4; i++) v[i] = lds128(sb + ((ch + (i >> 1) + 1) & 7) * CV_SL + 12288 + (i & 1) * 2048 + l * 128 + (((lane ^ l) & 7) << 4));
                    const int yr = (d0 & 128) + round * 68 + ((d0 >> 1 & 60) ^ 2 * wg) - (d0 & 8) * round;
                    bf16* gy = act + (size_t)(R_Y + w * 2048 + yr) * D_ + (d0 & ~255) + lane * 8;
#pragma unroll
                    for (int i = 0; i < 4; i++) stg128(gy + ((i & 1) * 8192 + (i >> 1)) * D_, v[i]);
                    named_bar_arrive(4 + 8 * round, 288);
                }
                DBG_S(9 + 3 * round);
            }
        }
    }
    int warp2 = warp;
    asm volatile("" : "+r"(warp2));
    if (warp2 >= 8) {
        asm volatile("setmaxnreg.dec.sync.aligned.u32 72;");
        if (warp == 8) { if (elect_one()) {
            if (rank == 0) {
                uint32_t smid;
                asm volatile("mov.u32 %0, %%smid;" : "=r"(smid));
                const int t = smid >> 1;
                int team = t < 32 ? t & 7 : t < 60 ? 1 + (t - 32) % 7 : t < 62 ? t - 54 : 0;
                const unsigned long long arr = atomicAdd(reinterpret_cast<unsigned long long*>(g_ticket + 16 * FL_PITCH), 1ull);
                const uint32_t e1 = (uint32_t)(arr / NCL) + 1;
                unsigned int* tk = g_ticket + (e1 & 1) * 8 * FL_PITCH;
                int slot = atomicAdd(tk + team * FL_PITCH, 1u);
                atomicAdd(g_ticket + 17 * FL_PITCH, 1u);
                if (blockIdx.x < 16) g_ticket[((~e1 & 1) * 8 + (blockIdx.x >> 1)) * FL_PITCH] = 0;
                if (slot >= 8) {
                    const long long t0 = clock64();
                    while ((int)(*(volatile unsigned int*)(g_ticket + 17 * FL_PITCH) - e1 * NCL) < 0 && clock64() - t0 < 100000) {}
                    for (team = 0; team < 8; team++)
                        if ((slot = atomicAdd(tk + team * FL_PITCH, 1u)) < 8) break;
                }
#pragma unroll
                for (int i = 0; i < 2; i++)
                    asm volatile("st.async.weak.shared::cluster.mbarrier::complete_tx::bytes.v2.b32 [%0], {%1, %2}, [%3];"
                                 ::"r"(mapa_u32(s_bar + 248, i)), "r"(team * 8 + slot), "r"(e1), "r"(mapa_u32(b_role, i)) : "memory");
            }
            if (get_role()) {
            TM(2);
            mbar_expect_tx(b_rfull, 32768);
            tma_load_2d(sbase + 16384, &tm.q, b_rfull, bj * 128, m0);
            tma_load_2d(sb + 8 * CV_SL, &tm.q, b_rfull, bj * 128 + 64, m0);
            int s5 = 0, s4 = 0;
            uint32_t p5 = 0, p4 = 1;
            auto putB = [&](const CUtensorMap* tB, int kc, uint32_t bytes) {
                const uint32_t full = f5 + 8 * s5;
                mbar_wait(full + 64, (p5 >> s5) & 1);
                mbar_expect_tx(full, bytes);
                tma_load_2d_mc(s_r + 16384 + rank * 8192 + s5 * R5_STAGE, tB, full, bj * 128 + rank * 64, kc);
                p5 ^= 1u << s5;
            };
            auto putA = [&](int c, int r) {
                tma_load_2d(s_r + s5 * R5_STAGE, &tm.act, f5 + 8 * s5, c, r);
                if (++s5 == R5_N) s5 = 0;
            };
            prefetch_tmap(&tm.act); prefetch_tmap(&tm.w1); prefetch_tmap(&tm.w2); prefetch_tmap(&tm.w3); prefetch_tmap(&tm.w4); prefetch_tmap(&tm.a64);
            auto own_first = [&](int it) {
                const int hf = it >= 9, c = it - 2 - 7 * hf;
                return (it < 2 ? 2 * bj + it : 2 * (c + (c >= bj)) + hf) * BK;
            };
            const unsigned int n8 = 8 * ep, nh = (bi == 0 || bi == 15) ? 12 * ep : 2 * n8;
#pragma unroll 1
            for (int layer = 0; layer < 2; layer++) {
                s5 = 2;
#pragma unroll 1
                for (int kk = -(layer | Y_FIRST); kk < 5 - (layer | Y_FIRST); kk++) {
                    if (kk & 4) {
                        mbar_wait(e5 + 8, (p5 >> 1) & 1);
                        mbar_expect_tx(f5 + 8, 32768);
#pragma unroll 1
                        for (int i = 0; i < 4; i++) {
                            if (layer == 0 && !(i & 1)) { wait_flag(flag_ptr(1 - (i >> 1), FL_CS, 8 + bj), 8 * n8); TM(4); fence_proxy_async(); }
                            tma_load_2d(s_r + R5_STAGE + (i & 1) * 16384 + (i >> 1) * 8192, &tm.a64, f5 + 8, (bj >> 1) * 256 + rank * 128 + (i & 1) * 64,
                                        R_Y + (tb & ~255) + (bj & 1) * 128 + (i >> 1) * 64);
                        }
                        p5 ^= 2;
                        if (layer == 0) TM(5);
                    } else {
                        if (kk == Y_HOLD && layer == 0) mbar_wait(f5 + 8, 0);
                        putB(&tm.w1, own_first(kk), kk < 2 ? 16384 : R5_STAGE);
                        if (++s5 == R5_N) s5 = 0;
                    }
                }
                s5 = 4;
#pragma unroll 1
                for (int kk = 2; kk < 16; kk++) {
                    const int kc = own_first(kk);
                    if (kk >= 4) putB(&tm.w1, kc, R5_STAGE);
                    if (kk == 2 || kk == 9) {
                        wait_flag(flag_ptr(layer, FL_XA + (kk & 1), bi), n8);
                        if (layer == 0 && kk == 2) TM(14);
                        DP(8 * (FL_XA + (kk & 1)) + 3);
                        fence_proxy_async();
                        DP(8 * (FL_XA + (kk & 1)) + 4);
                    }
                    putA(kc, R_XA + tb);
                }
                mbar_wait(e5 + 24, (p5 >> 3) & 1);
                mbar_arrive(f5 + 24);
                p5 ^= 8;
                s5 = 4;
#pragma unroll 1
                for (int kk = 0; kk < 5; kk++) { putB(&tm.w2, own_first(kk), kk < 2 ? 16384 : R5_STAGE); if (++s5 == R5_N) s5 = 0; }
                s5 = 1;
#pragma unroll 1
                for (int kk = 2; kk < 16; kk++) {
                    const int kc = own_first(kk);
                    if (kk >= 5) putB(&tm.w2, kc, R5_STAGE);
                    if (kk == 2 || kk == 9) {
                        wait_flag(flag_ptr(layer, FL_H + (kk & 1), bi), nh);
                        DP(8 * (FL_H + (kk & 1)) + 3);
                        fence_proxy_async();
                        DP(8 * (FL_H + (kk & 1)) + 4);
                    }
                    putA(kc, R_H + layer * R_HP + m0 + (int)((0x4031u >> (kc >> 6 & 12)) & 7) - 2);
                }
#pragma unroll 1
                for (int it = 0; it < 32; it++) {
                    const int kc = it >= 16 ? (it - 16) * BK : own_first(it);
                    const int nb = it < 16 ? 4 : 3, n0 = bj * 448 + (it < 16 ? 0 : 256);
                    if (it > 0 && it < 4) {
                        const int i = (it - 1) * 3 >> 1;
                        mbar_wait(e5 + 8 * i, (p5 >> i) & 1);
                        mbar_wait(e5 + 8 * i + 8, (p5 >> (i + 1)) & 1);
                    }
                    mbar_wait(e4 + 8 * s4, p4);
                    if (it >= 16 && it < 19) mbar_wait(e4 + 8 * s4 + 8, p4);
                    uint32_t sa = s_r + s4 * (it < 16 ? R4_STAGE : R4B_STAGE), full = f4 + 8 * s4;
                    mbar_expect_tx(full, (it < 2 ? 0 : 16384) + nb * 8192);
#pragma unroll 1
                    for (int j = (it ^ rank) & 1; j < nb; j += 2) tma_load_2d_mc(sa + (it < 16 ? -32768 : 16384) + j * 8192, &tm.w3, full, n0 + j * 64, kc);
                    if (it == 2 || it == 9) {
                        wait_flag(flag_ptr(layer, FL_X1 + (it >> 3), bi), n8);
                        DP(8 * (FL_X1 + (it >> 3)) + 3);
                        fence_proxy_async();
                        DP(8 * (FL_X1 + (it >> 3)) + 4);
                    }
                    if (it >= 2) tma_load_2d(sa, &tm.act, full, kc, R_X1 + tb);
                    if (it >= PF4A && it < PF4A + PF4N && layer == 0) tma_prefetch_2d(&tm.w4, bj * 128 + rank * 64, (7 * (bi >> 1) + it - PF4A) * BK);
                    if (++s4 == R4_N) { s4 = 0; p4 ^= 1; }
                }
                wait_flag(flag_ptr(layer, FL_H2, bi), n8);
                fence_proxy_async();
                s5 = 0;
#pragma unroll 1
                for (int j = 0; j < 7; j++) {
                    if (j > 0 && (j & 1) == 0) {
                        mbar_wait(b_h2 + 4 * j, layer);
                        fence_proxy_async();
                    }
                    const int ra = R_H2 + (j >> 1) * 256 + tb;
#pragma unroll 1
                    for (int b = 0; b < 8; b++) {
                        if (j == 0 && b < R4_N) mbar_wait(e4 + 8 * b, p4);
                        putB(&tm.w4, (7 * b + j) * BK, R5_STAGE);
                        putA(((j & 1) * 8 + b) * BK, ra);
                    }
                }
            }
        } } } else {
            auto colsum = [&](bool is1, int bi, int bj) {
                const int pitch = is1 ? D_ : F_, c = is1 ? bj * 128 + (lane & 15) * 8 : bj * 448 + min((warp & 2) * 128 + lane * 8, 440);
                const bf16* p = (is1 ? w1p : w3p) + ((bi * 64 + (is1 ? (lane >> 4) * 32 : 0)) * pitch + c);
                float a[8];
#pragma unroll
                for (int i = 0; i < 8; i++) a[i] = 0.f;
#pragma unroll 1
                for (int r0 = is1 ? 32 : 0; r0 < 64; r0 += 8) {
                    uint4 v[8];
#pragma unroll
                    for (int r = 0; r < 8; r++, p += pitch) v[r] = __ldg(reinterpret_cast<const uint4*>(p));
#pragma unroll
                    for (int r = 0; r < 8; r++) {
                        a[0] += lo2f(v[r].x); a[1] += hi2f(v[r].x); a[2] += lo2f(v[r].y); a[3] += hi2f(v[r].y);
                        a[4] += lo2f(v[r].z); a[5] += hi2f(v[r].z); a[6] += lo2f(v[r].w); a[7] += hi2f(v[r].w);
                    }
                }
                if (is1) {
#pragma unroll
                    for (int i = 0; i < 8; i++) a[i] += __shfl_xor_sync(0xffffffffu, a[i], 16);
                }
                float4* dst = reinterpret_cast<float4*>(g_cpart + bi * (F_ + D_) + (is1 ? F_ : 0) + c);
                dst[0] = make_float4(a[0], a[1], a[2], a[3]);
                dst[1] = make_float4(a[4], a[5], a[6], a[7]);
                __syncwarp();
                if (lane == 0) asm volatile("red.release.gpu.global.add.u32 [%0], 1;" ::"l"(flag_ptr(!is1, FL_CS, bj)) : "memory");
                __syncwarp();
            };
            if (cv && warp == 10) colsum(true, blockIdx.x >> 3, blockIdx.x & 7);
            if (cv && warp == 9) {
#pragma unroll 1
                for (int round = 0; round < 2; round++) {
                    named_bar_sync(4 + 8 * round, 288);
                    if (lane == 0) {
                        asm volatile("fence.release.gpu;" ::: "memory");
                        asm volatile("red.relaxed.gpu.global.add.u32 [%0], 4;" ::"l"(flag_ptr(round ^ 1, FL_CS, 8 + (blockIdx.x >> 4))) : "memory");
                    }
                    __syncwarp();
                }
            }
            auto halo = [&](int layer) {
                const int dn = bj & 2 ? 1 : -1;
                const uint4* gh = g_halo + (layer * 144 + 8 + bi * 8 + bj) * 64 + lane;
                uint4 v[2] = {};
#pragma unroll 1
                for (int n = (bi + dn) & 16 ? 1 << 20 : 0; n < (1 << 20); n++) {
#pragma unroll
                    for (int i = 0; i < 2; i++)
                        asm volatile("{\n.reg .b64 u, v;\nld.relaxed.gpu.global.v2.b64 {u, v}, [%4];\nmov.b64 {%0, %1}, u;\nmov.b64 {%2, %3}, v;\n}"
                                     : "=r"(v[i].x), "=r"(v[i].y), "=r"(v[i].z), "=r"(v[i].w) : "l"(gh + 32 * i) : "memory");
                    if (v[0].y == ep && v[0].w == ep && v[1].y == ep && v[1].w == ep) break;
                }
#pragma unroll
                for (int i = 0; i < 2; i++)
                    asm volatile("st.shared.v2.b32 [%0], {%1, %2};" ::"r"(s_stg + 1024 + i * OFF_EPI + (63 + 65 * dn) * 128 + 8 * lane), "r"(v[i].x), "r"(v[i].z) : "memory");
                fence_async_smem();
                __syncwarp();
                DP(8 * FL_H + 5);
                named_bar_arrive(14, 160);
            };
            float4 keep[2];
            const bool on = get_role();
            if (on && warp == 11) {
                uint4* ps = reinterpret_cast<uint4*>(g_stats + (bi * 8 + bj) * 128) + lane;
                ps[0] = ps[32] = make_uint4(0, 0, 0, 0);
                asm volatile("fence.acq_rel.gpu;" ::: "memory");
                __syncwarp();
                if (lane == 0) mbar_arrive(b_rfull);
            }
#pragma unroll 1
            for (int layer = on ? 0 : 2; layer < 2; layer++) {
                if (warp == 10) {
#pragma unroll 1
                    for (int kind = 0; kind < 6; kind += 2) {
                        const int dn = bj & 2 ? 1 : -1;
#pragma unroll 1
                        for (int hf = 0; hf < 2; hf++) {
                            named_bar_sync(5 + hf, 288);
                            DQ(0);
                            if (lane == 0 && hf && kind) {
                                fence_async_smem();
                                tma_store_2d(&tm.act, s_epi + (kind == FL_H ? 1024 : 16384), bj * 128 + 64, kind == FL_H ? R_H + layer * R_HP + m0 : R_X1 + tb);
                                asm volatile("cp.async.bulk.commit_group;" ::: "memory");
                            }
                            __syncwarp();
                            if (kind + hf == FL_H + 1) halo(layer);
                            if (lane == 0) {
                                asm volatile("cp.async.bulk.wait_group 0;" ::: "memory");
                                DQ(1);
                                asm volatile("fence.release.gpu;" ::: "memory");
                                DQ(2);
                                unsigned int* fp = flag_ptr(layer, kind + hf, bi);
                                asm volatile("red.relaxed.gpu.global.add.u32 [%0], 1;" ::"l"(fp) : "memory");
                                if (kind == FL_H) {
                                    if (bi > 0 && dn > 0) asm volatile("red.relaxed.gpu.global.add.u32 [%0], 1;" ::"l"(fp - FL_PITCH) : "memory");
                                    if (bi < 15 && dn < 0) asm volatile("red.relaxed.gpu.global.add.u32 [%0], 1;" ::"l"(fp + FL_PITCH) : "memory");
                                }
                            }
                            __syncwarp();
                        }
                    }
                } else {
                    uint32_t* rs = reinterpret_cast<uint32_t*>(sgen + OFF_RS);
                    float* cs = reinterpret_cast<float*>(sgen + OFF_CS);
#pragma unroll 1
                    for (int which = 0; which < 2; which++) {
                        if (layer < which) {
                            if (warp == 11 && lane == 0) {
                                asm volatile("cp.async.bulk.prefetch.L2.global [%0], %1;" ::"l"(w3p + (bi * 8 + bj) * 28672), "r"(57344) : "memory");
                            }
                            __syncwarp();
                            colsum(false, bi, bj);
                        }
                        if (warp == 11) continue;
                        if (layer == 0) {
                            if (lane == 0) wait_flag(flag_ptr(which, FL_CS, bj), (16 << which) * ep);
                            __syncwarp();
#pragma unroll 1
                            for (int c = (which ? 384 : 768) + lane * 4; c < 896; c += 128) {
                                const float* cp = g_cpart + (which ? bj * 448 + min(c & 511, 444) : F_ + bj * 128 + lane * 4);
                                float4 a = make_float4(0.f, 0.f, 0.f, 0.f);
#pragma unroll
                                for (int r0 = 0; r0 < 16; r0 += 8) {
                                    float4 v[8];
#pragma unroll
                                    for (int r = 0; r < 8; r++) v[r] = __ldcg(reinterpret_cast<const float4*>(cp + (r0 + r) * (F_ + D_)));
#pragma unroll
                                    for (int r = 0; r < 8; r++) { a.x += v[r].x; a.y += v[r].y; a.z += v[r].z; a.w += v[r].w; }
                                }
                                if (c < 768) *reinterpret_cast<float4*>(cs + min(c & 511, 444)) = a;
                                keep[0] = a;
                            }
                        }
                        if (lane == 0 && (layer | which)) wait_flag(flag_ptr(layer, which == 0 ? FL_XA : FL_X1, bi), 8 * ep);
                        __syncwarp();
                        *reinterpret_cast<float4*>(cs + 256 + lane * 4) = keep[0];
                        { const float4 k0 = keep[0]; keep[0] = keep[1]; keep[1] = k0; }
#pragma unroll 1
                        for (int i = 0; i < 4; i++) {
                            const int r = i * 32 + lane;
                            float mean, var;
                            row_stats(g_stats + (1 + which) * S_ * 8 + bi * 1024 + r, ~layer << 31, mean, var);
                            const uint32_t c0 = pack2(mean, fsqrt(bfr(bfr(var) + 1e-5f)));
                            if (lane < 19 && (layer | which | i) == 0) asm volatile("mbarrier.inval.shared::cta.b64 [%0];" ::"r"(b_full + 8 * lane) : "memory");
                            __syncwarp();
                            rs[r] = c0;
                            const float rd = frcp(hi2f(c0));
                            rs[128 + r] = pack2((mean - lo2f(c0)) * rd, fsqrt(bfr(bfr(var * rd * rd) + 1e-5f)));
                        }
                        __syncwarp();
                        named_bar_arrive(3, 160);
                        named_bar_arrive(11, 160);
                    }
                }
                const uint32_t s_cnt = s_bar + 224;
                auto ticket = [&](uint32_t a) {
                    uint32_t v = 0;
                    if (lane == 0) asm volatile("atom.acq_rel.cta.shared.add.u32 %0, [%1], 1;" : "=r"(v) : "r"(a) : "memory");
                    return v;
                };
                auto next = [&]() {
                    uint32_t v = 0;
                    if (lane == 0) asm volatile("atom.relaxed.cta.shared.add.u32 %0, [%1], 1;" : "=r"(v) : "r"(s_cnt + 16 + 4 * layer) : "memory");
                    return v;
                };
                mbar_wait(b_stg, layer);
                int u = __shfl_sync(0xffffffffu, next(), 0), step = 0;
#pragma unroll 1
                while (true) {
#pragma unroll 1
                    for (; step < 5 && u >= (int)((0x3830201810ull >> (8 * step)) & 255); step++) {
                        if (step == 1) { named_bar_arrive(4, 224); named_bar_arrive(12, 224); continue; }
                        const int part = step ? step - 1 : 0;
                        __syncwarp();
                        if (ticket(s_cnt + 4 * part) == 3 * layer + 2) {
                            asm volatile("fence.release.gpu;" ::: "memory");
                            unsigned int* fp = flag_ptr(layer, FL_H2 + part, bi);
                            asm volatile("red.relaxed.gpu.global.add.u32 [%0], 1;" ::"l"(fp) : "memory");
                            if (part > 0) { wait_flag(fp, 8 * ep); mbar_arrive(b_h2 + 8 * part); }
                        }
                        __syncwarp();
                    }
                    if (u >= 56) break;
                    const uint32_t un = next();
                    const int job = u >> 3, r = (u & 7) * 16 + (lane >> 3);
                    if (job >= 2) mbar_wait(s_bar + 168 + 8 * max(job, 3), layer);
                    const uint32_t sp = sbase + ((job & 2) ? OFF_STG5 : OFF_EPI) + r * 256 + (job & 1) * 128;
                    bf16* gp = act + (size_t)(R_H2 + (job >> 1) * 256 + tb + r) * D_ + ((job & 1) * 8 + bj) * 64 + (lane & 7) * 8;
                    uint4 v[4];
#pragma unroll
                    for (int e = 0; e < 4; e++) v[e] = lds128(sp + e * 1024 + (((lane & 7) ^ ((r + 4 * e) & 7)) << 4));
#pragma unroll
                    for (int e = 0; e < 4; e++) stg128(gp + 4 * e * D_, gelu8h(v[e]));
                    u = __shfl_sync(0xffffffffu, un, 0);
                }
                if (layer == 0 && warp == 11) {
                    const char* ps = reinterpret_cast<const char*>(g_stats + bi * 1024) + lane * 128;
                    const char* py = reinterpret_cast<const char*>(act + (size_t)(R_Y + (tb & ~255) + (bj & 1) * 128 + (lane >> 1)) * D_ + (bj >> 1) * 256 + rank * 128) + (lane & 1) * 128;
#pragma unroll 1
                    for (int i = 0; i < 8; i++) {
                        asm volatile("prefetch.global.L2 [%0];" ::"l"(py + (size_t)i * 16 * D_ * 2) : "memory");
                        if (i >= 6) asm volatile("prefetch.global.L2 [%0];" ::"l"(ps + (i & 1) * 4096) : "memory");
                        __nanosleep(400);
                    }
                }
            }
        }
        __syncwarp();
        asm volatile("barrier.cluster.arrive.relaxed.aligned;\nbarrier.cluster.wait.acquire.aligned; // helpers" ::: "memory");
    } else {
        DT_DECL;
        DT(0);
        DT(24);
        asm volatile("setmaxnreg.inc.sync.aligned.u32 216;");
        if (get_role()) {
        const bool rel_on = (tid & 95) == 0;
        const uint32_t rel5 = mapa_u32(e5, (warp & 1) ^ rank), rel4 = rel5 + (e4 - e5);
        const uint32_t da0 = desc_a(s_r + wg * 8192), db0 = desc_b(s_r + BM * BK * 2), dae = da0 + (OFF_EPI - OFF_R) / 16, db4 = db0 - 49152 / 16;
        auto skip5 = [&](RingState& rs) {
            if (rel_on) mbar_arrive_cluster(rel5 + 8 * rs.st);
            rs.st++;
        };
        const int t = lane & 3;
        const int row = warp * 16 + (lane >> 2);
        const uint32_t st_w = (uint32_t)((warp * 16 + ((lane >> 3) & 1) * 8 + (lane & 7)) * 256 + (((lane >> 4) ^ (lane & 7)) << 4));
        const uint32_t fr = (uint32_t)((warp * 16 + ((lane >> 3) & 1) * 8 + (lane & 7)) * 128 + (((lane >> 4) ^ (lane & 7)) << 4));
        auto copy_out = [&](bf16* dst, uint32_t src) {
            const int r = warp * 16 + (lane >> 4);
            bf16* ox = dst + (size_t)(m0 + r) * D_ + bj * 128 + (lane & 15) * 8;
            const uint32_t ra = src + ((lane & 15) >> 3) * 16384 + r * 128;
            uint4 v[8];
#pragma unroll
            for (int it = 0; it < 8; it++) v[it] = lds128(ra + it * 256 + (((lane & 7) ^ ((2 * it + (lane >> 4)) & 7)) << 4));
#pragma unroll
            for (int it = 0; it < 8; it++) *reinterpret_cast<uint4*>(ox + (size_t)it * 2 * D_) = v[it];
        };
        auto put_half = [&](uint32_t src, int r0, int hf) {
            const int r = warp * 16 + (lane >> 3);
            bf16* gp = act + (size_t)(r0 + r) * D_ + bj * 128 + hf * 64 + (lane & 7) * 8;
            uint4 v[4];
            __syncwarp();
#pragma unroll
            for (int i = 0; i < 4; i++) v[i] = lds128(src + (r + 4 * i) * 128 + (((lane ^ (r + 4 * i)) & 7) << 4));
#pragma unroll
            for (int i = 0; i < 4; i++) stg128(gp + 4 * i * D_, v[i]);
        };
        auto put_stats = [&](const uint32_t (&w)[32], int which, int layer) {
            float c[6][4];
#pragma unroll
            for (int e = 0; e < 32; e++) {
                hmma8(c[e & 3], w[e & ~1], w[e | 1], w[e], e < 4);
                if ((e & 3) == 0) hmma(c[4 + (e >> 2 & 1)], w[e], w[e + 1], w[e + 2], w[e + 3], 0x3f803f80u, 0x3f803f80u, e < 8);
            }
            if (t == lane >> 3) {
#pragma unroll
                for (int e = 0; e < 2; e++) {
                    const float q1 = lane & 4 ? c[e][2 * e + 1] + c[e + 2][2 * e + 1] : c[e][2 * e] + c[e + 2][2 * e], s1 = c[4][2 * e] + c[5][2 * e], mu = s1 * (1.0f / 128);
                    asm volatile("{\n.reg .b64 t;\nmov.b64 t, {%1, %2};\nst.relaxed.gpu.global.b64 [%0], t;\n}"
                                 ::"l"(g_stats + which * S_ * 8 + (bi * 8 + bj) * 128 + row + 8 * e), "f"(mu), "r"(__float_as_uint(fmaxf(q1 - s1 * mu, 0.f)) | ~layer << 31) : "memory");
                }
            }
        };
        auto split = [](float r) { const float h = bfr(r); return pack2(h, r - h); };
        auto norm2 = [](uint32_t x, uint32_t m, uint32_t r) {
            const uint32_t d = bsub2(x, m);
            return bfma2(d, __byte_perm(r, 0, 0x1010), bmul2(d, __byte_perm(r, 0, 0x3232)));
        };
        const float* csp = reinterpret_cast<const float*>(sgen + OFF_CS) + 2 * t;
        float mrow[2], rrow[2];
        const uint32_t* rsp = reinterpret_cast<const uint32_t*>(sgen + OFF_RS) + row;
        auto row_consts = [&](bool twice) {
#pragma unroll
            for (int e = 0; e < 2; e++) {
                const uint32_t q0 = rsp[8 * e], q1 = rsp[128 + 8 * e];
                mrow[e] = twice ? fmaf(lo2f(q1), hi2f(q0), lo2f(q0)) : lo2f(q0);
                rrow[e] = 0.5f * frcp(twice ? hi2f(q0) * hi2f(q1) : hi2f(q0));
            }
        };
        auto keep_consts = [&](float2 (&cs)[8]) {
#pragma unroll
            for (int e = 0; e < 8; e++) asm volatile("" : "+f"(cs[e].x), "+f"(cs[e].y));
            asm volatile("" : "+f"(mrow[0]), "+f"(mrow[1]), "+f"(rrow[0]), "+f"(rrow[1]));
        };
        RingState r5{1, 0}, r4{0, 0};
        DT(1);
        uint32_t x[32];
        mbar_wait(b_rfull, 0);
#pragma unroll
        for (int jp = 0; jp < 8; jp++) ldsm4(x[4 * jp], x[4 * jp + 1], x[4 * jp + 2], x[4 * jp + 3], sbase + 16384 + (fr ^ ((jp & 3) << 5)) + (jp >> 2) * (16384 + 8 * CV_SL));
#pragma unroll
        for (int e = 0; e < 32; e++) asm volatile("" : "+r"(x[e]));
        named_bar_sync(9 + wg, 128);
        if ((tid & 95) < R5_N) mbar_arrive_cluster(rel5 + 8 * lane);
#pragma unroll 1
        for (int layer = 0; layer < 2; layer++) {
            {
                DT(2 + 24 * layer);
                put_stats(x, 0, layer);
                DT(20 + 24 * layer);
                DT(22 + 24 * layer);
                uint32_t mb[2], rd[2];
                {
                    float mean, var;
                    row_stats(g_stats + bi * 1024 + warp * 16 + (lane & 15), ~layer << 31, mean, var);
                    __syncwarp();
                    const uint32_t r1 = split(frcp(bfr(fsqrt(bfr(bfr(var) + 1e-5f)))));
                    const uint32_t m1 = pack2(mean, mean);
#pragma unroll
                    for (int e = 0; e < 2; e++) { mb[e] = __shfl_sync(0xffffffffu, m1, (lane >> 2) + 8 * e); rd[e] = __shfl_sync(0xffffffffu, r1, (lane >> 2) + 8 * e); }
                }
                DT(21 + 24 * layer);
                mbar_wait(f5 + 8, r5.ph);
                DT(23 + 24 * layer);
                const int yl = ((lane >> 2 & 4) ^ (lane & 7)) + (lane & 4) * 16;
                const uint32_t ya = s_r + R5_STAGE + wg * 16384 + yl * 128 + ((((warp & 3) * 2 + ((lane >> 3) & 1)) ^ (yl & 7)) << 4);
                uint32_t y[16];
#pragma unroll
                for (int e = 0; e < 32; e++) {
                    if ((e & 15) == 0) {
#pragma unroll
                        for (int jp = 0; jp < 4; jp++) ldsm4t(y[4 * jp], y[4 * jp + 1], y[4 * jp + 2], y[4 * jp + 3], ya + jp * 1024 + e * 256);
                    }
                    x[e] = bfma2(norm2(x[e], mb[e & 1], rd[e & 1]), y[e & 15], x[e]);
                    if ((e & 3) == 3) stsm4(s_epi + (fr ^ (((e >> 2) & 3) << 5)) + (e >> 4) * 16384, x[e - 3], x[e - 2], x[e - 1], x[e]);
                    if ((e & 15) == 15) { put_half(s_epi + (e >> 4) * 16384, R_XA + tb, e >> 4); named_bar_arrive(5 + (e >> 4), 288); }
                    if (e == 15) mbar_wait(b_role, 0);
                }
                DT(19 + 24 * layer);
                fence_async_smem();
                if (PS1_EARLY) put_stats(x, 1, layer);
                named_bar_sync(9 + wg, 128);
                skip5(r5);
                DT(3 + 24 * layer);
            }
            {
                float acc[64];
                kblock<128, R5_N, 0>(acc, dae, db0 + 2 * (R5_STAGE / 16), f5, r5);
                kblock<128, R5_N>(acc, dae + 1024, db0 + 3 * (R5_STAGE / 16), f5, r5);
                if (!PS1_EARLY) put_stats(x, 1, layer);
                wgmma_wait<1>();
                if (rel_on) mbar_arrive_cluster(rel5 + 16);
                float2 cs[8];
                mainloop<128, R5_N, R5_STAGE, PA1>(acc, 14, da0, db0, f5, rel5, rel_on, r5, 15 + 24 * layer, [&]() {
                    named_bar_sync(3 + 8 * wg, 160);
                    row_consts(true);
#pragma unroll
                    for (int e = 0; e < 8; e++) cs[e] = *reinterpret_cast<const float2*>(csp + 256 + 8 * e);
                    keep_consts(cs);
                } DT_ARG, (wg ^ bj >> 1 ^ LAGX) & 1);
                DT(4 + 24 * layer);
#pragma unroll
                for (int j = 0; j < 16; j += 2) {
                    if (j == 8) {
#pragma unroll
                        for (int e = 0; e < 8; e++) cs[e] = *reinterpret_cast<const float2*>(csp + 256 + 8 * (j + e));
                    }
                    uint32_t w[4];
#pragma unroll
                    for (int e = 0; e < 4; e++) {
                        const float* a = acc + 4 * j + 2 * e;
                        const float2 c = cs[(j & 7) + (e >> 1)];
                        w[e] = gelu2h(pack2(fmaf(-mrow[e & 1], c.x, a[0]) * rrow[e & 1], fmaf(-mrow[e & 1], c.y, a[1]) * rrow[e & 1]));
                    }
                    stsm4(s_stg + 1024 + (fr ^ ((j & 7) << 4)) + (j >> 3) * OFF_EPI, w[0], w[1], w[2], w[3]);
                    if (j == 6) put_half(s_stg + 1024, R_H + layer * R_HP + m0, 0);
                    if ((j & 7) == 6) named_bar_arrive(5 + (j >> 3), 288);
                }
                if (warp == (bj & 2 ? 0 : 7)) {
                    __syncwarp();
                    uint32_t a[4];
                    lds64(a[0], a[1], s_stg + 1024 + 18 * 128 * warp + 8 * lane);
                    lds64(a[2], a[3], s_epi + 1024 + 18 * 128 * warp + 8 * lane);
                    uint4* gh = g_halo + (layer * 144 + (warp & 2) * 8 + bi * 8 + bj) * 64 + lane;
#pragma unroll
                    for (int i = 0; i < 2; i++)
                        asm volatile("{\n.reg .b64 u, v;\nmov.b64 u, {%1, %3};\nmov.b64 v, {%2, %3};\nst.relaxed.gpu.global.v2.b64 [%0], {u, v};\n}"
                                     ::"l"(gh + i * 32), "r"(a[2 * i]), "r"(a[2 * i + 1]), "r"(ep) : "memory");
                }
                fence_async_smem();
                if (wg == (bj >> 1 & 1)) named_bar_arrive(13, 256);
                DT(5 + 24 * layer);
            }
            {
                float acc[64];
                uint32_t u[32];
                {
                    uint32_t mb[2], rd[2];
#pragma unroll
                    for (int e = 0; e < 2; e++) { const uint32_t q0 = rsp[8 * e]; mb[e] = (q0 & 0xffffu) * 0x10001u; rd[e] = split(frcp(hi2f(q0))); }
#pragma unroll
                    for (int e = 0; e < 32; e++) {
                        u[e] = norm2(x[e], mb[e & 1], rd[e & 1]);
                        asm volatile("" : "+r"(u[e]));
                    }
                }
                if (!(warp & 2)) mbar_wait(f5 + 24, r5.ph);
                skip5(r5);
                {
                    const bool nb = wg == (bj >> 1 & 1);
                    named_bar_sync(nb ? 14 : 13, nb ? 160 : 256);
                }
                const uint32_t dah = da0 - (OFF_R - 1024 + 256) / 16 + ((0x4031u >> (2 * bj & 12)) & 7) * 8;
                kblock<128, R5_N, 0>(acc, dah, db0 + 4 * (R5_STAGE / 16), f5, r5);
                kblock<128, R5_N>(acc, dah + OFF_EPI / 16, db0, f5, r5);
                wgmma_wait<1>();
                if (rel_on) mbar_arrive_cluster(rel5 + 32);
                mainloop<128, R5_N, R5_STAGE, PA2>(acc, 14, da0, db0, f5, rel5, rel_on, r5, 16 + 24 * layer, []() {} DT_ARG, wg);
                DT(6 + 24 * layer);
#pragma unroll
                for (int j = 0; j < 16; j += 2) {
#pragma unroll
                    for (int e = 0; e < 4; e++) u[2 * j + e] = badd2(u[2 * j + e], pack2(acc[4 * j + 2 * e], acc[4 * j + 2 * e + 1]));
                    stsm4(s_epi + (fr ^ ((j & 7) << 4)) + (j >> 3) * 16384, u[2 * j], u[2 * j + 1], u[2 * j + 2], u[2 * j + 3]);
                    if (j == 6) put_half(s_epi, R_X1 + tb, 0);
                    if ((j & 7) == 6) { named_bar_arrive(5 + (j >> 3), 288); mbar_wait(b_role, 0); }
                }
                fence_async_smem();
#pragma unroll
                for (int e = 0; e < 32; e++) x[e] = badd2(x[e], u[e]);
                put_stats(u, 2, layer);
                named_bar_sync(9 + wg, 128);
                DT(7 + 24 * layer);
            }
            {
                float2 cs[NCS];
                auto piece = [&](const float* acc, auto pc) {
                    constexpr int j = 2 * decltype(pc)::v, jl = j & 31;
                    uint32_t w[4];
#pragma unroll
                    for (int e = 0; e < 2; e++) {
                        const float* a = acc + 4 * (jl + e);
                        const float2 cc = cs[(j + e) % NCS];
                        w[2 * e] = pack2(fmaf(-mrow[0], cc.x, a[0]) * rrow[0], fmaf(-mrow[0], cc.y, a[1]) * rrow[0]);
                        w[2 * e + 1] = pack2(fmaf(-mrow[1], cc.x, a[2]) * rrow[1], fmaf(-mrow[1], cc.y, a[3]) * rrow[1]);
                    }
                    stsm4(((jl < 16 ? s_epi : s_stg) + st_w) ^ ((j & 15) << 4), w[0], w[1], w[2], w[3]);
                    if (j + NCS < 56) {
#pragma unroll
                        for (int e = 0; e < 2; e++) { uint32_t u0, u1; lds64(u0, u1, smem_u32(csp + 8 * (j + e + NCS))); cs[(j + e) % NCS] = make_float2(__uint_as_float(u0), __uint_as_float(u1)); }
                    }
                    if (j == 14 || (j >= 30 && (j & 7) == 6)) {
                        __syncwarp();
                        if (lane == 0) mbar_arrive(j == 14 ? b_stg : s_bar + 168 + (j & 56));
                    }
                };
                auto pieces = [&](const float* acc, auto p0, auto p1) {
                    constexpr int a = decltype(p0)::v, b = decltype(p1)::v;
                    static_for<a, b>([&](auto i) { piece(acc, i); });
                };
                float ac3[128];
                kblock<256, R4_N, 0>(ac3, dae, db4, f4, r4);
                kblock<256, R4_N>(ac3, dae + 1024, db4 + R4_STAGE / 16, f4, r4);
                wgmma_wait<1>();
                if (rel_on) mbar_arrive_cluster(rel4);
                mainloop<256, R4_N, R4_STAGE, PA3A>(ac3, 14, da0, db4, f4, rel4, rel_on, r4, 17 + 24 * layer, [&]() {
                    named_bar_sync(3 + 8 * wg, 160);
                    mbar_wait(e4, 1);
                    row_consts(false);
#pragma unroll
                    for (int e = 0; e < NCS; e++) {
                        cs[e] = *reinterpret_cast<const float2*>(csp + 8 * e);
                        asm volatile("" : "+f"(cs[e].x), "+f"(cs[e].y));
                    }
                    asm volatile("" : "+f"(mrow[0]), "+f"(mrow[1]), "+f"(rrow[0]), "+f"(rrow[1]));
                } DT_ARG, wg);
                DT(8 + 24 * layer);
                pieces(ac3, IC<0>(), IC<NPRE>());
                DT(9 + 24 * layer);
                float acc[96];
                constexpr int NS3 = NPRE == 16 ? 1 : (16 - NPRE + PP3 - 1) / PP3;
                static_for<0, NS3>([&](auto cc) {
                    constexpr int c = decltype(cc)::v, q = NPRE + PP3 * c;
                    const uint32_t da = da0 + c * (R4B_STAGE / 16), db = db0 + c * (R4B_STAGE / 16);
                    mbar_wait(f4 + 8 * c, r4.ph);
                    wgmma_fence();
                    static_for<0, 4>([&](auto ic) {
                        constexpr int i = decltype(ic)::v, q0 = q + i * PP3 / 4, q1 = q + (i + 1) * PP3 / 4;
                        WG<192>::mma<(c | i) != 0>(acc, da + 2 * i, db + 128 * i);
                        if (i == 3) {
                            wgmma_commit();
                            if (c) {
                                wgmma_wait<1>();
                                if (rel_on) mbar_arrive_cluster(rel4 + 8 * ((c + 3) & 3));
                            }
                        }
                        pieces(ac3, IC<(q0 < 16 ? q0 : 16)>(), IC<(q1 < 16 ? q1 : 16)>());
                    });
                });
                r4.st = NS3 & 3;
                if (NS3 == 4) r4.ph ^= 1;
                float ac4[64];
                mainloop<192, R4_N, R4B_STAGE, PA3B, 1>(acc, 16 - NS3, da0, db0, f4, rel4, rel_on, r4, -1, [&]() {
#pragma unroll
                    for (int i = 0; i < 32; i++) asm volatile("shl.b32 %0, %2, 16;\nand.b32 %1, %2, 0xffff0000;" : "=f"(ac4[2 * i]), "=f"(ac4[2 * i + 1]) : "r"(x[i]));
                    kblock<128, R5_N>(ac4, da0, db0, f5, r5);
                } DT_ARG, wg);
                DT(10 + 24 * layer);
                named_bar_sync(4 + 8 * wg, 224);
                piece(acc, IC<16>());
                static_for<1, 7>([&](auto cc) {
                    constexpr int c = decltype(cc)::v;
                    const uint32_t da = da0 + (c % 5) * (R5_STAGE / 16), db = db0 + (c % 5) * (R5_STAGE / 16);
                    mbar_wait(f5 + 8 * (c % 5), r5.ph);
                    wgmma_fence();
                    WG<128>::mma<1>(ac4, da, db);
                    WG<128>::mma<1>(ac4, da + 2, db + 128);
                    piece(acc, IC<15 + 2 * c>());
                    WG<128>::mma<1>(ac4, da + 4, db + 256);
                    WG<128>::mma<1>(ac4, da + 6, db + 384);
                    wgmma_commit();
                    if (c % 5 == 4) r5.ph ^= 1;
                    wgmma_wait<1>();
                    if (rel_on) mbar_arrive_cluster(rel5 + 8 * ((c - 1) % 5));
                    if constexpr (c < 6) piece(acc, IC<16 + 2 * c>());
                });
                r5.st = 2;
                DT(11 + 24 * layer);
                DT(18 + 24 * layer);
                mainloop<128, R5_N, R5_STAGE, PA4>(ac4, 49, da0, db0, f5, rel5, rel_on, r5, 62 - 40 * (layer ^ 1), []() {} DT_ARG, wg);
                DT(12 + 24 * layer);
#pragma unroll
                for (int i = 0; i < 32; i++) x[i] = pack2(ac4[2 * i], ac4[2 * i + 1]);
                DT(13 + 24 * layer);
                DT(14 + 24 * layer);
            }
        }
#pragma unroll
        for (int jp = 0; jp < 8; jp++) stsm4(s_epi + (fr ^ ((jp & 3) << 5)) + (jp >> 2) * 16384, x[4 * jp], x[4 * jp + 1], x[4 * jp + 2], x[4 * jp + 3]);
        __syncwarp();
        copy_out(outp, s_epi);
        DT(38);
        DT_DUMP;
        GT(4);
        }
        cluster_arrive_relaxed();
        cluster_wait();
    }
}

typedef CUresult (*PFN_encodeTiled)(CUtensorMap*, CUtensorMapDataType, cuuint32_t, void*, const cuuint64_t*, const cuuint64_t*,
                                    const cuuint32_t*, const cuuint32_t*, CUtensorMapInterleave, CUtensorMapSwizzle,
                                    CUtensorMapL2promotion, CUtensorMapFloatOOBfill);

static CUtensorMap make_map(PFN_encodeTiled enc, const void* ptr, int inner, int outer, int box_inner, int box_outer,
                            CUtensorMapSwizzle swz = CU_TENSOR_MAP_SWIZZLE_128B) {
    CUtensorMap m;
    cuuint64_t dims[2] = {(cuuint64_t)inner, (cuuint64_t)outer};
    cuuint64_t strides[1] = {(cuuint64_t)inner * 2};
    cuuint32_t box[2] = {(cuuint32_t)box_inner, (cuuint32_t)box_outer};
    cuuint32_t es[2] = {1, 1};
    enc(&m, CU_TENSOR_MAP_DATA_TYPE_BFLOAT16, 2, const_cast<void*>(ptr), dims, strides, box, es, CU_TENSOR_MAP_INTERLEAVE_NONE,
        swz, CU_TENSOR_MAP_L2_PROMOTION_L2_256B, CU_TENSOR_MAP_FLOAT_OOB_FILL_NONE);
    return m;
}

extern "C" void kernel_launch(void* const* d_in, const int* in_sizes, int n_in, void* d_out, int out_size) {
    const bf16* A_q = (const bf16*)d_in[0];
    const bf16* A_k = (const bf16*)d_in[1];
    const bf16* A_v = (const bf16*)d_in[2];
    const bf16* A_shk = (const bf16*)d_in[3];
    const bf16* A_ssk = (const bf16*)d_in[4];
    const bf16* A_ssD = (const bf16*)d_in[5];
    const bf16* w1 = (const bf16*)d_in[7];
    const bf16* w2 = (const bf16*)d_in[8];
    const bf16* w3 = (const bf16*)d_in[9];
    const bf16* w4 = (const bf16*)d_in[10];
    bf16* out = (bf16*)d_out;

    static PFN_encodeTiled enc = nullptr;
    static bool attr_done = false;
    if (!enc) {
        void* fn = nullptr;
        cudaDriverEntryPointQueryResult qr;
        cudaGetDriverEntryPoint("cuTensorMapEncodeTiled", &fn, cudaEnableDefault, &qr);
        enc = (PFN_encodeTiled)fn;
    }
    if (!attr_done) {
        cudaFuncSetAttribute(mega_kernel, cudaFuncAttributeMaxDynamicSharedMemorySize, MEGA_SMEM);
        attr_done = true;
    }
    void* p_act;
    cudaGetSymbolAddress(&p_act, g_act);
    bf16* act = (bf16*)(((uintptr_t)p_act + 0x1fffff) & ~(uintptr_t)0x1fffff);

    MegaMaps tm;
    tm.q = make_map(enc, A_q, D_, S_, 64, 128);
    tm.act = make_map(enc, act, D_, R_END, 64, 128);
    tm.a64 = make_map(enc, act, D_, R_END, 64, 64);
    tm.w1 = make_map(enc, w1, D_, D_, 64, 64);
    tm.w2 = make_map(enc, w2, D_, D_, 64, 64);
    tm.w3 = make_map(enc, w3, F_, D_, 64, 64);
    tm.w4 = make_map(enc, w4, D_, F_, 64, 64);
    for (int i = 0; i < 2; i++) {
        cuuint64_t dims[4] = {D_, 4, 8, S_ / 32}, strides[3] = {8 * D_ * 2, D_ * 2, 32 * D_ * 2};
        cuuint32_t box[4] = {16, 4, 8, 4}, es[4] = {1, 1, 1, 1};
        enc(i ? &tm.v : &tm.k, CU_TENSOR_MAP_DATA_TYPE_BFLOAT16, 4, (void*)(i ? A_v : A_k), dims, strides, box, es, CU_TENSOR_MAP_INTERLEAVE_NONE,
            CU_TENSOR_MAP_SWIZZLE_32B, CU_TENSOR_MAP_L2_PROMOTION_NONE, CU_TENSOR_MAP_FLOAT_OOB_FILL_NONE);
    }
    mega_kernel<<<2 * NCL, 384, MEGA_SMEM, cudaStreamPerThread>>>(tm, out, act, w1, w2, w3, A_q, A_k, A_v, A_shk, A_ssk, A_ssD);
}
```

```cpp
#include <cuda_runtime.h>
#include <cuda_bf16.h>
#include <cuda.h>
#include <stdint.h>

typedef __nv_bfloat16 bf16;

constexpr int S_ = 2048;
constexpr int D_ = 1024;
constexpr int F_ = 3584;

constexpr int R_XA = 0, R_X1 = 256, R_H2 = 512, R_Y = 1536, R_H = 16384 + 8, R_HP = S_ + 8, R_END = R_H + 2 * R_HP;
__device__ __align__(1024) bf16 g_act[(size_t)(R_END + 1024) * D_];
__device__ __align__(16) float g_cpart[16 * (F_ + D_)];
__device__ __align__(128) float2 g_stats[3 * S_ * 8];
__device__ __align__(128) uint4 g_halo[2 * 144 * 64];

__device__ __forceinline__ float bfr(float x) { return __bfloat162float(__float2bfloat16_rn(x)); }
__device__ __forceinline__ uint32_t pack2(float lo, float hi) {
    __nv_bfloat162 v = __floats2bfloat162_rn(lo, hi);
    return *reinterpret_cast<uint32_t*>(&v);
}
__device__ __forceinline__ float lo2f(uint32_t v) { return __uint_as_float(v << 16); }
__device__ __forceinline__ float hi2f(uint32_t v) { return __uint_as_float(v & 0xffff0000u); }
__device__ __forceinline__ float frcp(float x) { float r; asm("rcp.approx.f32 %0, %1;" : "=f"(r) : "f"(x)); return r; }
__device__ __forceinline__ float fsqrt(float x) { float r; asm("sqrt.approx.f32 %0, %1;" : "=f"(r) : "f"(x)); return r; }
__device__ __forceinline__ uint32_t smem_u32(const void* p) { return (uint32_t)__cvta_generic_to_shared(p); }

__device__ __forceinline__ void mbar_init(uint32_t bar, uint32_t cnt) {
    asm volatile("mbarrier.init.shared::cta.b64 [%0], %1;" ::"r"(bar), "r"(cnt));
}
__device__ __forceinline__ void mbar_expect_tx(uint32_t bar, uint32_t bytes) {
    asm volatile("mbarrier.arrive.expect_tx.shared::cta.b64 _, [%0], %1;" ::"r"(bar), "r"(bytes) : "memory");
}
__device__ __forceinline__ void mbar_arrive(uint32_t bar) {
    asm volatile("mbarrier.arrive.shared::cta.b64 _, [%0];" ::"r"(bar) : "memory");
}
__device__ __forceinline__ void mbar_wait(uint32_t bar, uint32_t parity) {
    asm volatile(
        "{\n.reg .pred p;\n.reg .u32 n;\n"
        "mbarrier.try_wait.parity.shared::cta.b64 p, [%0], %1;\n"
        "@p bra LD;\n"
        "mov.u32 n, 0;\n"
        "LW:\n"
        "mbarrier.try_wait.parity.shared::cta.b64 p, [%0], %1;\n"
        "@p bra LD;\n"
        "add.u32 n, n, 1;\n"
        "setp.lt.u32 p, n, 0x400000;\n"
        "@p bra LW;\n"
        "LD:\n}\n"
        ::"r"(bar), "r"(parity) : "memory");
}
__device__ __forceinline__ void tma_load_2d(uint32_t dst, const CUtensorMap* tm, uint32_t bar, int c0, int c1) {
    asm volatile(
        "cp.async.bulk.tensor.2d.shared::cluster.global.mbarrier::complete_tx::bytes [%0], [%1, {%3, %4}], [%2];"
        ::"r"(dst), "l"((uint64_t)tm), "r"(bar), "r"(c0), "r"(c1) : "memory");
}
__device__ __forceinline__ void tma_load_2d_mc(uint32_t dst, const CUtensorMap* tm, uint32_t bar, int c0, int c1) {
    asm volatile(
        "cp.async.bulk.tensor.2d.shared::cluster.global.mbarrier::complete_tx::bytes.multicast::cluster [%0], [%1, {%3, %4}], [%2], %5;"
        ::"r"(dst), "l"((uint64_t)tm), "r"(bar), "r"(c0), "r"(c1), "h"((uint16_t)3) : "memory");
}
__device__ __forceinline__ void tma_prefetch_2d(const CUtensorMap* tm, int c0, int c1) {
    asm volatile("cp.async.bulk.prefetch.tensor.2d.L2.global.tile [%0, {%1, %2}];" ::"l"((uint64_t)tm), "r"(c0), "r"(c1) : "memory");
}
__device__ __forceinline__ void tma_store_2d(const CUtensorMap* tm, uint32_t src, int c0, int c1) {
    asm volatile("cp.async.bulk.tensor.2d.global.shared::cta.bulk_group [%0, {%2, %3}], [%1];"
                 ::"l"((uint64_t)tm), "r"(src), "r"(c0), "r"(c1) : "memory");
}
__device__ __forceinline__ void wgmma_fence() { asm volatile("wgmma.fence.sync.aligned;" ::: "memory"); }
__device__ __forceinline__ void wgmma_commit() { asm volatile("wgmma.commit_group.sync.aligned;" ::: "memory"); }
template <int N> __device__ __forceinline__ void wgmma_wait() { asm volatile("wgmma.wait_group.sync.aligned %0;" ::"n"(N) : "memory"); }
__device__ __forceinline__ void named_bar_arrive(int id, int n) { asm volatile("bar.arrive %0, %1;" ::"r"(id), "r"(n) : "memory"); }
__device__ __forceinline__ void named_bar_sync(int id, int n) { asm volatile("bar.sync %0, %1;" ::"r"(id), "r"(n) : "memory"); }

__device__ __forceinline__ uint32_t desc_a(uint32_t addr) { return ((addr & 0x3FFFF) >> 4) | (1u << 16); }
__device__ __forceinline__ uint32_t desc_b(uint32_t addr) { return ((addr & 0x3FFFF) >> 4) | (512u << 16); }

template <int ACC> __device__ __forceinline__ void wgmma_m64n192k16(float (&d)[96], uint32_t descA, uint32_t descB) {
  asm volatile("{\n.reg .pred p;\n.reg .b64 da, db;\nsetp.ne.b32 p, %99, 0;\nmov.b64 da, {%96, %98};\nmov.b64 db, {%97, %98};\n"
    "wgmma.mma_async.sync.aligned.m64n192k16.f32.bf16.bf16 "
    "{%0, %1, %2, %3, %4, %5, %6, %7, %8, %9, %10, %11, %12, %13, %14, %15, %16, %17, %18, %19, %20, %21, %22, %23, %24, %25, %26, %27, %28, %29, %30, %31, %32, %33, %34, %35, %36, %37, %38, %39, %40, %41, %42, %43, %44, %45, %46, %47, %48, %49, %50, %51, %52, %53, %54, %55, %56, %57, %58, %59, %60, %61, %62, %63, %64, %65, %66, %67, %68, %69, %70, %71, %72, %73, %74, %75, %76, %77, %78, %79, %80, %81, %82, %83, %84, %85, %86, %87, %88, %89, %90, %91, %92, %93, %94, %95}, "
    "da, db, p, 1, 1, 0, 1;\n}\n"
    : "+f"(d[0]), "+f"(d[1]), "+f"(d[2]), "+f"(d[3]), "+f"(d[4]), "+f"(d[5]), "+f"(d[6]), "+f"(d[7]), "+f"(d[8]), "+f"(d[9]), "+f"(d[10]), "+f"(d[11]), "+f"(d[12]), "+f"(d[13]), "+f"(d[14]), "+f"(d[15]), "+f"(d[16]), "+f"(d[17]), "+f"(d[18]), "+f"(d[19]), "+f"(d[20]), "+f"(d[21]), "+f"(d[22]), "+f"(d[23]), "+f"(d[24]), "+f"(d[25]), "+f"(d[26]), "+f"(d[27]), "+f"(d[28]), "+f"(d[29]), "+f"(d[30]), "+f"(d[31]), "+f"(d[32]), "+f"(d[33]), "+f"(d[34]), "+f"(d[35]), "+f"(d[36]), "+f"(d[37]), "+f"(d[38]), "+f"(d[39]), "+f"(d[40]), "+f"(d[41]), "+f"(d[42]), "+f"(d[43]), "+f"(d[44]), "+f"(d[45]), "+f"(d[46]), "+f"(d[47]), "+f"(d[48]), "+f"(d[49]), "+f"(d[50]), "+f"(d[51]), "+f"(d[52]), "+f"(d[53]), "+f"(d[54]), "+f"(d[55]), "+f"(d[56]), "+f"(d[57]), "+f"(d[58]), "+f"(d[59]), "+f"(d[60]), "+f"(d[61]), "+f"(d[62]), "+f"(d[63]), "+f"(d[64]), "+f"(d[65]), "+f"(d[66]), "+f"(d[67]), "+f"(d[68]), "+f"(d[69]), "+f"(d[70]), "+f"(d[71]), "+f"(d[72]), "+f"(d[73]), "+f"(d[74]), "+f"(d[75]), "+f"(d[76]), "+f"(d[77]), "+f"(d[78]), "+f"(d[79]), "+f"(d[80]), "+f"(d[81]), "+f"(d[82]), "+f"(d[83]), "+f"(d[84]), "+f"(d[85]), "+f"(d[86]), "+f"(d[87]), "+f"(d[88]), "+f"(d[89]), "+f"(d[90]), "+f"(d[91]), "+f"(d[92]), "+f"(d[93]), "+f"(d[94]), "+f"(d[95])
    : "r"(descA), "r"(descB), "r"(0x40000040u), "n"(ACC));
}

template <int ACC> __device__ __forceinline__ void wgmma_m64n256k16(float (&d)[128], uint32_t descA, uint32_t descB) {
  asm volatile("{\n.reg .pred p;\n.reg .b64 da, db;\nsetp.ne.b32 p, %131, 0;\nmov.b64 da, {%128, %130};\nmov.b64 db, {%129, %130};\n"
    "wgmma.mma_async.sync.aligned.m64n256k16.f32.bf16.bf16 "
    "{%0, %1, %2, %3, %4, %5, %6, %7, %8, %9, %10, %11, %12, %13, %14, %15, %16, %17, %18, %19, %20, %21, %22, %23, %24, %25, %26, %27, %28, %29, %30, %31, %32, %33, %34, %35, %36, %37, %38, %39, %40, %41, %42, %43, %44, %45, %46, %47, %48, %49, %50, %51, %52, %53, %54, %55, %56, %57, %58, %59, %60, %61, %62, %63, %64, %65, %66, %67, %68, %69, %70, %71, %72, %73, %74, %75, %76, %77, %78, %79, %80, %81, %82, %83, %84, %85, %86, %87, %88, %89, %90, %91, %92, %93, %94, %95, %96, %97, %98, %99, %100, %101, %102, %103, %104, %105, %106, %107, %108, %109, %110, %111, %112, %113, %114, %115, %116, %117, %118, %119, %120, %121, %122, %123, %124, %125, %126, %127}, "
    "da, db, p, 1, 1, 0, 1;\n}\n"
    : "+f"(d[0]), "+f"(d[1]), "+f"(d[2]), "+f"(d[3]), "+f"(d[4]), "+f"(d[5]), "+f"(d[6]), "+f"(d[7]), "+f"(d[8]), "+f"(d[9]), "+f"(d[10]), "+f"(d[11]), "+f"(d[12]), "+f"(d[13]), "+f"(d[14]), "+f"(d[15]), "+f"(d[16]), "+f"(d[17]), "+f"(d[18]), "+f"(d[19]), "+f"(d[20]), "+f"(d[21]), "+f"(d[22]), "+f"(d[23]), "+f"(d[24]), "+f"(d[25]), "+f"(d[26]), "+f"(d[27]), "+f"(d[28]), "+f"(d[29]), "+f"(d[30]), "+f"(d[31]), "+f"(d[32]), "+f"(d[33]), "+f"(d[34]), "+f"(d[35]), "+f"(d[36]), "+f"(d[37]), "+f"(d[38]), "+f"(d[39]), "+f"(d[40]), "+f"(d[41]), "+f"(d[42]), "+f"(d[43]), "+f"(d[44]), "+f"(d[45]), "+f"(d[46]), "+f"(d[47]), "+f"(d[48]), "+f"(d[49]), "+f"(d[50]), "+f"(d[51]), "+f"(d[52]), "+f"(d[53]), "+f"(d[54]), "+f"(d[55]), "+f"(d[56]), "+f"(d[57]), "+f"(d[58]), "+f"(d[59]), "+f"(d[60]), "+f"(d[61]), "+f"(d[62]), "+f"(d[63]), "+f"(d[64]), "+f"(d[65]), "+f"(d[66]), "+f"(d[67]), "+f"(d[68]), "+f"(d[69]), "+f"(d[70]), "+f"(d[71]), "+f"(d[72]), "+f"(d[73]), "+f"(d[74]), "+f"(d[75]), "+f"(d[76]), "+f"(d[77]), "+f"(d[78]), "+f"(d[79]), "+f"(d[80]), "+f"(d[81]), "+f"(d[82]), "+f"(d[83]), "+f"(d[84]), "+f"(d[85]), "+f"(d[86]), "+f"(d[87]), "+f"(d[88]), "+f"(d[89]), "+f"(d[90]), "+f"(d[91]), "+f"(d[92]), "+f"(d[93]), "+f"(d[94]), "+f"(d[95]), "+f"(d[96]), "+f"(d[97]), "+f"(d[98]), "+f"(d[99]), "+f"(d[100]), "+f"(d[101]), "+f"(d[102]), "+f"(d[103]), "+f"(d[104]), "+f"(d[105]), "+f"(d[106]), "+f"(d[107]), "+f"(d[108]), "+f"(d[109]), "+f"(d[110]), "+f"(d[111]), "+f"(d[112]), "+f"(d[113]), "+f"(d[114]), "+f"(d[115]), "+f"(d[116]), "+f"(d[117]), "+f"(d[118]), "+f"(d[119]), "+f"(d[120]), "+f"(d[121]), "+f"(d[122]), "+f"(d[123]), "+f"(d[124]), "+f"(d[125]), "+f"(d[126]), "+f"(d[127])
    : "r"(descA), "r"(descB), "r"(0x40000040u), "n"(ACC));
}

template <int ACC> __device__ __forceinline__ void wgmma_m64n128k16(float (&d)[64], uint32_t descA, uint32_t descB) {
  asm volatile("{\n.reg .pred p;\n.reg .b64 da, db;\nsetp.ne.b32 p, %67, 0;\nmov.b64 da, {%64, %66};\nmov.b64 db, {%65, %66};\n"
    "wgmma.mma_async.sync.aligned.m64n128k16.f32.bf16.bf16 "
    "{%0, %1, %2, %3, %4, %5, %6, %7, %8, %9, %10, %11, %12, %13, %14, %15, %16, %17, %18, %19, %20, %21, %22, %23, %24, %25, %26, %27, %28, %29, %30, %31, %32, %33, %34, %35, %36, %37, %38, %39, %40, %41, %42, %43, %44, %45, %46, %47, %48, %49, %50, %51, %52, %53, %54, %55, %56, %57, %58, %59, %60, %61, %62, %63}, "
    "da, db, p, 1, 1, 0, 1;\n}\n"
    : "+f"(d[0]), "+f"(d[1]), "+f"(d[2]), "+f"(d[3]), "+f"(d[4]), "+f"(d[5]), "+f"(d[6]), "+f"(d[7]), "+f"(d[8]), "+f"(d[9]), "+f"(d[10]), "+f"(d[11]), "+f"(d[12]), "+f"(d[13]), "+f"(d[14]), "+f"(d[15]), "+f"(d[16]), "+f"(d[17]), "+f"(d[18]), "+f"(d[19]), "+f"(d[20]), "+f"(d[21]), "+f"(d[22]), "+f"(d[23]), "+f"(d[24]), "+f"(d[25]), "+f"(d[26]), "+f"(d[27]), "+f"(d[28]), "+f"(d[29]), "+f"(d[30]), "+f"(d[31]), "+f"(d[32]), "+f"(d[33]), "+f"(d[34]), "+f"(d[35]), "+f"(d[36]), "+f"(d[37]), "+f"(d[38]), "+f"(d[39]), "+f"(d[40]), "+f"(d[41]), "+f"(d[42]), "+f"(d[43]), "+f"(d[44]), "+f"(d[45]), "+f"(d[46]), "+f"(d[47]), "+f"(d[48]), "+f"(d[49]), "+f"(d[50]), "+f"(d[51]), "+f"(d[52]), "+f"(d[53]), "+f"(d[54]), "+f"(d[55]), "+f"(d[56]), "+f"(d[57]), "+f"(d[58]), "+f"(d[59]), "+f"(d[60]), "+f"(d[61]), "+f"(d[62]), "+f"(d[63])
    : "r"(descA), "r"(descB), "r"(0x40000040u), "n"(ACC));
}

template <int BN> struct WG;
template <> struct WG<128> { template <int ACC> static __device__ __forceinline__ void mma(float (&d)[64], uint32_t a, uint32_t b) { wgmma_m64n128k16<ACC>(d, a, b); } };
template <> struct WG<256> { template <int ACC> static __device__ __forceinline__ void mma(float (&d)[128], uint32_t a, uint32_t b) { wgmma_m64n256k16<ACC>(d, a, b); } };
template <> struct WG<192> { template <int ACC> static __device__ __forceinline__ void mma(float (&d)[96], uint32_t a, uint32_t b) { wgmma_m64n192k16<ACC>(d, a, b); } };

#define DBG_T(i)
__device__ __forceinline__ void fence_async_smem() { asm volatile("fence.proxy.async.shared::cta;" ::: "memory"); }
__device__ __forceinline__ void prefetch_tmap(const CUtensorMap* tm) { asm volatile("prefetch.tensormap [%0];" ::"l"((uint64_t)tm) : "memory"); }
__device__ __forceinline__ uint32_t mapa_u32(uint32_t addr, uint32_t cta) {
    uint32_t r;
    asm volatile("mapa.shared::cluster.u32 %0, %1, %2;" : "=r"(r) : "r"(addr), "r"(cta));
    return r;
}
__device__ __forceinline__ void mbar_arrive_cluster(uint32_t cluster_addr) {
    asm volatile("mbarrier.arrive.shared::cluster.b64 _, [%0];" ::"r"(cluster_addr) : "memory");
}
__device__ __forceinline__ bool elect_one() {
    uint32_t p;
    asm volatile("{\n.reg .pred P;\nelect.sync _|P, 0xffffffff;\nselp.u32 %0, 1, 0, P;\n}\n" : "=r"(p));
    return p != 0;
}
__device__ __forceinline__ void cluster_arrive_relaxed() { asm volatile("barrier.cluster.arrive.relaxed.aligned;" ::: "memory"); }
__device__ __forceinline__ void cluster_wait() { asm volatile("barrier.cluster.wait.acquire.aligned;" ::: "memory"); }

__device__ __forceinline__ uint32_t bsub2(uint32_t a, uint32_t b) {
    __nv_bfloat162 r = __hsub2(*reinterpret_cast<__nv_bfloat162*>(&a), *reinterpret_cast<__nv_bfloat162*>(&b));
    return *reinterpret_cast<uint32_t*>(&r);
}
__device__ __forceinline__ uint32_t bmul2(uint32_t a, uint32_t b) {
    __nv_bfloat162 r = __hmul2(*reinterpret_cast<__nv_bfloat162*>(&a), *reinterpret_cast<__nv_bfloat162*>(&b));
    return *reinterpret_cast<uint32_t*>(&r);
}
__device__ __forceinline__ uint32_t badd2(uint32_t a, uint32_t b) {
    __nv_bfloat162 r = __hadd2(*reinterpret_cast<__nv_bfloat162*>(&a), *reinterpret_cast<__nv_bfloat162*>(&b));
    return *reinterpret_cast<uint32_t*>(&r);
}
constexpr int BM = 128, BK = 64;
constexpr int R5_STAGE = 32768, R5_N = 5;
constexpr int R4_STAGE = 49152, R4_N = 4;
constexpr int R4B_STAGE = 40960;
constexpr int OFF_STG5 = 0, OFF_R = 32768;
constexpr int OFF_EPI = 196608;
constexpr int OFF_BAR = OFF_EPI + 32768;
constexpr int OFF_RS = OFF_BAR + 256;
constexpr int OFF_CS = OFF_RS + 1024;
constexpr int MEGA_SMEM = OFF_CS + 1792;
enum { FL_XA = 0, FL_H = 2, FL_X1 = 4, FL_H2 = 6, FL_CS = 10, FL_KINDS = 11 };
constexpr int FL_PITCH = 64;
constexpr int FL_WORDS = 2 * FL_KINDS * 16 * FL_PITCH;
__device__ unsigned int g_flag[FL_WORDS];
__device__ __align__(8) unsigned int g_ticket[18 * FL_PITCH];
constexpr int NCL = 66;
__device__ __forceinline__ unsigned int* flag_ptr(int layer, int kind, int i) { return g_flag + ((layer * FL_KINDS + kind) * 16 + i) * FL_PITCH; }

__device__ __forceinline__ void wait_flag(const unsigned int* p, unsigned int target) {
    long long t0 = clock64();
    while (true) {
        unsigned int v;
        asm volatile("ld.relaxed.gpu.global.u32 %0, [%1];" : "=r"(v) : "l"(p) : "memory");
        if ((int)(v - target) >= 0) break;
        if (clock64() - t0 > 2000000000LL) break;
    }
    asm volatile("fence.acquire.gpu;" ::: "memory");
}
__device__ __forceinline__ void fence_proxy_async() {
    asm volatile("fence.proxy.async.global;" ::: "memory");
    asm volatile("fence.proxy.async.shared::cta;" ::: "memory");
}
__device__ __forceinline__ void stsm4(uint32_t addr, uint32_t r0, uint32_t r1, uint32_t r2, uint32_t r3) {
    asm volatile("stmatrix.sync.aligned.m8n8.x4.shared.b16 [%0], {%1,%2,%3,%4};" ::"r"(addr), "r"(r0), "r"(r1), "r"(r2), "r"(r3));
}
__device__ __forceinline__ uint4 lds128(uint32_t a) {
    uint4 v;
    asm volatile("ld.shared.v4.b32 {%0,%1,%2,%3}, [%4];" : "=r"(v.x), "=r"(v.y), "=r"(v.z), "=r"(v.w) : "r"(a) : "memory");
    return v;
}
__device__ __forceinline__ void stg128(void* p, uint4 v) {
    asm volatile("st.global.v4.b32 [%0], {%1,%2,%3,%4};" ::"l"(p), "r"(v.x), "r"(v.y), "r"(v.z), "r"(v.w) : "memory");
}
__device__ __forceinline__ float gelu_tanh_h(float hx) {
    float z = hx * fmaf(hx * hx, 8.0f * 0.035677408136300125f, 2.0f * 0.7978845608028654f);
    float t;
    asm("tanh.approx.f32 %0, %1;" : "=f"(t) : "f"(z));
    return fmaf(hx, t, hx);
}
__device__ __forceinline__ uint32_t gelu2h(uint32_t hx) {
    uint32_t r;
    asm("{\n.reg .b32 z;\nmul.rn.bf16x2 z, %1, %1;\nfma.rn.bf16x2 z, z, %2, %3;\nmul.rn.bf16x2 z, z, %1;\ntanh.approx.bf16x2 z, z;\nfma.rn.bf16x2 %0, %1, z, %1;\n}"
        : "=r"(r) : "r"(hx), "r"(0x3e923e92u), "r"(0x3fcc3fccu));
    return r;
}
__device__ __forceinline__ uint4 gelu8h(uint4 v) { return make_uint4(gelu2h(v.x), gelu2h(v.y), gelu2h(v.z), gelu2h(v.w)); }

__device__ __forceinline__ void row_stats(const float2* p, uint32_t tag, float& mean, float& var) {
    float2 v[8];
#pragma unroll 1
    for (int n = 0; n < (1 << 20); n++) {
#pragma unroll
        for (int i = 0; i < 8; i++)
            asm volatile("{\n.reg .b64 t;\nld.relaxed.gpu.global.b64 t, [%2];\nmov.b64 {%0, %1}, t;\n}" : "=f"(v[i].x), "=f"(v[i].y) : "l"(p + 128 * i) : "memory");
        uint32_t old = 0;
#pragma unroll
        for (int i = 0; i < 8; i++) old |= __float_as_uint(v[i].y) ^ tag;
        if ((int)old >= 0) break;
    }
    mean = (((v[0].x + v[1].x) + (v[2].x + v[3].x)) + ((v[4].x + v[5].x) + (v[6].x + v[7].x))) * 0.125f;
    float m2 = 0.f, d2 = 0.f;
#pragma unroll
    for (int i = 0; i < 8; i++) { m2 += fabsf(v[i].y); d2 = fmaf(v[i].x - mean, v[i].x - mean, d2); }
    var = fmaf(128.0f, d2, m2) * (1.0f / D_);
}
struct RingState { uint32_t st, ph; };

#define DT(i)
#define DT_DECL
#define DT_PAR
#define DT_ARG
#define DT_DUMP
#define DP(i)
#define DQ(i)
#define GT(i)
#define TM(i)

template <int BN, int NST, int ACC = 1>
__device__ __forceinline__ void kblock(float (&acc)[BN / 2], uint32_t da, uint32_t db, uint32_t bfull, RingState& rs) {
    mbar_wait(bfull + 8 * rs.st, rs.ph);
    wgmma_fence();
    WG<BN>::template mma<ACC>(acc, da, db);
#pragma unroll
    for (int k = 1; k < 4; k++) WG<BN>::template mma<1>(acc, da + k * 2, db + k * 128);
    wgmma_commit();
    if (++rs.st == NST) { rs.st = 0; rs.ph ^= 1; }
}
#define PA3A 1
#define RLX 1
#define NPRE 12
#define PP3 2
#define NCS 8
template <int V> struct IC { static constexpr int v = V; };
template <int A, int B, class F> __device__ __forceinline__ void static_for(F f) {
    if constexpr (A < B) { f(IC<A>()); static_for<A + 1, B>(f); }
}
#define PF4A 22
#define PF4N 1
#define PA1 44
#define PA2 44
#define PA4 33
#define LAGX 1
#define PA3B 0
template <int BN, int NST, int STAGE, int PS = 0, int TW = 0, class F>
__device__ __forceinline__ void mainloop(float (&acc)[BN / 2], int KB, uint32_t da0, uint32_t db0, uint32_t bfull, uint32_t rel, bool rel_on,
                                         RingState& rs, int dbg, F pre DT_PAR, int wg = 0) {
    constexpr int SG = PS / 10, PAUSE = PS % 10;
    uint32_t prev = rs.st ? rs.st - 1 : NST - 1;
    const int pause = wg ? KB - PAUSE : -1;
#pragma unroll 1
    for (int kk = 0; kk < KB; kk++) {
        const uint32_t cur = rs.st;
        if (PAUSE && kk == pause) {
            wgmma_wait<0>();
            if (rel_on) mbar_arrive_cluster(rel + 8 * prev);
            named_bar_sync(15, 256);
        }
        kblock<BN, NST>(acc, da0 + cur * (STAGE / 16), db0 + cur * (STAGE / 16), bfull, rs);
        if (PAUSE && SG >= 2 && wg == 0 && kk == KB + 1 - SG) named_bar_arrive(15, 256);
        wgmma_wait<1>();
        if (rel_on && !(PAUSE && kk == pause)) mbar_arrive_cluster(rel + 8 * prev);
        prev = cur;
    }
    if (PAUSE && SG == 0 && wg == 0) named_bar_arrive(15, 256);
    pre();
    wgmma_wait<TW>();
#pragma unroll
    for (int i = 0; i < BN / 2; i++) asm volatile("" : "+f"(acc[i])::"memory");
    if (PAUSE && SG == 1 && wg == 0) named_bar_arrive(15, 256);
    if (rel_on) mbar_arrive_cluster(rel + 8 * prev);
}
__device__ __forceinline__ void hmma(float (&c)[4], uint32_t a0, uint32_t a1, uint32_t a2, uint32_t a3, uint32_t b0, uint32_t b1, bool first) {
    if (first) asm("{\n.reg .f32 z;\nmov.f32 z, 0f00000000;\nmma.sync.aligned.m16n8k16.row.col.f32.bf16.bf16.f32 {%0,%1,%2,%3}, {%4,%5,%6,%7}, {%8,%9}, {z,z,z,z};\n}"
        : "=f"(c[0]), "=f"(c[1]), "=f"(c[2]), "=f"(c[3]) : "r"(a0), "r"(a1), "r"(a2), "r"(a3), "r"(b0), "r"(b1));
    else
    asm("mma.sync.aligned.m16n8k16.row.col.f32.bf16.bf16.f32 {%0,%1,%2,%3}, {%4,%5,%6,%7}, {%8,%9}, {%0,%1,%2,%3};"
        : "+f"(c[0]), "+f"(c[1]), "+f"(c[2]), "+f"(c[3]) : "r"(a0), "r"(a1), "r"(a2), "r"(a3), "r"(b0), "r"(b1));
}
__device__ __forceinline__ void hmma8(float (&c)[4], uint32_t a0, uint32_t a1, uint32_t b0, bool first) {
    if (first) asm("{\n.reg .f32 z;\nmov.f32 z, 0f00000000;\nmma.sync.aligned.m16n8k8.row.col.f32.bf16.bf16.f32 {%0,%1,%2,%3}, {%4,%5}, {%6}, {z,z,z,z};\n}"
        : "=f"(c[0]), "=f"(c[1]), "=f"(c[2]), "=f"(c[3]) : "r"(a0), "r"(a1), "r"(b0));
    else
    asm("mma.sync.aligned.m16n8k8.row.col.f32.bf16.bf16.f32 {%0,%1,%2,%3}, {%4,%5}, {%6}, {%0,%1,%2,%3};"
        : "+f"(c[0]), "+f"(c[1]), "+f"(c[2]), "+f"(c[3]) : "r"(a0), "r"(a1), "r"(b0));
}
template <int N> __device__ __forceinline__ void zero_acc(float (&acc)[N]) {
#pragma unroll
    for (int i = 0; i < N; i++) acc[i] = 0.f;
}
__device__ __forceinline__ void ldsm4(uint32_t& r0, uint32_t& r1, uint32_t& r2, uint32_t& r3, uint32_t addr) {
    asm volatile("ldmatrix.sync.aligned.m8n8.x4.shared.b16 {%0,%1,%2,%3}, [%4];" : "=r"(r0), "=r"(r1), "=r"(r2), "=r"(r3) : "r"(addr));
}

__device__ __forceinline__ void ldsm4t(uint32_t& r0, uint32_t& r1, uint32_t& r2, uint32_t& r3, uint32_t addr) {
    asm volatile("ldmatrix.sync.aligned.m8n8.x4.trans.shared.b16 {%0,%1,%2,%3}, [%4];" : "=r"(r0), "=r"(r1), "=r"(r2), "=r"(r3) : "r"(addr));
}

#define DBG_S(i)
#define DBG_OUT(r, o)
#define DBG_F(i)
#define DBG_W(i)
constexpr int CV_CH = 8;
constexpr int CV_SL = 16384;
constexpr int CV_QG = 128 * 8 + 16;
constexpr int CV_HPL = 2048 + 192;
constexpr int CV_0 = 32768, CV_H = 9 * CV_SL, CV_BAR = OFF_RS - CV_0;

template <int K> __device__ __forceinline__ void cv_mma(float (&d)[64], const uint32_t (&a)[4], uint32_t db, int acc);
template <> __device__ __forceinline__ void cv_mma<0>(float (&d)[64], const uint32_t (&a)[4], uint32_t db, int acc) {
    asm volatile("{\n.reg .pred p;\n.reg .b64 b;\nsetp.ne.b32 p, %70, 0;\nmov.b64 b, {%68, %69};\n"
        "wgmma.mma_async.sync.aligned.m64n128k16.f32.bf16.bf16 {%0,%1,%2,%3,%4,%5,%6,%7,%8,%9,%10,%11,%12,%13,%14,%15,%16,%17,%18,%19,%20,%21,%22,%23,%24,%25,%26,%27,%28,%29,%30,%31,%32,%33,%34,%35,%36,%37,%38,%39,%40,%41,%42,%43,%44,%45,%46,%47,%48,%49,%50,%51,%52,%53,%54,%55,%56,%57,%58,%59,%60,%61,%62,%63}, {%64,%65,%66,%67}, b, p, 1, 1, 0;\n}\n"
        : "+f"(d[0]), "+f"(d[1]), "+f"(d[2]), "+f"(d[3]), "+f"(d[4]), "+f"(d[5]), "+f"(d[6]), "+f"(d[7]), "+f"(d[8]), "+f"(d[9]), "+f"(d[10]), "+f"(d[11]), "+f"(d[12]), "+f"(d[13]), "+f"(d[14]), "+f"(d[15]), "+f"(d[16]), "+f"(d[17]), "+f"(d[18]), "+f"(d[19]), "+f"(d[20]), "+f"(d[21]), "+f"(d[22]), "+f"(d[23]), "+f"(d[24]), "+f"(d[25]), "+f"(d[26]), "+f"(d[27]), "+f"(d[28]), "+f"(d[29]), "+f"(d[30]), "+f"(d[31]), "+f"(d[32]), "+f"(d[33]), "+f"(d[34]), "+f"(d[35]), "+f"(d[36]), "+f"(d[37]), "+f"(d[38]), "+f"(d[39]), "+f"(d[40]), "+f"(d[41]), "+f"(d[42]), "+f"(d[43]), "+f"(d[44]), "+f"(d[45]), "+f"(d[46]), "+f"(d[47]), "+f"(d[48]), "+f"(d[49]), "+f"(d[50]), "+f"(d[51]), "+f"(d[52]), "+f"(d[53]), "+f"(d[54]), "+f"(d[55]), "+f"(d[56]), "+f"(d[57]), "+f"(d[58]), "+f"(d[59]), "+f"(d[60]), "+f"(d[61]), "+f"(d[62]), "+f"(d[63])
        : "r"(a[0]), "r"(a[1]), "r"(a[2]), "r"(a[3]), "r"(db), "r"(8u), "r"(acc));
}
template <> __device__ __forceinline__ void cv_mma<1>(float (&d)[64], const uint32_t (&a)[4], uint32_t db, int acc) {
    asm volatile("{\n.reg .pred p;\n.reg .b64 b;\nsetp.ne.b32 p, %62, 0;\nmov.b64 b, {%60, %61};\n"
        "wgmma.mma_async.sync.aligned.m64n112k16.f32.bf16.bf16 {%0,%1,%2,%3,%4,%5,%6,%7,%8,%9,%10,%11,%12,%13,%14,%15,%16,%17,%18,%19,%20,%21,%22,%23,%24,%25,%26,%27,%28,%29,%30,%31,%32,%33,%34,%35,%36,%37,%38,%39,%40,%41,%42,%43,%44,%45,%46,%47,%48,%49,%50,%51,%52,%53,%54,%55}, {%56,%57,%58,%59}, b, p, 1, 1, 0;\n}\n"
        : "+f"(d[0]), "+f"(d[1]), "+f"(d[2]), "+f"(d[3]), "+f"(d[4]), "+f"(d[5]), "+f"(d[6]), "+f"(d[7]), "+f"(d[8]), "+f"(d[9]), "+f"(d[10]), "+f"(d[11]), "+f"(d[12]), "+f"(d[13]), "+f"(d[14]), "+f"(d[15]), "+f"(d[16]), "+f"(d[17]), "+f"(d[18]), "+f"(d[19]), "+f"(d[20]), "+f"(d[21]), "+f"(d[22]), "+f"(d[23]), "+f"(d[24]), "+f"(d[25]), "+f"(d[26]), "+f"(d[27]), "+f"(d[28]), "+f"(d[29]), "+f"(d[30]), "+f"(d[31]), "+f"(d[32]), "+f"(d[33]), "+f"(d[34]), "+f"(d[35]), "+f"(d[36]), "+f"(d[37]), "+f"(d[38]), "+f"(d[39]), "+f"(d[40]), "+f"(d[41]), "+f"(d[42]), "+f"(d[43]), "+f"(d[44]), "+f"(d[45]), "+f"(d[46]), "+f"(d[47]), "+f"(d[48]), "+f"(d[49]), "+f"(d[50]), "+f"(d[51]), "+f"(d[52]), "+f"(d[53]), "+f"(d[54]), "+f"(d[55])
        : "r"(a[0]), "r"(a[1]), "r"(a[2]), "r"(a[3]), "r"(db), "r"(8u), "r"(acc));
}
template <> __device__ __forceinline__ void cv_mma<2>(float (&d)[64], const uint32_t (&a)[4], uint32_t db, int acc) {
    asm volatile("{\n.reg .pred p;\n.reg .b64 b;\nsetp.ne.b32 p, %54, 0;\nmov.b64 b, {%52, %53};\n"
        "wgmma.mma_async.sync.aligned.m64n96k16.f32.bf16.bf16 {%0,%1,%2,%3,%4,%5,%6,%7,%8,%9,%10,%11,%12,%13,%14,%15,%16,%17,%18,%19,%20,%21,%22,%23,%24,%25,%26,%27,%28,%29,%30,%31,%32,%33,%34,%35,%36,%37,%38,%39,%40,%41,%42,%43,%44,%45,%46,%47}, {%48,%49,%50,%51}, b, p, 1, 1, 0;\n}\n"
        : "+f"(d[0]), "+f"(d[1]), "+f"(d[2]), "+f"(d[3]), "+f"(d[4]), "+f"(d[5]), "+f"(d[6]), "+f"(d[7]), "+f"(d[8]), "+f"(d[9]), "+f"(d[10]), "+f"(d[11]), "+f"(d[12]), "+f"(d[13]), "+f"(d[14]), "+f"(d[15]), "+f"(d[16]), "+f"(d[17]), "+f"(d[18]), "+f"(d[19]), "+f"(d[20]), "+f"(d[21]), "+f"(d[22]), "+f"(d[23]), "+f"(d[24]), "+f"(d[25]), "+f"(d[26]), "+f"(d[27]), "+f"(d[28]), "+f"(d[29]), "+f"(d[30]), "+f"(d[31]), "+f"(d[32]), "+f"(d[33]), "+f"(d[34]), "+f"(d[35]), "+f"(d[36]), "+f"(d[37]), "+f"(d[38]), "+f"(d[39]), "+f"(d[40]), "+f"(d[41]), "+f"(d[42]), "+f"(d[43]), "+f"(d[44]), "+f"(d[45]), "+f"(d[46]), "+f"(d[47])
        : "r"(a[0]), "r"(a[1]), "r"(a[2]), "r"(a[3]), "r"(db), "r"(8u), "r"(acc));
}
template <> __device__ __forceinline__ void cv_mma<3>(float (&d)[64], const uint32_t (&a)[4], uint32_t db, int acc) {
    asm volatile("{\n.reg .pred p;\n.reg .b64 b;\nsetp.ne.b32 p, %46, 0;\nmov.b64 b, {%44, %45};\n"
        "wgmma.mma_async.sync.aligned.m64n80k16.f32.bf16.bf16 {%0,%1,%2,%3,%4,%5,%6,%7,%8,%9,%10,%11,%12,%13,%14,%15,%16,%17,%18,%19,%20,%21,%22,%23,%24,%25,%26,%27,%28,%29,%30,%31,%32,%33,%34,%35,%36,%37,%38,%39}, {%40,%41,%42,%43}, b, p, 1, 1, 0;\n}\n"
        : "+f"(d[0]), "+f"(d[1]), "+f"(d[2]), "+f"(d[3]), "+f"(d[4]), "+f"(d[5]), "+f"(d[6]), "+f"(d[7]), "+f"(d[8]), "+f"(d[9]), "+f"(d[10]), "+f"(d[11]), "+f"(d[12]), "+f"(d[13]), "+f"(d[14]), "+f"(d[15]), "+f"(d[16]), "+f"(d[17]), "+f"(d[18]), "+f"(d[19]), "+f"(d[20]), "+f"(d[21]), "+f"(d[22]), "+f"(d[23]), "+f"(d[24]), "+f"(d[25]), "+f"(d[26]), "+f"(d[27]), "+f"(d[28]), "+f"(d[29]), "+f"(d[30]), "+f"(d[31]), "+f"(d[32]), "+f"(d[33]), "+f"(d[34]), "+f"(d[35]), "+f"(d[36]), "+f"(d[37]), "+f"(d[38]), "+f"(d[39])
        : "r"(a[0]), "r"(a[1]), "r"(a[2]), "r"(a[3]), "r"(db), "r"(8u), "r"(acc));
}
template <> __device__ __forceinline__ void cv_mma<4>(float (&d)[64], const uint32_t (&a)[4], uint32_t db, int acc) {
    asm volatile("{\n.reg .pred p;\n.reg .b64 b;\nsetp.ne.b32 p, %38, 0;\nmov.b64 b, {%36, %37};\n"
        "wgmma.mma_async.sync.aligned.m64n64k16.f32.bf16.bf16 {%0,%1,%2,%3,%4,%5,%6,%7,%8,%9,%10,%11,%12,%13,%14,%15,%16,%17,%18,%19,%20,%21,%22,%23,%24,%25,%26,%27,%28,%29,%30,%31}, {%32,%33,%34,%35}, b, p, 1, 1, 0;\n}\n"
        : "+f"(d[0]), "+f"(d[1]), "+f"(d[2]), "+f"(d[3]), "+f"(d[4]), "+f"(d[5]), "+f"(d[6]), "+f"(d[7]), "+f"(d[8]), "+f"(d[9]), "+f"(d[10]), "+f"(d[11]), "+f"(d[12]), "+f"(d[13]), "+f"(d[14]), "+f"(d[15]), "+f"(d[16]), "+f"(d[17]), "+f"(d[18]), "+f"(d[19]), "+f"(d[20]), "+f"(d[21]), "+f"(d[22]), "+f"(d[23]), "+f"(d[24]), "+f"(d[25]), "+f"(d[26]), "+f"(d[27]), "+f"(d[28]), "+f"(d[29]), "+f"(d[30]), "+f"(d[31])
        : "r"(a[0]), "r"(a[1]), "r"(a[2]), "r"(a[3]), "r"(db), "r"(8u), "r"(acc));
}
template <> __device__ __forceinline__ void cv_mma<5>(float (&d)[64], const uint32_t (&a)[4], uint32_t db, int acc) {
    asm volatile("{\n.reg .pred p;\n.reg .b64 b;\nsetp.ne.b32 p, %30, 0;\nmov.b64 b, {%28, %29};\n"
        "wgmma.mma_async.sync.aligned.m64n48k16.f32.bf16.bf16 {%0,%1,%2,%3,%4,%5,%6,%7,%8,%9,%10,%11,%12,%13,%14,%15,%16,%17,%18,%19,%20,%21,%22,%23}, {%24,%25,%26,%27}, b, p, 1, 1, 0;\n}\n"
        : "+f"(d[0]), "+f"(d[1]), "+f"(d[2]), "+f"(d[3]), "+f"(d[4]), "+f"(d[5]), "+f"(d[6]), "+f"(d[7]), "+f"(d[8]), "+f"(d[9]), "+f"(d[10]), "+f"(d[11]), "+f"(d[12]), "+f"(d[13]), "+f"(d[14]), "+f"(d[15]), "+f"(d[16]), "+f"(d[17]), "+f"(d[18]), "+f"(d[19]), "+f"(d[20]), "+f"(d[21]), "+f"(d[22]), "+f"(d[23])
        : "r"(a[0]), "r"(a[1]), "r"(a[2]), "r"(a[3]), "r"(db), "r"(8u), "r"(acc));
}
template <> __device__ __forceinline__ void cv_mma<6>(float (&d)[64], const uint32_t (&a)[4], uint32_t db, int acc) {
    asm volatile("{\n.reg .pred p;\n.reg .b64 b;\nsetp.ne.b32 p, %22, 0;\nmov.b64 b, {%20, %21};\n"
        "wgmma.mma_async.sync.aligned.m64n32k16.f32.bf16.bf16 {%0,%1,%2,%3,%4,%5,%6,%7,%8,%9,%10,%11,%12,%13,%14,%15}, {%16,%17,%18,%19}, b, p, 1, 1, 0;\n}\n"
        : "+f"(d[0]), "+f"(d[1]), "+f"(d[2]), "+f"(d[3]), "+f"(d[4]), "+f"(d[5]), "+f"(d[6]), "+f"(d[7]), "+f"(d[8]), "+f"(d[9]), "+f"(d[10]), "+f"(d[11]), "+f"(d[12]), "+f"(d[13]), "+f"(d[14]), "+f"(d[15])
        : "r"(a[0]), "r"(a[1]), "r"(a[2]), "r"(a[3]), "r"(db), "r"(8u), "r"(acc));
}
template <> __device__ __forceinline__ void cv_mma<7>(float (&d)[64], const uint32_t (&a)[4], uint32_t db, int acc) {
    asm volatile("{\n.reg .pred p;\n.reg .b64 b;\nsetp.ne.b32 p, %14, 0;\nmov.b64 b, {%12, %13};\n"
        "wgmma.mma_async.sync.aligned.m64n16k16.f32.bf16.bf16 {%0,%1,%2,%3,%4,%5,%6,%7}, {%8,%9,%10,%11}, b, p, 1, 1, 0;\n}\n"
        : "+f"(d[0]), "+f"(d[1]), "+f"(d[2]), "+f"(d[3]), "+f"(d[4]), "+f"(d[5]), "+f"(d[6]), "+f"(d[7])
        : "r"(a[0]), "r"(a[1]), "r"(a[2]), "r"(a[3]), "r"(db), "r"(8u), "r"(acc));
}
__device__ __forceinline__ void stsm4t(uint32_t addr, uint32_t r0, uint32_t r1, uint32_t r2, uint32_t r3) {
    asm volatile("stmatrix.sync.aligned.m8n8.x4.trans.shared.b16 [%0], {%1,%2,%3,%4};" ::"r"(addr), "r"(r0), "r"(r1), "r"(r2), "r"(r3) : "memory");
}
__device__ __forceinline__ void cp16(uint32_t dst, const void* src, int n = 16) {
    asm volatile("cp.async.cg.shared.global.L2::128B [%0], [%1], 16, %2;" ::"r"(dst), "l"(src), "r"(n) : "memory");
}
__device__ __forceinline__ void cp_arrive(uint32_t bar) { asm volatile("cp.async.mbarrier.arrive.noinc.shared::cta.b64 [%0];" ::"r"(bar) : "memory"); }
__device__ __forceinline__ void lds64(uint32_t& x, uint32_t& y, uint32_t a) { asm volatile("ld.shared.v2.b32 {%0,%1}, [%2];" : "=r"(x), "=r"(y) : "r"(a) : "memory"); }
__device__ __forceinline__ void sts128(uint32_t a, uint32_t x, uint32_t y, uint32_t z, uint32_t w) {
    asm volatile("st.shared.v4.b32 [%0], {%1,%2,%3,%4};" ::"r"(a), "r"(x), "r"(y), "r"(z), "r"(w) : "memory");
}
__device__ __forceinline__ uint32_t bfma2(uint32_t a, uint32_t b, uint32_t c) {
    uint32_t r;
    asm("fma.rn.bf16x2 %0, %1, %2, %3;" : "=r"(r) : "r"(a), "r"(b), "r"(c));
    return r;
}
#define CV_NS 4
#define CV_W 1
constexpr int CV_GC = 8 / CV_NS, CV_NA = (CV_W + 2) * CV_NS;
struct CvAddr { uint32_t pa[2], p0[4], db, rdy, xw, xr, bar; bool wrap, neg[2]; };
template <int G> __device__ __forceinline__ void cv_load(uint32_t (&a)[CV_NA][4], const CvAddr& p) {
    if constexpr (G % CV_GC == 0) mbar_wait(p.rdy + 8 * (G / CV_GC), 0);
#pragma unroll
    for (int i = G * CV_NS; i < (G + 1) * CV_NS; i++) {
        const int of = (i / 2 % 2) * CV_QG + (i / 8) * CV_SL + 256 * (i % 2 + (i / 2 & 2));
        if ((i & 5) == 0) {
#pragma unroll
            for (int e = 0; e < 4; e++) asm volatile("ld.shared.b32 %0, [%1];" : "=r"(a[i % CV_NA][e]) : "r"(p.p0[e] + of) : "memory");
            if (i < 8) { if (p.neg[0]) a[i % CV_NA][0] = 0; if (p.neg[1]) a[i % CV_NA][2] = 0; }
        } else {
            lds64(a[i % CV_NA][0], a[i % CV_NA][1], p.pa[0] + of - 256);
            lds64(a[i % CV_NA][2], a[i % CV_NA][3], p.pa[1] + of - 256);
        }
    }
}
__device__ __forceinline__ float vadd(float a, float b) {
    float r;
    asm volatile("add.f32 %0, %1, %2;" : "=f"(r) : "f"(a), "f"(b));
    return r;
}
template <int K> __device__ __forceinline__ uint32_t cv_tail(float (&d)[64], bool wrap) {
    float* z = d + 56 - 8 * K;
    z[4] = vadd(z[4], K > 0 ? z[10] : 0.f);
    if constexpr (K > 0) z[5] = vadd(z[5], z[11]);
    z[0] = vadd(z[0], z[6]);
    z[1] = vadd(z[1], z[7]);
    return pack2(wrap ? (K > 0 ? z[8] : 0.f) : z[4], wrap ? z[4] : z[0]);
}
template <int K> __device__ __forceinline__ uint32_t cv_fin(const float (&d)[64], uint32_t x) { return pack2(d[61 - 8 * K] + lo2f(x), d[57 - 8 * K] + hi2f(x)); }
template <int G>
__device__ __forceinline__ void cv_steps(float (&d)[2][64], uint32_t (&a)[CV_NA][4], uint32_t (&tv)[2][8], const CvAddr& p) {
    constexpr int K = G / CV_GC, GN = 8 * CV_GC;
    constexpr int T = G - CV_W - CV_GC, F = T - 1, TK = T / CV_GC, FK = F / CV_GC;
    if constexpr (G == 0) cv_load<0>(a, p);
    if constexpr (G < GN) {
        wgmma_fence();
#pragma unroll
        for (int i = G * CV_NS; i < (G + 1) * CV_NS; i++)
            cv_mma<K>(d[i / 2 % 2], a[i % CV_NA], p.db + (i / 2 % 2) * (CV_HPL / 8) + 16 * K + 2 * (i % 2 + (i / 2 & 2)), i & ~2 ? 1 : p.bar >> 8);
        wgmma_commit();
    }
    if constexpr (G < GN - 1) cv_load<G + 1>(a, p);
    if constexpr (T >= 0 && T % CV_GC == 0) {
        tv[0][TK] = cv_tail<TK>(d[0], p.wrap);
        tv[1][TK] = cv_tail<TK>(d[1], p.wrap);
        if constexpr (TK & 1) sts128(p.xw + TK / 2 * 512, tv[0][TK - 1], tv[0][TK], tv[1][TK - 1], tv[1][TK]);
    }
    if constexpr (F >= 0 && F % (2 * CV_GC) == CV_GC) {
        const uint4 x = lds128(p.xr + FK / 2 * 512);
        tv[0][FK - 1] = cv_fin<FK - 1>(d[0], x.x); tv[0][FK] = cv_fin<FK>(d[0], x.y);
        tv[1][FK - 1] = cv_fin<FK - 1>(d[1], x.z); tv[1][FK] = cv_fin<FK>(d[1], x.w);
    }
    if constexpr (G < GN - 1) wgmma_wait<CV_W>();
    if constexpr (G == GN - 1) wgmma_wait<0>();
    if constexpr (T >= 0 && T % (2 * CV_GC) == CV_GC) named_bar_sync(p.bar, 128);
    if constexpr (F < GN - CV_GC) cv_steps<G + 1>(d, a, tv, p);
}

#define CV_PF 7
#define Y_FIRST 1
#define Y_HOLD 0
#define PS2_EARLY 1
#define PS1_EARLY 1
struct MegaMaps {
    CUtensorMap q, act;
    CUtensorMap a64, w1, w2, w3, w4;
    CUtensorMap k, v;
};

__global__ void __cluster_dims__(2, 1, 1) __launch_bounds__(384, 1)
mega_kernel(const __grid_constant__ MegaMaps tm, bf16* __restrict__ outp, bf16* act, const bf16* __restrict__ w1p, const bf16* __restrict__ w2p,
            const bf16* __restrict__ w3p, const bf16* __restrict__ xq, const bf16* __restrict__ kp, const bf16* __restrict__ vp,
            const bf16* __restrict__ shk, const bf16* __restrict__ ssk, const bf16* __restrict__ ssD) {
    extern __shared__ __align__(1024) uint8_t sgen[];
    const uint32_t sbase = smem_u32(sgen);
    const int warp = __shfl_sync(0xffffffffu, threadIdx.x >> 5, 0), lane = threadIdx.x & 31;
    const int rank = blockIdx.x & 1;
    const uint32_t s_bar = sbase + OFF_BAR;
    const uint32_t f5 = s_bar, e5 = s_bar + 64, f4 = s_bar + 144, e4 = s_bar + 104;
    const uint32_t b_rfull = s_bar + 176, b_role = s_bar + 184, b_stg = s_bar + 136, b_h2 = s_bar + 32;
    const uint32_t s_epi = sbase + OFF_EPI, s_stg = sbase + OFF_STG5, s_r = sbase + OFF_R;
    uint8_t* sm = sgen + CV_0;
    const uint32_t sb = sbase + CV_0;
    const int tid = threadIdx.x, wg = warp >> 2, w = warp & 3;
    const int d0 = blockIdx.x * CV_CH;
    const bool cv = blockIdx.x < D_ / CV_CH;
    const uint32_t b_full = sb + CV_BAR, b_rdy = b_full + 64, b_h = b_full + 128;
    GT(0);
    if (tid == 0) TM(0);
    auto row_at = [&](int r) { return sb + CV_SL + (r < 0 ? -8192 : 0) + ((r & 127) >> 5) * 1024 + (r & 7) * 128 + ((r >> 3) & 3) * 32 + ((r ^ rank) & 1) * 16; };
    auto load_kv = [&](int c) {
#pragma unroll
        for (int i = 0; i < 2; i++)
            asm volatile("cp.async.bulk.tensor.4d.shared::cluster.global.mbarrier::complete_tx::bytes.multicast::cluster [%0], [%1, {%3, %4, %4, %5}], [%2], %6;"
                         ::"r"(sb + (c + 1) * CV_SL + rank * 8192 + i * 4096), "l"((uint64_t)(i ? &tm.v : &tm.k)), "r"(b_full + 8 * c), "r"(d0 & ~15), "r"(0),
                         "r"(8 * c + 4 * rank), "h"((uint16_t)3) : "memory");
    };
    auto bulk = [&](uint32_t dst, const void* src, uint32_t n, uint32_t bar) {
        asm volatile("cp.async.bulk.shared::cluster.global.mbarrier::complete_tx::bytes [%0], [%1], %2, [%3];" ::"r"(dst), "l"(src), "r"(n), "r"(bar) : "memory");
    };
    auto put_h = [&](int ch) {
        const uint32_t dk = (tid & 127) ? 0 : *reinterpret_cast<const volatile uint32_t*>(sm + CV_BAR + 160 + 16 * wg + 2 * ch);
        uint4 v[4];
#pragma unroll
        for (int i = 0; i < 4; i++) v[i] = lds128(sbase + ch * 4096 + i * 2048 + (tid & 127) * 16);
        v[0].x = pack2(lo2f(v[0].x) + lo2f(dk), hi2f(v[0].x));
        v[2].x = pack2(lo2f(v[2].x) + hi2f(dk), hi2f(v[2].x));
#pragma unroll
        for (int i = 0; i < 4; i++)
            sts128(sb + CV_H + (2 * ch + (i & 2) + (tid & 1)) * CV_HPL + (127 - ((tid & 127) >> 1)) * 16 - (i & 1) * 1024, v[i].x, v[i].y, v[i].z, v[i].w);
    };
    int bi, bj, m0, tb;
    uint32_t ep;
    auto get_role = [&]() {
        mbar_wait(b_role, 0);
        int role;
        asm volatile("ld.shared.v2.b32 {%0,%1}, [%2];" : "=r"(role), "=r"(ep) : "r"(s_bar + 248) : "memory");
        bi = (role >> 3) * 2 + rank; bj = role & 7; m0 = bi * BM; tb = (role >> 3) * 2048 + rank * 128;
        return role < 64;
    };

    if (warp >= 8) {
        asm volatile("setmaxnreg.dec.sync.aligned.u32 88;");
        cluster_arrive_relaxed();
        if (!cv) cluster_wait(); else {
            const int bt = tid - 256, g = lane >> 2, t = lane & 3;
            if (bt < 16) sts128(row_at((bt & 7) - 8) + (bt >> 3) * 4096, 0, 0, 0, 0);
#pragma unroll
            for (int i = 0; i < 4; i++)
                cp16(row_at(bt) + i * 4096, (i & 1 ? vp : kp) + (size_t)(bt + (i >> 1) * 128) * D_ + d0);
            DBG_S(16 + (3));
            uint2 wa;
            asm volatile("ld.global.nc.v2.b32 {%0,%1}, [%2];" : "=r"(wa.x), "=r"(wa.y) : "l"(shk + (d0 + g) * 4));
            const int mi = lane >> 3, r0 = 32 * w + 8 * ((lane >> 1) & 3) - (lane & 1);
            const uint32_t ka0 = row_at(r0 + 2 * mi - 3), ka1 = row_at(r0 + 2 * (mi & 1) + 5) + (mi >> 1) * 8192;
            const uint32_t va0 = row_at(r0 + 2 * mi + 1) + 4096, va1 = row_at(r0 - 1) + 4096 + (mi & 1) * 8192;
            const uint32_t qd = sb + g * CV_QG + (32 * w + 8 * t) * 8, qd0 = qd + (t & 2) * 16, qd1 = qd + (~t & 2) * 16;
            const uint32_t w0 = __byte_perm(wa.x, 0, 0x1010), w1 = __byte_perm(wa.x, 0, 0x3232), w2 = __byte_perm(wa.y, 0, 0x1010), w3 = __byte_perm(wa.y, 0, 0x3232);
            cluster_wait();
            DBG_S(16 + (5));
            asm volatile("cp.async.wait_all;" ::: "memory");
            named_bar_sync(7, 128);
            DBG_S(16 + (1));
            struct KV { uint32_t k[2][6], v[2][5]; };
            auto get = [&](KV& x, uint32_t so) {
                ldsm4t(x.k[0][0], x.k[0][1], x.k[0][2], x.k[0][3], ka0 + so);
                ldsm4t(x.k[0][4], x.k[0][5], x.k[1][4], x.k[1][5], ka1 + so);
                ldsm4t(x.k[1][0], x.k[1][1], x.k[1][2], x.k[1][3], ka0 + so + 8192);
                asm volatile("ldmatrix.sync.aligned.m8n8.x2.trans.shared.b16 {%0,%1}, [%2];" : "=r"(x.v[0][0]), "=r"(x.v[1][0]) : "r"(va1 + so));
                ldsm4t(x.v[0][1], x.v[0][2], x.v[0][3], x.v[0][4], va0 + so);
                ldsm4t(x.v[1][1], x.v[1][2], x.v[1][3], x.v[1][4], va0 + so + 8192);
            };
            auto build = [&](int c, const KV& x, KV& nx) {
                const uint32_t so = c * CV_SL;
                DBG_F(1);
                uint32_t early;
                asm volatile("{\n.reg .pred p;\nmbarrier.test_wait.parity.shared::cta.b64 p, [%1], 0;\nvote.sync.all.pred p, p, -1;\nselp.u32 %0, 1, 0, p;\n}"
                             : "=r"(early) : "r"(b_full + 8 * (c < 7 ? c + 1 : c)) : "memory");
                if (early) get(nx, so + CV_SL);
                DBG_F(2);
                uint32_t p[8][2];
#pragma unroll
                for (int sg = 0; sg < 2; sg++) {
                    uint32_t u[5], ke[6];
#pragma unroll
                    for (int i = 0; i < 6; i++) ke[i] = __byte_perm(x.k[sg][i], x.k[sg][i ? i - 1 : 0], 0x5432);
#pragma unroll
                    for (int i = 0; i < 5; i++) {
                        u[i] = bmul2(bfma2(x.k[sg][i + 1], w0, bfma2(ke[i + 1], w1, bfma2(x.k[sg][i], w2, bmul2(ke[i], w3)))), x.v[sg][i]);
                        if (i) { p[2 * i - 1][sg] = u[i]; p[2 * i - 2][sg] = __byte_perm(u[i], u[i - 1], 0x5432); }
                    }
                }
                DBG_F(3);
#pragma unroll
                for (int j = 0; j < 4; j++) sts128((j & 2 ? qd1 : qd0) + so + 16 * (j & 1), p[2 * j][0], p[2 * j][1], p[2 * j + 1][0], p[2 * j + 1][1]);
                __syncwarp();
                DBG_F(4);
                if (lane == 0) {
                    mbar_arrive(b_rdy + 8 * c);
                    if (c == w) {
                        if (c < 3) load_kv(c + 5);
                        else { bulk(sbase + 16384, ssk + (size_t)(d0 + 4) * S_, 16384, b_h + 16); bulk(b_full + 192, ssD + d0, 16, b_h + 16); }
                    }
                    if (c == w + 4 && (CV_PF >> w & 1)) {
                        const uint32_t n = w == 0 ? 32768 : w == 3 ? 57344 : 16384;
                        const char* src = reinterpret_cast<const char*>(w == 0 ? xq : w == 1 ? w1p : w == 2 ? w2p : w3p) + (size_t)blockIdx.x * n;
                        asm volatile("cp.async.bulk.prefetch.L2.global [%0], %1;" ::"l"(src), "r"(n) : "memory");
                    }
                }
                DBG_F(5);
                named_bar_sync(7, 128);
                DBG_F(6);
                DBG_S(16 + (c == 0 ? 4 : 5 + c));
                if (!early) { mbar_wait(b_full + 8 * c + 8, 0); get(nx, so + CV_SL); }
                DBG_F(7);
            };
            KV x0, x1;
            get(x0, 0);
#pragma unroll 1
            for (int c = 0; c < 8; c += 2) { build(c, x0, x1); build(c + 1, x1, x0); }
            mbar_wait(b_h + 16, 0);
            put_h(4); put_h(6);
            fence_async_smem();
            __syncwarp();
            if (lane == 0) mbar_arrive(b_full);
            named_bar_sync(7, 128);
            DBG_S(16 + (13));
        }
    } else {
        if (elect_one()) {
            mbar_init(b_full + 8 * warp, warp ? 1 : 4);
            mbar_init(b_rdy + 8 * warp, 4);
            if (warp) mbar_expect_tx(b_full + 8 * warp, 16384);
            if (w == 0 && cv) {
                mbar_init(b_h + 8 * wg, 1);
                mbar_expect_tx(b_h + 8 * wg, 8192 + 16);
                fence_async_smem();
                bulk(sbase + wg * 8192, ssk + (size_t)(d0 + 2 * wg) * S_, 8192, b_h + 8 * wg);
                bulk(b_full + 160 + 16 * wg, ssD + d0, 16, b_h + 8 * wg);
            }
            mbar_init(s_bar + 8 * warp, 1);
            mbar_init(s_bar + 64 + 8 * warp, 4);
            mbar_init(s_bar + 128 + 8 * warp, warp < 2 ? 4 << warp : warp == 6 ? 2 : 1);
            if (wg) mbar_init(s_bar + 160 + 8 * warp, 8);
            if (warp == 0) mbar_arrive(f5);
            if (warp == 7) mbar_expect_tx(b_role, 8);
            if (warp == 1) { mbar_init(b_h + 16, 1); mbar_expect_tx(b_h + 16, 16384 + 16); }
            if (w == 2) sts128(s_bar + 224 + 16 * wg, 0, 0, 0, 0);
            asm volatile("fence.mbarrier_init.release.cluster;" ::: "memory");
            if (warp == 2) { prefetch_tmap(&tm.k); prefetch_tmap(&tm.v); }
        }
        __syncwarp();
        DBG_W(1);
        cluster_arrive_relaxed();
        asm volatile("setmaxnreg.inc.sync.aligned.u32 208;");
        DBG_W(2);
        const int zi = (tid & 127) - 32;
        if (zi >= 0 && zi < 48) sts128(sb + CV_H + (4 * wg + (zi / 6 & 3) + (zi / 24) * 8) * CV_HPL + 2048 + (zi % 6) * 16, 0, 0, 0, 0);
        DBG_W(3);
        cluster_wait();
        DBG_W(5);
        if (cv) {
            if (tid == 32) {
#pragma unroll 1
                for (int c = 1; c < 5; c++) load_kv(c);
            }
            __syncwarp();
            DBG_W(6);
            const int g = lane >> 2, t = lane & 3;
            const int x0 = 32 + 8 * w + g - 2 * t;
            CvAddr p;
            p.rdy = b_rdy;
            p.bar = 1 + wg;
            p.xr = sbase + (warp ^ 2) * 2048 + lane * 16;
            p.xw = sbase + warp * 2048 + (g * 4 + ((t - (w >> 1)) & 3)) * 16;
            p.wrap = t == 0 && w >= 2;
            mbar_wait(b_h + 8 * wg, 0);
            DBG_W(4);
            put_h(2 * wg);
            fence_async_smem();
            named_bar_sync(1 + wg, 128);
            float acc[2][64];
            zero_acc(acc[0]); zero_acc(acc[1]);
#pragma unroll 1
            for (int round = 0; round < 2; round++) {
                const int ch = round * 4 + 2 * wg;
                uint32_t a[CV_NA][4], tv[2][8];
#pragma unroll
                for (int e = 0; e < 2; e++) {
                    const int x = x0 - 8 * e;
                    p.neg[e] = x < 32;
                    p.pa[e] = sb + ch * CV_QG + 8 * (x ^ (x >> 2 & 4));
                    p.p0[2 * e] = p.pa[e] + (x < 32 ? 768 + 4 - CV_SL : -256);
                    p.p0[2 * e + 1] = p.pa[e] + (x < 32 ? 768 : -256 + 4);
                }
                p.db = (((sb + CV_H + ch * 2 * CV_HPL) & 0x3FFFF) >> 4) | ((CV_HPL / 16) << 16);
                if (round) mbar_wait(b_full, 0);
                DBG_S(7 + 3 * round);
                cv_steps<0>(acc, a, tv, p);
                DBG_S(8 + 3 * round);
                const int r128 = 4 * (lane >> 3) + 2 * (lane & 1) + ((~lane >> 2) & 1);
#pragma unroll
                for (int i = 0; i < 2; i++) {
                    const uint32_t ta = sb + ((ch + i + 1) & 7) * CV_SL + 12288 + r128 * 128 + ((((~lane & 2) * 2 + w) ^ (r128 & 7)) << 4);
                    stsm4t(ta, tv[i][0], tv[i][1], tv[i][2], tv[i][3]);
                    stsm4t(ta + 2048, tv[i][4], tv[i][5], tv[i][6], tv[i][7]);
                }
                named_bar_sync(1 + wg, 128);
                {
                    const int l = 4 * w + (lane >> 3);
                    uint4 v[4];
#pragma unroll
                    for (int i = 0; i < 4; i++) v[i] = lds128(sb + ((ch + (i >> 1) + 1) & 7) * CV_SL + 12288 + (i & 1) * 2048 + l * 128 + (((lane ^ l) & 7) << 4));
                    const int yr = (d0 & 128) + round * 68 + ((d0 >> 1 & 60) ^ 2 * wg) - (d0 & 8) * round;
                    bf16* gy = act + (size_t)(R_Y + w * 2048 + yr) * D_ + (d0 & ~255) + lane * 8;
#pragma unroll
                    for (int i = 0; i < 4; i++) stg128(gy + ((i & 1) * 8192 + (i >> 1)) * D_, v[i]);
                    named_bar_arrive(4 + 8 * round, 288);
                }
                DBG_S(9 + 3 * round);
            }
        }
    }
    int warp2 = warp;
    asm volatile("" : "+r"(warp2));
    if (warp2 >= 8) {
        asm volatile("setmaxnreg.dec.sync.aligned.u32 72;");
        if (warp == 8) { if (elect_one()) {
            if (rank == 0) {
                uint32_t smid;
                asm volatile("mov.u32 %0, %%smid;" : "=r"(smid));
                const int t = smid >> 1;
                int team = t < 32 ? t & 7 : t < 60 ? 1 + (t - 32) % 7 : t < 62 ? t - 54 : 0;
                const unsigned long long arr = atomicAdd(reinterpret_cast<unsigned long long*>(g_ticket + 16 * FL_PITCH), 1ull);
                const uint32_t e1 = (uint32_t)(arr / NCL) + 1;
                unsigned int* tk = g_ticket + (e1 & 1) * 8 * FL_PITCH;
                int slot = atomicAdd(tk + team * FL_PITCH, 1u);
                atomicAdd(g_ticket + 17 * FL_PITCH, 1u);
                if (blockIdx.x < 16) g_ticket[((~e1 & 1) * 8 + (blockIdx.x >> 1)) * FL_PITCH] = 0;
                if (slot >= 8) {
                    const long long t0 = clock64();
                    while ((int)(*(volatile unsigned int*)(g_ticket + 17 * FL_PITCH) - e1 * NCL) < 0 && clock64() - t0 < 100000) {}
                    for (team = 0; team < 8; team++)
                        if ((slot = atomicAdd(tk + team * FL_PITCH, 1u)) < 8) break;
                }
#pragma unroll
                for (int i = 0; i < 2; i++)
                    asm volatile("st.async.weak.shared::cluster.mbarrier::complete_tx::bytes.v2.b32 [%0], {%1, %2}, [%3];"
                                 ::"r"(mapa_u32(s_bar + 248, i)), "r"(team * 8 + slot), "r"(e1), "r"(mapa_u32(b_role, i)) : "memory");
            }
            if (get_role()) {
            TM(2);
            mbar_expect_tx(b_rfull, 32768);
            tma_load_2d(sbase + 16384, &tm.q, b_rfull, bj * 128, m0);
            tma_load_2d(sb + 8 * CV_SL, &tm.q, b_rfull, bj * 128 + 64, m0);
            int s5 = 0, s4 = 0;
            uint32_t p5 = 0, p4 = 1;
            auto putB = [&](const CUtensorMap* tB, int kc, uint32_t bytes) {
                const uint32_t full = f5 + 8 * s5;
                mbar_wait(full + 64, (p5 >> s5) & 1);
                mbar_expect_tx(full, bytes);
                tma_load_2d_mc(s_r + 16384 + rank * 8192 + s5 * R5_STAGE, tB, full, bj * 128 + rank * 64, kc);
                p5 ^= 1u << s5;
            };
            auto putA = [&](int c, int r) {
                tma_load_2d(s_r + s5 * R5_STAGE, &tm.act, f5 + 8 * s5, c, r);
                if (++s5 == R5_N) s5 = 0;
            };
            prefetch_tmap(&tm.act); prefetch_tmap(&tm.w1); prefetch_tmap(&tm.w2); prefetch_tmap(&tm.w3); prefetch_tmap(&tm.w4); prefetch_tmap(&tm.a64);
            auto own_first = [&](int it) {
                const int hf = it >= 9, c = it - 2 - 7 * hf;
                return (it < 2 ? 2 * bj + it : 2 * (c + (c >= bj)) + hf) * BK;
            };
            const unsigned int n8 = 8 * ep, nh = (bi == 0 || bi == 15) ? 12 * ep : 2 * n8;
#pragma unroll 1
            for (int layer = 0; layer < 2; layer++) {
                s5 = 2;
#pragma unroll 1
                for (int kk = -(layer | Y_FIRST); kk < 5 - (layer | Y_FIRST); kk++) {
                    if (kk & 4) {
                        mbar_wait(e5 + 8, (p5 >> 1) & 1);
                        mbar_expect_tx(f5 + 8, 32768);
#pragma unroll 1
                        for (int i = 0; i < 4; i++) {
                            if (layer == 0 && !(i & 1)) { wait_flag(flag_ptr(1 - (i >> 1), FL_CS, 8 + bj), 8 * n8); TM(4); fence_proxy_async(); }
                            tma_load_2d(s_r + R5_STAGE + (i & 1) * 16384 + (i >> 1) * 8192, &tm.a64, f5 + 8, (bj >> 1) * 256 + rank * 128 + (i & 1) * 64,
                                        R_Y + (tb & ~255) + (bj & 1) * 128 + (i >> 1) * 64);
                        }
                        p5 ^= 2;
                        if (layer == 0) TM(5);
                    } else {
                        if (kk == Y_HOLD && layer == 0) mbar_wait(f5 + 8, 0);
                        putB(&tm.w1, own_first(kk), kk < 2 ? 16384 : R5_STAGE);
                        if (++s5 == R5_N) s5 = 0;
                    }
                }
                s5 = 4;
#pragma unroll 1
                for (int kk = 2; kk < 16; kk++) {
                    const int kc = own_first(kk);
                    if (kk >= 4) putB(&tm.w1, kc, R5_STAGE);
                    if (kk == 2 || kk == 9) {
                        wait_flag(flag_ptr(layer, FL_XA + (kk & 1), bi), n8);
                        if (layer == 0 && kk == 2) TM(14);
                        DP(8 * (FL_XA + (kk & 1)) + 3);
                        fence_proxy_async();
                        DP(8 * (FL_XA + (kk & 1)) + 4);
                    }
                    putA(kc, R_XA + tb);
                }
                mbar_wait(e5 + 24, (p5 >> 3) & 1);
                mbar_arrive(f5 + 24);
                p5 ^= 8;
                s5 = 4;
#pragma unroll 1
                for (int kk = 0; kk < 5; kk++) { putB(&tm.w2, own_first(kk), kk < 2 ? 16384 : R5_STAGE); if (++s5 == R5_N) s5 = 0; }
                s5 = 1;
#pragma unroll 1
                for (int kk = 2; kk < 16; kk++) {
                    const int kc = own_first(kk);
                    if (kk >= 5) putB(&tm.w2, kc, R5_STAGE);
                    if (kk == 2 || kk == 9) {
                        wait_flag(flag_ptr(layer, FL_H + (kk & 1), bi), nh);
                        DP(8 * (FL_H + (kk & 1)) + 3);
                        fence_proxy_async();
                        DP(8 * (FL_H + (kk & 1)) + 4);
                    }
                    putA(kc, R_H + layer * R_HP + m0 + (int)((0x4031u >> (kc >> 6 & 12)) & 7) - 2);
                }
#pragma unroll 1
                for (int it = 0; it < 32; it++) {
                    const int kc = it >= 16 ? (it - 16) * BK : own_first(it);
                    const int nb = it < 16 ? 4 : 3, n0 = bj * 448 + (it < 16 ? 0 : 256);
                    if (it > 0 && it < 4) {
                        const int i = (it - 1) * 3 >> 1;
                        mbar_wait(e5 + 8 * i, (p5 >> i) & 1);
                        mbar_wait(e5 + 8 * i + 8, (p5 >> (i + 1)) & 1);
                    }
                    mbar_wait(e4 + 8 * s4, p4);
                    if (it >= 16 && it < 19) mbar_wait(e4 + 8 * s4 + 8, p4);
                    uint32_t sa = s_r + s4 * (it < 16 ? R4_STAGE : R4B_STAGE), full = f4 + 8 * s4;
                    mbar_expect_tx(full, (it < 2 ? 0 : 16384) + nb * 8192);
#pragma unroll 1
                    for (int j = (it ^ rank) & 1; j < nb; j += 2) tma_load_2d_mc(sa + (it < 16 ? -32768 : 16384) + j * 8192, &tm.w3, full, n0 + j * 64, kc);
                    if (it == 2 || it == 9) {
                        wait_flag(flag_ptr(layer, FL_X1 + (it >> 3), bi), n8);
                        DP(8 * (FL_X1 + (it >> 3)) + 3);
                        fence_proxy_async();
                        DP(8 * (FL_X1 + (it >> 3)) + 4);
                    }
                    if (it >= 2) tma_load_2d(sa, &tm.act, full, kc, R_X1 + tb);
                    if (it >= PF4A && it < PF4A + PF4N && layer == 0) tma_prefetch_2d(&tm.w4, bj * 128 + rank * 64, (7 * (bi >> 1) + it - PF4A) * BK);
                    if (++s4 == R4_N) { s4 = 0; p4 ^= 1; }
                }
                wait_flag(flag_ptr(layer, FL_H2, bi), n8);
                fence_proxy_async();
                s5 = 0;
#pragma unroll 1
                for (int j = 0; j < 7; j++) {
                    if (j > 0 && (j & 1) == 0) {
                        mbar_wait(b_h2 + 4 * j, layer);
                        fence_proxy_async();
                    }
                    const int ra = R_H2 + (j >> 1) * 256 + tb;
#pragma unroll 1
                    for (int b = 0; b < 8; b++) {
                        if (j == 0 && b < R4_N) mbar_wait(e4 + 8 * b, p4);
                        putB(&tm.w4, (7 * b + j) * BK, R5_STAGE);
                        putA(((j & 1) * 8 + b) * BK, ra);
                    }
                }
            }
        } } } else {
            auto colsum = [&](bool is1, int bi, int bj) {
                const int pitch = is1 ? D_ : F_, c = is1 ? bj * 128 + (lane & 15) * 8 : bj * 448 + min((warp & 2) * 128 + lane * 8, 440);
                const bf16* p = (is1 ? w1p : w3p) + ((bi * 64 + (is1 ? (lane >> 4) * 32 : 0)) * pitch + c);
                float a[8];
#pragma unroll
                for (int i = 0; i < 8; i++) a[i] = 0.f;
#pragma unroll 1
                for (int r0 = is1 ? 32 : 0; r0 < 64; r0 += 8) {
                    uint4 v[8];
#pragma unroll
                    for (int r = 0; r < 8; r++, p += pitch) v[r] = __ldg(reinterpret_cast<const uint4*>(p));
#pragma unroll
                    for (int r = 0; r < 8; r++) {
                        a[0] += lo2f(v[r].x); a[1] += hi2f(v[r].x); a[2] += lo2f(v[r].y); a[3] += hi2f(v[r].y);
                        a[4] += lo2f(v[r].z); a[5] += hi2f(v[r].z); a[6] += lo2f(v[r].w); a[7] += hi2f(v[r].w);
                    }
                }
                if (is1) {
#pragma unroll
                    for (int i = 0; i < 8; i++) a[i] += __shfl_xor_sync(0xffffffffu, a[i], 16);
                }
                float4* dst = reinterpret_cast<float4*>(g_cpart + bi * (F_ + D_) + (is1 ? F_ : 0) + c);
                dst[0] = make_float4(a[0], a[1], a[2], a[3]);
                dst[1] = make_float4(a[4], a[5], a[6], a[7]);
                __syncwarp();
                if (lane == 0) asm volatile("red.release.gpu.global.add.u32 [%0], 1;" ::"l"(flag_ptr(!is1, FL_CS, bj)) : "memory");
                __syncwarp();
            };
            if (cv && warp == 10) colsum(true, blockIdx.x >> 3, blockIdx.x & 7);
            if (cv && warp == 9) {
#pragma unroll 1
                for (int round = 0; round < 2; round++) {
                    named_bar_sync(4 + 8 * round, 288);
                    if (lane == 0) {
                        asm volatile("fence.release.gpu;" ::: "memory");
                        asm volatile("red.relaxed.gpu.global.add.u32 [%0], 4;" ::"l"(flag_ptr(round ^ 1, FL_CS, 8 + (blockIdx.x >> 4))) : "memory");
                    }
                    __syncwarp();
                }
            }
            auto halo = [&](int layer) {
                const int dn = bj & 2 ? 1 : -1;
                const uint4* gh = g_halo + (layer * 144 + 8 + bi * 8 + bj) * 64 + lane;
                uint4 v[2] = {};
#pragma unroll 1
                for (int n = (bi + dn) & 16 ? 1 << 20 : 0; n < (1 << 20); n++) {
#pragma unroll
                    for (int i = 0; i < 2; i++)
                        asm volatile("{\n.reg .b64 u, v;\nld.relaxed.gpu.global.v2.b64 {u, v}, [%4];\nmov.b64 {%0, %1}, u;\nmov.b64 {%2, %3}, v;\n}"
                                     : "=r"(v[i].x), "=r"(v[i].y), "=r"(v[i].z), "=r"(v[i].w) : "l"(gh + 32 * i) : "memory");
                    if (v[0].y == ep && v[0].w == ep && v[1].y == ep && v[1].w == ep) break;
                }
#pragma unroll
                for (int i = 0; i < 2; i++)
                    asm volatile("st.shared.v2.b32 [%0], {%1, %2};" ::"r"(s_stg + 1024 + i * OFF_EPI + (63 + 65 * dn) * 128 + 8 * lane), "r"(v[i].x), "r"(v[i].z) : "memory");
                fence_async_smem();
                __syncwarp();
                DP(8 * FL_H + 5);
                named_bar_arrive(14, 160);
            };
            float4 keep[2];
            const bool on = get_role();
            if (on && warp == 11) {
                uint4* ps = reinterpret_cast<uint4*>(g_stats + (bi * 8 + bj) * 128) + lane;
                ps[0] = ps[32] = make_uint4(0, 0, 0, 0);
                asm volatile("fence.acq_rel.gpu;" ::: "memory");
                __syncwarp();
                if (lane == 0) mbar_arrive(b_rfull);
            }
#pragma unroll 1
            for (int layer = on ? 0 : 2; layer < 2; layer++) {
                if (warp == 10) {
#pragma unroll 1
                    for (int kind = 0; kind < 6; kind += 2) {
                        const int dn = bj & 2 ? 1 : -1;
#pragma unroll 1
                        for (int hf = 0; hf < 2; hf++) {
                            named_bar_sync(5 + hf, 288);
                            DQ(0);
                            if (lane == 0 && hf && kind) {
                                fence_async_smem();
                                tma_store_2d(&tm.act, s_epi + (kind == FL_H ? 1024 : 16384), bj * 128 + 64, kind == FL_H ? R_H + layer * R_HP + m0 : R_X1 + tb);
                                asm volatile("cp.async.bulk.commit_group;" ::: "memory");
                            }
                            __syncwarp();
                            if (kind + hf == FL_H + 1) halo(layer);
                            if (lane == 0) {
                                asm volatile("cp.async.bulk.wait_group 0;" ::: "memory");
                                DQ(1);
                                asm volatile("fence.release.gpu;" ::: "memory");
                                DQ(2);
                                unsigned int* fp = flag_ptr(layer, kind + hf, bi);
                                asm volatile("red.relaxed.gpu.global.add.u32 [%0], 1;" ::"l"(fp) : "memory");
                                if (kind == FL_H) {
                                    if (bi > 0 && dn > 0) asm volatile("red.relaxed.gpu.global.add.u32 [%0], 1;" ::"l"(fp - FL_PITCH) : "memory");
                                    if (bi < 15 && dn < 0) asm volatile("red.relaxed.gpu.global.add.u32 [%0], 1;" ::"l"(fp + FL_PITCH) : "memory");
                                }
                            }
                            __syncwarp();
                        }
                    }
                } else {
                    uint32_t* rs = reinterpret_cast<uint32_t*>(sgen + OFF_RS);
                    float* cs = reinterpret_cast<float*>(sgen + OFF_CS);
#pragma unroll 1
                    for (int which = 0; which < 2; which++) {
                        if (layer < which) {
                            if (warp == 11 && lane == 0) {
                                asm volatile("cp.async.bulk.prefetch.L2.global [%0], %1;" ::"l"(w3p + (bi * 8 + bj) * 28672), "r"(57344) : "memory");
                            }
                            __syncwarp();
                            colsum(false, bi, bj);
                        }
                        if (warp == 11) continue;
                        if (layer == 0) {
                            if (lane == 0) wait_flag(flag_ptr(which, FL_CS, bj), (16 << which) * ep);
                            __syncwarp();
#pragma unroll 1
                            for (int c = (which ? 384 : 768) + lane * 4; c < 896; c += 128) {
                                const float* cp = g_cpart + (which ? bj * 448 + min(c & 511, 444) : F_ + bj * 128 + lane * 4);
                                float4 a = make_float4(0.f, 0.f, 0.f, 0.f);
#pragma unroll
                                for (int r0 = 0; r0 < 16; r0 += 8) {
                                    float4 v[8];
#pragma unroll
                                    for (int r = 0; r < 8; r++) v[r] = __ldcg(reinterpret_cast<const float4*>(cp + (r0 + r) * (F_ + D_)));
#pragma unroll
                                    for (int r = 0; r < 8; r++) { a.x += v[r].x; a.y += v[r].y; a.z += v[r].z; a.w += v[r].w; }
                                }
                                if (c < 768) *reinterpret_cast<float4*>(cs + min(c & 511, 444)) = a;
                                keep[0] = a;
                            }
                        }
                        if (lane == 0 && (layer | which)) wait_flag(flag_ptr(layer, which == 0 ? FL_XA : FL_X1, bi), 8 * ep);
                        __syncwarp();
                        *reinterpret_cast<float4*>(cs + 256 + lane * 4) = keep[0];
                        { const float4 k0 = keep[0]; keep[0] = keep[1]; keep[1] = k0; }
#pragma unroll 1
                        for (int i = 0; i < 4; i++) {
                            const int r = i * 32 + lane;
                            float mean, var;
                            row_stats(g_stats + (1 + which) * S_ * 8 + bi * 1024 + (r & ~15) + 2 * (lane & 7) + (lane >> 3 & 1), ~layer << 31, mean, var);
                            const uint32_t c0 = pack2(mean, fsqrt(bfr(bfr(var) + 1e-5f)));
                            if (lane < 19 && (layer | which | i) == 0) asm volatile("mbarrier.inval.shared::cta.b64 [%0];" ::"r"(b_full + 8 * lane) : "memory");
                            __syncwarp();
                            rs[r] = c0;
                            const float rd = frcp(hi2f(c0));
                            rs[128 + r] = pack2((mean - lo2f(c0)) * rd, fsqrt(bfr(bfr(var * rd * rd) + 1e-5f)));
                        }
                        __syncwarp();
                        named_bar_arrive(3, 160);
                        named_bar_arrive(11, 160);
                    }
                }
                const uint32_t s_cnt = s_bar + 224;
                auto ticket = [&](uint32_t a) {
                    uint32_t v = 0;
                    if (lane == 0) asm volatile("atom.acq_rel.cta.shared.add.u32 %0, [%1], 1;" : "=r"(v) : "r"(a) : "memory");
                    return v;
                };
                auto next = [&]() {
                    uint32_t v = 0;
                    if (lane == 0) asm volatile("atom.relaxed.cta.shared.add.u32 %0, [%1], 1;" : "=r"(v) : "r"(s_cnt + 16 + 4 * layer) : "memory");
                    return v;
                };
                mbar_wait(b_stg, layer);
                int u = __shfl_sync(0xffffffffu, next(), 0), step = 0;
#pragma unroll 1
                while (true) {
#pragma unroll 1
                    for (; step < 5 && u >= (int)((0x3830201810ull >> (8 * step)) & 255); step++) {
                        if (step == 1) { named_bar_arrive(4, 224); named_bar_arrive(12, 224); continue; }
                        const int part = step ? step - 1 : 0;
                        __syncwarp();
                        if (ticket(s_cnt + 4 * part) == 3 * layer + 2) {
                            asm volatile("fence.release.gpu;" ::: "memory");
                            unsigned int* fp = flag_ptr(layer, FL_H2 + part, bi);
                            asm volatile("red.relaxed.gpu.global.add.u32 [%0], 1;" ::"l"(fp) : "memory");
                            if (part > 0) { wait_flag(fp, 8 * ep); mbar_arrive(b_h2 + 8 * part); }
                        }
                        __syncwarp();
                    }
                    if (u >= 56) break;
                    const uint32_t un = next();
                    const int job = u >> 3, r = (u & 7) * 16 + (lane >> 3);
                    if (job >= 2) mbar_wait(s_bar + 168 + 8 * max(job, 3), layer);
                    const uint32_t sp = sbase + ((job & 2) ? OFF_STG5 : OFF_EPI) + r * 256 + (job & 1) * 128;
                    bf16* gp = act + (size_t)(R_H2 + (job >> 1) * 256 + tb + r) * D_ + ((job & 1) * 8 + bj) * 64 + (lane & 7) * 8;
                    uint4 v[4];
#pragma unroll
                    for (int e = 0; e < 4; e++) v[e] = lds128(sp + e * 1024 + (((lane & 7) ^ ((r + 4 * e) & 7)) << 4));
#pragma unroll
                    for (int e = 0; e < 4; e++) stg128(gp + 4 * e * D_, gelu8h(v[e]));
                    u = __shfl_sync(0xffffffffu, un, 0);
                }
                if (layer == 0 && warp == 11) {
                    const char* ps = reinterpret_cast<const char*>(g_stats + bi * 1024) + lane * 128;
                    const char* py = reinterpret_cast<const char*>(act + (size_t)(R_Y + (tb & ~255) + (bj & 1) * 128 + (lane >> 1)) * D_ + (bj >> 1) * 256 + rank * 128) + (lane & 1) * 128;
#pragma unroll 1
                    for (int i = 0; i < 8; i++) {
                        asm volatile("prefetch.global.L2 [%0];" ::"l"(py + (size_t)i * 16 * D_ * 2) : "memory");
                        if (i >= 6) asm volatile("prefetch.global.L2 [%0];" ::"l"(ps + (i & 1) * 4096) : "memory");
                        __nanosleep(400);
                    }
                }
            }
        }
        __syncwarp();
        asm volatile("barrier.cluster.arrive.relaxed.aligned;\nbarrier.cluster.wait.acquire.aligned; // helpers" ::: "memory");
    } else {
        DT_DECL;
        DT(0);
        DT(24);
        asm volatile("setmaxnreg.inc.sync.aligned.u32 216;");
        if (get_role()) {
        const bool rel_on = (tid & 95) == 0;
        const uint32_t rel5 = mapa_u32(e5, (warp & 1) ^ rank), rel4 = rel5 + (e4 - e5);
        const uint32_t da0 = desc_a(s_r + wg * 8192), db0 = desc_b(s_r + BM * BK * 2), dae = da0 + (OFF_EPI - OFF_R) / 16, db4 = db0 - 49152 / 16;
        auto skip5 = [&](RingState& rs) {
            if (rel_on) mbar_arrive_cluster(rel5 + 8 * rs.st);
            rs.st++;
        };
        const int t = lane & 3;
        const int row = warp * 16 + (lane >> 2);
        const uint32_t st_w = (uint32_t)((warp * 16 + ((lane >> 3) & 1) * 8 + (lane & 7)) * 256 + (((lane >> 4) ^ (lane & 7)) << 4));
        const uint32_t fr = (uint32_t)((warp * 16 + ((lane >> 3) & 1) * 8 + (lane & 7)) * 128 + (((lane >> 4) ^ (lane & 7)) << 4));
        auto copy_out = [&](bf16* dst, uint32_t src) {
            const int r = warp * 16 + (lane >> 4);
            bf16* ox = dst + (size_t)(m0 + r) * D_ + bj * 128 + (lane & 15) * 8;
            const uint32_t ra = src + ((lane & 15) >> 3) * 16384 + r * 128;
            uint4 v[8];
#pragma unroll
            for (int it = 0; it < 8; it++) v[it] = lds128(ra + it * 256 + (((lane & 7) ^ ((2 * it + (lane >> 4)) & 7)) << 4));
#pragma unroll
            for (int it = 0; it < 8; it++) *reinterpret_cast<uint4*>(ox + (size_t)it * 2 * D_) = v[it];
        };
        auto put_half = [&](uint32_t src, int r0, int hf) {
            const int r = warp * 16 + (lane >> 3);
            bf16* gp = act + (size_t)(r0 + r) * D_ + bj * 128 + hf * 64 + (lane & 7) * 8;
            uint4 v[4];
            __syncwarp();
#pragma unroll
            for (int i = 0; i < 4; i++) v[i] = lds128(src + (r + 4 * i) * 128 + (((lane ^ (r + 4 * i)) & 7) << 4));
#pragma unroll
            for (int i = 0; i < 4; i++) stg128(gp + 4 * i * D_, v[i]);
        };
        auto put_stats = [&](const uint32_t (&w)[32], int which, int layer) {
            float c[6][4];
#pragma unroll
            for (int e = 0; e < 32; e++) {
                hmma8(c[e & 3], w[e & ~1], w[e | 1], w[e], e < 4);
                if ((e & 3) == 0) hmma(c[4 + (e >> 2 & 1)], w[e], w[e + 1], w[e + 2], w[e + 3], 0x3f803f80u, 0x3f803f80u, e < 8);
            }
            if (t == lane >> 3) {
                float mu[2];
                uint32_t m2[2];
#pragma unroll
                for (int e = 0; e < 2; e++) {
                    const float q1 = lane & 4 ? c[e][2 * e + 1] + c[e + 2][2 * e + 1] : c[e][2 * e] + c[e + 2][2 * e], s1 = c[4][2 * e] + c[5][2 * e];
                    mu[e] = s1 * (1.0f / 128);
                    m2[e] = __float_as_uint(fmaxf(q1 - s1 * mu[e], 0.f)) | ~layer << 31;
                }
                asm volatile("{\n.reg .b64 u, v;\nmov.b64 u, {%1, %2};\nmov.b64 v, {%3, %4};\nst.relaxed.gpu.global.v2.b64 [%0], {u, v};\n}"
                             ::"l"(g_stats + which * S_ * 8 + (bi * 8 + bj) * 128 + row + (lane >> 2)), "f"(mu[0]), "r"(m2[0]), "f"(mu[1]), "r"(m2[1]) : "memory");
            }
        };
        auto split = [](float r) { const float h = bfr(r); return pack2(h, r - h); };
        auto norm2 = [](uint32_t x, uint32_t m, uint32_t r) {
            const uint32_t d = bsub2(x, m);
            return bfma2(d, __byte_perm(r, 0, 0x1010), bmul2(d, __byte_perm(r, 0, 0x3232)));
        };
        const float* csp = reinterpret_cast<const float*>(sgen + OFF_CS) + 2 * t;
        float mrow[2], rrow[2];
        const uint32_t* rsp = reinterpret_cast<const uint32_t*>(sgen + OFF_RS) + row;
        auto row_consts = [&](bool twice) {
#pragma unroll
            for (int e = 0; e < 2; e++) {
                const uint32_t q0 = rsp[8 * e], q1 = rsp[128 + 8 * e];
                mrow[e] = twice ? fmaf(lo2f(q1), hi2f(q0), lo2f(q0)) : lo2f(q0);
                rrow[e] = 0.5f * frcp(twice ? hi2f(q0) * hi2f(q1) : hi2f(q0));
            }
        };
        auto keep_consts = [&](float2 (&cs)[8]) {
#pragma unroll
            for (int e = 0; e < 8; e++) asm volatile("" : "+f"(cs[e].x), "+f"(cs[e].y));
            asm volatile("" : "+f"(mrow[0]), "+f"(mrow[1]), "+f"(rrow[0]), "+f"(rrow[1]));
        };
        RingState r5{1, 0}, r4{0, 0};
        DT(1);
        uint32_t x[32];
        mbar_wait(b_rfull, 0);
#pragma unroll
        for (int jp = 0; jp < 8; jp++) ldsm4(x[4 * jp], x[4 * jp + 1], x[4 * jp + 2], x[4 * jp + 3], sbase + 16384 + (fr ^ ((jp & 3) << 5)) + (jp >> 2) * (16384 + 8 * CV_SL));
#pragma unroll
        for (int e = 0; e < 32; e++) asm volatile("" : "+r"(x[e]));
        named_bar_sync(9 + wg, 128);
        if ((tid & 95) < R5_N) mbar_arrive_cluster(rel5 + 8 * lane);
#pragma unroll 1
        for (int layer = 0; layer < 2; layer++) {
            {
                DT(2 + 24 * layer);
                put_stats(x, 0, layer);
                DT(20 + 24 * layer);
                DT(22 + 24 * layer);
                uint32_t mb[2], rd[2];
                {
                    float mean, var;
                    row_stats(g_stats + bi * 1024 + warp * 16 + 2 * (lane & 7) + (lane >> 3 & 1), ~layer << 31, mean, var);
                    __syncwarp();
                    const uint32_t r1 = split(frcp(bfr(fsqrt(bfr(bfr(var) + 1e-5f)))));
                    const uint32_t m1 = pack2(mean, mean);
#pragma unroll
                    for (int e = 0; e < 2; e++) { mb[e] = __shfl_sync(0xffffffffu, m1, (lane >> 2) + 8 * e); rd[e] = __shfl_sync(0xffffffffu, r1, (lane >> 2) + 8 * e); }
                }
                DT(21 + 24 * layer);
                mbar_wait(f5 + 8, r5.ph);
                DT(23 + 24 * layer);
                const int yl = ((lane >> 2 & 4) ^ (lane & 7)) + (lane & 4) * 16;
                const uint32_t ya = s_r + R5_STAGE + wg * 16384 + yl * 128 + ((((warp & 3) * 2 + ((lane >> 3) & 1)) ^ (yl & 7)) << 4);
                uint32_t y[16];
#pragma unroll
                for (int e = 0; e < 32; e++) {
                    if ((e & 15) == 0) {
#pragma unroll
                        for (int jp = 0; jp < 4; jp++) ldsm4t(y[4 * jp], y[4 * jp + 1], y[4 * jp + 2], y[4 * jp + 3], ya + jp * 1024 + e * 256);
                    }
                    x[e] = bfma2(norm2(x[e], mb[e & 1], rd[e & 1]), y[e & 15], x[e]);
                    if ((e & 3) == 3) stsm4(s_epi + (fr ^ (((e >> 2) & 3) << 5)) + (e >> 4) * 16384, x[e - 3], x[e - 2], x[e - 1], x[e]);
                    if ((e & 15) == 15) { put_half(s_epi + (e >> 4) * 16384, R_XA + tb, e >> 4); named_bar_arrive(5 + (e >> 4), 288); }
                    if (e == 15) mbar_wait(b_role, 0);
                }
                DT(19 + 24 * layer);
                fence_async_smem();
                if (PS1_EARLY) put_stats(x, 1, layer);
                named_bar_sync(9 + wg, 128);
                skip5(r5);
                DT(3 + 24 * layer);
            }
            {
                float acc[64];
                kblock<128, R5_N, 0>(acc, dae, db0 + 2 * (R5_STAGE / 16), f5, r5);
                kblock<128, R5_N>(acc, dae + 1024, db0 + 3 * (R5_STAGE / 16), f5, r5);
                if (!PS1_EARLY) put_stats(x, 1, layer);
                wgmma_wait<1>();
                if (rel_on) mbar_arrive_cluster(rel5 + 16);
                float2 cs[8];
                mainloop<128, R5_N, R5_STAGE, PA1>(acc, 14, da0, db0, f5, rel5, rel_on, r5, 15 + 24 * layer, [&]() {
                    named_bar_sync(3 + 8 * wg, 160);
                    row_consts(true);
#pragma unroll
                    for (int e = 0; e < 8; e++) cs[e] = *reinterpret_cast<const float2*>(csp + 256 + 8 * e);
                    keep_consts(cs);
                } DT_ARG, (wg ^ bj >> 1 ^ LAGX) & 1);
                DT(4 + 24 * layer);
#pragma unroll
                for (int j = 0; j < 16; j += 2) {
                    if (j == 8) {
#pragma unroll
                        for (int e = 0; e < 8; e++) cs[e] = *reinterpret_cast<const float2*>(csp + 256 + 8 * (j + e));
                    }
                    uint32_t w[4];
#pragma unroll
                    for (int e = 0; e < 4; e++) {
                        const float* a = acc + 4 * j + 2 * e;
                        const float2 c = cs[(j & 7) + (e >> 1)];
                        w[e] = gelu2h(pack2(fmaf(-mrow[e & 1], c.x, a[0]) * rrow[e & 1], fmaf(-mrow[e & 1], c.y, a[1]) * rrow[e & 1]));
                    }
                    stsm4(s_stg + 1024 + (fr ^ ((j & 7) << 4)) + (j >> 3) * OFF_EPI, w[0], w[1], w[2], w[3]);
                    if (j == 6) put_half(s_stg + 1024, R_H + layer * R_HP + m0, 0);
                    if ((j & 7) == 6) named_bar_arrive(5 + (j >> 3), 288);
                }
                if (warp == (bj & 2 ? 0 : 7)) {
                    __syncwarp();
                    uint32_t a[4];
                    lds64(a[0], a[1], s_stg + 1024 + 18 * 128 * warp + 8 * lane);
                    lds64(a[2], a[3], s_epi + 1024 + 18 * 128 * warp + 8 * lane);
                    uint4* gh = g_halo + (layer * 144 + (warp & 2) * 8 + bi * 8 + bj) * 64 + lane;
#pragma unroll
                    for (int i = 0; i < 2; i++)
                        asm volatile("{\n.reg .b64 u, v;\nmov.b64 u, {%1, %3};\nmov.b64 v, {%2, %3};\nst.relaxed.gpu.global.v2.b64 [%0], {u, v};\n}"
                                     ::"l"(gh + i * 32), "r"(a[2 * i]), "r"(a[2 * i + 1]), "r"(ep) : "memory");
                }
                fence_async_smem();
                if (wg == (bj >> 1 & 1)) named_bar_arrive(13, 256);
                DT(5 + 24 * layer);
            }
            {
                float acc[64];
                uint32_t u[32];
                {
                    uint32_t mb[2], rd[2];
#pragma unroll
                    for (int e = 0; e < 2; e++) { const uint32_t q0 = rsp[8 * e]; mb[e] = (q0 & 0xffffu) * 0x10001u; rd[e] = split(frcp(hi2f(q0))); }
#pragma unroll
                    for (int e = 0; e < 32; e++) {
                        u[e] = norm2(x[e], mb[e & 1], rd[e & 1]);
                        asm volatile("" : "+r"(u[e]));
                    }
                }
                if (!(warp & 2)) mbar_wait(f5 + 24, r5.ph);
                skip5(r5);
                {
                    const bool nb = wg == (bj >> 1 & 1);
                    named_bar_sync(nb ? 14 : 13, nb ? 160 : 256);
                }
                const uint32_t dah = da0 - (OFF_R - 1024 + 256) / 16 + ((0x4031u >> (2 * bj & 12)) & 7) * 8;
                kblock<128, R5_N, 0>(acc, dah, db0 + 4 * (R5_STAGE / 16), f5, r5);
                kblock<128, R5_N>(acc, dah + OFF_EPI / 16, db0, f5, r5);
                wgmma_wait<1>();
                if (rel_on) mbar_arrive_cluster(rel5 + 32);
                mainloop<128, R5_N, R5_STAGE, PA2>(acc, 14, da0, db0, f5, rel5, rel_on, r5, 16 + 24 * layer, []() {} DT_ARG, wg);
                DT(6 + 24 * layer);
#pragma unroll
                for (int j = 0; j < 16; j += 2) {
#pragma unroll
                    for (int e = 0; e < 4; e++) u[2 * j + e] = badd2(u[2 * j + e], pack2(acc[4 * j + 2 * e], acc[4 * j + 2 * e + 1]));
                    stsm4(s_epi + (fr ^ ((j & 7) << 4)) + (j >> 3) * 16384, u[2 * j], u[2 * j + 1], u[2 * j + 2], u[2 * j + 3]);
                    if (j == 6) put_half(s_epi, R_X1 + tb, 0);
                    if ((j & 7) == 6) { named_bar_arrive(5 + (j >> 3), 288); mbar_wait(b_role, 0); }
                }
                fence_async_smem();
#pragma unroll
                for (int e = 0; e < 32; e++) x[e] = badd2(x[e], u[e]);
                put_stats(u, 2, layer);
                named_bar_sync(9 + wg, 128);
                DT(7 + 24 * layer);
            }
            {
                float2 cs[NCS];
                auto piece = [&](const float* acc, auto pc) {
                    constexpr int j = 2 * decltype(pc)::v, jl = j & 31;
                    uint32_t w[4];
#pragma unroll
                    for (int e = 0; e < 2; e++) {
                        const float* a = acc + 4 * (jl + e);
                        const float2 cc = cs[(j + e) % NCS];
                        w[2 * e] = pack2(fmaf(-mrow[0], cc.x, a[0]) * rrow[0], fmaf(-mrow[0], cc.y, a[1]) * rrow[0]);
                        w[2 * e + 1] = pack2(fmaf(-mrow[1], cc.x, a[2]) * rrow[1], fmaf(-mrow[1], cc.y, a[3]) * rrow[1]);
                    }
                    stsm4(((jl < 16 ? s_epi : s_stg) + st_w) ^ ((j & 15) << 4), w[0], w[1], w[2], w[3]);
                    if (j + NCS < 56) {
#pragma unroll
                        for (int e = 0; e < 2; e++) { uint32_t u0, u1; lds64(u0, u1, smem_u32(csp + 8 * (j + e + NCS))); cs[(j + e) % NCS] = make_float2(__uint_as_float(u0), __uint_as_float(u1)); }
                    }
                    if (j == 14 || (j >= 30 && (j & 7) == 6)) {
                        __syncwarp();
                        if (lane == 0) mbar_arrive(j == 14 ? b_stg : s_bar + 168 + (j & 56));
                    }
                };
                auto pieces = [&](const float* acc, auto p0, auto p1) {
                    constexpr int a = decltype(p0)::v, b = decltype(p1)::v;
                    static_for<a, b>([&](auto i) { piece(acc, i); });
                };
                float ac3[128];
                kblock<256, R4_N, 0>(ac3, dae, db4, f4, r4);
                kblock<256, R4_N>(ac3, dae + 1024, db4 + R4_STAGE / 16, f4, r4);
                wgmma_wait<1>();
                if (rel_on) mbar_arrive_cluster(rel4);
                mainloop<256, R4_N, R4_STAGE, PA3A>(ac3, 14, da0, db4, f4, rel4, rel_on, r4, 17 + 24 * layer, [&]() {
                    named_bar_sync(3 + 8 * wg, 160);
                    mbar_wait(e4, 1);
                    row_consts(false);
#pragma unroll
                    for (int e = 0; e < NCS; e++) {
                        cs[e] = *reinterpret_cast<const float2*>(csp + 8 * e);
                        asm volatile("" : "+f"(cs[e].x), "+f"(cs[e].y));
                    }
                    asm volatile("" : "+f"(mrow[0]), "+f"(mrow[1]), "+f"(rrow[0]), "+f"(rrow[1]));
                } DT_ARG, wg);
                DT(8 + 24 * layer);
                pieces(ac3, IC<0>(), IC<NPRE>());
                DT(9 + 24 * layer);
                float acc[96];
                constexpr int NS3 = NPRE == 16 ? 1 : (16 - NPRE + PP3 - 1) / PP3;
                static_for<0, NS3>([&](auto cc) {
                    constexpr int c = decltype(cc)::v, q = NPRE + PP3 * c;
                    const uint32_t da = da0 + c * (R4B_STAGE / 16), db = db0 + c * (R4B_STAGE / 16);
                    mbar_wait(f4 + 8 * c, r4.ph);
                    wgmma_fence();
                    static_for<0, 4>([&](auto ic) {
                        constexpr int i = decltype(ic)::v, q0 = q + i * PP3 / 4, q1 = q + (i + 1) * PP3 / 4;
                        WG<192>::mma<(c | i) != 0>(acc, da + 2 * i, db + 128 * i);
                        if (i == 3) {
                            wgmma_commit();
                            if (c) {
                                wgmma_wait<1>();
                                if (rel_on) mbar_arrive_cluster(rel4 + 8 * ((c + 3) & 3));
                            }
                        }
                        pieces(ac3, IC<(q0 < 16 ? q0 : 16)>(), IC<(q1 < 16 ? q1 : 16)>());
                    });
                });
                r4.st = NS3 & 3;
                if (NS3 == 4) r4.ph ^= 1;
                float ac4[64];
                mainloop<192, R4_N, R4B_STAGE, PA3B, 1>(acc, 16 - NS3, da0, db0, f4, rel4, rel_on, r4, -1, [&]() {
#pragma unroll
                    for (int i = 0; i < 32; i++) asm volatile("shl.b32 %0, %2, 16;\nand.b32 %1, %2, 0xffff0000;" : "=f"(ac4[2 * i]), "=f"(ac4[2 * i + 1]) : "r"(x[i]));
                    kblock<128, R5_N>(ac4, da0, db0, f5, r5);
                } DT_ARG, wg);
                DT(10 + 24 * layer);
                named_bar_sync(4 + 8 * wg, 224);
                piece(acc, IC<16>());
                static_for<1, 7>([&](auto cc) {
                    constexpr int c = decltype(cc)::v;
                    const uint32_t da = da0 + (c % 5) * (R5_STAGE / 16), db = db0 + (c % 5) * (R5_STAGE / 16);
                    mbar_wait(f5 + 8 * (c % 5), r5.ph);
                    wgmma_fence();
                    WG<128>::mma<1>(ac4, da, db);
                    WG<128>::mma<1>(ac4, da + 2, db + 128);
                    piece(acc, IC<15 + 2 * c>());
                    WG<128>::mma<1>(ac4, da + 4, db + 256);
                    WG<128>::mma<1>(ac4, da + 6, db + 384);
                    wgmma_commit();
                    if (c % 5 == 4) r5.ph ^= 1;
                    wgmma_wait<1>();
                    if (rel_on) mbar_arrive_cluster(rel5 + 8 * ((c - 1) % 5));
                    if constexpr (c < 6) piece(acc, IC<16 + 2 * c>());
                });
                r5.st = 2;
                DT(11 + 24 * layer);
                DT(18 + 24 * layer);
                mainloop<128, R5_N, R5_STAGE, PA4>(ac4, 49, da0, db0, f5, rel5, rel_on, r5, 62 - 40 * (layer ^ 1), []() {} DT_ARG, wg);
                DT(12 + 24 * layer);
#pragma unroll
                for (int i = 0; i < 32; i++) x[i] = pack2(ac4[2 * i], ac4[2 * i + 1]);
                DT(13 + 24 * layer);
                DT(14 + 24 * layer);
            }
        }
#pragma unroll
        for (int jp = 0; jp < 8; jp++) stsm4(s_epi + (fr ^ ((jp & 3) << 5)) + (jp >> 2) * 16384, x[4 * jp], x[4 * jp + 1], x[4 * jp + 2], x[4 * jp + 3]);
        __syncwarp();
        copy_out(outp, s_epi);
        DT(38);
        DT_DUMP;
        GT(4);
        }
        cluster_arrive_relaxed();
        cluster_wait();
    }
}

typedef CUresult (*PFN_encodeTiled)(CUtensorMap*, CUtensorMapDataType, cuuint32_t, void*, const cuuint64_t*, const cuuint64_t*,
                                    const cuuint32_t*, const cuuint32_t*, CUtensorMapInterleave, CUtensorMapSwizzle,
                                    CUtensorMapL2promotion, CUtensorMapFloatOOBfill);

static CUtensorMap make_map(PFN_encodeTiled enc, const void* ptr, int inner, int outer, int box_inner, int box_outer,
                            CUtensorMapSwizzle swz = CU_TENSOR_MAP_SWIZZLE_128B) {
    CUtensorMap m;
    cuuint64_t dims[2] = {(cuuint64_t)inner, (cuuint64_t)outer};
    cuuint64_t strides[1] = {(cuuint64_t)inner * 2};
    cuuint32_t box[2] = {(cuuint32_t)box_inner, (cuuint32_t)box_outer};
    cuuint32_t es[2] = {1, 1};
    enc(&m, CU_TENSOR_MAP_DATA_TYPE_BFLOAT16, 2, const_cast<void*>(ptr), dims, strides, box, es, CU_TENSOR_MAP_INTERLEAVE_NONE,
        swz, CU_TENSOR_MAP_L2_PROMOTION_L2_256B, CU_TENSOR_MAP_FLOAT_OOB_FILL_NONE);
    return m;
}

extern "C" void kernel_launch(void* const* d_in, const int* in_sizes, int n_in, void* d_out, int out_size) {
    const bf16* A_q = (const bf16*)d_in[0];
    const bf16* A_k = (const bf16*)d_in[1];
    const bf16* A_v = (const bf16*)d_in[2];
    const bf16* A_shk = (const bf16*)d_in[3];
    const bf16* A_ssk = (const bf16*)d_in[4];
    const bf16* A_ssD = (const bf16*)d_in[5];
    const bf16* w1 = (const bf16*)d_in[7];
    const bf16* w2 = (const bf16*)d_in[8];
    const bf16* w3 = (const bf16*)d_in[9];
    const bf16* w4 = (const bf16*)d_in[10];
    bf16* out = (bf16*)d_out;

    static PFN_encodeTiled enc = nullptr;
    static bool attr_done = false;
    if (!enc) {
        void* fn = nullptr;
        cudaDriverEntryPointQueryResult qr;
        cudaGetDriverEntryPoint("cuTensorMapEncodeTiled", &fn, cudaEnableDefault, &qr);
        enc = (PFN_encodeTiled)fn;
    }
    if (!attr_done) {
        cudaFuncSetAttribute(mega_kernel, cudaFuncAttributeMaxDynamicSharedMemorySize, MEGA_SMEM);
        attr_done = true;
    }
    void* p_act;
    cudaGetSymbolAddress(&p_act, g_act);
    bf16* act = (bf16*)(((uintptr_t)p_act + 0x1fffff) & ~(uintptr_t)0x1fffff);

    MegaMaps tm;
    tm.q = make_map(enc, A_q, D_, S_, 64, 128);
    tm.act = make_map(enc, act, D_, R_END, 64, 128);
    tm.a64 = make_map(enc, act, D_, R_END, 64, 64);
    tm.w1 = make_map(enc, w1, D_, D_, 64, 64);
    tm.w2 = make_map(enc, w2, D_, D_, 64, 64);
    tm.w3 = make_map(enc, w3, F_, D_, 64, 64);
    tm.w4 = make_map(enc, w4, D_, F_, 64, 64);
    for (int i = 0; i < 2; i++) {
        cuuint64_t dims[4] = {D_, 4, 8, S_ / 32}, strides[3] = {8 * D_ * 2, D_ * 2, 32 * D_ * 2};
        cuuint32_t box[4] = {16, 4, 8, 4}, es[4] = {1, 1, 1, 1};
        enc(i ? &tm.v : &tm.k, CU_TENSOR_MAP_DATA_TYPE_BFLOAT16, 4, (void*)(i ? A_v : A_k), dims, strides, box, es, CU_TENSOR_MAP_INTERLEAVE_NONE,
            CU_TENSOR_MAP_SWIZZLE_32B, CU_TENSOR_MAP_L2_PROMOTION_NONE, CU_TENSOR_MAP_FLOAT_OOB_FILL_NONE);
    }
    mega_kernel<<<2 * NCL, 384, MEGA_SMEM, cudaStreamPerThread>>>(tm, out, act, w1, w2, w3, A_q, A_k, A_v, A_shk, A_ssk, A_ssD);
}
```
